```python
import torch

def _softmax(x, axis=-1):
    return torch.softmax(x, dim=axis)

def _gelu(x):
    return torch.nn.functional.gelu(x, approximate='tanh')

def _silu(x):
    return torch.nn.functional.silu(x)

def _sigmoid(x):
    return torch.sigmoid(x)

def _layernorm(x, axis=-1, eps=1e-05):
    m = x.mean(dim=axis, keepdim=True)
    v = x.var(dim=axis, keepdim=True, unbiased=False)
    return (x - m) / torch.sqrt(v + eps)

def _scatter_add(tgt, idx, src, axis=0):
    return tgt.clone().index_add_(axis, idx, src)

def _segment_sum(src, seg, n):
    out = torch.zeros((n,) + src.shape[1:], dtype=src.dtype)
    return out.index_add_(0, seg, src)

def _pad(x, pw):
    flat = tuple((v for pair in reversed(pw) for v in pair))
    return torch.nn.functional.pad(x, flat)
kernel_name = 'adaLN_cond__compressed_kv_cla__dense_activation_relu__decode'

def setup_inputs():

    _w = lambda a: (lambda t: t.to(torch.bfloat16) if t.is_floating_point() else t)(torch.as_tensor(a))

    def _A_setup():
        B, H, Sq, Sk, D, M = (8, 32, 1, 4096, 128, 512)
        Dc = 4 * D
        return {'x': _w((lambda *s: torch.randn(*s, dtype=torch.bfloat16) * 0.05)(B, Sq, M)), 'c_kv': _w((lambda *s: torch.randn(*s, dtype=torch.bfloat16) * 1.6)(B, Sk, Dc)), 'w_q': _w((lambda *s: torch.randn(*s, dtype=torch.bfloat16) * 1.6)(M, H, D) * M ** (-0.5)), 'w_uk': _w((lambda *s: torch.randn(*s, dtype=torch.bfloat16) * 1.6)(Dc, H, D) * Dc ** (-0.5)), 'w_uv': _w((lambda *s: torch.randn(*s, dtype=torch.bfloat16) * 1.6)(Dc, H, D) * Dc ** (-0.5)), 'w_o': _w((lambda *s: torch.randn(*s, dtype=torch.bfloat16) * 1.6)(H, D, M) * (H * D) ** (-0.5))}
    _A_in = _A_setup()

    def _B_setup():
        B, S, D, Dff = (8, 1, 512, 1792)
        return {'x': _w((lambda *s: torch.randn(*s, dtype=torch.bfloat16) * 0.05)(B, S, D)), 'w1': _w((lambda *s: torch.randn(*s, dtype=torch.bfloat16) * 0.05)(D, Dff)), 'w2': _w((lambda *s: torch.randn(*s, dtype=torch.bfloat16) * 0.05)(Dff, D))}
    _B_in = _B_setup()
    return {'A_x': _A_in['x'], 'A_c_kv': _A_in['c_kv'], 'A_w_q': _A_in['w_q'], 'A_w_uk': _A_in['w_uk'], 'A_w_uv': _A_in['w_uv'], 'A_w_o': _A_in['w_o'], 'B_x': _B_in['x'], 'B_w1': _B_in['w1'], 'B_w2': _B_in['w2'], 'c': _w((lambda *s: torch.randn(*s, dtype=torch.bfloat16) * 0.2)(8, 512) * 8.0), 'w_mod': _w((lambda *s: torch.randn(*s, dtype=torch.bfloat16) * 0.2)(512, 6 * 512) * 512 ** (-0.5) * 8.0)}

def reference(A_x, A_c_kv, A_w_q, A_w_uk, A_w_uv, A_w_o, B_x, B_w1, B_w2, c, w_mod):

    def _A_ref(x, c_kv, w_q, w_uk, w_uv, w_o):
        B, Sq, M = (x.shape[0], x.shape[1], x.shape[2])
        Sk = c_kv.shape[1]
        H, D = (w_q.shape[1], w_q.shape[2])
        q = torch.einsum('bqm,mhd->bhqd', x, w_q)
        k = torch.einsum('bkc,chd->bhkd', c_kv, w_uk)
        v = torch.einsum('bkc,chd->bhkd', c_kv, w_uv)
        scores = torch.einsum('bhqd,bhkd->bhqk', q, k) * D ** (-0.5)
        off = Sk - Sq
        qi = torch.arange(Sq)[:, None]
        kj = torch.arange(Sk)[None, :]
        cmask = kj <= qi + off
        scores = torch.where(cmask[None, None], scores, -1000000000.0)
        p = _softmax(scores, axis=-1)
        ctx = torch.einsum('bhqk,bhkd->bhqd', p, v)
        return torch.einsum('bhqd,hdm->bqm', ctx, w_o)

    def _B_ref(x, w1, w2):
        h = torch.einsum('bsd,df->bsf', x, w1)
        zero = torch.zeros_like(h)
        h = torch.maximum(h, zero)
        return torch.einsum('bsf,fd->bsd', h, w2)
    x = A_x
    mod = (_silu(c) @ w_mod).reshape(c.shape[0], 6, 1, -1)
    sa, ca, ga, sb, cb, gb = (mod[:, 0].clone(), mod[:, 1].clone(), mod[:, 2].clone(), mod[:, 3].clone(), mod[:, 4].clone(), mod[:, 5].clone())
    h = _layernorm(x, axis=-1) * (1 + ca) + sa
    x = x + ga * _A_ref(h, A_c_kv, A_w_q, A_w_uk, A_w_uv, A_w_o)
    h = _layernorm(x, axis=-1) * (1 + cb) + sb
    x = x + gb * _B_ref(h, B_w1, B_w2)
    return x
```

```cpp
#include <cuda_runtime.h>
#include <cuda.h>
#include <cuda_bf16.h>
#include <stdint.h>

namespace {

constexpr int NCTA = 128;
constexpr int NTHREADS = 352;
constexpr int FCH = 16;
constexpr int NFF = 1792 / FCH;
constexpr int NREP = 8;

constexpr uint32_t OFF_BUFA = 0;
constexpr uint32_t OFF_BUFB = 65536;
constexpr uint32_t OFF_R0 = 131072;
constexpr uint32_t OFF_R1 = 163840;
constexpr uint32_t OFF_R2 = 196608;
constexpr uint32_t OFF_MISC = 229376;
constexpr uint32_t OFF_BARS = OFF_MISC;
constexpr uint32_t OFF_STATS = OFF_MISC + 640;
constexpr uint32_t OFF_EPOCH = OFF_MISC + 704;
constexpr uint32_t OFF_BS = OFF_MISC + 1024;
constexpr uint32_t SMEM_BYTES = OFF_MISC + 3072;
constexpr uint32_t OFF_P0S = OFF_R0 + 24576;
constexpr uint32_t OFF_BS2 = OFF_R0 + 30720;
constexpr uint32_t OFF_PT = OFF_R1;
constexpr uint32_t OFF_RED = OFF_BS + 1024;
constexpr uint32_t OFF_ALPHA = OFF_MISC + 736;
constexpr uint32_t OFF_XS = OFF_BUFB;
constexpr uint32_t OFF_CS = OFF_BUFB + 8192;
__host__ __device__ constexpr uint32_t box_off(int n) {
  return n < 16 ? n * 8192 : n < 19 ? OFF_R1 + (n - 15) * 8192 : n < 23 ? OFF_R2 + (n - 19) * 8192 : n < 31 ? (n - 23) * 8192 : OFF_BUFB;
}
__constant__ uint32_t c_box[32] = {box_off(0), box_off(1), box_off(2), box_off(3), box_off(4), box_off(5), box_off(6), box_off(7),
                                   box_off(8), box_off(9), box_off(10), box_off(11), box_off(12), box_off(13), box_off(14), box_off(15),
                                   box_off(16), box_off(17), box_off(18), box_off(19), box_off(20), box_off(21), box_off(22), box_off(23),
                                   box_off(24), box_off(25), box_off(26), box_off(27), box_off(28), box_off(29), box_off(30), box_off(31)};
constexpr uint32_t OFF_WUV = OFF_BUFB + 8192;
constexpr uint32_t OFF_WO0 = OFF_BUFB + 40960;
constexpr uint32_t OFF_WO1 = OFF_R2;
constexpr uint32_t OFF_CB = OFF_BUFB + 57344;
constexpr uint32_t OFF_W1 = OFF_R2 + 16384;
constexpr uint32_t OFF_W2 = OFF_R1 + 8192;
constexpr uint32_t OFF_SB = OFF_R1 + 24576;
constexpr uint32_t OFF_BS4 = OFF_R0;
constexpr uint32_t OFF_BS5 = OFF_R0 + 4096;
constexpr uint32_t OFF_BSX = OFF_R0 + 8192;
constexpr uint32_t OFF_BSY = OFF_R0 + 16384;
constexpr uint32_t OFF_LP = OFF_BUFA;
constexpr uint32_t OFF_REDG = OFF_R0 + 24576;
constexpr uint32_t OFF_REDS = OFF_R0 + 28672;
constexpr uint32_t OFF_REDU = OFF_BUFA + 8192;
constexpr uint32_t OFF_REDV = OFF_BUFA + 12288;
constexpr uint32_t OFF_H1 = OFF_BUFA + 16384;
constexpr uint32_t OFF_ST7 = OFF_BUFA + 17408;

constexpr int BAR_FULL = 0;
constexpr int BAR_EMPTY = 32;
constexpr int BAR_WMOD = 36, BAR_WQ = 37, BAR_WUK = 39, BAR_WUV = 41, BAR_WO = 43, BAR_W1 = 45, BAR_W2 = 46;
constexpr int BAR_XC = 47, BAR_HOP = 48, BAR_GO = 49, BAR_ALLCLR = 50, BAR_CBSB = 51, BAR_STATS = 52, BAR_EPOCH = 53;
constexpr int BAR_QPOK = 62;
constexpr int BAR_P1D = 64, BAR_P2D = 65;
constexpr int BAR_LP = 66;
constexpr int BAR_P5D = 54, BAR_P7D = 55;
constexpr int BAR_P0E = 57, BAR_P1E = 58, BAR_P2E = 59;
constexpr int BAR_QXG = 67;
constexpr int NBARS = 75;
#define WIN_PRE 4
#define WIN_MID 8
#define WIN_END 6
#define CLR_CLK 500
#define CLR_B 4
#define D_MOD 400
#define D_QP 600
#define D_QX 900
#define X1_D0 1800
#define X1_DQ 200
#define D_X2 300
#define D_X3A 300
#define D_FIN 600

struct Scratch {
  uint32_t MOD[2][3072 * 4];
  uint32_t QP[2][128 * 256 * 2];
  uint32_t QX[2][8 * 32 * 256];
  uint32_t ML[32 * 128 * 2];
  uint32_t X1[128 * 128 * 64];
  uint32_t X2[128 * 256 * 2];
  uint32_t X3A[128 * 32 * 16];
  uint32_t X3B[NREP * 512 * 4];
  uint32_t X4[128 * NFF * 16];
  uint32_t epoch;
  uint32_t pad[31];
  uint32_t cnt;
};
__device__ Scratch g_s;

#define TL(idx) do {} while (0)
#define CLK_DECL
#define ATT_TILE (-1)
#define CLK(i) do {} while (0)
#define CLK_DUMP(n, base) do {} while (0)

struct Params {
  CUtensorMap xm, cm, wmod, wq, wuk, ckv, wuv, wo, w1, w2;
};

__device__ __forceinline__ void mbar_init(uint32_t bar, int cnt) { asm volatile("mbarrier.init.shared::cta.b64 [%0], %1;" ::"r"(bar), "r"(cnt)); }
__device__ __forceinline__ void mbar_expect(uint32_t bar, uint32_t bytes) { asm volatile("mbarrier.arrive.expect_tx.shared::cta.b64 _, [%0], %1;" ::"r"(bar), "r"(bytes) : "memory"); }
__device__ __forceinline__ void mbar_arrive(uint32_t bar) { asm volatile("mbarrier.arrive.shared::cta.b64 _, [%0];" ::"r"(bar) : "memory"); }
__device__ __forceinline__ bool mbar_test(uint32_t bar, uint32_t parity) {
  uint32_t ok;
  asm volatile("{\n.reg .pred p;\nmbarrier.test_wait.parity.shared::cta.b64 p, [%1], %2;\nselp.u32 %0,1,0,p;\n}" : "=r"(ok) : "r"(bar), "r"(parity) : "memory");
  return ok;
}
__device__ __forceinline__ void backoff(int clocks) {
  if (clocks > 0) { long long c0, c1; asm volatile("mov.u64 %0, %%clock64;" : "=l"(c0)); do { asm volatile("mov.u64 %0, %%clock64;" : "=l"(c1)); } while (c1 - c0 < clocks); }
}
template <typename T> __device__ __forceinline__ T* pin(T* p) { asm volatile("" : "+l"(p)); return p; }
constexpr int SPIN_LIMIT = 1 << 22;
__device__ __forceinline__ void mbar_wait(uint32_t bar, uint32_t parity) {
  asm volatile("{\n.reg .pred p;\n.reg .u32 c;\nmov.u32 c, 0;\n"
               "MW_LOOP:\nmbarrier.try_wait.parity.shared::cta.b64 p, [%0], %1;\n@p bra MW_DONE;\n"
               "add.u32 c, c, 1;\nsetp.lt.u32 p, c, 4194304;\n@p bra MW_LOOP;\ntrap;\nMW_DONE:\n}"
               ::"r"(bar), "r"(parity) : "memory");
}
__device__ __forceinline__ void tma2d(uint32_t dst, const CUtensorMap* m, int c0, int c1, uint32_t bar, uint64_t pol) {
  asm volatile("cp.async.bulk.tensor.2d.shared::cluster.global.mbarrier::complete_tx::bytes.L2::cache_hint [%0], [%1, {%3,%4}], [%2], %5;"
               ::"r"(dst), "l"(m), "r"(bar), "r"(c0), "r"(c1), "l"(pol) : "memory");
}
__device__ __forceinline__ void tma3d_nohint(uint32_t dst, const CUtensorMap* m, int c0, int c1, int c2, uint32_t bar) {
  asm volatile("cp.async.bulk.tensor.3d.shared::cluster.global.mbarrier::complete_tx::bytes [%0], [%1, {%3,%4,%5}], [%2];"
               ::"r"(dst), "l"(m), "r"(bar), "r"(c0), "r"(c1), "r"(c2) : "memory");
}
__device__ __forceinline__ void tma2d_nohint(uint32_t dst, const CUtensorMap* m, int c0, int c1, uint32_t bar) {
  asm volatile("cp.async.bulk.tensor.2d.shared::cluster.global.mbarrier::complete_tx::bytes [%0], [%1, {%3,%4}], [%2];"
               ::"r"(dst), "l"(m), "r"(bar), "r"(c0), "r"(c1) : "memory");
}
__device__ __forceinline__ void bar_sync(int id, int n) { asm volatile("bar.sync %0, %1;" ::"r"(id), "r"(n) : "memory"); }
__device__ __forceinline__ void cbar() { bar_sync(1, 256); }

__device__ __forceinline__ uint4 ldg_rlx4(const void* p) { uint4 v; asm volatile("ld.relaxed.gpu.global.v4.u32 {%0,%1,%2,%3}, [%4];" : "=r"(v.x), "=r"(v.y), "=r"(v.z), "=r"(v.w) : "l"(p) : "memory"); return v; }
__device__ __forceinline__ uint32_t ldg_rlx1(const void* p) { uint32_t v; asm volatile("ld.relaxed.gpu.global.u32 %0, [%1];" : "=r"(v) : "l"(p) : "memory"); return v; }
__device__ __forceinline__ void stg4(void* p, uint4 v) { asm volatile("st.relaxed.gpu.global.v4.u32 [%0], {%1,%2,%3,%4};" ::"l"(p), "r"(v.x), "r"(v.y), "r"(v.z), "r"(v.w) : "memory"); }
__device__ __forceinline__ void stg1(void* p, uint32_t a) { asm volatile("st.relaxed.gpu.global.u32 [%0], %1;" ::"l"(p), "r"(a) : "memory"); }
__device__ __forceinline__ bool ok4(const uint4& v) { return v.x != 0 && v.y != 0 && v.z != 0 && v.w != 0; }
__device__ __forceinline__ uint32_t nz(uint32_t w) { return max(w, 1u); }

__device__ __forceinline__ uint32_t pack_bf16(float lo, float hi) { uint32_t r; asm("cvt.rn.bf16x2.f32 %0, %1, %2;" : "=r"(r) : "f"(hi), "f"(lo)); return r; }
__device__ __forceinline__ float bf_lo(uint32_t w) { return __uint_as_float(w << 16); }
__device__ __forceinline__ float bf_hi(uint32_t w) { return __uint_as_float(w & 0xffff0000u); }
__device__ __forceinline__ float ex2(float x) { float r; asm("ex2.approx.ftz.f32 %0, %1;" : "=f"(r) : "f"(x)); return r; }

__device__ __forceinline__ void ldsm4(uint32_t (&r)[4], uint32_t a) { asm volatile("ldmatrix.sync.aligned.m8n8.x4.shared.b16 {%0,%1,%2,%3}, [%4];" : "=r"(r[0]), "=r"(r[1]), "=r"(r[2]), "=r"(r[3]) : "r"(a) : "memory"); }
__device__ __forceinline__ void ldsm4t(uint32_t (&r)[4], uint32_t a) { asm volatile("ldmatrix.sync.aligned.m8n8.x4.trans.shared.b16 {%0,%1,%2,%3}, [%4];" : "=r"(r[0]), "=r"(r[1]), "=r"(r[2]), "=r"(r[3]) : "r"(a) : "memory"); }
__device__ __forceinline__ void ldsm2t(uint32_t& r0, uint32_t& r1, uint32_t a) { asm volatile("ldmatrix.sync.aligned.m8n8.x2.trans.shared.b16 {%0,%1}, [%2];" : "=r"(r0), "=r"(r1) : "r"(a) : "memory"); }
__device__ __forceinline__ void stsm4t(uint32_t a, uint32_t r0, uint32_t r1, uint32_t r2, uint32_t r3) { asm volatile("stmatrix.sync.aligned.m8n8.x4.trans.shared.b16 [%0], {%1,%2,%3,%4};" ::"r"(a), "r"(r0), "r"(r1), "r"(r2), "r"(r3) : "memory"); }
__device__ __forceinline__ void mma16816(float (&d)[4], const uint32_t (&a)[4], uint32_t b0, uint32_t b1) {
  asm volatile("mma.sync.aligned.m16n8k16.row.col.f32.bf16.bf16.f32 {%0,%1,%2,%3}, {%4,%5,%6,%7}, {%8,%9}, {%0,%1,%2,%3};"
               : "+f"(d[0]), "+f"(d[1]), "+f"(d[2]), "+f"(d[3]) : "r"(a[0]), "r"(a[1]), "r"(a[2]), "r"(a[3]), "r"(b0), "r"(b1));
}
__device__ __forceinline__ void sts1(uint32_t a, uint32_t v) { asm volatile("st.shared.u32 [%0], %1;" ::"r"(a), "r"(v) : "memory"); }
__device__ __forceinline__ void sts2(uint32_t a, uint32_t x, uint32_t y) { asm volatile("st.shared.v2.u32 [%0], {%1,%2};" ::"r"(a), "r"(x), "r"(y) : "memory"); }
__device__ __forceinline__ void sts4(uint32_t a, uint4 v) { asm volatile("st.shared.v4.u32 [%0], {%1,%2,%3,%4};" ::"r"(a), "r"(v.x), "r"(v.y), "r"(v.z), "r"(v.w) : "memory"); }
__device__ __forceinline__ void sts4f(uint32_t a, float x, float y, float z, float w) { asm volatile("st.shared.v4.f32 [%0], {%1,%2,%3,%4};" ::"r"(a), "f"(x), "f"(y), "f"(z), "f"(w) : "memory"); }
__device__ __forceinline__ void stsf(uint32_t a, float v) { asm volatile("st.shared.f32 [%0], %1;" ::"r"(a), "f"(v) : "memory"); }
__device__ __forceinline__ uint32_t lds1(uint32_t a) { uint32_t v; asm volatile("ld.shared.u32 %0, [%1];" : "=r"(v) : "r"(a) : "memory"); return v; }
__device__ __forceinline__ float lds_bf16(uint32_t a) { uint16_t v; asm volatile("ld.shared.u16 %0, [%1];" : "=h"(v) : "r"(a) : "memory"); return __uint_as_float((uint32_t)v << 16); }
__device__ __forceinline__ float ldsf(uint32_t a) { float v; asm volatile("ld.shared.f32 %0, [%1];" : "=f"(v) : "r"(a) : "memory"); return v; }
__device__ __forceinline__ float2 ldsf2(uint32_t a) { float2 v; asm volatile("ld.shared.v2.f32 {%0,%1}, [%2];" : "=f"(v.x), "=f"(v.y) : "r"(a) : "memory"); return v; }
__device__ __forceinline__ float4 ldsf4(uint32_t a) { float4 v; asm volatile("ld.shared.v4.f32 {%0,%1,%2,%3}, [%4];" : "=f"(v.x), "=f"(v.y), "=f"(v.z), "=f"(v.w) : "r"(a) : "memory"); return v; }
__device__ __forceinline__ uint4 lds4(uint32_t a) { uint4 v; asm volatile("ld.shared.v4.u32 {%0,%1,%2,%3}, [%4];" : "=r"(v.x), "=r"(v.y), "=r"(v.z), "=r"(v.w) : "r"(a) : "memory"); return v; }

__device__ __forceinline__ void wg_fence() { asm volatile("wgmma.fence.sync.aligned;" ::: "memory"); }
__device__ __forceinline__ void wg_commit() { asm volatile("wgmma.commit_group.sync.aligned;" ::: "memory"); }
__device__ __forceinline__ void wg_wait0() { asm volatile("wgmma.wait_group.sync.aligned 0;" ::: "memory"); }
__device__ __forceinline__ uint32_t desc_lo(uint32_t addr) { return (addr >> 4) | 0x10000u; }
template <int TA> __device__ __forceinline__ void wgmma_n32(float (&d)[16], uint32_t da, uint32_t db, int scale_d) {
  asm volatile("{\n.reg .pred p;\n.reg .b64 da, db;\nsetp.ne.b32 p, %18, 0;\n"
               "mov.b64 da, {%16, 0x40000040};\nmov.b64 db, {%17, 0x40000040};\n"
               "wgmma.mma_async.sync.aligned.m64n32k16.f32.bf16.bf16 {%0,%1,%2,%3,%4,%5,%6,%7,%8,%9,%10,%11,%12,%13,%14,%15}, da, db, p, 1, 1, %19, 0;\n}"
               : "+f"(d[0]), "+f"(d[1]), "+f"(d[2]), "+f"(d[3]), "+f"(d[4]), "+f"(d[5]), "+f"(d[6]), "+f"(d[7]),
                 "+f"(d[8]), "+f"(d[9]), "+f"(d[10]), "+f"(d[11]), "+f"(d[12]), "+f"(d[13]), "+f"(d[14]), "+f"(d[15])
               : "r"(da), "r"(db), "r"(scale_d), "n"(TA));
}

__device__ __forceinline__ uint2 ldg_u64(const void* p) {
  uint2 v; asm volatile("{\n.reg .b64 a;\nld.relaxed.gpu.global.b64 a, [%2];\nmov.b64 {%0,%1}, a;\n}" : "=r"(v.x), "=r"(v.y) : "l"(p) : "memory"); return v;
}
__device__ __forceinline__ uint4 ldg_2u64(const void* p) {
  uint4 v; asm volatile("{\n.reg .b64 a, b;\nld.relaxed.gpu.global.v2.b64 {a, b}, [%4];\nmov.b64 {%0,%1}, a;\nmov.b64 {%2,%3}, b;\n}" : "=r"(v.x), "=r"(v.y), "=r"(v.z), "=r"(v.w) : "l"(p) : "memory"); return v;
}
__device__ __forceinline__ uint4 ldg_u128(const void* p) {
  uint4 v; asm volatile("{\n.reg .b64 a, b;\n.reg .b128 q;\nld.relaxed.gpu.global.b128 q, [%4];\nmov.b128 {a, b}, q;\nmov.b64 {%0,%1}, a;\nmov.b64 {%2,%3}, b;\n}" : "=r"(v.x), "=r"(v.y), "=r"(v.z), "=r"(v.w) : "l"(p) : "memory"); return v;
}
__device__ __forceinline__ void stg_u64(void* p, uint32_t x, uint32_t y) {
  asm volatile("{\n.reg .b64 a;\nmov.b64 a, {%1,%2};\nst.relaxed.gpu.global.b64 [%0], a;\n}" ::"l"(p), "r"(x), "r"(max(y, 1u)) : "memory");
}
__device__ __forceinline__ void stg_u128(void* p, uint4 v) {
  asm volatile("{\n.reg .b64 a, b;\n.reg .b128 q;\nmov.b64 a, {%1,%2};\nmov.b64 b, {%3,%4};\nmov.b128 q, {a, b};\nst.relaxed.gpu.global.b128 [%0], q;\n}" ::"l"(p), "r"(v.x), "r"(v.y), "r"(v.z), "r"(max(v.w, 1u)) : "memory");
}
__device__ __forceinline__ uint32_t hmul2(uint32_t a, uint32_t b) { uint32_t r; asm("mul.rn.bf16x2 %0, %1, %2;" : "=r"(r) : "r"(a), "r"(b)); return r; }
__device__ __forceinline__ uint32_t hadd2(uint32_t a, uint32_t b) { uint32_t r; asm("add.rn.bf16x2 %0, %1, %2;" : "=r"(r) : "r"(a), "r"(b)); return r; }
__device__ __forceinline__ uint32_t hfma2(uint32_t a, uint32_t b, uint32_t c) { uint32_t r; asm("fma.rn.bf16x2 %0, %1, %2, %3;" : "=r"(r) : "r"(a), "r"(b), "r"(c)); return r; }
__device__ __forceinline__ void stsm2t(uint32_t a, uint32_t r0, uint32_t r1) { asm volatile("stmatrix.sync.aligned.m8n8.x2.trans.shared.b16 [%0], {%1,%2};" ::"r"(a), "r"(r0), "r"(r1) : "memory"); }
__device__ __forceinline__ void stsm4(uint32_t a, uint32_t r0, uint32_t r1, uint32_t r2, uint32_t r3) { asm volatile("stmatrix.sync.aligned.m8n8.x4.shared.b16 [%0], {%1,%2,%3,%4};" ::"r"(a), "r"(r0), "r"(r1), "r"(r2), "r"(r3) : "memory"); }
__device__ __forceinline__ uint32_t xs_addr(uint32_t base, int b, int m) { return base + (m >> 6) * 1024 + b * 128 + ((((m >> 3) & 7) ^ b) << 4) + (m & 7) * 2; }
template <bool B> struct BoolC { static constexpr bool value = B; };
constexpr uint32_t ONE2 = 0x3f803f80u;

__device__ __forceinline__ void sum4_to_smem(const uint32_t* x, int tid, uint32_t dst) {
  uint2 v[4];
#pragma unroll
  for (int i = 0; i < 4; i++) v[i] = ldg_u64(x + i * 512);
  int it = 0;
  while (v[0].y == 0 || v[1].y == 0 || v[2].y == 0 || v[3].y == 0) {
#pragma unroll
    for (int i = 0; i < 4; i++) if (v[i].y == 0) v[i] = ldg_u64(x + i * 512);
    if (++it > SPIN_LIMIT) __trap();
  }
  const float c0 = (bf_lo(v[0].x) + bf_lo(v[1].x)) + (bf_lo(v[2].x) + bf_lo(v[3].x));
  const float c1 = (bf_hi(v[0].x) + bf_hi(v[1].x)) + (bf_hi(v[2].x) + bf_hi(v[3].x));
  const float c2 = (bf_lo(v[0].y) + bf_lo(v[1].y)) + (bf_lo(v[2].y) + bf_lo(v[3].y));
  const float c3 = (bf_hi(v[0].y) + bf_hi(v[1].y)) + (bf_hi(v[2].y) + bf_hi(v[3].y));
  sts1(dst, pack_bf16(c0, c1));
  sts1(dst + 128, pack_bf16(c2, c3));
}
__device__ __forceinline__ void load_a_t(uint32_t (&a)[8][4], uint32_t wbase, int w, int lane) {
  const int mi = lane >> 3, r = lane & 7;
  const uint32_t base = wbase + (w >> 2) * 16384 + (8 * (mi >> 1) + r) * 128 + (((2 * (w & 3) + (mi & 1)) ^ r) << 4);
#pragma unroll
  for (int ks = 0; ks < 8; ks++) ldsm4t(a[ks], base + ks * 2048);
}
__device__ __forceinline__ void mma128(float (&d)[4], const uint32_t (&a)[8][4], uint32_t bs, int lane) {
  float e[4][4] = {{0.f, 0.f, 0.f, 0.f}, {0.f, 0.f, 0.f, 0.f}, {0.f, 0.f, 0.f, 0.f}, {0.f, 0.f, 0.f, 0.f}};
  uint32_t b[4][4];
#pragma unroll
  for (int kk = 0; kk < 4; kk++) ldsm4t(b[kk], bs + (32 * kk + lane) * 16);
#pragma unroll
  for (int kk = 0; kk < 4; kk++) { mma16816(e[(2 * kk) & 3], a[2 * kk], b[kk][0], b[kk][1]); mma16816(e[(2 * kk + 1) & 3], a[2 * kk + 1], b[kk][2], b[kk][3]); }
#pragma unroll
  for (int i = 0; i < 4; i++) d[i] = (e[0][i] + e[1][i]) + (e[2][i] + e[3][i]);
}
template <int NP, bool U128> __device__ __forceinline__ void sum_pieces(const uint32_t* base, int g, int t, float& v0, float& v1) {
  constexpr int NL = NP / 8;
  const uint32_t* p0 = base + (4 * (g >> 2) + t) * 16 + (g & 3) * 4;
  uint32_t v[NL][4];
  int it = 0;
  while (true) {
    uint32_t mn = 0xffffffffu;
#pragma unroll
    for (int i = 0; i < NL; i++) {
      const uint4 x = U128 ? ldg_u128(p0 + i * 128) : ldg_rlx4(p0 + i * 128);
      v[i][0] = x.x; v[i][1] = x.y; v[i][2] = x.z; v[i][3] = x.w;
    }
#pragma unroll
    for (int i = 0; i < NL; i++) mn = U128 ? min(mn, v[i][3]) : min(min(mn, v[i][3]), min(min(v[i][0], v[i][1]), v[i][2]));
    if (__all_sync(~0u, mn != 0)) break;
    if (++it > SPIN_LIMIT) __trap();
  }
  const uint32_t one = (g & 1) ? 0x3f800000u : 0x00003f80u;
  const uint32_t b0 = (g & 2) ? 0u : one, b1 = (g & 2) ? one : 0u;
  float d[4][4] = {{0.f, 0.f, 0.f, 0.f}, {0.f, 0.f, 0.f, 0.f}, {0.f, 0.f, 0.f, 0.f}, {0.f, 0.f, 0.f, 0.f}};
#pragma unroll
  for (int i = 0; i < NL; i++) mma16816(d[i & 3], v[i], b0, b1);
  const bool up = t & 2;
  const float x0 = up ? (d[0][2] + d[1][2]) + (d[2][2] + d[3][2]) : (d[0][0] + d[1][0]) + (d[2][0] + d[3][0]);
  const float x1 = up ? (d[0][3] + d[1][3]) + (d[2][3] + d[3][3]) : (d[0][1] + d[1][1]) + (d[2][1] + d[3][1]);
  v0 = x0 + __shfl_xor_sync(~0u, x0, 16);
  v1 = x1 + __shfl_xor_sync(~0u, x1, 16);
}

__global__ void __launch_bounds__(NTHREADS, 1)
fused_decode_kernel(__nv_bfloat16* __restrict__ gout, Scratch* __restrict__ gs, const uint8_t* __restrict__ gwmod,
                    const __grid_constant__ Params P) {
  extern __shared__ __align__(1024) uint8_t smem_raw[];
  const uint32_t sb = (uint32_t)__cvta_generic_to_shared(smem_raw);
  const int tid = threadIdx.x, lane = tid & 31;
  const int w = __shfl_sync(0xffffffffu, tid >> 5, 0);
  const int cta = blockIdx.x;
  const uint32_t bars = sb + OFF_BARS;
  auto BAR = [&](int i) { return bars + 8 * i; };
  const int g = lane >> 2, t = lane & 3;
  const int hI = cta >> 2, jI = cta & 3;
  const int bI = cta >> 4;

  uint32_t epoch0 = 0;
  if (tid == 320) epoch0 = ldg_rlx1(&gs->epoch);
  if (w < 8) {
    const uint8_t* wm = gwmod + 48 * cta + (size_t)256 * 6144;
#pragma unroll
    for (int i = 0; i < 3; i++) {
      const int ch = i * 256 + tid, row = ch / 3, q = ch - 3 * row;
      asm volatile("cp.async.cg.shared.global [%0], [%1], 16;" ::"r"(sb + OFF_R0 + 12288 + ch * 16), "l"(wm + row * 6144 + q * 16) : "memory");
    }
    asm volatile("cp.async.commit_group;" ::: "memory");
  }
  if (tid == 256) {
    if (sb & 1023) __trap();
    mbar_init(BAR(BAR_XC), 1); mbar_init(BAR(BAR_WMOD), 1);
    mbar_init(BAR(BAR_WQ), 1); mbar_init(BAR(BAR_WQ + 1), 1);
    asm volatile("fence.mbarrier_init.release.cluster;" ::: "memory");
    uint64_t pol; asm volatile("createpolicy.fractional.L2::evict_first.b64 %0, 1.0;" : "=l"(pol));
    auto ld_xc = [&] { mbar_expect(BAR(BAR_XC), 16384); tma3d_nohint(sb + OFF_CS, &P.cm, 0, 0, 0, BAR(BAR_XC)); tma3d_nohint(sb + OFF_XS, &P.xm, 0, 0, 0, BAR(BAR_XC)); };
    auto ld_wmod = [&] { mbar_expect(BAR(BAR_WMOD), 12288); tma2d_nohint(sb + OFF_R0, &P.wmod, 24 * cta, 0, BAR(BAR_WMOD)); };
    auto ld_wq = [&](int i) { mbar_expect(BAR(BAR_WQ + i), 16384); tma2d(sb + OFF_R1 + i * 16384, &P.wq, 128 * hI + 64 * i, 128 * jI, BAR(BAR_WQ + i), pol); };
    ld_wq(0); ld_wmod(); ld_xc(); ld_wq(1);
    TL(32);
  } else if (tid == 288) {
#pragma unroll
    for (int i = 0; i < NBARS; i++)
      if (i != BAR_XC && i != BAR_WMOD && i != BAR_WQ && i != BAR_WQ + 1)
        mbar_init(BAR(i), (i == BAR_STATS || (i >= BAR_EMPTY && i < BAR_EMPTY + 4) || i == BAR_P1D || i == BAR_P2D || i == BAR_P5D || i == BAR_P7D || i == BAR_P1E || i == BAR_P2E) ? 8 : i == BAR_P0E ? 2 : 1);
    asm volatile("fence.mbarrier_init.release.cluster;" ::: "memory");
  }
  __syncthreads();
  TL(0);

  if (w == 8) {
    const int h = hI, j = jI, b = bI, s = cta & 15;
    if (lane == 0) {
      uint64_t pol; asm volatile("createpolicy.fractional.L2::evict_first.b64 %0, 1.0;" : "=l"(pol));
      auto half = [&](const CUtensorMap* m, uint32_t dst, int c0, int c1, int bar) {
        mbar_expect(BAR(bar), 16384);
        tma2d(dst, m, c0, c1, BAR(bar), pol);
      };
      asm volatile("prefetch.tensormap [%0];" ::"l"(&P.wuk) : "memory");
      asm volatile("prefetch.tensormap [%0];" ::"l"(&P.ckv) : "memory");
      TL(33);
      mbar_wait(BAR(BAR_WMOD), 0);
      TL(34);
      half(&P.wuk, sb + OFF_R2, 128 * h, 128 * j, BAR_WUK);
      mbar_wait(BAR(BAR_WQ), 0);
      TL(35);
      half(&P.wuk, sb + OFF_R2 + 16384, 128 * h + 64, 128 * j, BAR_WUK + 1);
      mbar_wait(BAR(BAR_WQ + 1), 0);
      TL(36);
      bool go = false;
#pragma unroll 1
      for (int n = 0; n < 32; n++) {
        if (n == 2) { mbar_wait(BAR(BAR_WUK), 0); TL(37); }
        if (n == 4) { mbar_wait(BAR(BAR_WUK + 1), 0); TL(38); }
        if (n == 8) { mbar_wait(BAR(BAR_HOP), 0); TL(39); }
        if (n == 15) TL(40);
        if (!go) go = mbar_test(BAR(BAR_GO), 0);
        const int win = n >= 24 ? WIN_END : (go ? WIN_MID : WIN_PRE);
        if (n >= win) mbar_wait(BAR(BAR_FULL + n - win), 0);
        if (n == 16) mbar_wait(BAR(BAR_P1D), 0);
        if (n == 19) mbar_wait(BAR(BAR_P2D), 0);
        if (n == 23) { mbar_wait(BAR(BAR_EMPTY), 0); TL(24); }
        if (n == 31) { mbar_wait(BAR(BAR_EMPTY + 1), 0); TL(25); }
        mbar_expect(BAR(BAR_FULL + n), 8192);
        tma2d(sb + c_box[n], &P.ckv, (n & 7) * 64, b * 4096 + ((n >> 3) * 16 + s) * 64, BAR(BAR_FULL + n), pol);
      }
      asm volatile("prefetch.tensormap [%0];" ::"l"(&P.wuv) : "memory");
      asm volatile("prefetch.tensormap [%0];" ::"l"(&P.wo) : "memory");
      asm volatile("prefetch.tensormap [%0];" ::"l"(&P.w1) : "memory");
      asm volatile("prefetch.tensormap [%0];" ::"l"(&P.w2) : "memory");
      auto unit = [&](int u) {
        if (u == 0) half(&P.wuv, sb + OFF_WUV, 128 * h, 128 * j, BAR_WUV);
        if (u == 1) half(&P.wuv, sb + OFF_WUV + 16384, 128 * h + 64, 128 * j, BAR_WUV + 1);
        if (u == 2) half(&P.wo, sb + OFF_WO0, 128 * j, 128 * h, BAR_WO);
        if (u == 3) half(&P.wo, sb + OFF_WO1, 128 * j + 64, 128 * h, BAR_WO + 1);
        if (u == 4) {
          mbar_expect(BAR(BAR_W1), 16384);
          tma2d_nohint(sb + OFF_W1, &P.w1, FCH * cta, 0, BAR(BAR_W1));
          tma2d_nohint(sb + OFF_W1 + 8192, &P.w1, FCH * cta, 256, BAR(BAR_W1));
        }
        if (u == 5) {
          mbar_expect(BAR(BAR_W2), 16384);
#pragma unroll 1
          for (int jj = 0; jj < 8; jj++) tma2d(sb + OFF_W2 + jj * 2048, &P.w2, jj * 64, FCH * cta, BAR(BAR_W2), pol);
        }
      };
      const int nunits = cta < NFF ? 6 : 4;
      mbar_wait(BAR(BAR_FULL + 31), 0);
      TL(41);
#pragma unroll 1
      for (int u = 0; u < nunits; u++) {
        if (u == 3) { mbar_wait(BAR(BAR_EMPTY + 2), 0); TL(26); }
        if (u > 0) mbar_wait(BAR(BAR_WUV + u - 1), 0);
        unit(u);
      }
    }
    return;
  }

  if (w == 10) {
    const int mo = 4 * cta + (g & 3);
    const int bp = 2 * (t & 1) + (t >> 1);
    const uint32_t epoch = __shfl_sync(~0u, epoch0, 0);
    if (lane == 0) { sts1(sb + OFF_EPOCH, epoch); mbar_arrive(BAR(BAR_EPOCH)); }
    const int par = epoch & 1;
    const uint32_t* MOD = gs->MOD[par];
    float xo0, xo1;
    {
      uint4 v[8];
      const uint32_t* p[8];
#pragma unroll
      for (int i = 0; i < 4; i++) { p[i] = MOD + (128 * jI + 32 * i + lane) * 4; p[4 + i] = MOD + (512 + 128 * jI + 32 * i + lane) * 4; }
#pragma unroll
      for (int i = 0; i < 8; i++) v[i] = ldg_rlx4(p[i]);
      mbar_wait(BAR(BAR_STATS), 0);
      TL(45);
      uint32_t xn[4][4];
      {
        float mu[8], rs[8];
#pragma unroll
        for (int bb = 0; bb < 8; bb++) { const float2 st = ldsf2(sb + OFF_STATS + bb * 8); mu[bb] = st.x; rs[bb] = st.y; }
#pragma unroll
        for (int i = 0; i < 4; i++)
#pragma unroll
          for (int k = 0; k < 4; k++) {
            const int m = 128 * jI + 32 * i + lane;
            xn[i][k] = pack_bf16((lds_bf16(xs_addr(sb + OFF_XS, 2 * k, m)) - mu[2 * k]) * rs[2 * k], (lds_bf16(xs_addr(sb + OFF_XS, 2 * k + 1, m)) - mu[2 * k + 1]) * rs[2 * k + 1]);
          }
        xo0 = lds_bf16(xs_addr(sb + OFF_XS, 2 * bp, mo)); xo1 = lds_bf16(xs_addr(sb + OFF_XS, 2 * bp + 1, mo));
      }
      TL(46);
      mbar_wait(BAR(BAR_P0E), 0);
      backoff(D_MOD);
      int it = 0;
      while (true) {
        bool all = true;
#pragma unroll
        for (int i = 0; i < 8; i++) all = all && ok4(v[i]);
        if (all) break;
#pragma unroll
        for (int i = 0; i < 8; i++) if (!ok4(v[i])) v[i] = ldg_rlx4(p[i]);
        if (++it > SPIN_LIMIT) __trap();
      }
      __syncwarp();
      TL(47);
#pragma unroll
      for (int i = 0; i < 4; i++) {
        uint4 o;
        o.x = hfma2(xn[i][0], hadd2(v[4 + i].x, ONE2), v[i].x); o.y = hfma2(xn[i][1], hadd2(v[4 + i].y, ONE2), v[i].y);
        o.z = hfma2(xn[i][2], hadd2(v[4 + i].z, ONE2), v[i].z); o.w = hfma2(xn[i][3], hadd2(v[4 + i].w, ONE2), v[i].w);
        sts4(sb + OFF_BS + (32 * i + lane) * 16, o);
      }
      __syncwarp();
      if (lane == 0) mbar_arrive(BAR(BAR_HOP));
      TL(31);
    }
    uint32_t ga2, gb2;
    {
      int it = 0;
      do { ga2 = ldg_rlx1(MOD + (1024 + mo) * 4 + bp); gb2 = ldg_rlx1(MOD + (2560 + mo) * 4 + bp); if (++it > SPIN_LIMIT) __trap(); } while (ga2 == 0 || gb2 == 0);
    }
    {
      const uint4 z = make_uint4(0, 0, 0, 0);
      uint4* x1 = reinterpret_cast<uint4*>(gs->X1 + cta * 8192);
#pragma unroll 1
      for (int i0 = 0; i0 < 64; i0 += CLR_B) {
#pragma unroll
        for (int i = 0; i < CLR_B; i++) stg4(x1 + (i0 + i) * 32 + lane, z);
        backoff(CLR_CLK);
      }
#pragma unroll
      for (int i = 0; i < 4; i++) stg4(reinterpret_cast<uint4*>(gs->X3A + cta * 512) + i * 32 + lane, z);
#pragma unroll
      for (int i = 0; i < 4; i++) stg4(reinterpret_cast<uint4*>(gs->X2 + cta * 512) + i * 32 + lane, z);
      backoff(CLR_CLK);
      stg4(reinterpret_cast<uint4*>(gs->X3B + (lane >> 2) * 2048 + cta * 16) + (lane & 3), z);
      uint4* x4 = reinterpret_cast<uint4*>(gs->X4 + cta * NFF * 16);
#pragma unroll
      for (int i = 0; i < NFF / 16; i++) stg4(x4 + i * 32 + lane, z);
      backoff(CLR_CLK);
#pragma unroll
      for (int i = NFF / 16; i < NFF / 8; i++) stg4(x4 + i * 32 + lane, z);
      backoff(CLR_CLK);
#pragma unroll
      for (int i = 0; i < 4; i++) stg4(reinterpret_cast<uint4*>(gs->QP[par ^ 1] + cta * 512) + i * 32 + lane, z);
#pragma unroll
      for (int i = 0; i < 4; i++) stg4(reinterpret_cast<uint4*>(gs->QX[par ^ 1] + cta * 512) + i * 32 + lane, z);
      if (lane < 24) stg4(reinterpret_cast<uint4*>(gs->MOD[par ^ 1] + cta * 96) + lane, z);
      if (lane < 16) stg4(reinterpret_cast<uint4*>(gs->ML + cta * 64) + lane, z);
      asm volatile("fence.acq_rel.gpu;" ::: "memory");
      __syncwarp();
      if (lane == 0) {
        asm volatile("red.relaxed.gpu.global.add.u32 [%0], 1;" ::"l"(&gs->cnt) : "memory");
        const uint32_t target = (epoch + 1) * NCTA;
        uint32_t c; int it = 0;
        do { asm volatile("ld.acquire.gpu.global.u32 %0, [%1];" : "=r"(c) : "l"(&gs->cnt) : "memory"); if (++it > SPIN_LIMIT) __trap(); } while ((int)(c - target) < 0);
        mbar_arrive(BAR(BAR_ALLCLR));
        TL(44);
      }
      __syncwarp();
    }
    {
      const uint32_t a0 = sb + OFF_LP + ((lane >> 1) & 3) * 32 + ((lane >> 3) * 2 + (lane & 1)) * 4;
      mbar_wait(BAR(BAR_ALLCLR), 0);
      mbar_wait(BAR(BAR_LP), 0);
      float l0 = 0.f, l1 = 0.f, l2 = 0.f, l3 = 0.f;
#pragma unroll
      for (int i = 0; i < 8; i++) { l0 += ldsf(a0 + (4 * i) * 128); l1 += ldsf(a0 + (4 * i + 1) * 128); l2 += ldsf(a0 + (4 * i + 2) * 128); l3 += ldsf(a0 + (4 * i + 3) * 128); }
      const uint32_t mw = __float_as_uint(ldsf(sb + OFF_RED + 512 + lane * 4)), lw = __float_as_uint((l0 + l1) + (l2 + l3));
      stg_u64(gs->ML + (lane * 128 + cta) * 2, mw, lw);
      TL(27);
    }
    float v0, v1;
    uint32_t* const x3o = pin(gs->X3B + (lane >> 2) * 2048 + (4 * cta + (lane & 3)) * 4);
    __nv_bfloat16* const fo = pin(gout + (2 * bp) * 512 + mo);
    mbar_wait(BAR(BAR_P5D), 0);
    backoff(D_X3A);
    sum_pieces<32, false>(gs->X3A + cta * 512, g, t, v0, v1);
    const uint32_t x2w = pack_bf16(xo0 + bf_lo(ga2) * v0, xo1 + bf_hi(ga2) * v1);
    {
      const int src = 4 * (lane & 3);
      uint4 o;
      o.x = __shfl_sync(~0u, x2w, src); o.y = __shfl_sync(~0u, x2w, src + 2); o.z = __shfl_sync(~0u, x2w, src + 1); o.w = __shfl_sync(~0u, x2w, src + 3);
      stg_u128(x3o, o);
    }
    TL(20);
    if (cta < NFF) { mbar_wait(BAR(BAR_P7D), 0); backoff(D_FIN); } else __nanosleep(1000);
    sum_pieces<NFF, true>(gs->X4 + cta * NFF * 16, g, t, v0, v1);
    if (g < 4) {
      fo[0] = __float2bfloat16(bf_lo(x2w) + bf_lo(gb2) * v0);
      fo[512] = __float2bfloat16(bf_hi(x2w) + bf_hi(gb2) * v1);
    }
    TL(23);
    if (cta == 0 && lane == 0) stg1(&gs->epoch, epoch + 1);
    return;
  }

  if (w == 9) {
    mbar_wait(BAR(BAR_EPOCH), 0);
    const int par = lds1(sb + OFF_EPOCH) & 1;
    {
      const uint32_t* pq = gs->QP[par] + ((hI * 4 + (lane & 3)) * 256 + (lane >> 2) * 32 + 31) * 2 + 1;
      const uint32_t* px = gs->QX[par] + bI * 8192 + lane * 256 + 63;
      uint32_t u = ldg_rlx1(pq);
      uint32_t x0 = ldg_rlx1(px), x1 = ldg_rlx1(px + 64), x2 = ldg_rlx1(px + 128), x3 = ldg_rlx1(px + 192);
      int it = 0;
      mbar_wait(BAR(BAR_P1E), 0);
      backoff(D_QP);
      while (!__all_sync(~0u, u != 0)) { if (u == 0) u = ldg_rlx1(pq); if (++it > SPIN_LIMIT) __trap(); }
      if (lane == 0) mbar_arrive(BAR(BAR_QPOK));
      TL(29);
      mbar_wait(BAR(BAR_P2E), 0);
      backoff(D_QX);
      uint32_t donemask = 0;
      while (true) {
        const uint32_t okm = __ballot_sync(~0u, x0 != 0 && x1 != 0 && x2 != 0 && x3 != 0);
        const uint32_t full = okm & (okm >> 1) & (okm >> 2) & (okm >> 3) & 0x11111111u;
        if (((full & ~donemask) >> lane) & 1) mbar_arrive(BAR(BAR_QXG + (lane >> 2)));
        donemask |= full;
        if (donemask == 0x11111111u) break;
        if (x0 == 0) x0 = ldg_rlx1(px);
        if (x1 == 0) x1 = ldg_rlx1(px + 64);
        if (x2 == 0) x2 = ldg_rlx1(px + 128);
        if (x3 == 0) x3 = ldg_rlx1(px + 192);
        if (++it > SPIN_LIMIT) __trap();
      }
    }
    if (cta < NFF) {
      const uint32_t* MOD = gs->MOD[par];
#pragma unroll 1
      for (int which = 0; which < 2; which++) {
        mbar_wait(BAR(BAR_EMPTY + 1 + which), 0);
        const uint32_t* src = MOD + ((which ? 1536 : 2048) + lane) * 4;
        const uint32_t dst = sb + (which ? OFF_SB : OFF_CB) + lane * 16;
        uint4 v[16];
        int it = 0;
        while (true) {
          uint32_t mn = 0xffffffffu;
#pragma unroll
          for (int i = 0; i < 16; i++) v[i] = ldg_rlx4(src + i * 128);
#pragma unroll
          for (int i = 0; i < 16; i++) mn = min(mn, min(min(v[i].x, v[i].y), min(v[i].z, v[i].w)));
          if (mn != 0) break;
          if (++it > SPIN_LIMIT) __trap();
        }
#pragma unroll
        for (int i = 0; i < 16; i++)
          sts4(dst + i * 512, which ? v[i] : make_uint4(hadd2(v[i].x, ONE2), hadd2(v[i].y, ONE2), hadd2(v[i].z, ONE2), hadd2(v[i].w, ONE2)));
      }
      __syncwarp();
      if (lane == 0) mbar_arrive(BAR(BAR_CBSB));
      TL(30);
    }
    return;
  }

  uint32_t cf[8];
  mbar_wait(BAR(BAR_XC), 0);
  {
    uint32_t r4[4];
    ldsm4(r4, sb + OFF_CS + w * 1024 + (lane & 7) * 128 + (((lane >> 3) ^ (lane & 7)) << 4));
    cf[0] = r4[0]; cf[1] = r4[1]; cf[2] = r4[2]; cf[3] = r4[3];
    ldsm4(r4, sb + OFF_CS + w * 1024 + (lane & 7) * 128 + (((4 + (lane >> 3)) ^ (lane & 7)) << 4));
    cf[4] = r4[0]; cf[5] = r4[1]; cf[6] = r4[2]; cf[7] = r4[3];
  }
  {
    const uint4 xr0 = lds4(sb + OFF_XS + (lane >> 3) * 1024 + w * 128 + (lane & 7) * 16);
    const uint4 xr1 = lds4(sb + OFF_XS + (4 + (lane >> 3)) * 1024 + w * 128 + (lane & 7) * 16);
    float v[16];
    const uint32_t u[8] = {xr0.x, xr0.y, xr0.z, xr0.w, xr1.x, xr1.y, xr1.z, xr1.w};
#pragma unroll
    for (int i = 0; i < 8; i++) { v[2 * i] = bf_lo(u[i]); v[2 * i + 1] = bf_hi(u[i]); }
    float s = 0.f;
#pragma unroll
    for (int i = 0; i < 16; i++) s += v[i];
#pragma unroll
    for (int o = 16; o; o >>= 1) s += __shfl_xor_sync(~0u, s, o);
    const float mu = s * (1.f / 512.f);
    float q = 0.f;
#pragma unroll
    for (int i = 0; i < 16; i++) { const float dlt = v[i] - mu; q += dlt * dlt; }
#pragma unroll
    for (int o = 16; o; o >>= 1) q += __shfl_xor_sync(~0u, q, o);
    if (lane == 0) { stsf(sb + OFF_STATS + w * 8, mu); stsf(sb + OFF_STATS + w * 8 + 4, rsqrtf(q * (1.f / 512.f) + 1e-5f)); mbar_arrive(BAR(BAR_STATS)); }
  }
#pragma unroll
  for (int i = 0; i < 8; i++) {
    const float a = bf_lo(cf[i]), b = bf_hi(cf[i]);
    cf[i] = pack_bf16(__fdividef(a, 1.f + __expf(-a)), __fdividef(b, 1.f + __expf(-b)));
  }
  TL(1);
  mbar_wait(BAR(BAR_EPOCH), 0);
  const int par = lds1(sb + OFF_EPOCH) & 1;
  uint32_t* const MOD = gs->MOD[par];
  uint32_t* const QP = gs->QP[par];
  uint32_t* const QX = gs->QX[par];

  asm volatile("cp.async.wait_group 0;" ::: "memory");
  cbar();
  mbar_wait(BAR(BAR_WMOD), 0);
  TL(2);
  {
    float d0[4] = {0.f, 0.f, 0.f, 0.f}, d1[4] = {0.f, 0.f, 0.f, 0.f}, d2[4] = {0.f, 0.f, 0.f, 0.f}, d3[4] = {0.f, 0.f, 0.f, 0.f};
    const int mi = lane >> 3, r = lane & 7;
    const uint32_t abase = sb + OFF_R0 + (64 * w + 8 * (mi >> 1) + r) * 48 + (mi & 1) * 16;
    uint32_t a[8][4];
#pragma unroll
    for (int ks = 0; ks < 4; ks++) { ldsm4t(a[2 * ks], abase + ks * 768); ldsm4t(a[2 * ks + 1], abase + ks * 768 + 32); }
#pragma unroll
    for (int ks = 0; ks < 4; ks++) {
      mma16816((ks & 1) ? d2 : d0, a[2 * ks], cf[2 * ks], cf[2 * ks + 1]);
      mma16816((ks & 1) ? d3 : d1, a[2 * ks + 1], cf[2 * ks], cf[2 * ks + 1]);
    }
#pragma unroll
    for (int i = 0; i < 4; i++) { d0[i] += d2[i]; d1[i] += d3[i]; }
    sts4f(sb + OFF_P0S + (w * 32 + lane) * 16, d0[0], d0[1], d0[2], d0[3]);
    asm volatile("st.shared.v2.f32 [%0], {%1,%2};" ::"r"(sb + OFF_P0S + 4096 + (w * 32 + lane) * 8), "f"(d1[0]), "f"(d1[1]) : "memory");
    cbar();
    if (w == 0) {
      float4 v[8], acc;
#pragma unroll
      for (int i = 0; i < 8; i++) v[i] = ldsf4(sb + OFF_P0S + (i * 32 + lane) * 16);
      acc.x = ((v[0].x + v[1].x) + (v[2].x + v[3].x)) + ((v[4].x + v[5].x) + (v[6].x + v[7].x));
      acc.y = ((v[0].y + v[1].y) + (v[2].y + v[3].y)) + ((v[4].y + v[5].y) + (v[6].y + v[7].y));
      acc.z = ((v[0].z + v[1].z) + (v[2].z + v[3].z)) + ((v[4].z + v[5].z) + (v[6].z + v[7].z));
      acc.w = ((v[0].w + v[1].w) + (v[2].w + v[3].w)) + ((v[4].w + v[5].w) + (v[6].w + v[7].w));
      const int n = 24 * cta + g;
      stg1(MOD + n * 4 + t, nz(pack_bf16(acc.x, acc.y)));
      stg1(MOD + (n + 8) * 4 + t, nz(pack_bf16(acc.z, acc.w)));
      if (lane == 0) mbar_arrive(BAR(BAR_P0E));
    } else if (w == 1) {
      float2 v[8], acc;
#pragma unroll
      for (int i = 0; i < 8; i++) v[i] = ldsf2(sb + OFF_P0S + 4096 + (i * 32 + lane) * 8);
      acc.x = ((v[0].x + v[1].x) + (v[2].x + v[3].x)) + ((v[4].x + v[5].x) + (v[6].x + v[7].x));
      acc.y = ((v[0].y + v[1].y) + (v[2].y + v[3].y)) + ((v[4].y + v[5].y) + (v[6].y + v[7].y));
      stg1(MOD + (24 * cta + 16 + g) * 4 + t, nz(pack_bf16(acc.x, acc.y)));
      if (lane == 0) mbar_arrive(BAR(BAR_P0E));
    }
  }
  TL(3);

  {
    uint32_t a[8][4];
    mbar_wait(BAR(BAR_WQ + (w >> 2)), 0);
    load_a_t(a, sb + OFF_R1, w, lane);
    __syncwarp();
    if (lane == 0) mbar_arrive(BAR(BAR_P1D));
    uint32_t* const qpo = pin(QP + (cta * 256 + tid) * 2);
    mbar_wait(BAR(BAR_HOP), 0);
    float d[4];
    mma128(d, a, sb + OFF_BS, lane);
    stg_u64(qpo, pack_bf16(d[0], d[1]), pack_bf16(d[2], d[3]));
    if (lane == 0) mbar_arrive(BAR(BAR_P1E));
  }
  TL(6);
  {
    uint32_t a[8][4];
    {
      const int mi = lane >> 3, r = lane & 7;
      const int row = 16 * w + 8 * (mi & 1) + r;
      mbar_wait(BAR(BAR_WUK), 0); mbar_wait(BAR(BAR_WUK + 1), 0);
#pragma unroll
      for (int ks = 0; ks < 8; ks++) {
        const int chunk = 2 * ks + (mi >> 1);
        ldsm4(a[ks], sb + OFF_R2 + (chunk >> 3) * 16384 + row * 128 + (((chunk & 7) ^ r) << 4));
      }
    }
    __syncwarp();
    if (lane == 0) mbar_arrive(BAR(BAR_P2D));
    TL(8);
    mbar_wait(BAR(BAR_QPOK), 0);
    sum4_to_smem(QP + (hI * 4 * 256 + tid) * 2, tid, sb + OFF_BS2 + (16 * w + g) * 16 + t * 4);
    TL(7);
    cbar();
    float d[4];
    mma128(d, a, sb + OFF_BS2, lane);
    const float sc = 0.08838834764831845f * 1.4426950408889634f;
    const uint32_t stg = sb + OFF_P0S + w * 256;
    stsm2t(stg + (lane & 7) * 32 + ((lane >> 3) & 1) * 16, pack_bf16(d[0] * sc, d[1] * sc), pack_bf16(d[2] * sc, d[3] * sc));
    __syncwarp();
    if (lane < 16) {
      const uint4 o = lds4(stg + lane * 16);
      stg_u128(QX + ((lane >> 1) * 32 + hI) * 256 + (128 * jI + 16 * w + 8 * (lane & 1)) / 2, o);
    }
    if (lane == 0) mbar_arrive(BAR(BAR_P2E));
  }
  TL(9);
  {
    const uint32_t* qx = QX + bI * 8192 + w * 1024 + lane * 4;
    mbar_wait(BAR(BAR_QXG + w), 0);
    TL(4);
    uint4 v[8];
#pragma unroll
    for (int i = 0; i < 8; i++) v[i] = ldg_u128(qx + i * 128);
    cbar();
    int it = 0;
    while (true) {
      bool all = true;
#pragma unroll
      for (int i = 0; i < 8; i++) all = all && v[i].w != 0;
      if (all) break;
#pragma unroll
      for (int i = 0; i < 8; i++) if (v[i].w == 0) v[i] = ldg_u128(qx + i * 128);
      if (++it > SPIN_LIMIT) __trap();
    }
    TL(5);
#pragma unroll
    for (int i = 0; i < 8; i++) {
      const int hh = 4 * w + (i >> 1), ch = 32 * (i & 1) + lane;
      sts4(sb + OFF_R0 + (ch >> 3) * 4096 + hh * 128 + (((ch & 7) ^ (hh & 7)) << 4), v[i]);
    }
    asm volatile("fence.proxy.async.shared::cta;" ::: "memory");
    cbar();
    if (tid == 0) mbar_arrive(BAR(BAR_GO));
  }

  TL(10);

  const int wg = w >> 2, wq = w & 3;
  float O[4][16];
#pragma unroll
  for (int i = 0; i < 4; i++)
#pragma unroll
    for (int k = 0; k < 16; k++) O[i][k] = 0.f;
  float m_run = -INFINITY;
  float mh[8], lpart[8];
#pragma unroll
  for (int i = 0; i < 8; i++) { lpart[i] = 0.f; mh[i] = -INFINITY; }
  uint32_t* const x1o = gs->X1 + ((2 * t * 4 + 2 * wg) * 128 + cta) * 64 + (wq * 8 + g) * 2;

  auto tile = [&](const int tl, auto last_c) {
    constexpr bool LAST = decltype(last_c)::value;
    const int buf = tl & 1;
    const uint32_t pt = sb + OFF_PT + buf * 4096;
    const uint32_t al = sb + OFF_ALPHA + buf * 128;
    const uint32_t dq = desc_lo(sb + OFF_R0), dpt = desc_lo(pt);
    uint32_t dbx[8];
#pragma unroll
    for (int jj = 0; jj < 8; jj++) dbx[jj] = desc_lo(sb + c_box[tl * 8 + jj]);
    float alpha[8];
    float S[16];
    CLK_DECL;
    CLK(0);
    if (wg == 0) {
      float S2[16];
      if constexpr (LAST) {
#pragma unroll
        for (int jj = 0; jj < 8; jj++) {
          mbar_wait(BAR(BAR_FULL + tl * 8 + jj), 0);
          wg_fence();
#pragma unroll
          for (int ks = 0; ks < 4; ks += 2) {
            wgmma_n32<0>(S, dbx[jj] + ks * 2, dq + (jj * 4096 + ks * 32) / 16, (jj | ks) != 0);
            wgmma_n32<0>(S2, dbx[jj] + ks * 2 + 2, dq + (jj * 4096 + ks * 32 + 32) / 16, (jj | ks) != 0);
          }
          wg_commit();
        }
      } else {
#pragma unroll
        for (int jj = 0; jj < 8; jj++) mbar_wait(BAR(BAR_FULL + tl * 8 + jj), 0);
        wg_fence();
#pragma unroll
        for (int jj = 0; jj < 8; jj++)
#pragma unroll
          for (int ks = 0; ks < 4; ks += 2) {
            wgmma_n32<0>(S, dbx[jj] + ks * 2, dq + (jj * 4096 + ks * 32) / 16, (jj | ks) != 0);
            wgmma_n32<0>(S2, dbx[jj] + ks * 2 + 2, dq + (jj * 4096 + ks * 32 + 32) / 16, (jj | ks) != 0);
          }
        wg_commit();
      }
      CLK(1);
      wg_wait0();
#pragma unroll
      for (int i = 0; i < 16; i++) S[i] += S2[i];
      CLK(2);
      if (LAST) TL(11);
    }
    auto write_p = [&](const float (&S)[16], float (&ps)[8]) {
      uint32_t pk[8];
#pragma unroll
      for (int jn = 0; jn < 4; jn++) {
        const float p0 = ex2(S[4 * jn] - mh[2 * jn]), p1 = ex2(S[4 * jn + 1] - mh[2 * jn + 1]);
        const float p2 = ex2(S[4 * jn + 2] - mh[2 * jn]), p3 = ex2(S[4 * jn + 3] - mh[2 * jn + 1]);
        ps[2 * jn] = p0 + p2; ps[2 * jn + 1] = p1 + p3;
        pk[2 * jn] = pack_bf16(p0, p1);
        pk[2 * jn + 1] = pack_bf16(p2, p3);
      }
      const int mi = lane >> 3, r = lane & 7;
#pragma unroll
      for (int hf = 0; hf < 2; hf++) {
        const int head = 8 * (2 * hf + (mi >> 1)) + r;
        const int kc = 2 * wq + (mi & 1);
        stsm4t(pt + head * 128 + ((kc ^ (head & 7)) << 4), pk[4 * hf], pk[4 * hf + 1], pk[4 * hf + 2], pk[4 * hf + 3]);
      }
      asm volatile("fence.proxy.async.shared::cta;" ::: "memory");
    };
    auto write_l = [&](const float (&ps)[8]) {
      mbar_wait(BAR(BAR_EMPTY + 2), 0);
      sts4f(sb + OFF_LP + tid * 32, lpart[0] + ps[0], lpart[1] + ps[1], lpart[2] + ps[2], lpart[3] + ps[3]);
      sts4f(sb + OFF_LP + tid * 32 + 16, lpart[4] + ps[4], lpart[5] + ps[5], lpart[6] + ps[6], lpart[7] + ps[7]);
      if (wq == 0) stsf(sb + OFF_RED + 512 + lane * 4, m_run);
    };
    float ps[8];
    float ex = INFINITY;
    if (wg == 0 && tl > 0) {
      float x8[8];
#pragma unroll
      for (int i = 0; i < 8; i++) x8[i] = fmaxf(S[4 * (i >> 1) + (i & 1)], S[4 * (i >> 1) + 2 + (i & 1)]) - mh[i];
      ex = fmaxf(fmaxf(fmaxf(x8[0], x8[1]), fmaxf(x8[2], x8[3])), fmaxf(fmaxf(x8[4], x8[5]), fmaxf(x8[6], x8[7])));
      write_p(S, ps);
      if constexpr (LAST) write_l(ps);
    }
    uint32_t over;
    asm volatile("{\n.reg .pred p, q;\nsetp.leu.f32 p, %1, 0f41F00000;\nnot.pred p, p;\nsetp.ne.and.u32 p, %2, 0, p;\n"
                 "barrier.cta.red.or.aligned.pred q, 1, 256, p;\nselp.u32 %0, 1, 0, q;\n}" : "=r"(over) : "f"(ex), "r"(wg == 0 ? 1 : 0) : "memory");
    if (over) {
      if (wg == 0) {
        float mx[8];
#pragma unroll
        for (int jn = 0; jn < 4; jn++) { mx[2 * jn] = fmaxf(S[4 * jn], S[4 * jn + 2]); mx[2 * jn + 1] = fmaxf(S[4 * jn + 1], S[4 * jn + 3]); }
        float a4[4], a2[2], a1;
        {
          const bool up = lane & 16;
#pragma unroll
          for (int i = 0; i < 4; i++) { const float send = up ? mx[i] : mx[4 + i]; const float keep = up ? mx[4 + i] : mx[i]; a4[i] = fmaxf(keep, __shfl_xor_sync(~0u, send, 16)); }
        }
        {
          const bool up = lane & 8;
#pragma unroll
          for (int i = 0; i < 2; i++) { const float send = up ? a4[i] : a4[2 + i]; const float keep = up ? a4[2 + i] : a4[i]; a2[i] = fmaxf(keep, __shfl_xor_sync(~0u, send, 8)); }
        }
        {
          const bool up = lane & 4;
          const float send = up ? a2[0] : a2[1]; const float keep = up ? a2[1] : a2[0];
          a1 = fmaxf(keep, __shfl_xor_sync(~0u, send, 4));
        }
        const int vidx = ((lane >> 4) & 1) * 4 + ((lane >> 3) & 1) * 2 + ((lane >> 2) & 1);
        const int myhead = 8 * (vidx >> 1) + 2 * t + (vidx & 1);
        stsf(sb + OFF_RED + (wq * 32 + myhead) * 4, a1);
        bar_sync(2, 128);
        const float mt = fmaxf(fmaxf(ldsf(sb + OFF_RED + lane * 4), ldsf(sb + OFF_RED + 128 + lane * 4)),
                               fmaxf(ldsf(sb + OFF_RED + 256 + lane * 4), ldsf(sb + OFF_RED + 384 + lane * 4)));
        const float m_new = fmaxf(m_run, mt);
        const float al_l = ex2(m_run - m_new);
        m_run = m_new;
        if (wq == 0) stsf(al + lane * 4, al_l);
#pragma unroll
        for (int i = 0; i < 8; i++) {
          const int hh = 8 * (i >> 1) + 2 * t + (i & 1);
          mh[i] = __shfl_sync(~0u, m_new, hh);
          alpha[i] = __shfl_sync(~0u, al_l, hh);
          lpart[i] *= alpha[i];
        }
        write_p(S, ps);
        if constexpr (LAST) write_l(ps);
      }
      cbar();
      if (wg == 1) {
#pragma unroll
        for (int jn = 0; jn < 4; jn++) { const float2 a = ldsf2(al + (8 * jn + 2 * t) * 4); alpha[2 * jn] = a.x; alpha[2 * jn + 1] = a.y; }
      }
    }
    const bool resc = over && tl > 0;
    if (wg == 0) {
      if constexpr (LAST) {
        if (tid == 0) mbar_arrive(BAR(BAR_LP));
      } else {
#pragma unroll
        for (int i = 0; i < 8; i++) lpart[i] += ps[i];
      }
    } else {
#pragma unroll
      for (int jj = 4; jj < 8; jj++) mbar_wait(BAR(BAR_FULL + tl * 8 + jj), 0);
    }
    if (resc) {
#pragma unroll
      for (int mb = 0; mb < 4; mb++)
#pragma unroll
        for (int jn = 0; jn < 4; jn++) {
          O[mb][4 * jn] *= alpha[2 * jn]; O[mb][4 * jn + 1] *= alpha[2 * jn + 1];
          O[mb][4 * jn + 2] *= alpha[2 * jn]; O[mb][4 * jn + 3] *= alpha[2 * jn + 1];
        }
    }
    CLK(7);
    wg_fence();
#pragma unroll
    for (int mp = 0; mp < 4; mp += 2) {
#pragma unroll
      for (int ks = 0; ks < 4; ks++) {
        wgmma_n32<1>(O[mp], (wg ? dbx[4 + mp] : dbx[mp]) + ks * 128, dpt + ks * 2, 1);
        wgmma_n32<1>(O[mp + 1], (wg ? dbx[5 + mp] : dbx[mp + 1]) + ks * 128, dpt + ks * 2, 1);
      }
      wg_commit();
    }
    CLK(8);
    if constexpr (LAST) {
      mbar_wait(BAR(BAR_ALLCLR), 0);
      asm volatile("wgmma.wait_group.sync.aligned 1;" ::: "memory");
#pragma unroll
      for (int e = 0; e < 2; e++)
        stg_u64(x1o + ((e * 4) * 128) * 64, pack_bf16(O[0][e], O[0][2 + e]), pack_bf16(O[1][e], O[1][2 + e]));
    }
    wg_wait0();
    CLK(9);
    if (lane == 0) mbar_arrive(BAR(BAR_EMPTY + tl));
  };
#pragma unroll 1
  for (int tl = 0; tl < 3; tl++) tile(tl, BoolC<false>{});
  tile(3, BoolC<true>{});
  TL(12);
#pragma unroll
  for (int jn = 0; jn < 4; jn++)
#pragma unroll
    for (int jj = (jn == 0 ? 1 : 0); jj < 2; jj++)
#pragma unroll
      for (int e = 0; e < 2; e++)
        stg_u64(x1o + (((8 * jn + e) * 4 + jj) * 128) * 64, pack_bf16(O[2 * jj][4 * jn + e], O[2 * jj][4 * jn + 2 + e]),
                pack_bf16(O[2 * jj + 1][4 * jn + e], O[2 * jj + 1][4 * jn + 2 + e]));
  TL(13);

  uint32_t aw[8][4];
  {
    const uint32_t* pm = gs->ML + (hI * 128 + w * 16 + t) * 2;
    const uint32_t* px = gs->X1 + (cta * 128 + w * 16 + t) * 64 + 4 * g;
    uint2 ml[4];
    uint4 v[8];
    backoff(X1_D0 + (hI >> 3) * X1_DQ);
#pragma unroll
    for (int i = 0; i < 4; i++) ml[i] = ldg_u64(pm + i * 8);
#pragma unroll
    for (int i = 0; i < 4; i++) { v[2 * i] = ldg_2u64(px + i * 256); v[2 * i + 1] = ldg_2u64(px + i * 256 + 32); }
    uint32_t bh[4][2], bl[4][2];
    float ew[4];
    {
      int it = 0;
      while (!__all_sync(~0u, ml[0].y != 0 && ml[1].y != 0 && ml[2].y != 0 && ml[3].y != 0)) {
#pragma unroll
        for (int i = 0; i < 4; i++) if (ml[i].y == 0) ml[i] = ldg_u64(pm + i * 8);
        if (++it > SPIN_LIMIT) __trap();
      }
      if (w == 0) TL(14);
      float M = fmaxf(fmaxf(__uint_as_float(ml[0].x), __uint_as_float(ml[1].x)), fmaxf(__uint_as_float(ml[2].x), __uint_as_float(ml[3].x)));
      M = fmaxf(M, __shfl_xor_sync(~0u, M, 1)); M = fmaxf(M, __shfl_xor_sync(~0u, M, 2));
#pragma unroll
      for (int i = 0; i < 4; i++) {
        const float a = ew[i] = ex2(__uint_as_float(ml[i].x) - M);
        const uint32_t hi = pack_bf16(a, 0.f), lo = pack_bf16(a - bf_lo(hi), 0.f);
        asm("shl.b32 %0, %1, %2;" : "=r"(bh[i][0]) : "r"(hi), "r"(16 * g));
        asm("shl.b32 %0, %1, %2;" : "=r"(bh[i][1]) : "r"(hi), "r"(16 * g - 32));
        asm("shl.b32 %0, %1, %2;" : "=r"(bl[i][0]) : "r"(lo), "r"(16 * g));
        asm("shl.b32 %0, %1, %2;" : "=r"(bl[i][1]) : "r"(lo), "r"(16 * g - 32));
      }
    }
    uint32_t* const x2o = pin(gs->X2 + (cta * 256 + tid) * 2);
    mbar_wait(BAR(BAR_WUV + (w >> 2)), 0);
    load_a_t(aw, sb + OFF_WUV, w, lane);
    int it = 0;
    while (true) {
      bool all = true;
#pragma unroll
      for (int i = 0; i < 8; i++) all = all && v[i].y != 0 && v[i].w != 0;
      if (all) break;
#pragma unroll
      for (int i = 0; i < 8; i++) if (v[i].y == 0 || v[i].w == 0) v[i] = ldg_2u64(px + (i >> 1) * 256 + (i & 1) * 32);
      if (++it > SPIN_LIMIT) __trap();
    }
    __syncwarp();
    if (w == 0) TL(15);
    float dd[2][2][2][4];
#pragma unroll
    for (int i = 0; i < 8; i++) dd[i >> 2][(i >> 1) & 1][i & 1][0] = dd[i >> 2][(i >> 1) & 1][i & 1][1] = dd[i >> 2][(i >> 1) & 1][i & 1][2] = dd[i >> 2][(i >> 1) & 1][i & 1][3] = 0.f;
#pragma unroll
    for (int i = 0; i < 4; i++)
#pragma unroll
      for (int hf = 0; hf < 2; hf++) {
        const uint32_t a[4] = {v[2 * i + hf].x, v[2 * i + hf].y, v[2 * i + hf].z, v[2 * i + hf].w};
        mma16816(dd[hf][0][i & 1], a, bh[i][0], bh[i][1]);
        mma16816(dd[hf][1][i & 1], a, bl[i][0], bl[i][1]);
      }
    float L = (ew[0] * __uint_as_float(ml[0].y) + ew[1] * __uint_as_float(ml[1].y)) + (ew[2] * __uint_as_float(ml[2].y) + ew[3] * __uint_as_float(ml[3].y));
    L += __shfl_xor_sync(~0u, L, 1); L += __shfl_xor_sync(~0u, L, 2);
    const float inv = __fdividef(1.f, L);
    float d[2][4];
#pragma unroll
    for (int hf = 0; hf < 2; hf++)
#pragma unroll
      for (int k = 0; k < 4; k++) d[hf][k] = ((dd[hf][0][0][k] + dd[hf][0][1][k]) + (dd[hf][1][0][k] + dd[hf][1][1][k])) * inv;
    uint32_t ow[2][2];
#pragma unroll
    for (int hf = 0; hf < 2; hf++)
#pragma unroll
      for (int e = 0; e < 2; e++) {
        const float k0 = d[hf][e], k1 = d[hf][2 + e];
        const float keep = (t & 1) ? k1 : k0, send = (t & 1) ? k0 : k1;
        const float recv = __shfl_xor_sync(~0u, send, 1);
        ow[e][hf] = (t & 1) ? pack_bf16(recv, keep) : pack_bf16(keep, recv);
      }
    mbar_wait(BAR(BAR_EMPTY + 3), 0);
    if (t < 2) {
      const uint32_t base = sb + OFF_BS4 + w * 272 + (64 * t + 16 * (g >> 2) + 2 * (g & 3)) * 2;
      sts1(base, ow[0][0]); sts1(base + 64, ow[0][1]);
      sts1(base + 16, ow[1][0]); sts1(base + 80, ow[1][1]);
    }
    cbar();
    TL(16);
    float o[4][4] = {{0.f, 0.f, 0.f, 0.f}, {0.f, 0.f, 0.f, 0.f}, {0.f, 0.f, 0.f, 0.f}, {0.f, 0.f, 0.f, 0.f}};
    uint32_t b[4][4];
#pragma unroll
    for (int kk = 0; kk < 4; kk++) ldsm4(b[kk], sb + OFF_BS4 + (lane & 7) * 272 + (4 * kk + (lane >> 3)) * 16);
#pragma unroll
    for (int kk = 0; kk < 4; kk++) { mma16816(o[(2 * kk) & 3], aw[2 * kk], b[kk][0], b[kk][1]); mma16816(o[(2 * kk + 1) & 3], aw[2 * kk + 1], b[kk][2], b[kk][3]); }
    stg_u64(x2o, pack_bf16((o[0][0] + o[1][0]) + (o[2][0] + o[3][0]), (o[0][1] + o[1][1]) + (o[2][1] + o[3][1])),
            pack_bf16((o[0][2] + o[1][2]) + (o[2][2] + o[3][2]), (o[0][3] + o[1][3]) + (o[2][3] + o[3][3])));
  }
  TL(17);
  {
    mbar_wait(BAR(BAR_WO + (w >> 2)), 0);
    load_a_t(aw, sb + ((w >> 2) ? OFF_WO1 - 16384 : OFF_WO0), w, lane);
    const int m = 128 * jI + 16 * w + g;
    uint32_t* const o = pin(gs->X3A + ((m >> 2) * 32 + hI) * 16 + (m & 3) * 4 + t);
    const uint32_t* const x2i = pin(gs->X2 + (hI * 4 * 256 + tid) * 2);
    backoff(D_X2);
    sum4_to_smem(x2i, tid, sb + OFF_BS5 + (16 * w + g) * 16 + t * 4);
    cbar();
    TL(18);
    float d[4];
    mma128(d, aw, sb + OFF_BS5, lane);
    stg1(o, nz(pack_bf16(d[0], d[1])));
    stg1(o + 2 * 32 * 16, nz(pack_bf16(d[2], d[3])));
    if (lane == 0) mbar_arrive(BAR(BAR_P5D));
  }
  TL(19);
  if (cta < NFF) {
    const int mi = lane >> 3, r = lane & 7;
    uint32_t a1[4][4], a2[4][4];
    mbar_wait(BAR(BAR_W1), 0);
#pragma unroll
    for (int ks = 0; ks < 4; ks++) ldsm4t(a1[ks], sb + OFF_W1 + (64 * w + 16 * ks + 8 * (mi >> 1) + r) * 32 + (mi & 1) * 16);
    mbar_wait(BAR(BAR_CBSB), 0);
    {
      float u[4] = {0.f, 0.f, 0.f, 0.f}, vv[4] = {0.f, 0.f, 0.f, 0.f};
#pragma unroll
      for (int kk = 0; kk < 2; kk++) {
        uint32_t bc[4], bs[4];
        ldsm4t(bc, sb + OFF_CB + (64 * w + 32 * kk + lane) * 16);
        ldsm4t(bs, sb + OFF_SB + (64 * w + 32 * kk + lane) * 16);
        mma16816(u, a1[2 * kk], bc[0], bc[1]); mma16816(vv, a1[2 * kk], bs[0], bs[1]);
        mma16816(u, a1[2 * kk + 1], bc[2], bc[3]); mma16816(vv, a1[2 * kk + 1], bs[2], bs[3]);
      }
      sts4f(sb + OFF_REDU + (w * 32 + lane) * 16, u[0], u[1], u[2], u[3]);
      sts4f(sb + OFF_REDV + (w * 32 + lane) * 16, vv[0], vv[1], vv[2], vv[3]);
    }
    const int m0 = 64 * w + lane, m1 = m0 + 32;
    const uint4 c0 = lds4(sb + OFF_CB + m0 * 16), c1 = lds4(sb + OFF_CB + m1 * 16);
    cbar();
    const int lp = (tid >> 2) & 31, kq = tid & 3;
    const int fo = (lp >> 2) + 8 * (kq >> 1), bo = 2 * (lp & 3) + (kq & 1);
    float U = 0.f, V = 0.f;
    if (tid < 128) {
#pragma unroll
      for (int i = 0; i < 8; i++) { U += ldsf(sb + OFF_REDU + i * 512 + tid * 4); V += ldsf(sb + OFF_REDV + i * 512 + tid * 4); }
    }
    mbar_wait(BAR(BAR_W2), 0);
#pragma unroll
    for (int mb = 0; mb < 4; mb++) {
      const int f = 8 * (mi >> 1) + r;
      ldsm4t(a2[mb], sb + OFF_W2 + w * 2048 + f * 128 + (((2 * mb + (mi & 1)) ^ r) << 4));
    }
    const uint32_t* xb = pin(gs->X3B + (cta & (NREP - 1)) * 2048 + (64 * w + lane) * 4);
    uint32_t* const ox = pin(gs->X4 + (((64 * w + lane) >> 2) * NFF + cta) * 16 + (lane & 3) * 4);
    uint4 x0 = ldg_u128(xb), x1 = ldg_u128(xb + 128);
    {
      int it = 0;
      while (x0.w == 0 || x1.w == 0) {
        if (x0.w == 0) x0 = ldg_u128(xb);
        if (x1.w == 0) x1 = ldg_u128(xb + 128);
        if (++it > SPIN_LIMIT) __trap();
      }
    }
    TL(21);
    sts4(sb + OFF_BSX + m0 * 16, x0);
    sts4(sb + OFF_BSX + m1 * 16, x1);
    sts4(sb + OFF_BSY + m0 * 16, make_uint4(hmul2(x0.x, c0.x), hmul2(x0.y, c0.y), hmul2(x0.z, c0.z), hmul2(x0.w, c0.w)));
    sts4(sb + OFF_BSY + m1 * 16, make_uint4(hmul2(x1.x, c1.x), hmul2(x1.y, c1.y), hmul2(x1.z, c1.z), hmul2(x1.w, c1.w)));
    __syncwarp();
    float G[4][4] = {{0.f, 0.f, 0.f, 0.f}, {0.f, 0.f, 0.f, 0.f}, {0.f, 0.f, 0.f, 0.f}, {0.f, 0.f, 0.f, 0.f}};
    float S[4][4] = {{0.f, 0.f, 0.f, 0.f}, {0.f, 0.f, 0.f, 0.f}, {0.f, 0.f, 0.f, 0.f}, {0.f, 0.f, 0.f, 0.f}};
    {
      uint32_t bx[2][4], by[2][4];
#pragma unroll
      for (int kk = 0; kk < 2; kk++) { ldsm4t(by[kk], sb + OFF_BSY + (64 * w + 32 * kk + lane) * 16); ldsm4t(bx[kk], sb + OFF_BSX + (64 * w + 32 * kk + lane) * 16); }
#pragma unroll
      for (int kk = 0; kk < 2; kk++) {
        mma16816(G[2 * kk], a1[2 * kk], by[kk][0], by[kk][1]); mma16816(G[2 * kk + 1], a1[2 * kk + 1], by[kk][2], by[kk][3]);
        const uint32_t s0[4] = {bx[kk][0], ONE2, bx[kk][1], ONE2}, s1[4] = {bx[kk][2], ONE2, bx[kk][3], ONE2};
        mma16816(S[2 * kk], s0, bx[kk][0], bx[kk][1]); mma16816(S[2 * kk + 1], s1, bx[kk][2], bx[kk][3]);
      }
    }
    sts4f(sb + OFF_REDG + (w * 32 + lane) * 16, (G[0][0] + G[1][0]) + (G[2][0] + G[3][0]), (G[0][1] + G[1][1]) + (G[2][1] + G[3][1]),
          (G[0][2] + G[1][2]) + (G[2][2] + G[3][2]), (G[0][3] + G[1][3]) + (G[2][3] + G[3][3]));
    sts4f(sb + OFF_REDS + (w * 32 + lane) * 16, (S[0][0] + S[1][0]) + (S[2][0] + S[3][0]), (S[0][1] + S[1][1]) + (S[2][1] + S[3][1]),
          (S[0][2] + S[1][2]) + (S[2][2] + S[3][2]), (S[0][3] + S[1][3]) + (S[2][3] + S[3][3]));
    cbar();
    if (tid < 128) {
      float gv[8], sv1[8], sv2[8];
      const uint32_t o1 = sb + OFF_REDS + (bo >> 1) * 16 + (2 + (bo & 1)) * 4;
      const uint32_t o2 = sb + OFF_REDS + (4 * bo + (bo >> 1)) * 16 + (bo & 1) * 4;
#pragma unroll
      for (int i = 0; i < 8; i++) { gv[i] = ldsf(sb + OFF_REDG + i * 512 + tid * 4); sv1[i] = ldsf(o1 + i * 512); sv2[i] = ldsf(o2 + i * 512); }
      const float gs = ((gv[0] + gv[1]) + (gv[2] + gv[3])) + ((gv[4] + gv[5]) + (gv[6] + gv[7]));
      const float s1 = ((sv1[0] + sv1[1]) + (sv1[2] + sv1[3])) + ((sv1[4] + sv1[5]) + (sv1[6] + sv1[7]));
      const float s2 = ((sv2[0] + sv2[1]) + (sv2[2] + sv2[3])) + ((sv2[4] + sv2[5]) + (sv2[6] + sv2[7]));
      const float mu = s1 * (1.f / 512.f);
      const float rs = rsqrtf(fmaxf(s2 * (1.f / 512.f) - mu * mu, 0.f) + 1e-5f);
      const float hv = fmaxf(rs * (gs - mu * U) + V, 0.f);
      asm volatile("st.shared.u16 [%0], %1;" ::"r"(sb + OFF_H1 + fo * 16 + bo * 2), "h"(__bfloat16_as_ushort(__float2bfloat16(hv))) : "memory");
    }
    cbar();
    uint32_t b0, b1;
    ldsm2t(b0, b1, sb + OFF_H1 + (lane & 15) * 16);
    uint32_t pk[8];
#pragma unroll
    for (int mb = 0; mb < 4; mb++) {
      float o[4] = {0.f, 0.f, 0.f, 0.f};
      mma16816(o, a2[mb], b0, b1);
      pk[2 * mb] = pack_bf16(o[0], o[1]); pk[2 * mb + 1] = pack_bf16(o[2], o[3]);
    }
    const uint32_t st7 = sb + OFF_ST7 + w * 1024;
    stsm4(st7 + lane * 16, pk[0], pk[1], pk[2], pk[3]);
    stsm4(st7 + (32 + lane) * 16, pk[4], pk[5], pk[6], pk[7]);
    __syncwarp();
    const uint4 o0 = lds4(st7 + lane * 16), o1v = lds4(st7 + (32 + lane) * 16);
    stg_u128(ox, o0);
    stg_u128(ox + 8 * NFF * 16, o1v);
    if (lane == 0) mbar_arrive(BAR(BAR_P7D));
    TL(22);
  }
}

typedef CUresult (*EncodeTiledFn)(CUtensorMap*, CUtensorMapDataType, cuuint32_t, void*, const cuuint64_t*, const cuuint64_t*,
                                  const cuuint32_t*, const cuuint32_t*, CUtensorMapInterleave, CUtensorMapSwizzle,
                                  CUtensorMapL2promotion, CUtensorMapFloatOOBfill);

void make_map(EncodeTiledFn enc, CUtensorMap* m, const void* base, uint64_t cols, uint64_t rows, uint32_t bc, uint32_t br,
              CUtensorMapSwizzle sw, CUtensorMapL2promotion promo) {
  cuuint64_t dims[2] = {cols, rows};
  cuuint64_t strides[1] = {cols * 2};
  cuuint32_t box[2] = {bc, br};
  cuuint32_t es[2] = {1, 1};
  enc(m, CU_TENSOR_MAP_DATA_TYPE_BFLOAT16, 2, const_cast<void*>(base), dims, strides, box, es, CU_TENSOR_MAP_INTERLEAVE_NONE, sw, promo,
      CU_TENSOR_MAP_FLOAT_OOB_FILL_NONE);
}

}

extern "C" void kernel_launch(void* const* d_in, const int* in_sizes, int n_in, void* d_out, int out_size) {
  (void)in_sizes; (void)n_in; (void)out_size;
  static EncodeTiledFn enc = nullptr;
  static Scratch* scratch = nullptr;
  if (!enc) {
    void* sp = nullptr;
    cudaGetSymbolAddress(&sp, g_s);
    scratch = (Scratch*)sp;
    void* fn = nullptr;
    cudaDriverEntryPointQueryResult q;
    cudaGetDriverEntryPoint("cuTensorMapEncodeTiled", &fn, cudaEnableDefault, &q);
    enc = (EncodeTiledFn)fn;
    cudaFuncSetAttribute(fused_decode_kernel, cudaFuncAttributeMaxDynamicSharedMemorySize, SMEM_BYTES);
  }
  Params P;
  for (int i = 0; i < 2; i++) {
    cuuint64_t dims[3] = {64, 8, 8};
    cuuint64_t strides[2] = {1024, 128};
    cuuint32_t box[3] = {64, 8, 8};
    cuuint32_t es[3] = {1, 1, 1};
    enc(i ? &P.cm : &P.xm, CU_TENSOR_MAP_DATA_TYPE_BFLOAT16, 3, d_in[i ? 9 : 0], dims, strides, box, es, CU_TENSOR_MAP_INTERLEAVE_NONE,
        CU_TENSOR_MAP_SWIZZLE_128B, CU_TENSOR_MAP_L2_PROMOTION_NONE, CU_TENSOR_MAP_FLOAT_OOB_FILL_NONE);
  }
  make_map(enc, &P.ckv, d_in[1], 512, 8 * 4096, 64, 64, CU_TENSOR_MAP_SWIZZLE_128B, CU_TENSOR_MAP_L2_PROMOTION_NONE);
  make_map(enc, &P.wq, d_in[2], 4096, 512, 64, 128, CU_TENSOR_MAP_SWIZZLE_128B, CU_TENSOR_MAP_L2_PROMOTION_NONE);
  make_map(enc, &P.wuk, d_in[3], 4096, 512, 64, 128, CU_TENSOR_MAP_SWIZZLE_128B, CU_TENSOR_MAP_L2_PROMOTION_NONE);
  make_map(enc, &P.wuv, d_in[4], 4096, 512, 64, 128, CU_TENSOR_MAP_SWIZZLE_128B, CU_TENSOR_MAP_L2_PROMOTION_NONE);
  make_map(enc, &P.wo, d_in[5], 512, 4096, 64, 128, CU_TENSOR_MAP_SWIZZLE_128B, CU_TENSOR_MAP_L2_PROMOTION_NONE);
  make_map(enc, &P.w1, d_in[7], 1792, 512, FCH, 256, CU_TENSOR_MAP_SWIZZLE_NONE, CU_TENSOR_MAP_L2_PROMOTION_L2_128B);
  make_map(enc, &P.w2, d_in[8], 512, 1792, 64, FCH, CU_TENSOR_MAP_SWIZZLE_128B, CU_TENSOR_MAP_L2_PROMOTION_NONE);
  make_map(enc, &P.wmod, d_in[10], 3072, 512, 24, 256, CU_TENSOR_MAP_SWIZZLE_NONE, CU_TENSOR_MAP_L2_PROMOTION_L2_128B);
  fused_decode_kernel<<<NCTA, NTHREADS, SMEM_BYTES>>>((__nv_bfloat16*)d_out, scratch, (const uint8_t*)d_in[10], P);
}
```

```cpp
#include <cuda_runtime.h>
#include <cuda.h>
#include <cuda_bf16.h>
#include <stdint.h>
#define V4 1

namespace {

constexpr int NCTA = 128;
constexpr int NTHREADS = 320;
constexpr int FCH = 16;
constexpr int NFF = 1792 / FCH;
constexpr int NREP = 8;

constexpr uint32_t OFF_RING = 0;
constexpr uint32_t OFF_WUK = 131072;
constexpr uint32_t OFF_WQ = 131072 + 32768;
constexpr uint32_t OFF_WM2 = 131072 + 49152;
constexpr uint32_t OFF_WUV = 131072;
constexpr uint32_t OFF_WO = 131072 + 32768;
constexpr uint32_t OFF_W1 = 0;
constexpr uint32_t OFF_W2 = 16384;
constexpr uint32_t OFF_Q = 196608;
constexpr uint32_t OFF_PT = 212992;
constexpr uint32_t OFF_SCR = 217088;
constexpr uint32_t OFF_XS = 65536;
constexpr uint32_t OFF_CS = 65536 + 8192;
constexpr uint32_t OFF_P0S = 65536 + 16384;
constexpr uint32_t OFF_BS1 = OFF_SCR + 2048;
constexpr uint32_t OFF_BS2 = OFF_SCR + 4096;
constexpr uint32_t OFF_P0B = OFF_SCR + 6144;
constexpr uint32_t OFF_XN = OFF_SCR + 8192;
constexpr uint32_t OFF_RED = OFF_SCR + 10496;
constexpr uint32_t OFF_REDL = OFF_SCR + 10752;
constexpr uint32_t OFF_MH = OFF_SCR + 11008;
constexpr uint32_t OFF_ALPHA = OFF_SCR + 11072;
constexpr uint32_t OFF_BARS = OFF_SCR + 11264;
constexpr uint32_t SMEM_BYTES = OFF_BARS + 512;
constexpr uint32_t OFF_BS4 = OFF_Q;
constexpr uint32_t OFF_H1 = OFF_Q + 2304;
constexpr uint32_t OFF_REDS = OFF_Q + 2560;
constexpr uint32_t OFF_BS5 = OFF_Q + 4096;
constexpr uint32_t OFF_REDG = OFF_Q + 8192;
constexpr uint32_t OFF_REDU = OFF_Q + 12288;
constexpr uint32_t OFF_REDV = OFF_SCR;

constexpr int BAR_FULL = 0;
constexpr int BAR_LAST = 28;
constexpr int BAR_WUK = 33, BAR_WM2 = 35, BAR_WUV = 36, BAR_WO = 38, BAR_W1 = 40, BAR_W2 = 41;
constexpr int BAR_ALLCLR = 42;
constexpr int BAR_EMPTY = 43;
constexpr int BAR_P0BD = 50;
constexpr int BAR_P1D = 51, BAR_P2D = 52;
constexpr int BAR_P5D = 53, BAR_P7D = 54;
constexpr int BAR_GO = 55;
constexpr int BAR_X1R = 56;
constexpr int NBARS = 57;
constexpr int BAR_XC = 57, BAR_WQ = 58;
constexpr int BAR_END = 60;
constexpr uint32_t SB = 1024;

#define TUNE_LIST(X) \
  X(PC_T0, 420) X(PC_XC, 300) X(PC_P1, 328) X(PC_N1, 0) X(PC_P2, 322) X(PC_STAG, 330) X(PC_SL, 500) \
  X(PW_A, 2) X(PW_0, -200) X(PW_UV, 420) X(PW_O, 360) X(PW_F, 480) X(CLR_T0, 5500) X(CLR_CLK, 340) \
  X(D_MOD, 1200) X(D_QP, 1000) X(D_QX, 1300) X(D_ML, 2350) X(D_X2, 800) X(D_X3A, 600) X(D_X3B, 1600) X(D_FIN, 600) X(D_FIN2, 2000) X(RB, 0)
struct Tune {
#define X(n, v) static constexpr int n = v;
  TUNE_LIST(X)
#undef X
};

struct Scratch {
  uint32_t MOD1[2][4 * 64 * 64];
  uint32_t MOD2[2][128 * 64];
  uint32_t QP[2][128 * 256 * 2];
  uint32_t QX[2][8 * 32 * 256];
  uint32_t ML[64 * 32 * 2];
  uint32_t X1[128 * 64 * 64];
  uint32_t X2[128 * 256 * 2];
  uint32_t X3A[128 * 32 * 16];
  uint32_t X3B[NREP * 128 * 16];
  uint32_t X4[128 * NFF * 16];
  uint32_t epoch;
  uint32_t pad[31];
  uint32_t cnt;
};
__device__ Scratch g_s;

#define CLK_DECL
#define CLK(i) do {} while (0)
#define CLK_DUMP() do {} while (0)
#define ITS(i, v) do {} while (0)

struct Params {
  CUtensorMap wq, wuk, wm2, ckv2, ckv1, wuv, wo, w1, w2;
};

__device__ __forceinline__ void mbar_init(uint32_t bar, int cnt) { asm volatile("mbarrier.init.shared::cta.b64 [%0], %1;" ::"r"(bar), "r"(cnt)); }
__device__ __forceinline__ void mbar_expect(uint32_t bar, uint32_t bytes) { asm volatile("mbarrier.arrive.expect_tx.shared::cta.b64 _, [%0], %1;" ::"r"(bar), "r"(bytes) : "memory"); }
__device__ __forceinline__ void mbar_arrive(uint32_t bar) { asm volatile("mbarrier.arrive.shared::cta.b64 _, [%0];" ::"r"(bar) : "memory"); }
__device__ __forceinline__ uint32_t clk32() { unsigned long long c; asm volatile("mov.u64 %0, %%clock64;" : "=l"(c) :: "memory"); return (uint32_t)c; }
__device__ __forceinline__ uint32_t gtime32() { uint32_t c; asm volatile("mov.u32 %0, %%globaltimer_lo;" : "=r"(c) :: "memory"); return c; }
__device__ __forceinline__ void wait_clk(uint32_t t0, int clocks) { while ((int)(clk32() - t0) < clocks) {} }
__device__ __forceinline__ void backoff(int clocks) { if (clocks > 0) wait_clk(clk32(), clocks); }
__device__ __forceinline__ void until_ns(uint32_t ns) { while ((int)(gtime32() - ns) < 0) {} }
__device__ __forceinline__ void slot(uint32_t& tn, int slack) {
  uint32_t now;
  do { now = gtime32(); } while ((int)(now - tn) < 0);
  if ((int)(now - tn) > slack) tn = now - slack;
}
template <typename T> __device__ __forceinline__ T* pin(T* p) { asm volatile("" : "+l"(p)); return p; }
constexpr int SPIN_LIMIT = 1 << 22;
__device__ __forceinline__ void mbar_wait(uint32_t bar) {
  asm volatile("{\n.reg .pred p;\n.reg .u32 c;\nmov.u32 c, 0;\n"
               "MW_LOOP:\nmbarrier.try_wait.parity.shared::cta.b64 p, [%0], 0;\n@p bra MW_DONE;\n"
               "add.u32 c, c, 1;\nsetp.lt.u32 p, c, 4194304;\n@p bra MW_LOOP;\ntrap;\nMW_DONE:\n}"
               ::"r"(bar) : "memory");
}
__device__ __forceinline__ bool mbar_test(uint32_t bar) {
  uint32_t ok;
  asm volatile("{\n.reg .pred p;\nmbarrier.test_wait.parity.shared::cta.b64 p, [%1], 0;\nselp.u32 %0,1,0,p;\n}" : "=r"(ok) : "r"(bar) : "memory");
  return ok;
}
__device__ __forceinline__ void tma2d(uint32_t dst, const CUtensorMap* m, int c0, int c1, uint32_t bar, uint64_t pol) {
  asm volatile("cp.async.bulk.tensor.2d.shared::cluster.global.mbarrier::complete_tx::bytes.L2::cache_hint [%0], [%1, {%3,%4}], [%2], %5;"
               ::"r"(dst), "l"(m), "r"(bar), "r"(c0), "r"(c1), "l"(pol) : "memory");
}
__device__ __forceinline__ void tma2d_nohint(uint32_t dst, const CUtensorMap* m, int c0, int c1, uint32_t bar) {
  asm volatile("cp.async.bulk.tensor.2d.shared::cluster.global.mbarrier::complete_tx::bytes [%0], [%1, {%3,%4}], [%2];"
               ::"r"(dst), "l"(m), "r"(bar), "r"(c0), "r"(c1) : "memory");
}
__device__ __forceinline__ void tma3d(uint32_t dst, const CUtensorMap* m, int c0, int c1, int c2, uint32_t bar, uint64_t pol) {
  asm volatile("cp.async.bulk.tensor.3d.shared::cluster.global.mbarrier::complete_tx::bytes.L2::cache_hint [%0], [%1, {%3,%4,%5}], [%2], %6;"
               ::"r"(dst), "l"(m), "r"(bar), "r"(c0), "r"(c1), "r"(c2), "l"(pol) : "memory");
}
__device__ __forceinline__ void tma5d(uint32_t dst, const CUtensorMap* m, int c0, int c1, int c2, int c3, int c4, uint32_t bar, uint64_t pol) {
  asm volatile("cp.async.bulk.tensor.5d.shared::cluster.global.mbarrier::complete_tx::bytes.L2::cache_hint [%0], [%1, {%3,%4,%5,%6,%7}], [%2], %8;"
               ::"r"(dst), "l"(m), "r"(bar), "r"(c0), "r"(c1), "r"(c2), "r"(c3), "r"(c4), "l"(pol) : "memory");
}
__device__ __forceinline__ void bulk_ld(uint32_t dst, const void* src, uint32_t bytes, uint32_t bar) {
  asm volatile("cp.async.bulk.shared::cluster.global.mbarrier::complete_tx::bytes [%0], [%1], %2, [%3];" ::"r"(dst), "l"(src), "r"(bytes), "r"(bar) : "memory");
}
__device__ __forceinline__ void bar_sync(int id, int n) { asm volatile("barrier.cta.sync.aligned %0, %1;" ::"r"(id), "r"(n) : "memory"); }
__device__ __forceinline__ void cbar() { asm volatile("barrier.cta.sync.aligned 1, 256;" ::: "memory"); }
__device__ __forceinline__ bool bar_over(float ex) {
  uint32_t over;
  asm volatile("{\n.reg .pred p, q;\nsetp.gtu.f32 p, %1, 0f41F00000;\nbarrier.cta.red.or.aligned.pred q, 4, 256, p;\nselp.u32 %0, 1, 0, q;\n}"
               : "=r"(over) : "f"(ex) : "memory");
  return over;
}

__device__ __forceinline__ uint32_t ldg_nc1(const void* p) { uint32_t v; asm volatile("ld.global.nc.L1::no_allocate.u32 %0, [%1];" : "=r"(v) : "l"(p)); return v; }
__device__ __forceinline__ uint2 ldg_nc2(const void* p) { uint2 v; asm volatile("ld.global.nc.v2.u32 {%0,%1}, [%2];" : "=r"(v.x), "=r"(v.y) : "l"(p)); return v; }
__device__ __forceinline__ uint4 ldg_nc4(const void* p) { uint4 v; asm volatile("ld.global.nc.L1::no_allocate.v4.u32 {%0,%1,%2,%3}, [%4];" : "=r"(v.x), "=r"(v.y), "=r"(v.z), "=r"(v.w) : "l"(p)); return v; }
__device__ __forceinline__ uint32_t ldg_rlx1(const void* p) { uint32_t v; asm volatile("ld.relaxed.gpu.global.u32 %0, [%1];" : "=r"(v) : "l"(p) : "memory"); return v; }
__device__ __forceinline__ void stg4(void* p, uint4 v) { asm volatile("st.relaxed.gpu.global.v4.u32 [%0], {%1,%2,%3,%4};" ::"l"(p), "r"(v.x), "r"(v.y), "r"(v.z), "r"(v.w) : "memory"); }
__device__ __forceinline__ void stg1(void* p, uint32_t a) { asm volatile("st.relaxed.gpu.global.u32 [%0], %1;" ::"l"(p), "r"(a) : "memory"); }
__device__ __forceinline__ uint32_t nz(uint32_t w) { return max(w, 1u); }
__device__ __forceinline__ uint2 ldg_u64(const void* p) {
  uint2 v; asm volatile("{\n.reg .b64 a;\nld.relaxed.gpu.global.b64 a, [%2];\nmov.b64 {%0,%1}, a;\n}" : "=r"(v.x), "=r"(v.y) : "l"(p) : "memory"); return v;
}
__device__ __forceinline__ uint4 ldg_2u64(const void* p) {
  uint4 v; asm volatile("{\n.reg .b64 a, b;\nld.relaxed.gpu.global.v2.b64 {a, b}, [%4];\nmov.b64 {%0,%1}, a;\nmov.b64 {%2,%3}, b;\n}" : "=r"(v.x), "=r"(v.y), "=r"(v.z), "=r"(v.w) : "l"(p) : "memory"); return v;
}
__device__ __forceinline__ void stg_u64(void* p, uint32_t x, uint32_t y) {
  asm volatile("{\n.reg .b64 a;\nmov.b64 a, {%1,%2};\nst.relaxed.gpu.global.b64 [%0], a;\n}" ::"l"(p), "r"(x), "r"(max(y, 1u)) : "memory");
}
__device__ __forceinline__ void stg_2u64(void* p, uint4 v) {
  asm volatile("{\n.reg .b64 a, b;\nmov.b64 a, {%1,%2};\nmov.b64 b, {%3,%4};\nst.relaxed.gpu.global.v2.b64 [%0], {a, b};\n}" ::"l"(p), "r"(v.x), "r"(max(v.y, 1u)), "r"(v.z), "r"(max(v.w, 1u)) : "memory");
}

__device__ __forceinline__ uint32_t pack_bf16(float lo, float hi) { uint32_t r; asm("cvt.rn.bf16x2.f32 %0, %1, %2;" : "=r"(r) : "f"(hi), "f"(lo)); return r; }
__device__ __forceinline__ float bf_lo(uint32_t w) { return __uint_as_float(w << 16); }
__device__ __forceinline__ float bf_hi(uint32_t w) { return __uint_as_float(w & 0xffff0000u); }
__device__ __forceinline__ float ex2(float x) { float r; asm("ex2.approx.ftz.f32 %0, %1;" : "=f"(r) : "f"(x)); return r; }
__device__ __forceinline__ uint32_t hmul2(uint32_t a, uint32_t b) { uint32_t r; asm("mul.rn.bf16x2 %0, %1, %2;" : "=r"(r) : "r"(a), "r"(b)); return r; }
__device__ __forceinline__ uint32_t hadd2(uint32_t a, uint32_t b) { uint32_t r; asm("add.rn.bf16x2 %0, %1, %2;" : "=r"(r) : "r"(a), "r"(b)); return r; }
__device__ __forceinline__ uint32_t hfma2(uint32_t a, uint32_t b, uint32_t c) { uint32_t r; asm("fma.rn.bf16x2 %0, %1, %2, %3;" : "=r"(r) : "r"(a), "r"(b), "r"(c)); return r; }
__device__ __forceinline__ uint32_t silu2(uint32_t v) { const float a = bf_lo(v), b = bf_hi(v); return pack_bf16(__fdividef(a, 1.f + __expf(-a)), __fdividef(b, 1.f + __expf(-b))); }
constexpr uint32_t ONE2 = 0x3f803f80u;

__device__ __forceinline__ void ldsm4(uint32_t (&r)[4], uint32_t a) { asm volatile("ldmatrix.sync.aligned.m8n8.x4.shared.b16 {%0,%1,%2,%3}, [%4];" : "=r"(r[0]), "=r"(r[1]), "=r"(r[2]), "=r"(r[3]) : "r"(a) : "memory"); }
__device__ __forceinline__ void ldsm4t(uint32_t (&r)[4], uint32_t a) { asm volatile("ldmatrix.sync.aligned.m8n8.x4.trans.shared.b16 {%0,%1,%2,%3}, [%4];" : "=r"(r[0]), "=r"(r[1]), "=r"(r[2]), "=r"(r[3]) : "r"(a) : "memory"); }
__device__ __forceinline__ void ldsm2t(uint32_t& r0, uint32_t& r1, uint32_t a) { asm volatile("ldmatrix.sync.aligned.m8n8.x2.trans.shared.b16 {%0,%1}, [%2];" : "=r"(r0), "=r"(r1) : "r"(a) : "memory"); }
__device__ __forceinline__ void stsm4t(uint32_t a, uint32_t r0, uint32_t r1, uint32_t r2, uint32_t r3) { asm volatile("stmatrix.sync.aligned.m8n8.x4.trans.shared.b16 [%0], {%1,%2,%3,%4};" ::"r"(a), "r"(r0), "r"(r1), "r"(r2), "r"(r3) : "memory"); }
__device__ __forceinline__ uint32_t movm(uint32_t a) { uint32_t d; asm volatile("movmatrix.sync.aligned.m8n8.trans.b16 %0, %1;" : "=r"(d) : "r"(a)); return d; }
__device__ __forceinline__ void mma16816(float (&d)[4], const uint32_t (&a)[4], uint32_t b0, uint32_t b1) {
  asm volatile("mma.sync.aligned.m16n8k16.row.col.f32.bf16.bf16.f32 {%0,%1,%2,%3}, {%4,%5,%6,%7}, {%8,%9}, {%0,%1,%2,%3};"
               : "+f"(d[0]), "+f"(d[1]), "+f"(d[2]), "+f"(d[3]) : "r"(a[0]), "r"(a[1]), "r"(a[2]), "r"(a[3]), "r"(b0), "r"(b1));
}
__device__ __forceinline__ void sts1(uint32_t a, uint32_t v) { asm volatile("st.shared.u32 [%0], %1;" ::"r"(a), "r"(v) : "memory"); }
__device__ __forceinline__ void sts2(uint32_t a, uint32_t x, uint32_t y) { asm volatile("st.shared.v2.u32 [%0], {%1,%2};" ::"r"(a), "r"(x), "r"(y) : "memory"); }
__device__ __forceinline__ void sts4(uint32_t a, uint4 v) { asm volatile("st.shared.v4.u32 [%0], {%1,%2,%3,%4};" ::"r"(a), "r"(v.x), "r"(v.y), "r"(v.z), "r"(v.w) : "memory"); }
__device__ __forceinline__ void sts2f(uint32_t a, float x, float y) { asm volatile("st.shared.v2.f32 [%0], {%1,%2};" ::"r"(a), "f"(x), "f"(y) : "memory"); }
__device__ __forceinline__ void sts4f(uint32_t a, float x, float y, float z, float w) { asm volatile("st.shared.v4.f32 [%0], {%1,%2,%3,%4};" ::"r"(a), "f"(x), "f"(y), "f"(z), "f"(w) : "memory"); }
__device__ __forceinline__ void stsf(uint32_t a, float v) { asm volatile("st.shared.f32 [%0], %1;" ::"r"(a), "f"(v) : "memory"); }
__device__ __forceinline__ uint32_t lds1(uint32_t a) { uint32_t v; asm volatile("ld.shared.u32 %0, [%1];" : "=r"(v) : "r"(a) : "memory"); return v; }
__device__ __forceinline__ float ldsf(uint32_t a) { float v; asm volatile("ld.shared.f32 %0, [%1];" : "=f"(v) : "r"(a) : "memory"); return v; }
__device__ __forceinline__ float2 ldsf2(uint32_t a) { float2 v; asm volatile("ld.shared.v2.f32 {%0,%1}, [%2];" : "=f"(v.x), "=f"(v.y) : "r"(a) : "memory"); return v; }
__device__ __forceinline__ float4 ldsf4(uint32_t a) { float4 v; asm volatile("ld.shared.v4.f32 {%0,%1,%2,%3}, [%4];" : "=f"(v.x), "=f"(v.y), "=f"(v.z), "=f"(v.w) : "r"(a) : "memory"); return v; }
__device__ __forceinline__ void lds4(uint32_t (&r)[4], uint32_t a) { asm volatile("ld.shared.v4.u32 {%0,%1,%2,%3}, [%4];" : "=r"(r[0]), "=r"(r[1]), "=r"(r[2]), "=r"(r[3]) : "r"(a) : "memory"); }

__device__ __forceinline__ void wg_fence() { asm volatile("wgmma.fence.sync.aligned;" ::: "memory"); }
__device__ __forceinline__ void wg_commit() { asm volatile("wgmma.commit_group.sync.aligned;" ::: "memory"); }
template <int N> __device__ __forceinline__ void wg_wait() { asm volatile("wgmma.wait_group.sync.aligned %0;" ::"n"(N) : "memory"); }
__host__ __device__ constexpr uint32_t desc_lo(uint32_t off) { return ((SB + off) >> 4) | 0x10000u; }
template <int TA, int ACC> __device__ __forceinline__ void wgmma_n16(float (&d)[8], uint32_t da, uint32_t db) {
  asm volatile("{\n.reg .b64 da, db;\nmov.b64 da, {%8, 0x40000040};\nmov.b64 db, {%9, 0x40000040};\n"
               "wgmma.mma_async.sync.aligned.m64n16k16.f32.bf16.bf16 {%0,%1,%2,%3,%4,%5,%6,%7}, da, db, %11, 1, 1, %10, 0;\n}"
               : "+f"(d[0]), "+f"(d[1]), "+f"(d[2]), "+f"(d[3]), "+f"(d[4]), "+f"(d[5]), "+f"(d[6]), "+f"(d[7])
               : "r"(da), "r"(db), "n"(TA), "n"(ACC));
}
__device__ __forceinline__ void acc_fence(float (&d)[8]) {
  asm volatile("" : "+f"(d[0]), "+f"(d[1]), "+f"(d[2]), "+f"(d[3]), "+f"(d[4]), "+f"(d[5]), "+f"(d[6]), "+f"(d[7]) :: "memory");
}

template <int N, int STRIDE> __device__ __forceinline__ void load_units(uint2 (&v)[N], const uint32_t* p) {
#pragma unroll
  for (int i = 0; i < N; i++) v[i] = ldg_u64(p + i * STRIDE);
}
template <int N, int STRIDE> __device__ __forceinline__ int check_units(uint2 (&v)[N], const uint32_t* p, int rb) {
  int it = 0;
  while (true) {
    uint32_t mn = v[0].y;
#pragma unroll
    for (int i = 1; i < N; i++) mn = min(mn, v[i].y);
    if (mn != 0) break;
    backoff(rb);
#pragma unroll
    for (int i = 0; i < N; i++) if (v[i].y == 0) v[i] = ldg_u64(p + i * STRIDE);
    if (++it > SPIN_LIMIT) __trap();
  }
  return it;
}
__device__ __forceinline__ void sum4_to_smem(const uint2 (&v)[4], uint32_t dst) {
  const float c0 = (bf_lo(v[0].x) + bf_lo(v[1].x)) + (bf_lo(v[2].x) + bf_lo(v[3].x));
  const float c1 = (bf_hi(v[0].x) + bf_hi(v[1].x)) + (bf_hi(v[2].x) + bf_hi(v[3].x));
  const float c2 = (bf_lo(v[0].y) + bf_lo(v[1].y)) + (bf_lo(v[2].y) + bf_lo(v[3].y));
  const float c3 = (bf_hi(v[0].y) + bf_hi(v[1].y)) + (bf_hi(v[2].y) + bf_hi(v[3].y));
  sts1(dst, pack_bf16(c0, c1));
  sts1(dst + 128, pack_bf16(c2, c3));
}
__device__ __forceinline__ void load_a_t(uint32_t (&a)[8][4], uint32_t wbase, int w, int lane) {
  const int mi = lane >> 3, r = lane & 7;
  const uint32_t base = wbase + (w >> 2) * 16384 + (8 * (mi >> 1) + r) * 128 + (((2 * (w & 3) + (mi & 1)) ^ r) << 4);
#pragma unroll
  for (int ks = 0; ks < 8; ks++) ldsm4t(a[ks], base + ks * 2048);
}
__device__ __forceinline__ void mma128(float (&d)[4], const uint32_t (&a)[8][4], const uint32_t (&b)[4][4]) {
  float e[4][4] = {{0.f, 0.f, 0.f, 0.f}, {0.f, 0.f, 0.f, 0.f}, {0.f, 0.f, 0.f, 0.f}, {0.f, 0.f, 0.f, 0.f}};
#pragma unroll
  for (int kk = 0; kk < 4; kk++) { mma16816(e[(2 * kk) & 3], a[2 * kk], b[kk][0], b[kk][1]); mma16816(e[(2 * kk + 1) & 3], a[2 * kk + 1], b[kk][2], b[kk][3]); }
#pragma unroll
  for (int i = 0; i < 4; i++) d[i] = (e[0][i] + e[1][i]) + (e[2][i] + e[3][i]);
}
template <int NP> __device__ __forceinline__ int sum_pieces(const uint32_t* p0, int g, int t, float& v0, float& v1, int rb) {
  constexpr int NL = NP / 8;
  uint32_t v[NL][4];
#pragma unroll
  for (int i = 0; i < NL; i++) { const uint4 x = ldg_2u64(p0 + i * 128); v[i][0] = x.x; v[i][1] = x.y; v[i][2] = x.z; v[i][3] = x.w; }
  int it = 0;
  while (true) {
    uint32_t mn = 0xffffffffu;
#pragma unroll
    for (int i = 0; i < NL; i++) mn = min(mn, min(v[i][1], v[i][3]));
    if (mn != 0) break;
    backoff(rb);
#pragma unroll
    for (int i = 0; i < NL; i++)
      if (v[i][1] == 0 || v[i][3] == 0) { const uint4 x = ldg_2u64(p0 + i * 128); v[i][0] = x.x; v[i][1] = x.y; v[i][2] = x.z; v[i][3] = x.w; }
    if (++it > SPIN_LIMIT) __trap();
  }
  __syncwarp();
  const uint32_t one = (g & 1) ? 0x3f800000u : 0x00003f80u;
  const uint32_t b0 = (g & 2) ? 0u : one, b1 = (g & 2) ? one : 0u;
  float d[4][4] = {{0.f, 0.f, 0.f, 0.f}, {0.f, 0.f, 0.f, 0.f}, {0.f, 0.f, 0.f, 0.f}, {0.f, 0.f, 0.f, 0.f}};
#pragma unroll
  for (int i = 0; i < NL; i++) mma16816(d[i & 3], v[i], b0, b1);
  const bool up = t & 2;
  const float x0 = up ? (d[0][2] + d[1][2]) + (d[2][2] + d[3][2]) : (d[0][0] + d[1][0]) + (d[2][0] + d[3][0]);
  const float x1 = up ? (d[0][3] + d[1][3]) + (d[2][3] + d[3][3]) : (d[0][1] + d[1][1]) + (d[2][1] + d[3][1]);
  v0 = x0 + __shfl_xor_sync(~0u, x0, 16);
  v1 = x1 + __shfl_xor_sync(~0u, x1, 16);
  return it;
}
template <typename F> __device__ __forceinline__ float reduce_g(const float (&x)[4], int lane, F f) {
  const bool u4 = lane & 16, u3 = lane & 8;
  const float a0 = f(u4 ? x[2] : x[0], __shfl_xor_sync(~0u, u4 ? x[0] : x[2], 16));
  const float a1 = f(u4 ? x[3] : x[1], __shfl_xor_sync(~0u, u4 ? x[1] : x[3], 16));
  const float b = f(u3 ? a1 : a0, __shfl_xor_sync(~0u, u3 ? a0 : a1, 8));
  return f(b, __shfl_xor_sync(~0u, b, 4));
}

__global__ void __launch_bounds__(NTHREADS, 1)
fused_decode_kernel(__nv_bfloat16* __restrict__ gout, Scratch* __restrict__ gs, const uint8_t* __restrict__ gwmod,
                    const uint8_t* __restrict__ gx, const uint8_t* __restrict__ gc,
                    const __grid_constant__ Params P) {
  constexpr Tune T{};
  extern __shared__ __align__(1024) uint8_t smem_raw[];
  const uint32_t sb = (uint32_t)__cvta_generic_to_shared(smem_raw);
  const int tid = threadIdx.x, lane = tid & 31;
  const int w = __shfl_sync(0xffffffffu, tid >> 5, 0);
  const int cta = blockIdx.x;
  const uint32_t bars = sb + OFF_BARS;
  auto BAR = [&](int i) { return bars + 8 * i; };
  const int g = lane >> 2, t = lane & 3;
  const int hI = cta >> 2, jI = cta & 3;
  const int bs = cta >> 1, hh = cta & 1;

  CLK_DECL;
  CLK(0);
  if (w == 8) {
    CLK(7);
    const uint32_t t_entry = gtime32();
    CLK(8);
    if (lane == 0) {
      if ((sb & 0xffffff) != SB) __trap();
      mbar_init(BAR(BAR_WQ), 1); mbar_init(BAR(BAR_WQ + 1), 1); mbar_init(BAR(BAR_XC), 1);
      asm volatile("fence.mbarrier_init.release.cluster;" ::: "memory");
      asm volatile("prefetch.tensormap [%0];" ::"l"(&P.wq) : "memory");
      mbar_expect(BAR(BAR_XC), 16384); mbar_expect(BAR(BAR_WQ), 16384); mbar_expect(BAR(BAR_WQ + 1), 16384);
      CLK(9);
    }
    __syncwarp();
    asm volatile("barrier.cta.arrive.aligned 0, %0;" ::"n"(NTHREADS) : "memory");
    CLK(10);
    uint32_t tn = t_entry + T.PC_T0 + ((bs * 37) & 63) * T.PC_STAG / 64;
    const int h = hI, j = jI;
    if (lane == 0) {
      uint64_t pol; asm volatile("createpolicy.fractional.L2::evict_first.b64 %0, 1.0;" : "=l"(pol));
#pragma unroll
      for (int u = 0; u < 4; u++) {
        until_ns(tn + u * T.PC_P1);
        if (u == 0) CLK(11);
        tma2d(sb + OFF_WQ + u * 8192, &P.wq, 128 * h + 64 * (u >> 1), 128 * j + 64 * (u & 1), BAR(BAR_WQ + (u >> 1)), pol);
        if (u == 0) {
          CLK(1);
          until_ns(t_entry + T.PC_XC);
          bulk_ld(sb + OFF_XS, gx, 8192, BAR(BAR_XC));
          bulk_ld(sb + OFF_CS, gc, 8192, BAR(BAR_XC));
          asm volatile("prefetch.tensormap [%0];" ::"l"(&P.wuk) : "memory");
          asm volatile("prefetch.tensormap [%0];" ::"l"(&P.wm2) : "memory");
          asm volatile("prefetch.tensormap [%0];" ::"l"(&P.ckv2) : "memory");
        }
      }
    }
    __syncwarp();
    tn += 4 * T.PC_P1;
    bar_sync(5, 64);
    if (lane == 0) {
      uint64_t pol; asm volatile("createpolicy.fractional.L2::evict_first.b64 %0, 1.0;" : "=l"(pol));
#pragma unroll
      for (int u = 0; u < 4; u++) {
        until_ns(tn);
        tma5d(sb + OFF_WUK + u * 8192, &P.wuk, 128 * h + 64 * (u >> 1), 0, 0, 0, 8 * j + 4 * (u & 1), BAR(BAR_WUK + (u >> 1)), pol);
        tn += T.PC_P1;
      }
      mbar_wait(BAR(BAR_P1D));
#pragma unroll
      for (int u = 0; u < 2; u++) {
        slot(tn, T.PC_SL);
        tma2d_nohint(sb + OFF_WM2 + u * 8192, &P.wm2, 1024 + 16 * cta, 256 * u, BAR(BAR_WM2));
        tn += T.PC_P1;
      }
      const int row0 = (bs >> 3) * 4096 + (bs & 7) * 64;
      uint32_t pos = sb + OFF_RING;
#pragma unroll 1
      for (int tl = 0; tl < 7; tl++) {
        if (tl == 2) mbar_wait(BAR(BAR_P2D));
        if (tl >= 3) mbar_wait(BAR(BAR_EMPTY + tl - 3));
        if (tl == 1) CLK(2);
        if (tl == 3) CLK(3);
        if (tl == 5) CLK(4);
        if (tl == 6) {
          asm volatile("prefetch.tensormap [%0];" ::"l"(&P.ckv1) : "memory");
          asm volatile("prefetch.tensormap [%0];" ::"l"(&P.wuv) : "memory");
          asm volatile("prefetch.tensormap [%0];" ::"l"(&P.wo) : "memory");
          asm volatile("prefetch.tensormap [%0];" ::"l"(&P.w1) : "memory");
          asm volatile("prefetch.tensormap [%0];" ::"l"(&P.w2) : "memory");
        }
#pragma unroll
        for (int u = 0; u < 4; u++) {
          if (u == 3 && tl == 2) mbar_wait(BAR(BAR_P0BD));
          slot(tn, T.PC_SL);
          tma3d(pos + u * 16384, &P.ckv2, 0, row0 + tl * 512, 2 * u, BAR(BAR_FULL + 4 * tl + u), pol);
          tn += (4 * tl + u < T.PC_N1) ? T.PC_P1 : T.PC_P2;
        }
        pos = (tl == 2 || tl == 5) ? sb + OFF_RING : pos + 65536;
      }
      mbar_wait(BAR(BAR_EMPTY + 4));
      CLK(5);
#pragma unroll
      for (int u = 0; u < 3; u++) {
        slot(tn, T.PC_SL);
        tma3d(pos + u * 16384, &P.ckv2, 0, row0 + 7 * 512, 2 * u, BAR(BAR_LAST + u), pol);
        tn += T.PC_P2;
      }
      until_ns(tn);
      tma3d(pos + 49152, &P.ckv1, 0, row0 + 7 * 512, 6, BAR(BAR_LAST + 3), pol);
      tma3d(pos + 57344, &P.ckv1, 0, row0 + 7 * 512, 7, BAR(BAR_LAST + 4), pol);
      tn += T.PC_P2;
      CLK(6);
      auto unit = [&](int u) {
        if (u < 4) tma5d(sb + OFF_WUV + u * 8192, &P.wuv, 128 * h + 64 * (u >> 1), 0, 2 * j, 0, 2 * (u & 1), BAR(BAR_WUV + (u >> 1)), pol);
        else if (u < 8) tma2d(sb + OFF_WO + (u - 4) * 8192, &P.wo, 128 * j + 64 * ((u - 4) >> 1), 128 * h + 64 * (u & 1), BAR(BAR_WO + ((u - 4) >> 1)), pol);
        else if (u < 10) { if (cta < NFF) tma2d_nohint(sb + OFF_W1 + (u - 8) * 8192, &P.w1, FCH * cta, 256 * (u - 8), BAR(BAR_W1)); }
        else if (cta < NFF) tma3d(sb + OFF_W2 + (u - 10) * 8192, &P.w2, 0, FCH * cta, 4 * (u - 10), BAR(BAR_W2), pol);
      };
      mbar_wait(BAR(BAR_EMPTY + 5));
      if (T.PW_A >= 0) { mbar_wait(BAR(BAR_LAST + T.PW_A)); tn = gtime32(); }
      tn += T.PW_0;
#pragma unroll
      for (int u = 0; u < 12; u++) {
        if (u == 8) mbar_wait(BAR(BAR_EMPTY + 6));
        until_ns(tn);
        unit(u);
        tn += u < 4 ? T.PW_UV : u < 8 ? T.PW_O : T.PW_F;
      }
      CLK_DUMP();
    }
    return;
  }

  if (w == 9) {
    if (lane == 0) {
#pragma unroll
      for (int i = 0; i < NBARS; i++) mbar_init(BAR(i), i >= BAR_P1D ? 8 : i >= BAR_EMPTY ? 4 : 1);
      asm volatile("fence.mbarrier_init.release.cluster;" ::: "memory");
    }
    __syncwarp();
    mbar_expect(BAR(lane), lane == BAR_LAST + 3 ? 8192 : 16384);
    if (lane < BAR_ALLCLR - 32) mbar_expect(BAR(32 + lane), lane == 0 ? 8192 : 16384);
    CLK(9);
    asm volatile("barrier.cta.arrive.aligned 5, 64;" ::: "memory");
    asm volatile("barrier.cta.arrive.aligned 0, %0;" ::"n"(NTHREADS) : "memory");
  }
  const uint32_t epoch = ldg_rlx1(&gs->epoch);

  if (w == 9) {
    const int wd = 2 * (t & 1) + (t >> 1), bo = 2 * (g & 3) + (wd >> 1), mo = 16 * hI + 2 * jI + 8 * (wd & 1);
    const uint32_t xo = ldg_nc1(gx + (bo * 512 + mo) * 2);
    const int par = epoch & 1;
    until_ns(gtime32() + T.CLR_T0);
    {
      const uint4 z = make_uint4(0, 0, 0, 0);
      uint4* x1 = reinterpret_cast<uint4*>(gs->X1 + cta * 4096);
#pragma unroll 1
      for (int i0 = 0; i0 < 32; i0 += 4) {
#pragma unroll
        for (int i = 0; i < 4; i++) stg4(x1 + (i0 + i) * 32 + lane, z);
        backoff(T.CLR_CLK);
      }
#pragma unroll
      for (int i = 0; i < 4; i++) stg4(reinterpret_cast<uint4*>(gs->X3A + cta * 512) + i * 32 + lane, z);
      backoff(T.CLR_CLK);
#pragma unroll
      for (int i = 0; i < 4; i++) stg4(reinterpret_cast<uint4*>(gs->X2 + cta * 512) + i * 32 + lane, z);
      backoff(T.CLR_CLK);
      stg4(reinterpret_cast<uint4*>(gs->X3B + (lane >> 2) * 2048 + cta * 16) + (lane & 3), z);
      if (lane < 8) stg4(reinterpret_cast<uint4*>(gs->ML + cta * 32) + lane, z);
      uint4* x4 = reinterpret_cast<uint4*>(gs->X4 + cta * NFF * 16);
#pragma unroll
      for (int i = 0; i < NFF / 8; i++) { stg4(x4 + i * 32 + lane, z); if ((i & 3) == 1) backoff(T.CLR_CLK); }
      CLK(1);
      asm volatile("fence.acq_rel.gpu;" ::: "memory");
      CLK(2);
      __syncwarp();
      if (lane == 0) asm volatile("red.relaxed.gpu.global.add.u32 [%0], 1;" ::"l"(&gs->cnt) : "memory");
#pragma unroll
      for (int i = 0; i < 4; i++) stg4(reinterpret_cast<uint4*>(gs->QP[par ^ 1] + cta * 512) + i * 32 + lane, z);
      backoff(T.CLR_CLK);
#pragma unroll
      for (int i = 0; i < 4; i++) stg4(reinterpret_cast<uint4*>(gs->QX[par ^ 1] + cta * 512) + i * 32 + lane, z);
      stg4(reinterpret_cast<uint4*>(gs->MOD1[par ^ 1] + cta * 128) + lane, z);
      if (lane < 16) stg4(reinterpret_cast<uint4*>(gs->MOD2[par ^ 1] + cta * 64) + lane, z);
      if (lane == 0) {
        const uint32_t target = (epoch + 1) * NCTA;
        uint32_t c; int it = 0;
        do { backoff(T.CLR_CLK); asm volatile("ld.acquire.gpu.global.u32 %0, [%1];" : "=r"(c) : "l"(&gs->cnt) : "memory"); if (++it > SPIN_LIMIT) __trap(); } while ((int)(c - target) < 0);
        mbar_arrive(BAR(BAR_ALLCLR));
      }
      __syncwarp();
    }
    CLK(3);
    uint2 gg[2];
    {
      const uint32_t* pg = gs->MOD2[par] + cta * 16 + bo * 2;
      load_units<2, 3 * 2048>(gg, pg);
      check_units<2, 3 * 2048>(gg, pg, T.RB);
    }
    const uint32_t ga2 = (wd & 1) ? gg[0].y : gg[0].x, gb2 = (wd & 1) ? gg[1].y : gg[1].x;
    float v0, v1;
    uint32_t* const x3o = pin(gs->X3B + (lane >> 2) * 2048 + cta * 16 + (lane & 3) * 4);
    uint32_t* const fo = pin(reinterpret_cast<uint32_t*>(gout) + (bo * 512 + mo) / 2);
    const int po = (4 * (g >> 2) + t) * 16 + (g & 3) * 4;
    const uint32_t* const p3 = pin(gs->X3A + cta * 512 + po);
    const uint32_t* const p4 = pin(gs->X4 + cta * NFF * 16 + po);
    mbar_wait(BAR(BAR_P5D));
    backoff(T.D_X3A);
    CLK(4);
    { const int it = sum_pieces<32>(p3, g, t, v0, v1, T.RB); ITS(0, it); }
    CLK(5);
    const uint32_t x2w = pack_bf16(bf_lo(xo) + bf_lo(ga2) * v0, bf_hi(xo) + bf_hi(ga2) * v1);
    {
      const int src = 4 * (lane & 3);
      uint4 o;
      o.x = __shfl_sync(~0u, x2w, src); o.y = __shfl_sync(~0u, x2w, src + 2); o.z = __shfl_sync(~0u, x2w, src + 1); o.w = __shfl_sync(~0u, x2w, src + 3);
      stg_2u64(x3o, o);
    }
    CLK(6);
    if (cta < NFF) { mbar_wait(BAR(BAR_P7D)); backoff(T.D_FIN); } else backoff(T.D_FIN2);
    CLK(7);
    { const int it = sum_pieces<NFF>(p4, g, t, v0, v1, T.RB); ITS(1, it); }
    if (g < 4) *fo = pack_bf16(bf_lo(x2w) + bf_lo(gb2) * v0, bf_hi(x2w) + bf_hi(gb2) * v1);
    CLK(8);
    CLK_DUMP();
    if (cta == 0 && lane == 0) stg1(&gs->epoch, epoch + 1);
    return;
  }

  const int wg = w >> 2, wq = w & 3;
  uint32_t tstore;
  {
    const uint8_t* pw = gwmod + (size_t)(128 * jI + 16 * w + 4 * (g >> 1) + (g & 1)) * 6144 + 64 * hI + 16 * t;
    const uint4 w0 = ldg_nc4(pw), w1 = ldg_nc4(pw + 2 * 6144);
    const uint2 cc = ldg_nc2(gc + g * 1024 + 256 * jI + 32 * w + 8 * t);
    CLK(40);
    const uint32_t a[4] = {silu2(cc.x), 0u, silu2(cc.y), 0u};
    float d[4][4] = {{0.f, 0.f, 0.f, 0.f}, {0.f, 0.f, 0.f, 0.f}, {0.f, 0.f, 0.f, 0.f}, {0.f, 0.f, 0.f, 0.f}};
    mma16816(d[0], a, movm(w0.x), movm(w1.x)); mma16816(d[1], a, movm(w0.y), movm(w1.y));
    mma16816(d[2], a, movm(w0.z), movm(w1.z)); mma16816(d[3], a, movm(w0.w), movm(w1.w));
    CLK(1);
    sts4f(sb + OFF_P0S + w * 1088 + lane * 16, d[0][0], d[0][1], d[1][0], d[1][1]);
    sts4f(sb + OFF_P0S + w * 1088 + 544 + lane * 16, d[2][0], d[2][1], d[3][0], d[3][1]);
    bar_sync(0, NTHREADS);
    if (tid < 128) {
      const uint32_t src = sb + OFF_P0S + ((tid >> 2) & 1) * 544 + (((tid >> 3) & 7) * 4 + 2 * (tid >> 6) + (tid & 1)) * 16 + ((tid >> 1) & 1) * 8;
      float2 v[8];
#pragma unroll
      for (int i = 0; i < 8; i++) v[i] = ldsf2(src + i * 1088);
      const float ax = ((v[0].x + v[1].x) + (v[2].x + v[3].x)) + ((v[4].x + v[5].x) + (v[6].x + v[7].x));
      const float ay = ((v[0].y + v[1].y) + (v[2].y + v[3].y)) + ((v[4].y + v[5].y) + (v[6].y + v[7].y));
      stg1(gs->MOD1[epoch & 1] + jI * 4096 + hI * 128 + tid, nz(pack_bf16(ax, ay)));
    }
    tstore = clk32();
  }
  CLK(2);
  const int par = epoch & 1;
  uint32_t cf[4][4];
  mbar_wait(BAR(BAR_XC));
  {
    uint32_t u[2][4];
    lds4(u[0], sb + OFF_XS + w * 1024 + lane * 16); lds4(u[1], sb + OFF_XS + w * 1024 + 512 + lane * 16);
#pragma unroll
    for (int i = 0; i < 4; i++) lds4(cf[i], sb + OFF_CS + g * 1024 + wq * 256 + i * 64 + t * 16);
    float v[16];
#pragma unroll
    for (int i = 0; i < 8; i++) { v[2 * i] = bf_lo(u[i >> 2][i & 3]); v[2 * i + 1] = bf_hi(u[i >> 2][i & 3]); }
    float s = 0.f;
#pragma unroll
    for (int i = 0; i < 16; i++) s += v[i];
#pragma unroll
    for (int o = 16; o; o >>= 1) s += __shfl_xor_sync(~0u, s, o);
    const float mu = s * (1.f / 512.f);
    float q = 0.f;
#pragma unroll
    for (int i = 0; i < 16; i++) { v[i] -= mu; q += v[i] * v[i]; }
#pragma unroll
    for (int o = 16; o; o >>= 1) q += __shfl_xor_sync(~0u, q, o);
    const float rs = rsqrtf(q * (1.f / 512.f) + 1e-5f);
    const bool hi = jI & 2;
    uint32_t o[4];
#pragma unroll
    for (int i = 0; i < 4; i++) o[i] = pack_bf16((hi ? v[8 + 2 * i] : v[2 * i]) * rs, (hi ? v[9 + 2 * i] : v[2 * i + 1]) * rs);
    if ((lane >> 4) == (jI & 1)) sts4(sb + OFF_XN + w * 272 + (lane & 15) * 16, make_uint4(o[0], o[1], o[2], o[3]));
  }
  CLK(3);
  uint32_t aw[8][4];
  {
    const uint32_t* pm = pin(gs->MOD1[par] + (8 * jI + w) * 64 + lane * 2);
    uint32_t* const qpo = pin(gs->QP[par] + (cta * 256 + tid) * 2);
    wait_clk(tstore, T.D_MOD);
    CLK(4);
    uint2 v[8];
    load_units<8, 2048>(v, pm);
    cbar();
    const uint32_t xn0 = lds1(sb + OFF_XN + g * 272 + w * 32 + t * 4), xn1 = lds1(sb + OFF_XN + g * 272 + w * 32 + 16 + t * 4);
    int it = 0;
    while (true) {
      uint32_t mn = 0xffffffffu;
#pragma unroll
      for (int i = 0; i < 8; i++) mn = min(mn, min(v[i].x, v[i].y));
      if (mn != 0) break;
#pragma unroll
      for (int i = 0; i < 8; i++) if (v[i].x == 0 || v[i].y == 0) v[i] = ldg_u64(pm + i * 2048);
      if (++it > SPIN_LIMIT) __trap();
    }
    CLK(5);
    ITS(0, it);
    float sc[2][4];
#pragma unroll
    for (int i = 0; i < 2; i++) {
      sc[i][0] = (bf_lo(v[i].x) + bf_lo(v[2 + i].x)) + (bf_lo(v[4 + i].x) + bf_lo(v[6 + i].x));
      sc[i][1] = (bf_hi(v[i].x) + bf_hi(v[2 + i].x)) + (bf_hi(v[4 + i].x) + bf_hi(v[6 + i].x));
      sc[i][2] = (bf_lo(v[i].y) + bf_lo(v[2 + i].y)) + (bf_lo(v[4 + i].y) + bf_lo(v[6 + i].y));
      sc[i][3] = (bf_hi(v[i].y) + bf_hi(v[2 + i].y)) + (bf_hi(v[4 + i].y) + bf_hi(v[6 + i].y));
    }
    sts2(sb + OFF_BS1 + (w >> 1) * 512 + lane * 16 + (w & 1) * 8,
         pack_bf16(bf_lo(xn0) * (1.f + sc[1][0]) + sc[0][0], bf_hi(xn0) * (1.f + sc[1][1]) + sc[0][1]),
         pack_bf16(bf_lo(xn1) * (1.f + sc[1][2]) + sc[0][2], bf_hi(xn1) * (1.f + sc[1][3]) + sc[0][3]));
    mbar_wait(BAR(BAR_WQ + wg));
    load_a_t(aw, sb + OFF_WQ, w, lane);
    CLK(6);
    cbar();
    uint32_t b[4][4];
#pragma unroll
    for (int kk = 0; kk < 4; kk++) lds4(b[kk], sb + OFF_BS1 + kk * 512 + lane * 16);
    float d[4];
    mma128(d, aw, b);
    stg_u64(qpo, pack_bf16(d[0], d[1]), pack_bf16(d[2], d[3]));
    tstore = clk32();
    CLK(7);
    if (lane == 0) mbar_arrive(BAR(BAR_P1D));
    if (wg) {
#pragma unroll
      for (int i = 0; i < 16; i++) cf[i >> 2][i & 3] = silu2(cf[i >> 2][i & 3]);
    }
  }
  {
    const uint32_t* pq = pin(gs->QP[par] + (hI * 4 * 256 + tid) * 2);
    uint32_t* const qxo = pin(gs->QX[par] + (g * 32 + hI) * 256 + 64 * jI + 8 * w + 2 * t);
    uint2 v[4];
    wait_clk(tstore, T.D_QP);
    CLK(8);
    load_units<4, 512>(v, pq);
    const int it = check_units<4, 512>(v, pq, T.RB);
    CLK(9);
    ITS(1, it);
    sum4_to_smem(v, sb + OFF_BS2 + (16 * w + g) * 16 + t * 4);
    {
      const int mi = lane >> 3, r = lane & 7;
      const int row = 16 * w + 8 * (mi & 1) + r;
      mbar_wait(BAR(BAR_WUK));
#pragma unroll
      for (int ks = 0; ks < 8; ks++) {
        if (ks == 4) mbar_wait(BAR(BAR_WUK + 1));
        const int chunk = 2 * ks + (mi >> 1);
        ldsm4(aw[ks], sb + OFF_WUK + (chunk >> 3) * 16384 + row * 128 + (((chunk & 7) ^ r) << 4));
      }
    }
    CLK(10);
    cbar();
    uint32_t b[4][4];
#pragma unroll
    for (int kk = 0; kk < 4; kk++) ldsm4t(b[kk], sb + OFF_BS2 + (32 * kk + lane) * 16);
    float d[4];
    mma128(d, aw, b);
    const float sc = 0.08838834764831845f * 1.4426950408889634f;
    stg_u64(qxo, movm(pack_bf16(d[0] * sc, d[1] * sc)), movm(pack_bf16(d[2] * sc, d[3] * sc)));
    tstore = clk32();
    CLK(11);
    if (lane == 0) mbar_arrive(BAR(BAR_P2D));
  }
  if (wg) {
    const int mi = lane >> 3, r = lane & 7;
    const uint32_t a0 = sb + OFF_WM2 + (8 * (r >> 1) + (r & 1) + 2 * (mi >> 1)) * 32 + (mi & 1) * 16;
    mbar_wait(BAR(BAR_WM2));
#pragma unroll
    for (int s = 0; s < 8; s++) ldsm4t(aw[s], a0 + (128 * wq + 32 * (s >> 1) + 4 * (s & 1)) * 32);
    float d[4];
    mma128(d, aw, cf);
    sts4f(sb + OFF_P0B + (tid - 128) * 16, d[0], d[1], d[2], d[3]);
    if (lane == 0) mbar_arrive(BAR(BAR_P0BD));
    bar_sync(3, 128);
    if (w == 4) {
      float4 v[4];
#pragma unroll
      for (int i = 0; i < 4; i++) v[i] = ldsf4(sb + OFF_P0B + (i * 32 + lane) * 16);
      stg_u64(gs->MOD2[par] + cta * 64 + t * 16 + g * 2, movm(pack_bf16((v[0].x + v[1].x) + (v[2].x + v[3].x), (v[0].y + v[1].y) + (v[2].y + v[3].y))),
              movm(pack_bf16((v[0].z + v[1].z) + (v[2].z + v[3].z), (v[0].w + v[1].w) + (v[2].w + v[3].w))));
    }
    CLK(15);
  }
  {
    const uint32_t* qx = pin(gs->QX[par] + ((bs >> 3) * 32 + 16 * hh) * 256 + tid * 4);
    const int ch = tid & 63, h0 = tid >> 6;
    const uint32_t dst = sb + OFF_Q + (ch >> 3) * 2048 + h0 * 128;
    wait_clk(tstore, T.D_QX);
    CLK(12);
    uint4 v[4];
#pragma unroll
    for (int i = 0; i < 4; i++) v[i] = ldg_2u64(qx + i * 1024);
    int it = 0;
    while (true) {
      uint32_t mn = 0xffffffffu;
#pragma unroll
      for (int i = 0; i < 4; i++) mn = min(mn, min(v[i].y, v[i].w));
      if (mn != 0) break;
#pragma unroll
      for (int i = 0; i < 4; i++) if (v[i].y == 0 || v[i].w == 0) v[i] = ldg_2u64(qx + i * 1024);
      if (++it > SPIN_LIMIT) __trap();
    }
    CLK(13);
    ITS(2, it);
#pragma unroll
    for (int i = 0; i < 4; i++) sts4(dst + i * 512 + (((ch & 7) ^ ((4 * i + h0) & 7)) << 4), v[i]);
    asm volatile("fence.proxy.async.shared::cta;" ::: "memory");
    CLK(14);
    if (lane == 0) mbar_arrive(BAR(BAR_GO));
    cbar();
  }

  uint2 cbf[4], sbf[4];
  const uint32_t* const pcb = gs->MOD2[par] + 2048 + (16 * w + t) * 16 + g * 2;
  uint32_t thand;
  if (wg == 0) {
    float mh[4], lpart[4];
#pragma unroll
    for (int i = 0; i < 4; i++) { lpart[i] = 0.f; mh[i] = -INFINITY; }
    constexpr uint32_t dq = desc_lo(OFF_Q);
    const uint32_t ptw = sb + OFF_PT + (8 * (lane >> 4) + (lane & 7)) * 128 + (((2 * wq + ((lane >> 3) & 1)) ^ (lane & 7)) << 4);
    float S[8];
    auto softmax = [&](int tl) {
      float ps[4];
      auto write_p = [&](const float (&x)[8]) {
        float p[8];
#pragma unroll
        for (int i = 0; i < 8; i++) p[i] = ex2(x[i]);
        stsm4t(ptw + (tl & 1) * 2048, pack_bf16(p[0], p[1]), pack_bf16(p[2], p[3]), pack_bf16(p[4], p[5]), pack_bf16(p[6], p[7]));
        asm volatile("fence.proxy.async.shared::cta;" ::: "memory");
#pragma unroll
        for (int i = 0; i < 4; i++) ps[i] = p[4 * (i >> 1) + (i & 1)] + p[4 * (i >> 1) + 2 + (i & 1)];
      };
      float x[8];
#pragma unroll
      for (int i = 0; i < 8; i++) x[i] = S[i] - mh[2 * (i >> 2) + (i & 1)];
      write_p(x);
      const float ex = fmaxf(fmaxf(fmaxf(x[0], x[1]), fmaxf(x[2], x[3])), fmaxf(fmaxf(x[4], x[5]), fmaxf(x[6], x[7])));
      if (tl == 0 || bar_over(ex)) {
        float mx[4];
#pragma unroll
        for (int i = 0; i < 4; i++) mx[i] = fmaxf(S[4 * (i >> 1) + (i & 1)], S[4 * (i >> 1) + 2 + (i & 1)]);
        const float a = reduce_g(mx, lane, [](float u, float v) { return fmaxf(u, v); });
        stsf(sb + OFF_RED + wq * 64 + (8 * (lane >> 4) + 2 * t + ((lane >> 3) & 1)) * 4, a);
        bar_sync(2, 128);
#pragma unroll
        for (int jn = 0; jn < 2; jn++) {
          float m0 = mh[2 * jn], m1 = mh[2 * jn + 1];
#pragma unroll
          for (int i = 0; i < 4; i++) { const float2 v = ldsf2(sb + OFF_RED + i * 64 + (8 * jn + 2 * t) * 4); m0 = fmaxf(m0, v.x); m1 = fmaxf(m1, v.y); }
          const float a0 = ex2(mh[2 * jn] - m0), a1 = ex2(mh[2 * jn + 1] - m1);
          mh[2 * jn] = m0; mh[2 * jn + 1] = m1;
          lpart[2 * jn] *= a0; lpart[2 * jn + 1] *= a1;
          if (tid < 4) { sts2f(sb + OFF_ALPHA + (8 * jn + 2 * t) * 4, a0, a1); sts2f(sb + OFF_MH + (8 * jn + 2 * t) * 4, m0, m1); }
        }
#pragma unroll
        for (int i = 0; i < 8; i++) x[i] = S[i] - mh[2 * (i >> 2) + (i & 1)];
        write_p(x);
        cbar();
      }
#pragma unroll
      for (int i = 0; i < 4; i++) lpart[i] += ps[i];
    };
    uint32_t da = desc_lo(OFF_RING);
#pragma unroll 1
    for (int tl = 0; tl < 7; tl++) {
      uint32_t ok = 0;
#pragma unroll
      for (int u = 0; u < 4; u++) ok += mbar_test(BAR(BAR_FULL + 4 * tl + u));
      ok = __reduce_min_sync(~0u, ok);
      const uint32_t du = __shfl_sync(~0u, da, 0);
#pragma unroll
      for (int u = 0; u < 4; u++) {
        if (ok != 4) mbar_wait(BAR(BAR_FULL + 4 * tl + u));
        wg_fence();
#pragma unroll
        for (int k = 0; k < 8; k++) {
          const int i = 8 * u + k;
          if (i == 0) wgmma_n16<0, 0>(S, du, dq); else wgmma_n16<0, 1>(S, du + (i >> 2) * 512 + (i & 3) * 2, dq + (i >> 2) * 128 + (i & 3) * 2);
        }
        wg_commit();
      }
      wg_wait<0>();
      acc_fence(S);
      if (tl == 0) CLK(15);
      if (tl == 1) CLK(17);
      softmax(tl);
      if (tl == 0) CLK(16);
      if (tl == 1) CLK(18);
      if (tl == 3) CLK(19);
      if (tl == 6) CLK(20);
      da = (tl == 2 || tl == 5) ? da - 8192 : da + 4096;
    }
    if (cta < NFF) { load_units<4, 64>(sbf, pcb); load_units<4, 64>(cbf, pcb + 2048); }
    mbar_wait(BAR(BAR_ALLCLR));
    uint32_t* const mlo = pin(gs->ML + cta * 32 + (lane & 15) * 2);
#pragma unroll
    for (int i = 0; i < 32; i++) {
      if (i == 0 || i == 8 || i == 16 || i == 24 || i == 28) {
        if (i) wg_commit();
        mbar_wait(BAR(BAR_LAST + (i == 28 ? 4 : i >> 3)));
        if (i == 28) CLK(21);
        wg_fence();
      }
      if (i == 0) wgmma_n16<0, 0>(S, da, dq); else wgmma_n16<0, 1>(S, da + (i >> 2) * 512 + (i & 3) * 2, dq + (i >> 2) * 128 + (i & 3) * 2);
    }
    wg_commit();
    wg_wait<0>();
    acc_fence(S);
    CLK(22);
    softmax(7);
    CLK(23);
    thand = clk32();
    const float l = reduce_g(lpart, lane, [](float u, float v) { return u + v; });
    stsf(sb + OFF_REDL + wq * 64 + (8 * (lane >> 4) + 2 * t + ((lane >> 3) & 1)) * 4, l);
    bar_sync(2, 128);
    if (w == 0) {
      const uint32_t a = sb + OFF_REDL + (lane & 15) * 4;
      const float ls = (ldsf(a) + ldsf(a + 64)) + (ldsf(a + 128) + ldsf(a + 192));
      const uint32_t mw = lds1(sb + OFF_MH + (lane & 15) * 4);
      if (lane < 16) stg_u64(mlo, mw, __float_as_uint(ls));
    }
    CLK(24);
  } else {
    float O[8][8];
#pragma unroll
    for (int i = 0; i < 8; i++)
#pragma unroll
      for (int k = 0; k < 8; k++) O[i][k] = 0.f;
    constexpr uint32_t dp = desc_lo(OFF_PT);
    auto handover = [&](int tl) {
      if (tl == 0 || bar_over(0.f)) {
        cbar();
#pragma unroll
        for (int jn = 0; jn < 2; jn++) {
          const float2 a = ldsf2(sb + OFF_ALPHA + (8 * jn + 2 * t) * 4);
#pragma unroll
          for (int mb = 0; mb < 8; mb++) { O[mb][4 * jn] *= a.x; O[mb][4 * jn + 1] *= a.y; O[mb][4 * jn + 2] *= a.x; O[mb][4 * jn + 3] *= a.y; }
        }
      }
    };
    uint32_t da = desc_lo(OFF_RING);
#pragma unroll 1
    for (int tl = 0; tl < 7; tl++) {
      handover(tl);
      const uint32_t dpt = dp + (tl & 1) * 128;
      wg_fence();
#pragma unroll
      for (int i = 0; i < 32; i++) wgmma_n16<1, 1>(O[i >> 2], da + (i >> 2) * 512 + (i & 3) * 128, dpt + (i & 3) * 2);
      wg_commit();
      wg_wait<0>();
#pragma unroll
      for (int mb = 0; mb < 8; mb++) acc_fence(O[mb]);
      if (lane == 0) mbar_arrive(BAR(BAR_EMPTY + tl));
      if (tl == 0) CLK(16);
      if (tl == 1) CLK(18);
      if (tl == 3) CLK(19);
      if (tl == 6) CLK(20);
      da = (tl == 2 || tl == 5) ? da - 8192 : da + 4096;
    }
    if (cta < NFF) { load_units<4, 64>(sbf, pcb); load_units<4, 64>(cbf, pcb + 2048); }
    mbar_wait(BAR(BAR_ALLCLR));
    uint32_t* const x1o = pin(gs->X1 + ((16 * hh + 2 * t) * 4 * 64 + bs) * 64 + (wq * 8 + g) * 2);
    handover(7);
    CLK(23);
    thand = clk32();
    auto pv = [&](int j) {
      wg_fence();
#pragma unroll
      for (int i = 0; i < 8; i++) wgmma_n16<1, 1>(O[2 * j + (i >> 2)], desc_lo(65536) + (2 * j + (i >> 2)) * 512 + (i & 3) * 128, dp + 128 + (i & 3) * 2);
      wg_commit();
    };
    auto publish = [&](int j) {
      acc_fence(O[2 * j]); acc_fence(O[2 * j + 1]);
#pragma unroll
      for (int i = 0; i < 4; i++) {
        const int k = 4 * (i >> 1) + (i & 1);
        stg_u64(x1o + ((8 * (i >> 1) + (i & 1)) * 4 + j) * 4096, pack_bf16(O[2 * j][k], O[2 * j][k + 2]), pack_bf16(O[2 * j + 1][k], O[2 * j + 1][k + 2]));
      }
    };
    pv(0); pv(1);
    wg_wait<1>(); publish(0);
    pv(2);
    wg_wait<1>(); publish(1);
    pv(3);
    wg_wait<1>(); publish(2);
    wg_wait<0>(); publish(3);
    CLK(24);
  }

  {
    const uint32_t* pm = pin(gs->ML + ((w * 8 + (lane & 7)) * 32 + hI) * 2);
    const uint32_t* px = pin(gs->X1 + (cta * 64 + w * 8) * 64 + lane * 2);
    uint32_t* const x2o = pin(gs->X2 + (cta * 256 + tid) * 2);
    wait_clk(thand, T.D_ML);
    CLK(25);
    uint2 ml = ldg_u64(pm);
    uint2 v[8];
    load_units<8, 64>(v, px);
    {
      int it = 0;
      while (!__all_sync(~0u, ml.y != 0)) {
        backoff(T.RB);
        if (ml.y == 0) ml = ldg_u64(pm);
        if (++it > SPIN_LIMIT) __trap();
      }
      ITS(3, it);
    }
    CLK(26);
    float wv[8];
    {
      float M = __uint_as_float(ml.x);
      M = fmaxf(M, __shfl_xor_sync(~0u, M, 1)); M = fmaxf(M, __shfl_xor_sync(~0u, M, 2)); M = fmaxf(M, __shfl_xor_sync(~0u, M, 4));
      const float e = ex2(__uint_as_float(ml.x) - M);
      float L = e * __uint_as_float(ml.y);
      L += __shfl_xor_sync(~0u, L, 1); L += __shfl_xor_sync(~0u, L, 2); L += __shfl_xor_sync(~0u, L, 4);
      const float wn = __fdividef(e, L);
#pragma unroll
      for (int i = 0; i < 8; i++) wv[i] = __shfl_sync(~0u, wn, i);
    }
    mbar_wait(BAR(BAR_WUV + wg));
    load_a_t(aw, sb + OFF_WUV, w, lane);
    CLK(27);
    const int it = check_units<8, 64>(v, px, T.RB);
    CLK(28);
    ITS(4, it);
    float a0 = 0.f, a1 = 0.f, a2 = 0.f, a3 = 0.f;
#pragma unroll
    for (int i = 0; i < 8; i++) { a0 += wv[i] * bf_lo(v[i].x); a1 += wv[i] * bf_hi(v[i].x); a2 += wv[i] * bf_lo(v[i].y); a3 += wv[i] * bf_hi(v[i].y); }
    sts2(sb + OFF_BS4 + w * 272 + lane * 8, pack_bf16(a0, a1), pack_bf16(a2, a3));
    CLK(29);
    cbar();
    uint32_t b[4][4];
#pragma unroll
    for (int kk = 0; kk < 4; kk++) ldsm4(b[kk], sb + OFF_BS4 + (lane & 7) * 272 + (4 * kk + (lane >> 3)) * 16);
    float d[4];
    mma128(d, aw, b);
    stg_u64(x2o, pack_bf16(d[0], d[1]), pack_bf16(d[2], d[3]));
    tstore = clk32();
    CLK(30);
    if (lane == 0) mbar_arrive(BAR(BAR_X1R));
  }
  {
    uint32_t* const o = pin(gs->X3A + ((4 * (8 * jI + w) + t) * 32 + hI) * 16 + g * 2);
    const uint32_t* const x2i = pin(gs->X2 + (hI * 4 * 256 + tid) * 2);
    wait_clk(tstore, T.D_X2);
    uint2 v[4];
    load_units<4, 512>(v, x2i);
    mbar_wait(BAR(BAR_WO + wg));
    load_a_t(aw, sb + OFF_WO, w, lane);
    CLK(31);
    const int it = check_units<4, 512>(v, x2i, T.RB);
    CLK(32);
    ITS(5, it);
    sum4_to_smem(v, sb + OFF_BS5 + (16 * w + g) * 16 + t * 4);
    cbar();
    uint32_t b[4][4];
#pragma unroll
    for (int kk = 0; kk < 4; kk++) ldsm4t(b[kk], sb + OFF_BS5 + (32 * kk + lane) * 16);
    float d[4];
    mma128(d, aw, b);
    stg_u64(o, movm(pack_bf16(d[0], d[1])), movm(pack_bf16(d[2], d[3])));
    tstore = clk32();
    CLK(33);
    if (lane == 0) mbar_arrive(BAR(BAR_P5D));
  }
  if (cta < NFF) {
    const int mi = lane >> 3, r = lane & 7;
    uint32_t a1[4][4], a2[4][4];
    check_units<4, 64>(sbf, pcb, T.RB);
    check_units<4, 64>(cbf, pcb + 2048, T.RB);
    __syncwarp();
#pragma unroll
    for (int s = 0; s < 4; s++) { cbf[s].x = hadd2(cbf[s].x, ONE2); cbf[s].y = hadd2(cbf[s].y, ONE2); }
    mbar_wait(BAR(BAR_W1));
#pragma unroll
    for (int ks = 0; ks < 4; ks++) ldsm4t(a1[ks], sb + OFF_W1 + (64 * w + 16 * ks + 8 * (mi >> 1) + r) * 32 + (mi & 1) * 16);
    {
      float u[4] = {0.f, 0.f, 0.f, 0.f}, vv[4] = {0.f, 0.f, 0.f, 0.f};
#pragma unroll
      for (int s = 0; s < 4; s++) { mma16816(u, a1[s], cbf[s].x, cbf[s].y); mma16816(vv, a1[s], sbf[s].x, sbf[s].y); }
      sts4f(sb + OFF_REDU + tid * 16, u[0], u[1], u[2], u[3]);
      sts4f(sb + OFF_REDV + tid * 16, vv[0], vv[1], vv[2], vv[3]);
    }
    cbar();
    const int lp = (tid >> 2) & 31, kq = tid & 3;
    const int fo = (lp >> 2) + 8 * (kq >> 1), bo = 2 * (lp & 3) + (kq & 1);
    float U = 0.f, V = 0.f;
    if (tid < 128) {
#pragma unroll
      for (int i = 0; i < 8; i++) { U += ldsf(sb + OFF_REDU + i * 512 + tid * 4); V += ldsf(sb + OFF_REDV + i * 512 + tid * 4); }
    }
    const uint32_t* xb = pin(gs->X3B + (cta & (NREP - 1)) * 2048 + (16 * w + t) * 16 + g * 2);
    uint32_t* const ox = pin(gs->X4 + ((16 * w + t) * NFF + cta) * 16 + g * 2);
    CLK(34);
    wait_clk(tstore, T.D_X3B);
    uint2 x[4];
    load_units<4, 64>(x, xb);
    mbar_wait(BAR(BAR_W2));
#pragma unroll
    for (int mb = 0; mb < 4; mb++) ldsm4t(a2[mb], sb + OFF_W2 + w * 2048 + (8 * (mi >> 1) + r) * 128 + (((2 * mb + (mi & 1)) ^ r) << 4));
    CLK(35);
    const int it = check_units<4, 64>(x, xb, T.RB);
    __syncwarp();
    CLK(36);
    ITS(6, it);
    float G[2][4] = {{0.f, 0.f, 0.f, 0.f}, {0.f, 0.f, 0.f, 0.f}}, S[2][4] = {{0.f, 0.f, 0.f, 0.f}, {0.f, 0.f, 0.f, 0.f}};
#pragma unroll
    for (int s = 0; s < 4; s++) {
      const uint32_t sx[4] = {x[s].x, ONE2, x[s].y, ONE2};
      mma16816(S[s & 1], sx, x[s].x, x[s].y);
      mma16816(G[s & 1], a1[s], hmul2(x[s].x, cbf[s].x), hmul2(x[s].y, cbf[s].y));
    }
    sts4f(sb + OFF_REDG + tid * 16, G[0][0] + G[1][0], G[0][1] + G[1][1], G[0][2] + G[1][2], G[0][3] + G[1][3]);
    if (t == (g >> 1)) sts2f(sb + OFF_REDS + g * 80 + w * 8, (g & 1) ? S[0][3] + S[1][3] : S[0][2] + S[1][2], (g & 1) ? S[0][1] + S[1][1] : S[0][0] + S[1][0]);
    CLK(37);
    cbar();
    if (tid < 128) {
      float gv[8];
      float4 sv[4];
#pragma unroll
      for (int i = 0; i < 4; i++) sv[i] = ldsf4(sb + OFF_REDS + bo * 80 + i * 16);
#pragma unroll
      for (int i = 0; i < 8; i++) gv[i] = ldsf(sb + OFF_REDG + i * 512 + tid * 4);
      const float s1 = ((sv[0].x + sv[0].z) + (sv[1].x + sv[1].z)) + ((sv[2].x + sv[2].z) + (sv[3].x + sv[3].z));
      const float s2 = ((sv[0].y + sv[0].w) + (sv[1].y + sv[1].w)) + ((sv[2].y + sv[2].w) + (sv[3].y + sv[3].w));
      const float gsum = ((gv[0] + gv[1]) + (gv[2] + gv[3])) + ((gv[4] + gv[5]) + (gv[6] + gv[7]));
      const float mu = s1 * (1.f / 512.f);
      const float rs = rsqrtf(fmaxf(s2 * (1.f / 512.f) - mu * mu, 0.f) + 1e-5f);
      const float hv = fmaxf(rs * (gsum - mu * U) + V, 0.f);
      asm volatile("st.shared.u16 [%0], %1;" ::"r"(sb + OFF_H1 + fo * 16 + bo * 2), "h"(__bfloat16_as_ushort(__float2bfloat16(hv))) : "memory");
    }
    CLK(38);
    cbar();
    uint32_t b0, b1;
    ldsm2t(b0, b1, sb + OFF_H1 + (lane & 15) * 16);
    float o[4][4] = {{0.f, 0.f, 0.f, 0.f}, {0.f, 0.f, 0.f, 0.f}, {0.f, 0.f, 0.f, 0.f}, {0.f, 0.f, 0.f, 0.f}};
#pragma unroll
    for (int mb = 0; mb < 4; mb++) mma16816(o[mb], a2[mb], b0, b1);
#pragma unroll
    for (int mb = 0; mb < 4; mb++) stg_u64(ox + mb * 4 * NFF * 16, movm(pack_bf16(o[mb][0], o[mb][1])), movm(pack_bf16(o[mb][2], o[mb][3])));
    CLK(39);
    if (lane == 0) mbar_arrive(BAR(BAR_P7D));
  }
  CLK_DUMP();
}

typedef CUresult (*EncodeTiledFn)(CUtensorMap*, CUtensorMapDataType, cuuint32_t, void*, const cuuint64_t*, const cuuint64_t*,
                                  const cuuint32_t*, const cuuint32_t*, CUtensorMapInterleave, CUtensorMapSwizzle,
                                  CUtensorMapL2promotion, CUtensorMapFloatOOBfill);

struct Dim { uint64_t size, stride; uint32_t box; };
template <int R> void encode_map(EncodeTiledFn enc, CUtensorMap* m, const void* base, const Dim (&d)[R], CUtensorMapSwizzle sw, CUtensorMapL2promotion promo) {
  cuuint64_t dims[R], strides[R];
  cuuint32_t box[R], es[R];
  for (int i = 0; i < R; i++) { dims[i] = d[i].size; strides[i] = d[i].stride; box[i] = d[i].box; es[i] = 1; }
  enc(m, CU_TENSOR_MAP_DATA_TYPE_BFLOAT16, R, const_cast<void*>(base), dims, strides + 1, box, es, CU_TENSOR_MAP_INTERLEAVE_NONE, sw, promo,
      CU_TENSOR_MAP_FLOAT_OOB_FILL_NONE);
}

}

extern "C" void kernel_launch(void* const* d_in, const int* in_sizes, int n_in, void* d_out, int out_size) {
  (void)in_sizes; (void)n_in; (void)out_size;
  static EncodeTiledFn enc = nullptr;
  static Scratch* scratch = nullptr;
  if (!enc) {
    void* sp = nullptr;
    cudaGetSymbolAddress(&sp, g_s);
    scratch = (Scratch*)sp;
    void* fn = nullptr;
    cudaDriverEntryPointQueryResult q;
    cudaGetDriverEntryPoint("cuTensorMapEncodeTiled", &fn, cudaEnableDefault, &q);
    enc = (EncodeTiledFn)fn;
    cudaFuncSetAttribute(fused_decode_kernel, cudaFuncAttributeMaxDynamicSharedMemorySize, SMEM_BYTES);
  }
  const CUtensorMapSwizzle S128 = CU_TENSOR_MAP_SWIZZLE_128B, S0 = CU_TENSOR_MAP_SWIZZLE_NONE;
  const CUtensorMapL2promotion L0 = CU_TENSOR_MAP_L2_PROMOTION_NONE, L128 = CU_TENSOR_MAP_L2_PROMOTION_L2_128B;
  Params P;
  encode_map<2>(enc, &P.wq, d_in[2], {{4096, 2, 64}, {512, 8192, 64}}, S128, L0);
  encode_map<5>(enc, &P.wuk, d_in[3], {{4096, 2, 64}, {2, 8192, 2}, {4, 4 * 8192, 4}, {2, 2 * 8192, 2}, {32, 16 * 8192, 4}}, S128, L0);
  encode_map<2>(enc, &P.wm2, d_in[10], {{3072, 2, 16}, {512, 6144, 256}}, S0, L128);
  encode_map<3>(enc, &P.ckv2, d_in[1], {{64, 2, 64}, {8 * 4096, 1024, 64}, {8, 128, 2}}, S128, L0);
  encode_map<3>(enc, &P.ckv1, d_in[1], {{64, 2, 64}, {8 * 4096, 1024, 64}, {8, 128, 1}}, S128, L0);
  encode_map<5>(enc, &P.wuv, d_in[4], {{4096, 2, 64}, {2, 8 * 8192, 2}, {8, 64 * 8192, 2}, {8, 8192, 8}, {4, 16 * 8192, 2}}, S128, L0);
  encode_map<2>(enc, &P.wo, d_in[5], {{512, 2, 64}, {4096, 1024, 64}}, S128, L0);
  encode_map<2>(enc, &P.w1, d_in[7], {{1792, 2, FCH}, {512, 3584, 256}}, S0, L128);
  encode_map<3>(enc, &P.w2, d_in[8], {{64, 2, 64}, {1792, 1024, FCH}, {8, 128, 4}}, S128, L0);
  cudaLaunchConfig_t cfg = {};
  cfg.gridDim = dim3(NCTA);
  cfg.blockDim = dim3(NTHREADS);
  cfg.dynamicSmemBytes = SMEM_BYTES;
  cfg.stream = cudaStreamPerThread;
  cudaLaunchAttribute at[1];
  at[0].id = cudaLaunchAttributeClusterDimension;
  at[0].val.clusterDim.x = 2; at[0].val.clusterDim.y = 1; at[0].val.clusterDim.z = 1;
  cfg.attrs = at;
  cfg.numAttrs = 0;
  cudaLaunchKernelEx(&cfg, fused_decode_kernel, (__nv_bfloat16*)d_out, scratch, (const uint8_t*)d_in[10], (const uint8_t*)d_in[0],
                     (const uint8_t*)d_in[9],
                     P);
}
```

```cpp
#include <cuda_runtime.h>
#include <cuda.h>
#include <cuda_bf16.h>
#include <stdint.h>
#define V4 1

namespace {

constexpr int NCTA = 128;
constexpr int NTHREADS = 320;
constexpr int FCH = 16;
constexpr int NFF = 1792 / FCH;
constexpr int NSYNC = 4;
constexpr int NREP = 8;

constexpr uint32_t OFF_RING = 0;
constexpr uint32_t OFF_WUK = 131072;
constexpr uint32_t OFF_WQ = 131072 + 32768;
constexpr uint32_t OFF_WM2 = 65536 + 49152;
constexpr uint32_t OFF_WUV = 131072;
constexpr uint32_t OFF_WO = 131072 + 32768;
constexpr uint32_t OFF_W1 = 0;
constexpr uint32_t OFF_W2 = 16384;
constexpr uint32_t OFF_Q = 196608;
constexpr uint32_t OFF_PT = 212992;
constexpr uint32_t OFF_SCR = 217088;
constexpr uint32_t OFF_XS = 65536;
constexpr uint32_t OFF_CS = 65536 + 8192;
constexpr uint32_t OFF_P0S = 65536 + 16384;
constexpr uint32_t OFF_BS1 = OFF_SCR + 2048;
constexpr uint32_t OFF_BS2 = OFF_SCR + 4096;
constexpr uint32_t OFF_P0B = OFF_SCR + 6144;
constexpr uint32_t OFF_XN = OFF_SCR + 8192;
constexpr uint32_t OFF_RED = OFF_SCR + 10496;
constexpr uint32_t OFF_ALPHA = OFF_SCR + 11072;
constexpr uint32_t OFF_WV = OFF_SCR + 6144;
constexpr uint32_t OFF_TS = OFF_SCR + 11136;
constexpr uint32_t OFF_BARS = OFF_SCR + 11264;
constexpr uint32_t SMEM_BYTES = OFF_BARS + 512;
constexpr uint32_t OFF_BS4 = OFF_Q;
constexpr uint32_t OFF_H1 = OFF_Q + 2304;
constexpr uint32_t OFF_REDS = OFF_Q + 2560;
constexpr uint32_t OFF_BS5 = OFF_Q + 4096;
constexpr uint32_t OFF_REDG = OFF_Q + 8192;
constexpr uint32_t OFF_REDU = OFF_Q + 12288;
constexpr uint32_t OFF_REDV = OFF_SCR;

constexpr int BAR_FULL = 0;
constexpr int BAR_LAST = 28;
constexpr int BAR_WUK = 33, BAR_WM2 = 35, BAR_WUV = 36, BAR_WO = 38, BAR_W1 = 40, BAR_W2 = 41;
constexpr int BAR_ALLCLR = 42, BAR_TS = 43, BAR_WV = 44;
constexpr int BAR_EMPTY = 45;
constexpr int BAR_P0BD = 52;
constexpr int BAR_P1D = 53, BAR_P2D = 54;
constexpr int BAR_P5D = 55, BAR_P7D = 56;
constexpr int NBARS = 57;
constexpr int BAR_XC = 57, BAR_WQ = 58;
constexpr int BAR_C = 60, BAR_END = 61;
constexpr uint32_t SB = 1024;

#define TUNE_LIST(X) \
  X(PC_T0, 340) X(PC_XC, 0) X(PC_C, 0) X(PC_P1, 320) X(PC_P2, 322) X(PC_STAG, 390) X(PC_DS, 0) X(PC_SL, 500) X(PC_W, 4) X(PC_NW, 10) \
  X(PW_A, -1) X(PW_0, 160) X(PW_ST, 0) X(PW_UV, 380) X(PW_G, 630) X(PW_O, 335) X(PW_F, 410) X(CLR_T0, 5000) X(CLR_CLK, 340) \
  X(D_MOD, 1500) X(D_QP, 1300) X(D_QX, 1300) X(D_TS, 1000) X(A_M, 2000) X(D_X1, 1400) X(A_X1, 2150) X(A_X1J, 60) \
  X(D_X2, 350) X(A_X2, 5180) X(D_X3A, 330) X(A_X3A, 0) X(D_X3B, 1780) X(D_FIN, 560) X(D_FIN2, 2300) X(RB, 0)
struct Tune {
#define X(n, v) static constexpr int n = v;
  TUNE_LIST(X)
#undef X
};

#define PFENCE 0
#define PVV 0
#define CLRSIDE 1
struct Scratch {
  uint32_t MOD1[2][4 * 64 * 64];
  uint32_t MOD2[2][128 * 64];
  uint32_t QP[2][128 * 256 * 2];
  uint32_t QX[2][8 * 32 * 256];
  uint32_t ML[32 * 64 * 2];
  uint32_t X1[128 * 64 * 64];
  uint32_t X2[128 * 256 * 2];
  uint32_t X3A[128 * 32 * 16];
  uint32_t X3B[NREP * 128 * 16];
  uint32_t X4[128 * NFF * 16];
  uint32_t epoch;
  uint32_t pad[31];
  uint32_t sync[NSYNC][32];
};
__device__ Scratch g_s;

#define CLK_DECL
#define CLK(i) do {} while (0)
#define CLK_DUMP() do {} while (0)
#define ITS(i, v) do {} while (0)

struct Params {
  CUtensorMap wq, wuk, wm2, ckv2, ckv1, wuv, wo, w1, w2;
};

__device__ __forceinline__ void mbar_init(uint32_t bar, int cnt) { asm volatile("mbarrier.init.shared::cta.b64 [%0], %1;" ::"r"(bar), "r"(cnt)); }
__device__ __forceinline__ void mbar_expect(uint32_t bar, uint32_t bytes) { asm volatile("mbarrier.arrive.expect_tx.shared::cta.b64 _, [%0], %1;" ::"r"(bar), "r"(bytes) : "memory"); }
__device__ __forceinline__ void mbar_arrive(uint32_t bar) { asm volatile("mbarrier.arrive.shared::cta.b64 _, [%0];" ::"r"(bar) : "memory"); }
__device__ __forceinline__ uint32_t clk32() { unsigned long long c; asm volatile("mov.u64 %0, %%clock64;" : "=l"(c) :: "memory"); return (uint32_t)c; }
__device__ __forceinline__ uint32_t gtime32() { uint32_t c; asm volatile("mov.u32 %0, %%globaltimer_lo;" : "=r"(c) :: "memory"); return c; }
__device__ __forceinline__ void wait_clk(uint32_t t0, int clocks) { while ((int)(clk32() - t0) < clocks) {} }
__device__ __forceinline__ void backoff(int clocks) { if (clocks > 0) wait_clk(clk32(), clocks); }
__device__ __forceinline__ void until_ns(uint32_t ns) { while ((int)(gtime32() - ns) < 0) {} }
__device__ __forceinline__ void slot(uint32_t& tn, int slack) {
  uint32_t now;
  do { now = gtime32(); } while ((int)(now - tn) < 0);
  if ((int)(now - tn) > slack) tn = now - slack;
}
template <typename T> __device__ __forceinline__ T* pin(T* p) { asm volatile("" : "+l"(p)); return p; }
constexpr int SPIN_LIMIT = 1 << 22;
__device__ __forceinline__ void mbar_wait(uint32_t bar) {
  asm volatile("{\n.reg .pred p;\n.reg .u32 c;\nmov.u32 c, 0;\n"
               "MW_LOOP:\nmbarrier.try_wait.parity.shared::cta.b64 p, [%0], 0;\n@p bra MW_DONE;\n"
               "add.u32 c, c, 1;\nsetp.lt.u32 p, c, 4194304;\n@p bra MW_LOOP;\ntrap;\nMW_DONE:\n}"
               ::"r"(bar) : "memory");
}
__device__ __forceinline__ bool mbar_test(uint32_t bar) {
  uint32_t ok;
  asm volatile("{\n.reg .pred p;\nmbarrier.test_wait.parity.shared::cta.b64 p, [%1], 0;\nselp.u32 %0,1,0,p;\n}" : "=r"(ok) : "r"(bar) : "memory");
  return ok;
}
__device__ __forceinline__ void tma2d(uint32_t dst, const CUtensorMap* m, int c0, int c1, uint32_t bar, uint64_t pol) {
  asm volatile("cp.async.bulk.tensor.2d.shared::cluster.global.mbarrier::complete_tx::bytes.L2::cache_hint [%0], [%1, {%3,%4}], [%2], %5;"
               ::"r"(dst), "l"(m), "r"(bar), "r"(c0), "r"(c1), "l"(pol) : "memory");
}
__device__ __forceinline__ void tma2d_nohint(uint32_t dst, const CUtensorMap* m, int c0, int c1, uint32_t bar) {
  asm volatile("cp.async.bulk.tensor.2d.shared::cluster.global.mbarrier::complete_tx::bytes [%0], [%1, {%3,%4}], [%2];"
               ::"r"(dst), "l"(m), "r"(bar), "r"(c0), "r"(c1) : "memory");
}
__device__ __forceinline__ void tma3d(uint32_t dst, const CUtensorMap* m, int c0, int c1, int c2, uint32_t bar, uint64_t pol) {
  asm volatile("cp.async.bulk.tensor.3d.shared::cluster.global.mbarrier::complete_tx::bytes.L2::cache_hint [%0], [%1, {%3,%4,%5}], [%2], %6;"
               ::"r"(dst), "l"(m), "r"(bar), "r"(c0), "r"(c1), "r"(c2), "l"(pol) : "memory");
}
__device__ __forceinline__ void tma5d(uint32_t dst, const CUtensorMap* m, int c0, int c1, int c2, int c3, int c4, uint32_t bar, uint64_t pol) {
  asm volatile("cp.async.bulk.tensor.5d.shared::cluster.global.mbarrier::complete_tx::bytes.L2::cache_hint [%0], [%1, {%3,%4,%5,%6,%7}], [%2], %8;"
               ::"r"(dst), "l"(m), "r"(bar), "r"(c0), "r"(c1), "r"(c2), "r"(c3), "r"(c4), "l"(pol) : "memory");
}
__device__ __forceinline__ void bulk_ld(uint32_t dst, const void* src, uint32_t bytes, uint32_t bar) {
  asm volatile("cp.async.bulk.shared::cluster.global.mbarrier::complete_tx::bytes [%0], [%1], %2, [%3];" ::"r"(dst), "l"(src), "r"(bytes), "r"(bar) : "memory");
}
__device__ __forceinline__ void bar_sync(int id, int n) { asm volatile("barrier.cta.sync.aligned %0, %1;" ::"r"(id), "r"(n) : "memory"); }
__device__ __forceinline__ void cbar() { asm volatile("barrier.cta.sync.aligned 1, 256;" ::: "memory"); }
__device__ __forceinline__ bool bar_over(float ex) {
  uint32_t over;
  asm volatile("{\n.reg .pred p, q;\nsetp.gtu.f32 p, %1, 0f41F00000;\nbarrier.cta.red.or.aligned.pred q, 4, 256, p;\nselp.u32 %0, 1, 0, q;\n}"
               : "=r"(over) : "f"(ex) : "memory");
  return over;
}

__device__ __forceinline__ uint32_t ldg_nc1(const void* p) { uint32_t v; asm volatile("ld.global.nc.L1::no_allocate.u32 %0, [%1];" : "=r"(v) : "l"(p)); return v; }
__device__ __forceinline__ uint2 ldg_nc2(const void* p) { uint2 v; asm volatile("ld.global.nc.v2.u32 {%0,%1}, [%2];" : "=r"(v.x), "=r"(v.y) : "l"(p)); return v; }
__device__ __forceinline__ uint4 ldg_nc4(const void* p) { uint4 v; asm volatile("ld.global.nc.L1::no_allocate.v4.u32 {%0,%1,%2,%3}, [%4];" : "=r"(v.x), "=r"(v.y), "=r"(v.z), "=r"(v.w) : "l"(p)); return v; }
__device__ __forceinline__ uint32_t ldg_rlx1(const void* p) { uint32_t v; asm volatile("ld.relaxed.gpu.global.u32 %0, [%1];" : "=r"(v) : "l"(p) : "memory"); return v; }
__device__ __forceinline__ void stg4(void* p, uint4 v) { asm volatile("st.relaxed.gpu.global.v4.u32 [%0], {%1,%2,%3,%4};" ::"l"(p), "r"(v.x), "r"(v.y), "r"(v.z), "r"(v.w) : "memory"); }
__device__ __forceinline__ void stg1(void* p, uint32_t a) { asm volatile("st.relaxed.gpu.global.u32 [%0], %1;" ::"l"(p), "r"(a) : "memory"); }
__device__ __forceinline__ uint32_t nz(uint32_t w) { return max(w, 1u); }
__device__ __forceinline__ uint2 ldg_u64(const void* p) {
  uint2 v; asm volatile("{\n.reg .b64 a;\nld.relaxed.gpu.global.b64 a, [%2];\nmov.b64 {%0,%1}, a;\n}" : "=r"(v.x), "=r"(v.y) : "l"(p) : "memory"); return v;
}
__device__ __forceinline__ uint4 ldg_2u64(const void* p) {
  uint4 v; asm volatile("{\n.reg .b64 a, b;\nld.relaxed.gpu.global.v2.b64 {a, b}, [%4];\nmov.b64 {%0,%1}, a;\nmov.b64 {%2,%3}, b;\n}" : "=r"(v.x), "=r"(v.y), "=r"(v.z), "=r"(v.w) : "l"(p) : "memory"); return v;
}
__device__ __forceinline__ void stg_u64(void* p, uint32_t x, uint32_t y) {
  asm volatile("{\n.reg .b64 a;\nmov.b64 a, {%1,%2};\nst.relaxed.gpu.global.b64 [%0], a;\n}" ::"l"(p), "r"(x), "r"(max(y, 1u)) : "memory");
}
__device__ __forceinline__ void stg_2u64(void* p, uint4 v) {
  asm volatile("{\n.reg .b64 a, b;\nmov.b64 a, {%1,%2};\nmov.b64 b, {%3,%4};\nst.relaxed.gpu.global.v2.b64 [%0], {a, b};\n}" ::"l"(p), "r"(v.x), "r"(max(v.y, 1u)), "r"(v.z), "r"(max(v.w, 1u)) : "memory");
}

__device__ __forceinline__ uint32_t pack_bf16(float lo, float hi) { uint32_t r; asm("cvt.rn.bf16x2.f32 %0, %1, %2;" : "=r"(r) : "f"(hi), "f"(lo)); return r; }
__device__ __forceinline__ float bf_lo(uint32_t w) { return __uint_as_float(w << 16); }
__device__ __forceinline__ float bf_hi(uint32_t w) { return __uint_as_float(w & 0xffff0000u); }
__device__ __forceinline__ float ex2(float x) { float r; asm("ex2.approx.ftz.f32 %0, %1;" : "=f"(r) : "f"(x)); return r; }
__device__ __forceinline__ uint32_t hmul2(uint32_t a, uint32_t b) { uint32_t r; asm("mul.rn.bf16x2 %0, %1, %2;" : "=r"(r) : "r"(a), "r"(b)); return r; }
__device__ __forceinline__ uint32_t hadd2(uint32_t a, uint32_t b) { uint32_t r; asm("add.rn.bf16x2 %0, %1, %2;" : "=r"(r) : "r"(a), "r"(b)); return r; }
__device__ __forceinline__ uint32_t hfma2(uint32_t a, uint32_t b, uint32_t c) { uint32_t r; asm("fma.rn.bf16x2 %0, %1, %2, %3;" : "=r"(r) : "r"(a), "r"(b), "r"(c)); return r; }
__device__ __forceinline__ uint32_t silu2(uint32_t v) { const float a = bf_lo(v), b = bf_hi(v); return pack_bf16(__fdividef(a, 1.f + __expf(-a)), __fdividef(b, 1.f + __expf(-b))); }
constexpr uint32_t ONE2 = 0x3f803f80u;

__device__ __forceinline__ void ldsm4(uint32_t (&r)[4], uint32_t a) { asm volatile("ldmatrix.sync.aligned.m8n8.x4.shared.b16 {%0,%1,%2,%3}, [%4];" : "=r"(r[0]), "=r"(r[1]), "=r"(r[2]), "=r"(r[3]) : "r"(a) : "memory"); }
__device__ __forceinline__ void ldsm4t(uint32_t (&r)[4], uint32_t a) { asm volatile("ldmatrix.sync.aligned.m8n8.x4.trans.shared.b16 {%0,%1,%2,%3}, [%4];" : "=r"(r[0]), "=r"(r[1]), "=r"(r[2]), "=r"(r[3]) : "r"(a) : "memory"); }
__device__ __forceinline__ void ldsm2t(uint32_t& r0, uint32_t& r1, uint32_t a) { asm volatile("ldmatrix.sync.aligned.m8n8.x2.trans.shared.b16 {%0,%1}, [%2];" : "=r"(r0), "=r"(r1) : "r"(a) : "memory"); }
__device__ __forceinline__ void stsm4t(uint32_t a, uint32_t r0, uint32_t r1, uint32_t r2, uint32_t r3) { asm volatile("stmatrix.sync.aligned.m8n8.x4.trans.shared.b16 [%0], {%1,%2,%3,%4};" ::"r"(a), "r"(r0), "r"(r1), "r"(r2), "r"(r3) : "memory"); }
__device__ __forceinline__ uint32_t movm(uint32_t a) { uint32_t d; asm volatile("movmatrix.sync.aligned.m8n8.trans.b16 %0, %1;" : "=r"(d) : "r"(a)); return d; }
__device__ __forceinline__ void mma16816(float (&d)[4], const uint32_t (&a)[4], uint32_t b0, uint32_t b1) {
  asm volatile("mma.sync.aligned.m16n8k16.row.col.f32.bf16.bf16.f32 {%0,%1,%2,%3}, {%4,%5,%6,%7}, {%8,%9}, {%0,%1,%2,%3};"
               : "+f"(d[0]), "+f"(d[1]), "+f"(d[2]), "+f"(d[3]) : "r"(a[0]), "r"(a[1]), "r"(a[2]), "r"(a[3]), "r"(b0), "r"(b1));
}
__device__ __forceinline__ void sts1(uint32_t a, uint32_t v) { asm volatile("st.shared.u32 [%0], %1;" ::"r"(a), "r"(v) : "memory"); }
__device__ __forceinline__ void sts2(uint32_t a, uint32_t x, uint32_t y) { asm volatile("st.shared.v2.u32 [%0], {%1,%2};" ::"r"(a), "r"(x), "r"(y) : "memory"); }
__device__ __forceinline__ void sts4(uint32_t a, uint4 v) { asm volatile("st.shared.v4.u32 [%0], {%1,%2,%3,%4};" ::"r"(a), "r"(v.x), "r"(v.y), "r"(v.z), "r"(v.w) : "memory"); }
__device__ __forceinline__ void sts2f(uint32_t a, float x, float y) { asm volatile("st.shared.v2.f32 [%0], {%1,%2};" ::"r"(a), "f"(x), "f"(y) : "memory"); }
__device__ __forceinline__ void sts4f(uint32_t a, float x, float y, float z, float w) { asm volatile("st.shared.v4.f32 [%0], {%1,%2,%3,%4};" ::"r"(a), "f"(x), "f"(y), "f"(z), "f"(w) : "memory"); }
__device__ __forceinline__ void stsf(uint32_t a, float v) { asm volatile("st.shared.f32 [%0], %1;" ::"r"(a), "f"(v) : "memory"); }
__device__ __forceinline__ uint32_t lds1(uint32_t a) { uint32_t v; asm volatile("ld.shared.u32 %0, [%1];" : "=r"(v) : "r"(a) : "memory"); return v; }
__device__ __forceinline__ float ldsf(uint32_t a) { float v; asm volatile("ld.shared.f32 %0, [%1];" : "=f"(v) : "r"(a) : "memory"); return v; }
__device__ __forceinline__ float2 ldsf2(uint32_t a) { float2 v; asm volatile("ld.shared.v2.f32 {%0,%1}, [%2];" : "=f"(v.x), "=f"(v.y) : "r"(a) : "memory"); return v; }
__device__ __forceinline__ float4 ldsf4(uint32_t a) { float4 v; asm volatile("ld.shared.v4.f32 {%0,%1,%2,%3}, [%4];" : "=f"(v.x), "=f"(v.y), "=f"(v.z), "=f"(v.w) : "r"(a) : "memory"); return v; }
__device__ __forceinline__ void lds4(uint32_t (&r)[4], uint32_t a) { asm volatile("ld.shared.v4.u32 {%0,%1,%2,%3}, [%4];" : "=r"(r[0]), "=r"(r[1]), "=r"(r[2]), "=r"(r[3]) : "r"(a) : "memory"); }

__device__ __forceinline__ void wg_fence() { asm volatile("wgmma.fence.sync.aligned;" ::: "memory"); }
__device__ __forceinline__ void wg_commit() { asm volatile("wgmma.commit_group.sync.aligned;" ::: "memory"); }
template <int N> __device__ __forceinline__ void wg_wait() { asm volatile("wgmma.wait_group.sync.aligned %0;" ::"n"(N) : "memory"); }
__host__ __device__ constexpr uint32_t desc_lo(uint32_t off) { return ((SB + off) >> 4) | 0x10000u; }
template <int TA, int ACC> __device__ __forceinline__ void wgmma_n16(float (&d)[8], uint32_t da, uint32_t db) {
  asm volatile("{\n.reg .b64 da, db;\nmov.b64 da, {%8, 0x40000040};\nmov.b64 db, {%9, 0x40000040};\n"
               "wgmma.mma_async.sync.aligned.m64n16k16.f32.bf16.bf16 {%0,%1,%2,%3,%4,%5,%6,%7}, da, db, %11, 1, 1, %10, 0;\n}"
               : "+f"(d[0]), "+f"(d[1]), "+f"(d[2]), "+f"(d[3]), "+f"(d[4]), "+f"(d[5]), "+f"(d[6]), "+f"(d[7])
               : "r"(da), "r"(db), "n"(TA), "n"(ACC));
}
__device__ __forceinline__ void wgmma_n16_ones(float (&d)[8], uint32_t one, uint32_t db) {
  asm volatile("{\n.reg .b64 db;\nmov.b64 db, {%9, 0x40000040};\n"
               "wgmma.mma_async.sync.aligned.m64n16k16.f32.bf16.bf16 {%0,%1,%2,%3,%4,%5,%6,%7}, {%8,%8,%8,%8}, db, 1, 1, 1, 0;\n}"
               : "+f"(d[0]), "+f"(d[1]), "+f"(d[2]), "+f"(d[3]), "+f"(d[4]), "+f"(d[5]), "+f"(d[6]), "+f"(d[7])
               : "r"(one), "r"(db));
}
__device__ __forceinline__ void acc_fence(float (&d)[8]) {
  asm volatile("" : "+f"(d[0]), "+f"(d[1]), "+f"(d[2]), "+f"(d[3]), "+f"(d[4]), "+f"(d[5]), "+f"(d[6]), "+f"(d[7]) :: "memory");
}

template <int N, int STRIDE> __device__ __forceinline__ void load_units(uint2 (&v)[N], const uint32_t* p) {
#pragma unroll
  for (int i = 0; i < N; i++) v[i] = ldg_u64(p + i * STRIDE);
}
template <int N, int STRIDE> __device__ __forceinline__ int check_units(uint2 (&v)[N], const uint32_t* p, int rb) {
  int it = 0;
  while (true) {
    uint32_t mn = v[0].y;
#pragma unroll
    for (int i = 1; i < N; i++) mn = min(mn, v[i].y);
    if (mn != 0) break;
    backoff(rb);
#pragma unroll
    for (int i = 0; i < N; i++) if (v[i].y == 0) v[i] = ldg_u64(p + i * STRIDE);
    if (++it > SPIN_LIMIT) __trap();
  }
  return it;
}
__device__ __forceinline__ void sum4_to_smem(const uint2 (&v)[4], uint32_t dst) {
  const float c0 = (bf_lo(v[0].x) + bf_lo(v[1].x)) + (bf_lo(v[2].x) + bf_lo(v[3].x));
  const float c1 = (bf_hi(v[0].x) + bf_hi(v[1].x)) + (bf_hi(v[2].x) + bf_hi(v[3].x));
  const float c2 = (bf_lo(v[0].y) + bf_lo(v[1].y)) + (bf_lo(v[2].y) + bf_lo(v[3].y));
  const float c3 = (bf_hi(v[0].y) + bf_hi(v[1].y)) + (bf_hi(v[2].y) + bf_hi(v[3].y));
  sts1(dst, pack_bf16(c0, c1));
  sts1(dst + 128, pack_bf16(c2, c3));
}
__device__ __forceinline__ void load_a_t(uint32_t (&a)[8][4], uint32_t wbase, int w, int lane) {
  const int mi = lane >> 3, r = lane & 7;
  const uint32_t base = wbase + (w >> 2) * 16384 + (8 * (mi >> 1) + r) * 128 + (((2 * (w & 3) + (mi & 1)) ^ r) << 4);
#pragma unroll
  for (int ks = 0; ks < 8; ks++) ldsm4t(a[ks], base + ks * 2048);
}
__device__ __forceinline__ void mma128(float (&d)[4], const uint32_t (&a)[8][4], const uint32_t (&b)[4][4]) {
  float e[4][4] = {{0.f, 0.f, 0.f, 0.f}, {0.f, 0.f, 0.f, 0.f}, {0.f, 0.f, 0.f, 0.f}, {0.f, 0.f, 0.f, 0.f}};
#pragma unroll
  for (int kk = 0; kk < 4; kk++) { mma16816(e[(2 * kk) & 3], a[2 * kk], b[kk][0], b[kk][1]); mma16816(e[(2 * kk + 1) & 3], a[2 * kk + 1], b[kk][2], b[kk][3]); }
#pragma unroll
  for (int i = 0; i < 4; i++) d[i] = (e[0][i] + e[1][i]) + (e[2][i] + e[3][i]);
}
template <int NP> __device__ __forceinline__ int sum_pieces(const uint32_t* p0, int g, int t, float& v0, float& v1, int rb) {
  constexpr int NL = NP / 8;
  uint32_t v[NL][4];
#pragma unroll
  for (int i = 0; i < NL; i++) { const uint4 x = ldg_2u64(p0 + i * 128); v[i][0] = x.x; v[i][1] = x.y; v[i][2] = x.z; v[i][3] = x.w; }
  int it = 0;
  while (true) {
    uint32_t mn = 0xffffffffu;
#pragma unroll
    for (int i = 0; i < NL; i++) mn = min(mn, min(v[i][1], v[i][3]));
    if (mn != 0) break;
    backoff(rb);
#pragma unroll
    for (int i = 0; i < NL; i++)
      if (v[i][1] == 0 || v[i][3] == 0) { const uint4 x = ldg_2u64(p0 + i * 128); v[i][0] = x.x; v[i][1] = x.y; v[i][2] = x.z; v[i][3] = x.w; }
    if (++it > SPIN_LIMIT) __trap();
  }
  __syncwarp();
  const uint32_t one = (g & 1) ? 0x3f800000u : 0x00003f80u;
  const uint32_t b0 = (g & 2) ? 0u : one, b1 = (g & 2) ? one : 0u;
  float d[4][4] = {{0.f, 0.f, 0.f, 0.f}, {0.f, 0.f, 0.f, 0.f}, {0.f, 0.f, 0.f, 0.f}, {0.f, 0.f, 0.f, 0.f}};
#pragma unroll
  for (int i = 0; i < NL; i++) mma16816(d[i & 3], v[i], b0, b1);
  const bool up = t & 2;
  const float x0 = up ? (d[0][2] + d[1][2]) + (d[2][2] + d[3][2]) : (d[0][0] + d[1][0]) + (d[2][0] + d[3][0]);
  const float x1 = up ? (d[0][3] + d[1][3]) + (d[2][3] + d[3][3]) : (d[0][1] + d[1][1]) + (d[2][1] + d[3][1]);
  v0 = x0 + __shfl_xor_sync(~0u, x0, 16);
  v1 = x1 + __shfl_xor_sync(~0u, x1, 16);
  return it;
}
template <typename F> __device__ __forceinline__ float reduce_g(const float (&x)[4], int lane, F f) {
  const bool u4 = lane & 16, u3 = lane & 8;
  const float a0 = f(u4 ? x[2] : x[0], __shfl_xor_sync(~0u, u4 ? x[0] : x[2], 16));
  const float a1 = f(u4 ? x[3] : x[1], __shfl_xor_sync(~0u, u4 ? x[1] : x[3], 16));
  const float b = f(u3 ? a1 : a0, __shfl_xor_sync(~0u, u3 ? a0 : a1, 8));
  return f(b, __shfl_xor_sync(~0u, b, 4));
}

__global__ void __launch_bounds__(NTHREADS, 1)
fused_decode_kernel(__nv_bfloat16* __restrict__ gout, Scratch* __restrict__ gs, const uint8_t* __restrict__ gwmod,
                    const uint8_t* __restrict__ gx, const uint8_t* __restrict__ gc,
                    const __grid_constant__ Params P) {
  constexpr Tune T{};
  extern __shared__ __align__(1024) uint8_t smem_raw[];
  const uint32_t sb = (uint32_t)__cvta_generic_to_shared(smem_raw);
  const int tid = threadIdx.x, lane = tid & 31;
  const int w = __shfl_sync(0xffffffffu, tid >> 5, 0);
  const int cta = blockIdx.x;
  const uint32_t bars = sb + OFF_BARS;
  auto BAR = [&](int i) { return bars + 8 * i; };
  const int g = lane >> 2, t = lane & 3;
  const int hI = cta >> 2, jI = cta & 3;
  const int bs = cta >> 1, hh = cta & 1;

  CLK_DECL;
  CLK(0);
  if (w == 8) {
    CLK(7);
    const uint32_t t_entry = gtime32();
    CLK(8);
    if (lane == 0) {
      if ((sb & 0xffffff) != SB) __trap();
      mbar_init(BAR(BAR_WQ), 1); mbar_init(BAR(BAR_WQ + 1), 1); mbar_init(BAR(BAR_XC), 1); mbar_init(BAR(BAR_C), 1);
      asm volatile("fence.mbarrier_init.release.cluster;" ::: "memory");
      asm volatile("prefetch.tensormap [%0];" ::"l"(&P.wq) : "memory");
      mbar_expect(BAR(BAR_XC), 8192); mbar_expect(BAR(BAR_C), 8192); mbar_expect(BAR(BAR_WQ), 16384); mbar_expect(BAR(BAR_WQ + 1), 16384);
      CLK(9);
    }
    __syncwarp();
    asm volatile("barrier.cta.arrive.aligned 0, %0;" ::"n"(NTHREADS) : "memory");
    CLK(10);
    uint32_t tn = t_entry + T.PC_T0 + ((bs * 37) & 63) * T.PC_STAG / 64;
    const int h = hI, j = jI;
    if (lane == 0) {
      uint64_t pol; asm volatile("createpolicy.fractional.L2::evict_first.b64 %0, 1.0;" : "=l"(pol));
#pragma unroll
      for (int u = 0; u < 4; u++) {
        until_ns(tn + u * T.PC_P1);
        if (u == 0) CLK(11);
        tma2d(sb + OFF_WQ + u * 8192, &P.wq, 128 * h + 64 * (u >> 1), 128 * j + 64 * (u & 1), BAR(BAR_WQ + (u >> 1)), pol);
        if (u == T.PC_XC) {
#pragma unroll
          for (int i = 0; i < 4; i++) { const int o = ((i + cta) & 3) * 2048; bulk_ld(sb + OFF_XS + o, gx + o, 2048, BAR(BAR_XC)); }
        }
        if (u == T.PC_C) {
#pragma unroll
          for (int i = 0; i < 4; i++) { const int o = ((i + cta) & 3) * 2048; bulk_ld(sb + OFF_CS + o, gc + o, 2048, BAR(BAR_C)); }
        }
        if (u == 0) {
          CLK(1);
          asm volatile("prefetch.tensormap [%0];" ::"l"(&P.wuk) : "memory");
          asm volatile("prefetch.tensormap [%0];" ::"l"(&P.wm2) : "memory");
          asm volatile("prefetch.tensormap [%0];" ::"l"(&P.ckv2) : "memory");
        }
      }
    }
    __syncwarp();
    tn += 4 * T.PC_P1;
    bar_sync(5, 64);
    if (lane == 0) {
      uint64_t pol; asm volatile("createpolicy.fractional.L2::evict_first.b64 %0, 1.0;" : "=l"(pol));
#pragma unroll
      for (int u = 0; u < 4; u++) {
        if ((u & 1) == (T.PC_W > 3) && T.PC_NW) mbar_wait(BAR(BAR_WQ + (u >> 1)));
        slot(tn, T.PC_SL);
        tma5d(sb + OFF_WUK + u * 8192, &P.wuk, 128 * h + 64 * (u >> 1), 0, 0, 0, 8 * j + 4 * (u & 1), BAR(BAR_WUK + (u >> 1)), pol);
        tn += T.PC_P1;
      }
#pragma unroll
      for (int u = 0; u < 2; u++) {
        if (u == (T.PC_W > 3) && T.PC_NW) mbar_wait(BAR(BAR_WUK));
        slot(tn, T.PC_SL);
        tma2d_nohint(sb + OFF_WM2 + u * 8192, &P.wm2, 1024 + 16 * cta, 256 * u, BAR(BAR_WM2));
        tn += T.PC_P1;
      }
      const int row0 = (bs >> 3) * 4096 + (bs & 7) * 64;
      uint32_t dst = sb + OFF_RING;
      const int p2 = T.PC_P2 + (32 - ((bs * 37) & 63)) * T.PC_DS / 1024;
#pragma unroll 1
      for (int n = 0; n < 31; n++) {
        if (n >= 4 && (n < 12 || (n & 3) == 0)) mbar_wait(BAR(n >= 12 ? BAR_EMPTY + (n >> 2) - 3 : n == 7 ? BAR_P0BD : (n == 8 || n == 9) ? BAR_P2D : BAR_P1D));
        if (n < T.PC_NW) {
          if (n >= T.PC_W) mbar_wait(BAR(BAR_FULL + n - T.PC_W));
          else if ((n & 1) == (T.PC_W > 3)) mbar_wait(BAR(n < 2 ? BAR_WUK + 1 : BAR_WM2));
        }
        slot(tn, T.PC_SL);
        tma3d(dst, &P.ckv2, 0, row0 + (n >> 2) * 512, 2 * (n & 3), BAR(BAR_FULL + n), pol);
        dst = (n == 11 || n == 23) ? sb + OFF_RING : dst + 16384;
        tn += n >= 15 ? p2 : T.PC_P2;
        if (n == 4) CLK(2);
        if (n == 12) CLK(3);
        if (n == 20) CLK(4);
        if (n == 28) CLK(5);
        if (n == 24) {
          asm volatile("prefetch.tensormap [%0];" ::"l"(&P.ckv1) : "memory");
          asm volatile("prefetch.tensormap [%0];" ::"l"(&P.wuv) : "memory");
          asm volatile("prefetch.tensormap [%0];" ::"l"(&P.wo) : "memory");
          asm volatile("prefetch.tensormap [%0];" ::"l"(&P.w1) : "memory");
          asm volatile("prefetch.tensormap [%0];" ::"l"(&P.w2) : "memory");
        }
      }
      slot(tn, T.PC_SL);
      tma3d(dst, &P.ckv1, 0, row0 + 7 * 512, 6, BAR(BAR_LAST + 3), pol);
      tma3d(dst + 8192, &P.ckv1, 0, row0 + 7 * 512, 7, BAR(BAR_LAST + 4), pol);
      tn += T.PC_P2;
      CLK(6);
      auto unit = [&](int u) {
        if (u < 4) tma5d(sb + OFF_WUV + u * 8192, &P.wuv, 128 * h + 64 * (u >> 1), 0, 4 * (j >> 1), 0, 2 * (j & 1) + (u & 1), BAR(BAR_WUV + (u >> 1)), pol);
        else if (u < 8) tma2d(sb + OFF_WO + (u - 4) * 8192, &P.wo, 128 * j + 64 * ((u - 4) >> 1), 128 * h + 64 * (u & 1), BAR(BAR_WO + ((u - 4) >> 1)), pol);
        else if (u < 10) { if (cta < NFF) tma2d_nohint(sb + OFF_W1 + (u - 8) * 8192, &P.w1, FCH * cta, 256 * (u - 8), BAR(BAR_W1)); }
        else if (cta < NFF) tma3d(sb + OFF_W2 + (u - 10) * 8192, &P.w2, 0, FCH * cta, 4 * (u - 10), BAR(BAR_W2), pol);
      };
      mbar_wait(BAR(BAR_EMPTY + 5));
      if (T.PW_A >= 0) { mbar_wait(BAR(BAR_LAST + T.PW_A)); tn = gtime32(); }
      tn += T.PW_0 + ((cta * 37) & 127) * T.PW_ST / 128;
#pragma unroll
      for (int u = 0; u < 12; u++) {
        if (u == 8) mbar_wait(BAR(BAR_EMPTY + 6));
        until_ns(tn);
        unit(u);
        tn += u < 3 ? T.PW_UV : u == 3 ? T.PW_G : u < 8 ? T.PW_O : T.PW_F;
      }
      CLK_DUMP();
    }
    return;
  }

  if (w == 9) {
    if (lane == 0) {
#pragma unroll
      for (int i = 0; i < NBARS; i++) mbar_init(BAR(i), i >= BAR_P1D ? 8 : i >= BAR_EMPTY ? 4 : 1);
      asm volatile("fence.mbarrier_init.release.cluster;" ::: "memory");
    }
    __syncwarp();
    mbar_expect(BAR(lane), lane == BAR_LAST + 3 ? 8192 : 16384);
    if (lane < BAR_ALLCLR - 32) mbar_expect(BAR(32 + lane), lane == 0 ? 8192 : 16384);
    CLK(9);
    asm volatile("barrier.cta.arrive.aligned 5, 64;" ::: "memory");
    asm volatile("barrier.cta.arrive.aligned 0, %0;" ::"n"(NTHREADS) : "memory");
  }
  const uint32_t epoch = ldg_rlx1(&gs->epoch);

  if (w == 9) {
    const int wd = 2 * (t & 1) + (t >> 1), bo = 2 * (g & 3) + (wd >> 1), mo = 16 * hI + 2 * jI + 8 * (wd & 1);
    const uint32_t xo = ldg_nc1(gx + (bo * 512 + mo) * 2);
    const int par = epoch & 1;
    until_ns(gtime32() + T.CLR_T0);
    {
      const uint4 z = make_uint4(0, 0, 0, 0);
      uint4* x1 = reinterpret_cast<uint4*>(gs->X1 + ((64 * hh + (lane >> 4)) * 64 + bs) * 64) + (lane & 15);
      constexpr int sx1 = 2 * 64 * 16, sx3 = 8 * 32 * 4, sx4 = 8 * NFF * 4, nx4 = 16;
      uint4* x3 = reinterpret_cast<uint4*>(gs->X3A + ((32 * jI + g) * 32 + hI) * 16) + t;
      uint4* x4 = reinterpret_cast<uint4*>(gs->X4 + (g * NFF + cta) * 16) + t;
#pragma unroll 1
      for (int i0 = 0; i0 < 32; i0 += 4) {
#pragma unroll
        for (int i = 0; i < 4; i++) stg4(x1 + (i0 + i) * sx1, z);
        backoff(T.CLR_CLK);
      }
#pragma unroll
      for (int i = 0; i < 4; i++) stg4(x3 + i * sx3, z);
      backoff(T.CLR_CLK);
#pragma unroll
      for (int i = 0; i < 4; i++) stg4(reinterpret_cast<uint4*>(gs->X2 + cta * 512) + i * 32 + lane, z);
      backoff(T.CLR_CLK);
      stg4(reinterpret_cast<uint4*>(gs->X3B + (lane >> 2) * 2048 + cta * 16) + (lane & 3), z);
      if (lane < 8) stg4(reinterpret_cast<uint4*>(gs->ML + cta * 32) + lane, z);
      if (CLRSIDE == 0 || cta < NFF) {
#pragma unroll
        for (int i = 0; i < nx4; i++) { stg4(x4 + i * sx4, z); if ((i & 3) == 1) backoff(T.CLR_CLK); }
      }
      CLK(1);
      asm volatile("fence.acq_rel.gpu;" ::: "memory");
      CLK(2);
      __syncwarp();
      if (lane < NSYNC) asm volatile("red.relaxed.gpu.global.add.u32 [%0], 1;" ::"l"(&gs->sync[lane][0]) : "memory");
#pragma unroll
      for (int i = 0; i < 4; i++) stg4(reinterpret_cast<uint4*>(gs->QP[par ^ 1] + cta * 512) + i * 32 + lane, z);
      backoff(T.CLR_CLK);
#pragma unroll
      for (int i = 0; i < 4; i++) stg4(reinterpret_cast<uint4*>(gs->QX[par ^ 1] + cta * 512) + i * 32 + lane, z);
      stg4(reinterpret_cast<uint4*>(gs->MOD1[par ^ 1] + cta * 128) + lane, z);
      if (lane < 16) stg4(reinterpret_cast<uint4*>(gs->MOD2[par ^ 1] + cta * 64) + lane, z);
      if (lane == 0) {
        const uint32_t target = (epoch + 1) * NCTA;
        uint32_t c; int it = 0;
        do { backoff(T.CLR_CLK); asm volatile("ld.acquire.gpu.global.u32 %0, [%1];" : "=r"(c) : "l"(&gs->sync[cta % NSYNC][0]) : "memory"); if (++it > SPIN_LIMIT) __trap(); } while ((int)(c - target) < 0);
        mbar_arrive(BAR(BAR_ALLCLR));
      }
      __syncwarp();
    }
    CLK(3);
    uint2 gg[2];
    {
      const uint32_t* pg = gs->MOD2[par] + cta * 16 + bo * 2;
      load_units<2, 3 * 2048>(gg, pg);
      check_units<2, 3 * 2048>(gg, pg, T.RB);
    }
    const uint32_t ga2 = (wd & 1) ? gg[0].y : gg[0].x, gb2 = (wd & 1) ? gg[1].y : gg[1].x;
    uint32_t anchor;
    {
      mbar_wait(BAR(BAR_LAST + 4));
      unsigned long long now; asm volatile("mov.u64 %0, %%globaltimer;" : "=l"(now));
      if (lane < NSYNC) {
        asm volatile("red.relaxed.gpu.global.max.u64 [%0], %1;" ::"l"(&gs->sync[lane][2]), "l"(now) : "memory");
        asm volatile("red.relaxed.gpu.global.add.u32 [%0], 1;" ::"l"(&gs->sync[lane][1]) : "memory");
      }
      backoff(T.D_TS);
      const uint32_t target = (epoch + 1) * NCTA;
      uint4 v; int it = 0;
      do { v = ldg_2u64(gs->sync[cta % NSYNC]); if (++it > SPIN_LIMIT) __trap(); } while ((int)(v.y - target) < 0);
      const int age = min(max((int)(gtime32() - v.z), 0), 4000);
      anchor = clk32() - age * 7 / 4;
      if (lane == 0) { sts1(sb + OFF_TS, anchor); mbar_arrive(BAR(BAR_TS)); }
      CLK(10);
    }
    {
      const uint32_t* pm = pin(gs->ML + hI * 128 + lane * 4);
      wait_clk(anchor, T.A_M);
      uint4 ml = ldg_2u64(pm);
      int it = 0;
      while (ml.y == 0 || ml.w == 0) { ml = ldg_2u64(pm); if (++it > SPIN_LIMIT) __trap(); }
      __syncwarp();
      ITS(2, it);
      float M = fmaxf(__uint_as_float(ml.x), __uint_as_float(ml.z));
      M = fmaxf(M, __shfl_xor_sync(~0u, M, 1)); M = fmaxf(M, __shfl_xor_sync(~0u, M, 2));
      const float e0 = ex2(__uint_as_float(ml.x) - M), e1 = ex2(__uint_as_float(ml.z) - M);
      float l = e0 * __uint_as_float(ml.y) + e1 * __uint_as_float(ml.w);
      l += __shfl_xor_sync(~0u, l, 1); l += __shfl_xor_sync(~0u, l, 2);
      const float inv = __fdividef(1.f, l);
      sts2f(sb + OFF_WV + lane * 8, e0 * inv, e1 * inv);
      __syncwarp();
      if (lane == 0) mbar_arrive(BAR(BAR_WV));
      CLK(11);
    }
    float v0, v1;
    uint32_t* const x3o = pin(gs->X3B + (lane >> 2) * 2048 + cta * 16 + (lane & 3) * 4);
    uint32_t* const fo = pin(reinterpret_cast<uint32_t*>(gout) + (bo * 512 + mo) / 2);
    const int po = (4 * (g >> 2) + t) * 16 + (g & 3) * 4;
    const uint32_t* const p3 = pin(gs->X3A + cta * 512 + po);
    const uint32_t* const p4 = pin(gs->X4 + cta * NFF * 16 + po);
    mbar_wait(BAR(BAR_P5D));
    backoff(T.D_X3A);
    wait_clk(anchor, T.A_X3A);
    CLK(4);
    { const int it = sum_pieces<32>(p3, g, t, v0, v1, T.RB); ITS(0, it); }
    CLK(5);
    const uint32_t x2w = pack_bf16(bf_lo(xo) + bf_lo(ga2) * v0, bf_hi(xo) + bf_hi(ga2) * v1);
    {
      const int src = 4 * (lane & 3);
      uint4 o;
      o.x = __shfl_sync(~0u, x2w, src); o.y = __shfl_sync(~0u, x2w, src + 2); o.z = __shfl_sync(~0u, x2w, src + 1); o.w = __shfl_sync(~0u, x2w, src + 3);
      stg_2u64(x3o, o);
    }
    CLK(6);
    if (cta < NFF) { mbar_wait(BAR(BAR_P7D)); backoff(T.D_FIN); } else backoff(T.D_FIN2);
    CLK(7);
    { const int it = sum_pieces<NFF>(p4, g, t, v0, v1, T.RB); ITS(1, it); }
    if (g < 4) *fo = pack_bf16(bf_lo(x2w) + bf_lo(gb2) * v0, bf_hi(x2w) + bf_hi(gb2) * v1);
    CLK(8);
    CLK_DUMP();
    if (cta == 0 && lane == 0) stg1(&gs->epoch, epoch + 1);
    return;
  }

  const int wg = w >> 2, wq = w & 3;
  uint32_t tstore;
  {
    const uint8_t* pw = gwmod + (size_t)(128 * jI + 16 * w + 4 * (g >> 1) + (g & 1)) * 6144 + 64 * hI + 16 * t;
    const uint4 w0 = ldg_nc4(pw), w1 = ldg_nc4(pw + 2 * 6144);
    const uint2 cc = ldg_nc2(gc + g * 1024 + 256 * jI + 32 * w + 8 * t);
    CLK(40);
    const uint32_t a[4] = {silu2(cc.x), 0u, silu2(cc.y), 0u};
    float d[4][4] = {{0.f, 0.f, 0.f, 0.f}, {0.f, 0.f, 0.f, 0.f}, {0.f, 0.f, 0.f, 0.f}, {0.f, 0.f, 0.f, 0.f}};
    mma16816(d[0], a, movm(w0.x), movm(w1.x)); mma16816(d[1], a, movm(w0.y), movm(w1.y));
    mma16816(d[2], a, movm(w0.z), movm(w1.z)); mma16816(d[3], a, movm(w0.w), movm(w1.w));
    CLK(1);
    sts4f(sb + OFF_P0S + w * 1088 + lane * 16, d[0][0], d[0][1], d[1][0], d[1][1]);
    sts4f(sb + OFF_P0S + w * 1088 + 544 + lane * 16, d[2][0], d[2][1], d[3][0], d[3][1]);
    bar_sync(0, NTHREADS);
    if (tid < 128) {
      const uint32_t src = sb + OFF_P0S + ((tid >> 2) & 1) * 544 + (((tid >> 3) & 7) * 4 + 2 * (tid >> 6) + (tid & 1)) * 16 + ((tid >> 1) & 1) * 8;
      float2 v[8];
#pragma unroll
      for (int i = 0; i < 8; i++) v[i] = ldsf2(src + i * 1088);
      const float ax = ((v[0].x + v[1].x) + (v[2].x + v[3].x)) + ((v[4].x + v[5].x) + (v[6].x + v[7].x));
      const float ay = ((v[0].y + v[1].y) + (v[2].y + v[3].y)) + ((v[4].y + v[5].y) + (v[6].y + v[7].y));
      stg1(gs->MOD1[epoch & 1] + jI * 4096 + hI * 128 + tid, nz(pack_bf16(ax, ay)));
    }
    tstore = clk32();
  }
  CLK(2);
  const int par = epoch & 1;
  uint32_t cf[4][4];
  mbar_wait(BAR(BAR_XC));
  {
    uint32_t u[2][4];
    lds4(u[0], sb + OFF_XS + w * 1024 + lane * 16); lds4(u[1], sb + OFF_XS + w * 1024 + 512 + lane * 16);
    float v[16];
#pragma unroll
    for (int i = 0; i < 8; i++) { v[2 * i] = bf_lo(u[i >> 2][i & 3]); v[2 * i + 1] = bf_hi(u[i >> 2][i & 3]); }
    float s = 0.f;
#pragma unroll
    for (int i = 0; i < 16; i++) s += v[i];
#pragma unroll
    for (int o = 16; o; o >>= 1) s += __shfl_xor_sync(~0u, s, o);
    const float mu = s * (1.f / 512.f);
    float q = 0.f;
#pragma unroll
    for (int i = 0; i < 16; i++) { v[i] -= mu; q += v[i] * v[i]; }
#pragma unroll
    for (int o = 16; o; o >>= 1) q += __shfl_xor_sync(~0u, q, o);
    const float rs = rsqrtf(q * (1.f / 512.f) + 1e-5f);
    const bool hi = jI & 2;
    uint32_t o[4];
#pragma unroll
    for (int i = 0; i < 4; i++) o[i] = pack_bf16((hi ? v[8 + 2 * i] : v[2 * i]) * rs, (hi ? v[9 + 2 * i] : v[2 * i + 1]) * rs);
    if ((lane >> 4) == (jI & 1)) sts4(sb + OFF_XN + w * 272 + (lane & 15) * 16, make_uint4(o[0], o[1], o[2], o[3]));
  }
  CLK(3);
  uint32_t aw[8][4];
  {
    const uint32_t* pm = pin(gs->MOD1[par] + (8 * jI + w) * 64 + lane * 2);
    uint32_t* const qpo = pin(gs->QP[par] + (cta * 256 + tid) * 2);
    wait_clk(tstore, T.D_MOD);
    CLK(4);
    uint2 v[8];
    load_units<8, 2048>(v, pm);
    cbar();
    const uint32_t xn0 = lds1(sb + OFF_XN + g * 272 + w * 32 + t * 4), xn1 = lds1(sb + OFF_XN + g * 272 + w * 32 + 16 + t * 4);
    const bool early = __all_sync(~0u, mbar_test(BAR(BAR_WQ + wg)));
    if (early) load_a_t(aw, sb + OFF_WQ, w, lane);
    int it = 0;
    while (true) {
      uint32_t mn = 0xffffffffu;
#pragma unroll
      for (int i = 0; i < 8; i++) mn = min(mn, min(v[i].x, v[i].y));
      if (mn != 0) break;
#pragma unroll
      for (int i = 0; i < 8; i++) if (v[i].x == 0 || v[i].y == 0) v[i] = ldg_u64(pm + i * 2048);
      if (++it > SPIN_LIMIT) __trap();
    }
    CLK(5);
    ITS(0, it);
    float sc[2][4];
#pragma unroll
    for (int i = 0; i < 2; i++) {
      sc[i][0] = (bf_lo(v[i].x) + bf_lo(v[2 + i].x)) + (bf_lo(v[4 + i].x) + bf_lo(v[6 + i].x));
      sc[i][1] = (bf_hi(v[i].x) + bf_hi(v[2 + i].x)) + (bf_hi(v[4 + i].x) + bf_hi(v[6 + i].x));
      sc[i][2] = (bf_lo(v[i].y) + bf_lo(v[2 + i].y)) + (bf_lo(v[4 + i].y) + bf_lo(v[6 + i].y));
      sc[i][3] = (bf_hi(v[i].y) + bf_hi(v[2 + i].y)) + (bf_hi(v[4 + i].y) + bf_hi(v[6 + i].y));
    }
    sts2(sb + OFF_BS1 + (w >> 1) * 512 + lane * 16 + (w & 1) * 8,
         pack_bf16(bf_lo(xn0) * (1.f + sc[1][0]) + sc[0][0], bf_hi(xn0) * (1.f + sc[1][1]) + sc[0][1]),
         pack_bf16(bf_lo(xn1) * (1.f + sc[1][2]) + sc[0][2], bf_hi(xn1) * (1.f + sc[1][3]) + sc[0][3]));
    if (!early) { mbar_wait(BAR(BAR_WQ + wg)); load_a_t(aw, sb + OFF_WQ, w, lane); }
    CLK(6);
    cbar();
    uint32_t b[4][4];
#pragma unroll
    for (int kk = 0; kk < 4; kk++) lds4(b[kk], sb + OFF_BS1 + kk * 512 + lane * 16);
    float d[4];
    mma128(d, aw, b);
    stg_u64(qpo, pack_bf16(d[0], d[1]), pack_bf16(d[2], d[3]));
    tstore = clk32();
    CLK(7);
    if (wg) {
      mbar_wait(BAR(BAR_C));
#pragma unroll
      for (int i = 0; i < 4; i++) lds4(cf[i], sb + OFF_CS + g * 1024 + wq * 256 + i * 64 + t * 16);
#pragma unroll
      for (int i = 0; i < 16; i++) cf[i >> 2][i & 3] = silu2(cf[i >> 2][i & 3]);
    }
    __syncwarp();
    if (lane == 0) mbar_arrive(BAR(BAR_P1D));
  }
  {
    const uint32_t* pq = pin(gs->QP[par] + (hI * 4 * 256 + tid) * 2);
    uint32_t* const qxo = pin(gs->QX[par] + (g * 32 + hI) * 256 + 64 * jI + 8 * w + 2 * t);
    uint2 v[4];
    wait_clk(tstore, T.D_QP);
    CLK(8);
    load_units<4, 512>(v, pq);
    const uint32_t abase = sb + OFF_WUK + (16 * w + (lane & 15)) * 128;
    auto load_half = [&](int hf) {
#pragma unroll
      for (int ks = 0; ks < 4; ks++) ldsm4(aw[4 * hf + ks], abase + hf * 16384 + (((2 * ks + (lane >> 4)) ^ (lane & 7)) << 4));
    };
    mbar_wait(BAR(BAR_WUK));
    load_half(0);
    const bool early = __all_sync(~0u, mbar_test(BAR(BAR_WUK + 1)));
    if (early) load_half(1);
    const int it = check_units<4, 512>(v, pq, T.RB);
    CLK(9);
    ITS(1, it);
    sum4_to_smem(v, sb + OFF_BS2 + (16 * w + g) * 16 + t * 4);
    if (!early) { mbar_wait(BAR(BAR_WUK + 1)); load_half(1); }
    CLK(10);
    cbar();
    uint32_t b[4][4];
#pragma unroll
    for (int kk = 0; kk < 4; kk++) ldsm4t(b[kk], sb + OFF_BS2 + (32 * kk + lane) * 16);
    float d[4];
    mma128(d, aw, b);
    const float sc = 0.08838834764831845f * 1.4426950408889634f;
    stg_u64(qxo, movm(pack_bf16(d[0] * sc, d[1] * sc)), movm(pack_bf16(d[2] * sc, d[3] * sc)));
    tstore = clk32();
    CLK(11);
    if (lane == 0) mbar_arrive(BAR(BAR_P2D));
  }
  if (wg) {
    const int mi = lane >> 3, r = lane & 7;
    const uint32_t a0 = sb + OFF_WM2 + (8 * (r >> 1) + (r & 1) + 2 * (mi >> 1)) * 32 + (mi & 1) * 16;
    mbar_wait(BAR(BAR_WM2));
#pragma unroll
    for (int s = 0; s < 8; s++) ldsm4t(aw[s], a0 + (128 * wq + 32 * (s >> 1) + 4 * (s & 1)) * 32);
    float d[4];
    mma128(d, aw, cf);
    sts4f(sb + OFF_P0B + (tid - 128) * 16, d[0], d[1], d[2], d[3]);
    if (lane == 0) mbar_arrive(BAR(BAR_P0BD));
    bar_sync(3, 128);
    if (w == 4) {
      float4 v[4];
#pragma unroll
      for (int i = 0; i < 4; i++) v[i] = ldsf4(sb + OFF_P0B + (i * 32 + lane) * 16);
      stg_u64(gs->MOD2[par] + cta * 64 + t * 16 + g * 2, movm(pack_bf16((v[0].x + v[1].x) + (v[2].x + v[3].x), (v[0].y + v[1].y) + (v[2].y + v[3].y))),
              movm(pack_bf16((v[0].z + v[1].z) + (v[2].z + v[3].z), (v[0].w + v[1].w) + (v[2].w + v[3].w))));
    }
    CLK(15);
  }
  {
    const uint32_t* qx = pin(gs->QX[par] + ((bs >> 3) * 32 + 16 * hh) * 256 + tid * 4);
    const int ch = tid & 63, h0 = tid >> 6;
    const uint32_t dst = sb + OFF_Q + (ch >> 3) * 2048 + h0 * 128;
    wait_clk(tstore, T.D_QX);
    CLK(12);
    uint4 v[4];
#pragma unroll
    for (int i = 0; i < 4; i++) v[i] = ldg_2u64(qx + i * 1024);
    int it = 0;
    while (true) {
      uint32_t mn = 0xffffffffu;
#pragma unroll
      for (int i = 0; i < 4; i++) mn = min(mn, min(v[i].y, v[i].w));
      if (mn != 0) break;
#pragma unroll
      for (int i = 0; i < 4; i++) if (v[i].y == 0 || v[i].w == 0) v[i] = ldg_2u64(qx + i * 1024);
      if (++it > SPIN_LIMIT) __trap();
    }
    CLK(13);
    ITS(2, it);
#pragma unroll
    for (int i = 0; i < 4; i++) sts4(dst + i * 512 + (((ch & 7) ^ ((4 * i + h0) & 7)) << 4), v[i]);
    asm volatile("fence.proxy.async.shared::cta;" ::: "memory");
    CLK(14);
    cbar();
  }

  uint2 cbf[4], sbf[4];
  const uint32_t* const pcb = gs->MOD2[par] + 2048 + (16 * w + t) * 16 + g * 2;
  uint32_t thand, anchor;
  if (wg == 0) {
    float mh[4];
    float L[8];
#pragma unroll
    for (int i = 0; i < 4; i++) { L[2 * i] = L[2 * i + 1] = 0.f; mh[i] = -INFINITY; }
    constexpr uint32_t dq = desc_lo(OFF_Q);
    const uint32_t ptw = sb + OFF_PT + (8 * (lane >> 4) + (lane & 7)) * 128 + (((2 * wq + ((lane >> 3) & 1)) ^ (lane & 7)) << 4);
    float S[8];
    auto softmax = [&](int tl) {
      auto write_p = [&](const float (&x)[8]) {
        float p[8];
#pragma unroll
        for (int i = 0; i < 8; i++) p[i] = ex2(x[i]);
        stsm4t(ptw + (tl & 1) * 2048, pack_bf16(p[0], p[1]), pack_bf16(p[2], p[3]), pack_bf16(p[4], p[5]), pack_bf16(p[6], p[7]));
        asm volatile("fence.proxy.async.shared::cta;" ::: "memory");
      };
      float x[8];
#pragma unroll
      for (int i = 0; i < 8; i++) x[i] = S[i] - mh[2 * (i >> 2) + (i & 1)];
      if (tl) write_p(x);
      const float ex = fmaxf(fmaxf(fmaxf(x[0], x[1]), fmaxf(x[2], x[3])), fmaxf(fmaxf(x[4], x[5]), fmaxf(x[6], x[7])));
      if (tl == 0 || bar_over(ex)) {
        float mx[4];
#pragma unroll
        for (int i = 0; i < 4; i++) mx[i] = fmaxf(S[4 * (i >> 1) + (i & 1)], S[4 * (i >> 1) + 2 + (i & 1)]);
        const float a = reduce_g(mx, lane, [](float u, float v) { return fmaxf(u, v); });
        stsf(sb + OFF_RED + wq * 64 + (8 * (lane >> 4) + 2 * t + ((lane >> 3) & 1)) * 4, a);
        bar_sync(2, 128);
#pragma unroll
        for (int jn = 0; jn < 2; jn++) {
          float m0 = mh[2 * jn], m1 = mh[2 * jn + 1];
#pragma unroll
          for (int i = 0; i < 4; i++) { const float2 v = ldsf2(sb + OFF_RED + i * 64 + (8 * jn + 2 * t) * 4); m0 = fmaxf(m0, v.x); m1 = fmaxf(m1, v.y); }
          const float a0 = ex2(mh[2 * jn] - m0), a1 = ex2(mh[2 * jn + 1] - m1);
          mh[2 * jn] = m0; mh[2 * jn + 1] = m1;
          L[4 * jn] *= a0; L[4 * jn + 1] *= a1; L[4 * jn + 2] *= a0; L[4 * jn + 3] *= a1;
          if (tid < 4) sts2f(sb + OFF_ALPHA + (8 * jn + 2 * t) * 4, a0, a1);
        }
#pragma unroll
        for (int i = 0; i < 8; i++) x[i] = S[i] - mh[2 * (i >> 2) + (i & 1)];
        write_p(x);
        cbar();
      }
      const uint32_t dpt = __shfl_sync(~0u, desc_lo(OFF_PT) + (tl & 1) * 128, 0);
      wg_fence();
#pragma unroll
      for (int ks = 0; ks < 4; ks++) wgmma_n16_ones(L, ONE2, dpt + ks * 2);
      wg_commit();
    };
    uint32_t da = desc_lo(OFF_RING);
#pragma unroll 1
    for (int tl = 0; tl < 7; tl++) {
      uint32_t ok = 0;
#pragma unroll
      for (int u = 0; u < 4; u++) ok += mbar_test(BAR(BAR_FULL + 4 * tl + u));
      ok = __reduce_min_sync(~0u, ok);
      const uint32_t du = __shfl_sync(~0u, da, 0);
#pragma unroll
      for (int u = 0; u < 4; u++) {
        if (ok != 4) mbar_wait(BAR(BAR_FULL + 4 * tl + u));
        wg_fence();
#pragma unroll
        for (int k = 0; k < 8; k++) {
          const int i = 8 * u + k;
          if (i == 0) wgmma_n16<0, 0>(S, du, dq); else wgmma_n16<0, 1>(S, du + (i >> 2) * 512 + (i & 3) * 2, dq + (i >> 2) * 128 + (i & 3) * 2);
        }
        wg_commit();
      }
      wg_wait<0>();
      acc_fence(S); acc_fence(L);
      if (tl == 0) CLK(15);
      if (tl == 1) CLK(17);
      softmax(tl);
      if (tl == 0) CLK(16);
      if (tl == 1) CLK(18);
      if (tl == 3) CLK(19);
      if (tl == 6) CLK(20);
      da = (tl == 2 || tl == 5) ? da - 8192 : da + 4096;
    }
    if (cta < NFF) { load_units<4, 64>(sbf, pcb); load_units<4, 64>(cbf, pcb + 2048); }
    mbar_wait(BAR(BAR_ALLCLR));
    uint32_t* const mlo = pin(gs->ML + ((16 * hh + 4 * (g & 2) + 2 * t + (g & 1)) * 64 + bs) * 2);
#pragma unroll
    for (int i = 0; i < 32; i++) {
      if (i == 0 || i == 8 || i == 16 || i == 24 || i == 28) {
        if (i) wg_commit();
        mbar_wait(BAR(BAR_LAST + (i == 28 ? 4 : i >> 3)));
        if (i == 28) CLK(21);
        wg_fence();
      }
      if (i == 0) wgmma_n16<0, 0>(S, da, dq); else wgmma_n16<0, 1>(S, da + (i >> 2) * 512 + (i & 3) * 2, dq + (i >> 2) * 128 + (i & 3) * 2);
    }
    wg_commit();
    wg_wait<0>();
    acc_fence(S); acc_fence(L);
    CLK(22);
    softmax(7);
    CLK(23);
    thand = clk32();
    wg_wait<0>();
    acc_fence(L);
    if (tid < 16) stg_u64(mlo, __float_as_uint(g & 2 ? (g & 1 ? mh[3] : mh[2]) : (g & 1 ? mh[1] : mh[0])), __float_as_uint(g & 2 ? (g & 1 ? L[5] : L[4]) : (g & 1 ? L[1] : L[0])));
    CLK(24);
  } else {
    float O[8][8];
#pragma unroll
    for (int i = 0; i < 8; i++)
#pragma unroll
      for (int k = 0; k < 8; k++) O[i][k] = 0.f;
    constexpr uint32_t dp = desc_lo(OFF_PT);
    auto handover = [&](int tl) {
      if (tl == 0) { cbar(); return; }
      if (bar_over(0.f)) {
        cbar();
#pragma unroll
        for (int jn = 0; jn < 2; jn++) {
          const float2 a = ldsf2(sb + OFF_ALPHA + (8 * jn + 2 * t) * 4);
#pragma unroll
          for (int mb = 0; mb < 8; mb++) { O[mb][4 * jn] *= a.x; O[mb][4 * jn + 1] *= a.y; O[mb][4 * jn + 2] *= a.x; O[mb][4 * jn + 3] *= a.y; }
        }
      }
    };
    uint32_t da = desc_lo(OFF_RING);
#pragma unroll 1
    for (int tl = 0; tl < 7; tl++) {
      handover(tl);
      const uint32_t dpt = dp + (tl & 1) * 128;
      wg_fence();
#pragma unroll
      for (int i = 0; i < 32; i++) wgmma_n16<1, 1>(O[i >> 2], da + (i >> 2) * 512 + (i & 3) * 128, dpt + (i & 3) * 2);
      wg_commit();
      wg_wait<0>();
#pragma unroll
      for (int mb = 0; mb < 8; mb++) acc_fence(O[mb]);
      if (lane == 0) mbar_arrive(BAR(BAR_EMPTY + tl));
      if (tl == 0) CLK(16);
      if (tl == 1) CLK(18);
      if (tl == 3) CLK(19);
      if (tl == 6) CLK(20);
      da = (tl == 2 || tl == 5) ? da - 8192 : da + 4096;
    }
    if (cta < NFF) { load_units<4, 64>(sbf, pcb); load_units<4, 64>(cbf, pcb + 2048); }
    mbar_wait(BAR(BAR_ALLCLR));
    uint32_t* const x1o = pin(gs->X1 + (((16 * hh + 2 * t) * 4 + (wq >> 1)) * 64 + bs) * 64 + ((wq & 1) * 8 + g) * 4);
    handover(7);
    CLK(23);
    thand = clk32();
    auto pv = [&](int J) {
      wg_fence();
#pragma unroll
      for (int i = 0; i < 16; i++) wgmma_n16<1, 1>(O[4 * J + (i >> 2)], desc_lo(65536) + (4 * J + (i >> 2)) * 512 + (i & 3) * 128, dp + 128 + (i & 3) * 2);
      wg_commit();
    };
    auto publish = [&](int J) {
#pragma unroll
      for (int k = 0; k < 4; k++) acc_fence(O[4 * J + k]);
#pragma unroll
      for (int i = 0; i < 4; i++) {
        const int k = 4 * (i >> 1) + (i & 1);
        stg_2u64(x1o + ((8 * (i >> 1) + (i & 1)) * 4 + 2 * J) * 4096,
                 make_uint4(pack_bf16(O[4 * J][k], O[4 * J][k + 2]), pack_bf16(O[4 * J + 1][k], O[4 * J + 1][k + 2]),
                            pack_bf16(O[4 * J + 2][k], O[4 * J + 2][k + 2]), pack_bf16(O[4 * J + 3][k], O[4 * J + 3][k + 2])));
      }
    };
    pv(0); pv(1);
    wg_wait<1>(); publish(0);
    wg_wait<0>(); publish(1);
    CLK(24);
  }

  {
    const uint32_t* px = pin(gs->X1 + (cta * 64 + w * 8) * 64 + lane * 2);
    uint32_t* const x2o = pin(gs->X2 + (cta * 256 + tid) * 2);
    mbar_wait(BAR(BAR_TS));
    anchor = lds1(sb + OFF_TS);
    wait_clk(thand, T.D_X1);
    wait_clk(anchor, T.A_X1 + (jI >> 1) * T.A_X1J);
    CLK(25);
    uint2 v[8];
    load_units<8, 64>(v, px);
    const bool early = __all_sync(~0u, mbar_test(BAR(BAR_WUV + wg)));
    if (early) load_a_t(aw, sb + OFF_WUV, w, lane);
    mbar_wait(BAR(BAR_WV));
    const float4 wa = ldsf4(sb + OFF_WV + w * 32), wb = ldsf4(sb + OFF_WV + w * 32 + 16);
    const float wv[8] = {wa.x, wa.y, wa.z, wa.w, wb.x, wb.y, wb.z, wb.w};
    CLK(27);
    const int it = check_units<8, 64>(v, px, T.RB);
    CLK(28);
    ITS(4, it);
    float a0 = 0.f, a1 = 0.f, a2 = 0.f, a3 = 0.f;
#pragma unroll
    for (int i = 0; i < 8; i++) { a0 += wv[i] * bf_lo(v[i].x); a1 += wv[i] * bf_hi(v[i].x); a2 += wv[i] * bf_lo(v[i].y); a3 += wv[i] * bf_hi(v[i].y); }
    sts2(sb + OFF_BS4 + w * 272 + lane * 8, pack_bf16(a0, a1), pack_bf16(a2, a3));
    CLK(29);
    if (!early) { mbar_wait(BAR(BAR_WUV + wg)); load_a_t(aw, sb + OFF_WUV, w, lane); }
    cbar();
    uint32_t b[4][4];
#pragma unroll
    for (int kk = 0; kk < 4; kk++) ldsm4(b[kk], sb + OFF_BS4 + (lane & 7) * 272 + (4 * kk + (lane >> 3)) * 16);
    float d[4];
    mma128(d, aw, b);
    stg_u64(x2o, pack_bf16(d[0], d[1]), pack_bf16(d[2], d[3]));
    tstore = clk32();
    CLK(30);
  }
  {
    uint32_t* const o = pin(gs->X3A + ((4 * (8 * jI + w) + t) * 32 + hI) * 16 + g * 2);
    const uint32_t* const x2i = pin(gs->X2 + (hI * 4 * 256 + tid) * 2);
    wait_clk(tstore, T.D_X2);
    wait_clk(anchor, T.A_X2);
    uint2 v[4];
    load_units<4, 512>(v, x2i);
    mbar_wait(BAR(BAR_WO + wg));
    load_a_t(aw, sb + OFF_WO, w, lane);
    CLK(31);
    const int it = check_units<4, 512>(v, x2i, T.RB);
    CLK(32);
    ITS(5, it);
    sum4_to_smem(v, sb + OFF_BS5 + (16 * w + g) * 16 + t * 4);
    cbar();
    uint32_t b[4][4];
#pragma unroll
    for (int kk = 0; kk < 4; kk++) ldsm4t(b[kk], sb + OFF_BS5 + (32 * kk + lane) * 16);
    float d[4];
    mma128(d, aw, b);
    stg_u64(o, movm(pack_bf16(d[0], d[1])), movm(pack_bf16(d[2], d[3])));
    tstore = clk32();
    CLK(33);
    if (lane == 0) mbar_arrive(BAR(BAR_P5D));
  }
  if (cta < NFF) {
    const int mi = lane >> 3, r = lane & 7;
    uint32_t a1[4][4], a2[4][4];
    check_units<4, 64>(sbf, pcb, T.RB);
    check_units<4, 64>(cbf, pcb + 2048, T.RB);
    __syncwarp();
#pragma unroll
    for (int s = 0; s < 4; s++) { cbf[s].x = hadd2(cbf[s].x, ONE2); cbf[s].y = hadd2(cbf[s].y, ONE2); }
    mbar_wait(BAR(BAR_W1));
#pragma unroll
    for (int ks = 0; ks < 4; ks++) ldsm4t(a1[ks], sb + OFF_W1 + (64 * w + 16 * ks + 8 * (mi >> 1) + r) * 32 + (mi & 1) * 16);
    {
      float u[4] = {0.f, 0.f, 0.f, 0.f}, vv[4] = {0.f, 0.f, 0.f, 0.f};
#pragma unroll
      for (int s = 0; s < 4; s++) { mma16816(u, a1[s], cbf[s].x, cbf[s].y); mma16816(vv, a1[s], sbf[s].x, sbf[s].y); }
      sts4f(sb + OFF_REDU + tid * 16, u[0], u[1], u[2], u[3]);
      sts4f(sb + OFF_REDV + tid * 16, vv[0], vv[1], vv[2], vv[3]);
    }
    cbar();
    const int lp = (tid >> 2) & 31, kq = tid & 3;
    const int fo = (lp >> 2) + 8 * (kq >> 1), bo = 2 * (lp & 3) + (kq & 1);
    float U = 0.f, V = 0.f;
    if (tid < 128) {
#pragma unroll
      for (int i = 0; i < 8; i++) { U += ldsf(sb + OFF_REDU + i * 512 + tid * 4); V += ldsf(sb + OFF_REDV + i * 512 + tid * 4); }
    }
    const uint32_t* xb = pin(gs->X3B + (cta & (NREP - 1)) * 2048 + (16 * w + t) * 16 + g * 2);
    uint32_t* const ox = pin(gs->X4 + ((16 * w + t) * NFF + cta) * 16 + g * 2);
    CLK(34);
    wait_clk(tstore, T.D_X3B);
    uint2 x[4];
    load_units<4, 64>(x, xb);
    mbar_wait(BAR(BAR_W2));
#pragma unroll
    for (int mb = 0; mb < 4; mb++) ldsm4t(a2[mb], sb + OFF_W2 + w * 2048 + (8 * (mi >> 1) + r) * 128 + (((2 * mb + (mi & 1)) ^ r) << 4));
    CLK(35);
    const int it = check_units<4, 64>(x, xb, T.RB);
    __syncwarp();
    CLK(36);
    ITS(6, it);
    float G[2][4] = {{0.f, 0.f, 0.f, 0.f}, {0.f, 0.f, 0.f, 0.f}}, S[2][4] = {{0.f, 0.f, 0.f, 0.f}, {0.f, 0.f, 0.f, 0.f}};
#pragma unroll
    for (int s = 0; s < 4; s++) {
      const uint32_t sx[4] = {x[s].x, ONE2, x[s].y, ONE2};
      mma16816(S[s & 1], sx, x[s].x, x[s].y);
      mma16816(G[s & 1], a1[s], hmul2(x[s].x, cbf[s].x), hmul2(x[s].y, cbf[s].y));
    }
    sts4f(sb + OFF_REDG + tid * 16, G[0][0] + G[1][0], G[0][1] + G[1][1], G[0][2] + G[1][2], G[0][3] + G[1][3]);
    if (t == (g >> 1)) sts2f(sb + OFF_REDS + g * 80 + w * 8, (g & 1) ? S[0][3] + S[1][3] : S[0][2] + S[1][2], (g & 1) ? S[0][1] + S[1][1] : S[0][0] + S[1][0]);
    CLK(37);
    cbar();
    if (tid < 128) {
      float gv[8];
      float4 sv[4];
#pragma unroll
      for (int i = 0; i < 4; i++) sv[i] = ldsf4(sb + OFF_REDS + bo * 80 + i * 16);
#pragma unroll
      for (int i = 0; i < 8; i++) gv[i] = ldsf(sb + OFF_REDG + i * 512 + tid * 4);
      const float s1 = ((sv[0].x + sv[0].z) + (sv[1].x + sv[1].z)) + ((sv[2].x + sv[2].z) + (sv[3].x + sv[3].z));
      const float s2 = ((sv[0].y + sv[0].w) + (sv[1].y + sv[1].w)) + ((sv[2].y + sv[2].w) + (sv[3].y + sv[3].w));
      const float gsum = ((gv[0] + gv[1]) + (gv[2] + gv[3])) + ((gv[4] + gv[5]) + (gv[6] + gv[7]));
      const float mu = s1 * (1.f / 512.f);
      const float rs = rsqrtf(fmaxf(s2 * (1.f / 512.f) - mu * mu, 0.f) + 1e-5f);
      const float hv = fmaxf(rs * (gsum - mu * U) + V, 0.f);
      asm volatile("st.shared.u16 [%0], %1;" ::"r"(sb + OFF_H1 + fo * 16 + bo * 2), "h"(__bfloat16_as_ushort(__float2bfloat16(hv))) : "memory");
    }
    CLK(38);
    cbar();
    uint32_t b0, b1;
    ldsm2t(b0, b1, sb + OFF_H1 + (lane & 15) * 16);
    float o[4][4] = {{0.f, 0.f, 0.f, 0.f}, {0.f, 0.f, 0.f, 0.f}, {0.f, 0.f, 0.f, 0.f}, {0.f, 0.f, 0.f, 0.f}};
#pragma unroll
    for (int mb = 0; mb < 4; mb++) mma16816(o[mb], a2[mb], b0, b1);
#pragma unroll
    for (int mb = 0; mb < 4; mb++) stg_u64(ox + mb * 4 * NFF * 16, movm(pack_bf16(o[mb][0], o[mb][1])), movm(pack_bf16(o[mb][2], o[mb][3])));
    CLK(39);
    if (lane == 0) mbar_arrive(BAR(BAR_P7D));
  }
  CLK_DUMP();
}

typedef CUresult (*EncodeTiledFn)(CUtensorMap*, CUtensorMapDataType, cuuint32_t, void*, const cuuint64_t*, const cuuint64_t*,
                                  const cuuint32_t*, const cuuint32_t*, CUtensorMapInterleave, CUtensorMapSwizzle,
                                  CUtensorMapL2promotion, CUtensorMapFloatOOBfill);

struct Dim { uint64_t size, stride; uint32_t box; };
template <int R> void encode_map(EncodeTiledFn enc, CUtensorMap* m, const void* base, const Dim (&d)[R], CUtensorMapSwizzle sw, CUtensorMapL2promotion promo) {
  cuuint64_t dims[R], strides[R];
  cuuint32_t box[R], es[R];
  for (int i = 0; i < R; i++) { dims[i] = d[i].size; strides[i] = d[i].stride; box[i] = d[i].box; es[i] = 1; }
  enc(m, CU_TENSOR_MAP_DATA_TYPE_BFLOAT16, R, const_cast<void*>(base), dims, strides + 1, box, es, CU_TENSOR_MAP_INTERLEAVE_NONE, sw, promo,
      CU_TENSOR_MAP_FLOAT_OOB_FILL_NONE);
}

}

extern "C" void kernel_launch(void* const* d_in, const int* in_sizes, int n_in, void* d_out, int out_size) {
  (void)in_sizes; (void)n_in; (void)out_size;
  static EncodeTiledFn enc = nullptr;
  static Scratch* scratch = nullptr;
  if (!enc) {
    void* sp = nullptr;
    cudaGetSymbolAddress(&sp, g_s);
    scratch = (Scratch*)sp;
    void* fn = nullptr;
    cudaDriverEntryPointQueryResult q;
    cudaGetDriverEntryPoint("cuTensorMapEncodeTiled", &fn, cudaEnableDefault, &q);
    enc = (EncodeTiledFn)fn;
    cudaFuncSetAttribute(fused_decode_kernel, cudaFuncAttributeMaxDynamicSharedMemorySize, SMEM_BYTES);
  }
  const CUtensorMapSwizzle S128 = CU_TENSOR_MAP_SWIZZLE_128B, S0 = CU_TENSOR_MAP_SWIZZLE_NONE;
  const CUtensorMapL2promotion L0 = CU_TENSOR_MAP_L2_PROMOTION_NONE, L128 = CU_TENSOR_MAP_L2_PROMOTION_L2_128B;
  Params P;
  encode_map<2>(enc, &P.wq, d_in[2], {{4096, 2, 64}, {512, 8192, 64}}, S128, L0);
  encode_map<5>(enc, &P.wuk, d_in[3], {{4096, 2, 64}, {2, 8192, 2}, {4, 4 * 8192, 4}, {2, 2 * 8192, 2}, {32, 16 * 8192, 4}}, S128, L0);
  encode_map<2>(enc, &P.wm2, d_in[10], {{3072, 2, 16}, {512, 6144, 256}}, S0, L128);
  encode_map<3>(enc, &P.ckv2, d_in[1], {{64, 2, 64}, {8 * 4096, 1024, 64}, {8, 128, 2}}, S128, L0);
  encode_map<3>(enc, &P.ckv1, d_in[1], {{64, 2, 64}, {8 * 4096, 1024, 64}, {8, 128, 1}}, S128, L0);
  encode_map<5>(enc, &P.wuv, d_in[4], {{4096, 2, 64}, {2, 8 * 8192, 2}, {8, 64 * 8192, 4}, {8, 8192, 8}, {4, 16 * 8192, 1}}, S128, L0);
  encode_map<2>(enc, &P.wo, d_in[5], {{512, 2, 64}, {4096, 1024, 64}}, S128, L0);
  encode_map<2>(enc, &P.w1, d_in[7], {{1792, 2, FCH}, {512, 3584, 256}}, S0, L128);
  encode_map<3>(enc, &P.w2, d_in[8], {{64, 2, 64}, {1792, 1024, FCH}, {8, 128, 4}}, S128, L0);
  cudaLaunchConfig_t cfg = {};
  cfg.gridDim = dim3(NCTA);
  cfg.blockDim = dim3(NTHREADS);
  cfg.dynamicSmemBytes = SMEM_BYTES;
  cfg.stream = cudaStreamPerThread;
  cudaLaunchAttribute at[1];
  at[0].id = cudaLaunchAttributeClusterDimension;
  at[0].val.clusterDim.x = 2; at[0].val.clusterDim.y = 1; at[0].val.clusterDim.z = 1;
  cfg.attrs = at;
  cfg.numAttrs = 0;
  cudaLaunchKernelEx(&cfg, fused_decode_kernel, (__nv_bfloat16*)d_out, scratch, (const uint8_t*)d_in[10], (const uint8_t*)d_in[0],
                     (const uint8_t*)d_in[9],
                     P);
}
```

```cpp
#include <cuda_runtime.h>
#include <cuda.h>
#include <cuda_bf16.h>
#include <stdint.h>
#define V4 1

namespace {

constexpr int NCTA = 128;
constexpr int NTHREADS = 320;
constexpr int NFG = 56;
constexpr int NFF = 2 * NFG;
constexpr int NSYNC = 4;
constexpr int NREP = 8;

constexpr uint32_t OFF_RING = 0;
constexpr uint32_t OFF_WUK = 131072;
constexpr uint32_t OFF_WQ = 131072 + 32768;
constexpr uint32_t OFF_WM2 = 65536 + 49152;
constexpr uint32_t OFF_WUV = 131072;
constexpr uint32_t OFF_WO = 131072 + 32768;
constexpr uint32_t OFF_W1 = 0;
constexpr uint32_t OFF_W2 = 32768;
constexpr uint32_t OFF_Q = 196608;
constexpr uint32_t OFF_PT = 212992;
constexpr uint32_t OFF_SCR = 217088;
constexpr uint32_t OFF_XS = 65536;
constexpr uint32_t OFF_CS = 65536 + 8192;
constexpr uint32_t OFF_P0S = 65536 + 16384;
constexpr uint32_t OFF_BS1 = OFF_SCR + 2048;
constexpr uint32_t OFF_BS2 = OFF_SCR + 4096;
constexpr uint32_t OFF_P0B = OFF_SCR + 6144;
constexpr uint32_t OFF_XN = OFF_SCR + 8192;
constexpr uint32_t OFF_RED = OFF_SCR + 10496;
constexpr uint32_t OFF_ALPHA = OFF_SCR + 11072;
constexpr uint32_t OFF_WV = OFF_SCR + 6144;
constexpr uint32_t OFF_TS = OFF_SCR + 11136;
constexpr uint32_t OFF_BARS = OFF_SCR + 11264;
constexpr uint32_t SMEM_BYTES = OFF_BARS + 512;
constexpr uint32_t OFF_BS4 = OFF_Q;
constexpr uint32_t OFF_H1 = OFF_Q + 2304;
constexpr uint32_t OFF_REDS = OFF_Q + 2816;
constexpr uint32_t OFF_BS5 = OFF_Q + 4096;
constexpr uint32_t OFF_REDG = OFF_Q + 8192;
constexpr uint32_t OFF_REDU = 65536;
constexpr uint32_t OFF_REDV = 65536 + 8192;

constexpr int BAR_FULL = 0;
constexpr int BAR_LAST = 28;
constexpr int BAR_WUK = 33, BAR_WM2 = 35, BAR_WUV = 36, BAR_WO = 38, BAR_W1 = 40, BAR_W2 = 41;
constexpr int BAR_ALLCLR = 42, BAR_TS = 43, BAR_WV = 44;
constexpr int BAR_EMPTY = 45;
constexpr int BAR_P0BD = 52;
constexpr int BAR_P1D = 53, BAR_P2D = 54;
constexpr int BAR_P5D = 55, BAR_P7D = 56;
constexpr int NBARS = 57;
constexpr int BAR_XC = 57, BAR_WQ = 58;
constexpr int BAR_C = 60, BAR_END = 61;
constexpr uint32_t SB = 1024;

#define TUNE_LIST(X) \
  X(PC_T0, 340) X(PC_XC, 0) X(PC_C, 0) X(PC_P1, 320) X(PC_P2, 322) X(PC_STAG, 390) X(PC_DS, 0) X(PC_SL, 500) X(PC_W, 4) X(PC_NW, 10) \
  X(PW_A, -1) X(PW_0, 160) X(PW_ST, 0) X(PW_UV, 380) X(PW_G, 630) X(PW_O, 335) X(PW_F, 410) X(CLR_T0, 5000) X(CLR_CLK, 340) \
  X(D_MOD, 1500) X(D_QP, 1300) X(D_QX, 1300) X(D_TS, 1000) X(A_M, 2000) X(D_X1, 1400) X(A_X1, 2150) X(A_X1J, 60) \
  X(D_X2, 350) X(A_X2, 5180) X(D_X3A, 330) X(A_X3A, 0) X(D_X3B, 1780) X(D_FIN, 560) X(D_FIN2, 2300) X(RB, 0)
struct Tune {
#define X(n, v) static constexpr int n = v;
  TUNE_LIST(X)
#undef X
};

#define PFENCE 0
#define PVV 0
struct Scratch {
  uint32_t MOD1[2][4 * 64 * 64];
  uint32_t MOD2[2][128 * 64];
  uint32_t QP[2][128 * 256 * 2];
  uint32_t QX[2][8 * 32 * 256];
  uint32_t ML[32 * 64 * 2];
  uint32_t X1[128 * 64 * 64];
  uint32_t X2[128 * 256 * 2];
  uint32_t X3A[128 * 32 * 16];
  uint32_t X3B[NREP * 128 * 16];
  uint32_t X4[128 * NFG * 16];
  uint32_t epoch;
  uint32_t pad[31];
  uint32_t sync[NSYNC][32];
};
__device__ Scratch g_s;

#define CLK_DECL
#define CLK(i) do {} while (0)
#define CLK_DUMP() do {} while (0)
#define ITS(i, v) do {} while (0)

struct Params {
  CUtensorMap wq, wuk, wm2, ckv2, ckv1, wuv, wo, w1, w2;
};

__device__ __forceinline__ void mbar_init(uint32_t bar, int cnt) { asm volatile("mbarrier.init.shared::cta.b64 [%0], %1;" ::"r"(bar), "r"(cnt)); }
__device__ __forceinline__ void mbar_expect(uint32_t bar, uint32_t bytes) { asm volatile("mbarrier.arrive.expect_tx.shared::cta.b64 _, [%0], %1;" ::"r"(bar), "r"(bytes) : "memory"); }
__device__ __forceinline__ void mbar_arrive(uint32_t bar) { asm volatile("mbarrier.arrive.shared::cta.b64 _, [%0];" ::"r"(bar) : "memory"); }
__device__ __forceinline__ uint32_t clk32() { unsigned long long c; asm volatile("mov.u64 %0, %%clock64;" : "=l"(c) :: "memory"); return (uint32_t)c; }
__device__ __forceinline__ uint32_t gtime32() { uint32_t c; asm volatile("mov.u32 %0, %%globaltimer_lo;" : "=r"(c) :: "memory"); return c; }
__device__ __forceinline__ void wait_clk(uint32_t t0, int clocks) { while ((int)(clk32() - t0) < clocks) {} }
__device__ __forceinline__ void backoff(int clocks) { if (clocks > 0) wait_clk(clk32(), clocks); }
__device__ __forceinline__ void until_ns(uint32_t ns) { while ((int)(gtime32() - ns) < 0) {} }
__device__ __forceinline__ void slot(uint32_t& tn, int slack) {
  uint32_t now;
  do { now = gtime32(); } while ((int)(now - tn) < 0);
  if ((int)(now - tn) > slack) tn = now - slack;
}
template <typename T> __device__ __forceinline__ T* pin(T* p) { asm volatile("" : "+l"(p)); return p; }
constexpr int SPIN_LIMIT = 1 << 22;
__device__ __forceinline__ void mbar_wait(uint32_t bar) {
  asm volatile("{\n.reg .pred p;\n.reg .u32 c;\nmov.u32 c, 0;\n"
               "MW_LOOP:\nmbarrier.try_wait.parity.shared::cta.b64 p, [%0], 0;\n@p bra MW_DONE;\n"
               "add.u32 c, c, 1;\nsetp.lt.u32 p, c, 4194304;\n@p bra MW_LOOP;\ntrap;\nMW_DONE:\n}"
               ::"r"(bar) : "memory");
}
__device__ __forceinline__ bool mbar_test(uint32_t bar) {
  uint32_t ok;
  asm volatile("{\n.reg .pred p;\nmbarrier.test_wait.parity.shared::cta.b64 p, [%1], 0;\nselp.u32 %0,1,0,p;\n}" : "=r"(ok) : "r"(bar) : "memory");
  return ok;
}
__device__ __forceinline__ void tma2d(uint32_t dst, const CUtensorMap* m, int c0, int c1, uint32_t bar, uint64_t pol) {
  asm volatile("cp.async.bulk.tensor.2d.shared::cluster.global.mbarrier::complete_tx::bytes.L2::cache_hint [%0], [%1, {%3,%4}], [%2], %5;"
               ::"r"(dst), "l"(m), "r"(bar), "r"(c0), "r"(c1), "l"(pol) : "memory");
}
__device__ __forceinline__ void tma2d_nohint(uint32_t dst, const CUtensorMap* m, int c0, int c1, uint32_t bar) {
  asm volatile("cp.async.bulk.tensor.2d.shared::cluster.global.mbarrier::complete_tx::bytes [%0], [%1, {%3,%4}], [%2];"
               ::"r"(dst), "l"(m), "r"(bar), "r"(c0), "r"(c1) : "memory");
}
__device__ __forceinline__ void tma3d(uint32_t dst, const CUtensorMap* m, int c0, int c1, int c2, uint32_t bar, uint64_t pol) {
  asm volatile("cp.async.bulk.tensor.3d.shared::cluster.global.mbarrier::complete_tx::bytes.L2::cache_hint [%0], [%1, {%3,%4,%5}], [%2], %6;"
               ::"r"(dst), "l"(m), "r"(bar), "r"(c0), "r"(c1), "r"(c2), "l"(pol) : "memory");
}
__device__ __forceinline__ void tma5d(uint32_t dst, const CUtensorMap* m, int c0, int c1, int c2, int c3, int c4, uint32_t bar, uint64_t pol) {
  asm volatile("cp.async.bulk.tensor.5d.shared::cluster.global.mbarrier::complete_tx::bytes.L2::cache_hint [%0], [%1, {%3,%4,%5,%6,%7}], [%2], %8;"
               ::"r"(dst), "l"(m), "r"(bar), "r"(c0), "r"(c1), "r"(c2), "r"(c3), "r"(c4), "l"(pol) : "memory");
}
__device__ __forceinline__ void bulk_ld(uint32_t dst, const void* src, uint32_t bytes, uint32_t bar) {
  asm volatile("cp.async.bulk.shared::cluster.global.mbarrier::complete_tx::bytes [%0], [%1], %2, [%3];" ::"r"(dst), "l"(src), "r"(bytes), "r"(bar) : "memory");
}
__device__ __forceinline__ void bar_sync(int id, int n) { asm volatile("barrier.cta.sync.aligned %0, %1;" ::"r"(id), "r"(n) : "memory"); }
__device__ __forceinline__ void cbar() { asm volatile("barrier.cta.sync.aligned 1, 256;" ::: "memory"); }
__device__ __forceinline__ bool bar_over(float ex) {
  uint32_t over;
  asm volatile("{\n.reg .pred p, q;\nsetp.gtu.f32 p, %1, 0f41F00000;\nbarrier.cta.red.or.aligned.pred q, 4, 256, p;\nselp.u32 %0, 1, 0, q;\n}"
               : "=r"(over) : "f"(ex) : "memory");
  return over;
}

__device__ __forceinline__ uint32_t ldg_nc1(const void* p) { uint32_t v; asm volatile("ld.global.nc.L1::no_allocate.u32 %0, [%1];" : "=r"(v) : "l"(p)); return v; }
__device__ __forceinline__ uint2 ldg_nc2(const void* p) { uint2 v; asm volatile("ld.global.nc.v2.u32 {%0,%1}, [%2];" : "=r"(v.x), "=r"(v.y) : "l"(p)); return v; }
__device__ __forceinline__ uint4 ldg_nc4(const void* p) { uint4 v; asm volatile("ld.global.nc.L1::no_allocate.v4.u32 {%0,%1,%2,%3}, [%4];" : "=r"(v.x), "=r"(v.y), "=r"(v.z), "=r"(v.w) : "l"(p)); return v; }
__device__ __forceinline__ uint32_t ldg_rlx1(const void* p) { uint32_t v; asm volatile("ld.relaxed.gpu.global.u32 %0, [%1];" : "=r"(v) : "l"(p) : "memory"); return v; }
__device__ __forceinline__ void stg4(void* p, uint4 v) { asm volatile("st.relaxed.gpu.global.v4.u32 [%0], {%1,%2,%3,%4};" ::"l"(p), "r"(v.x), "r"(v.y), "r"(v.z), "r"(v.w) : "memory"); }
__device__ __forceinline__ void stg1(void* p, uint32_t a) { asm volatile("st.relaxed.gpu.global.u32 [%0], %1;" ::"l"(p), "r"(a) : "memory"); }
__device__ __forceinline__ uint32_t nz(uint32_t w) { return max(w, 1u); }
__device__ __forceinline__ uint2 ldg_u64(const void* p) {
  uint2 v; asm volatile("{\n.reg .b64 a;\nld.relaxed.gpu.global.b64 a, [%2];\nmov.b64 {%0,%1}, a;\n}" : "=r"(v.x), "=r"(v.y) : "l"(p) : "memory"); return v;
}
__device__ __forceinline__ uint4 ldg_2u64(const void* p) {
  uint4 v; asm volatile("{\n.reg .b64 a, b;\nld.relaxed.gpu.global.v2.b64 {a, b}, [%4];\nmov.b64 {%0,%1}, a;\nmov.b64 {%2,%3}, b;\n}" : "=r"(v.x), "=r"(v.y), "=r"(v.z), "=r"(v.w) : "l"(p) : "memory"); return v;
}
__device__ __forceinline__ void stg_u64(void* p, uint32_t x, uint32_t y) {
  asm volatile("{\n.reg .b64 a;\nmov.b64 a, {%1,%2};\nst.relaxed.gpu.global.b64 [%0], a;\n}" ::"l"(p), "r"(x), "r"(max(y, 1u)) : "memory");
}
__device__ __forceinline__ void stg_2u64(void* p, uint4 v) {
  asm volatile("{\n.reg .b64 a, b;\nmov.b64 a, {%1,%2};\nmov.b64 b, {%3,%4};\nst.relaxed.gpu.global.v2.b64 [%0], {a, b};\n}" ::"l"(p), "r"(v.x), "r"(max(v.y, 1u)), "r"(v.z), "r"(max(v.w, 1u)) : "memory");
}

__device__ __forceinline__ uint32_t pack_bf16(float lo, float hi) { uint32_t r; asm("cvt.rn.bf16x2.f32 %0, %1, %2;" : "=r"(r) : "f"(hi), "f"(lo)); return r; }
__device__ __forceinline__ float bf_lo(uint32_t w) { return __uint_as_float(w << 16); }
__device__ __forceinline__ float bf_hi(uint32_t w) { return __uint_as_float(w & 0xffff0000u); }
__device__ __forceinline__ float ex2(float x) { float r; asm("ex2.approx.ftz.f32 %0, %1;" : "=f"(r) : "f"(x)); return r; }
__device__ __forceinline__ uint32_t hmul2(uint32_t a, uint32_t b) { uint32_t r; asm("mul.rn.bf16x2 %0, %1, %2;" : "=r"(r) : "r"(a), "r"(b)); return r; }
__device__ __forceinline__ uint32_t hadd2(uint32_t a, uint32_t b) { uint32_t r; asm("add.rn.bf16x2 %0, %1, %2;" : "=r"(r) : "r"(a), "r"(b)); return r; }
__device__ __forceinline__ uint32_t hfma2(uint32_t a, uint32_t b, uint32_t c) { uint32_t r; asm("fma.rn.bf16x2 %0, %1, %2, %3;" : "=r"(r) : "r"(a), "r"(b), "r"(c)); return r; }
__device__ __forceinline__ uint32_t silu2(uint32_t v) { const float a = bf_lo(v), b = bf_hi(v); return pack_bf16(__fdividef(a, 1.f + __expf(-a)), __fdividef(b, 1.f + __expf(-b))); }
constexpr uint32_t ONE2 = 0x3f803f80u;

__device__ __forceinline__ void ldsm4(uint32_t (&r)[4], uint32_t a) { asm volatile("ldmatrix.sync.aligned.m8n8.x4.shared.b16 {%0,%1,%2,%3}, [%4];" : "=r"(r[0]), "=r"(r[1]), "=r"(r[2]), "=r"(r[3]) : "r"(a) : "memory"); }
__device__ __forceinline__ void ldsm4t(uint32_t (&r)[4], uint32_t a) { asm volatile("ldmatrix.sync.aligned.m8n8.x4.trans.shared.b16 {%0,%1,%2,%3}, [%4];" : "=r"(r[0]), "=r"(r[1]), "=r"(r[2]), "=r"(r[3]) : "r"(a) : "memory"); }
__device__ __forceinline__ void ldsm2t(uint32_t& r0, uint32_t& r1, uint32_t a) { asm volatile("ldmatrix.sync.aligned.m8n8.x2.trans.shared.b16 {%0,%1}, [%2];" : "=r"(r0), "=r"(r1) : "r"(a) : "memory"); }
__device__ __forceinline__ void stsm4t(uint32_t a, uint32_t r0, uint32_t r1, uint32_t r2, uint32_t r3) { asm volatile("stmatrix.sync.aligned.m8n8.x4.trans.shared.b16 [%0], {%1,%2,%3,%4};" ::"r"(a), "r"(r0), "r"(r1), "r"(r2), "r"(r3) : "memory"); }
__device__ __forceinline__ uint32_t movm(uint32_t a) { uint32_t d; asm volatile("movmatrix.sync.aligned.m8n8.trans.b16 %0, %1;" : "=r"(d) : "r"(a)); return d; }
__device__ __forceinline__ void mma16816(float (&d)[4], const uint32_t (&a)[4], uint32_t b0, uint32_t b1) {
  asm volatile("mma.sync.aligned.m16n8k16.row.col.f32.bf16.bf16.f32 {%0,%1,%2,%3}, {%4,%5,%6,%7}, {%8,%9}, {%0,%1,%2,%3};"
               : "+f"(d[0]), "+f"(d[1]), "+f"(d[2]), "+f"(d[3]) : "r"(a[0]), "r"(a[1]), "r"(a[2]), "r"(a[3]), "r"(b0), "r"(b1));
}
__device__ __forceinline__ void sts1(uint32_t a, uint32_t v) { asm volatile("st.shared.u32 [%0], %1;" ::"r"(a), "r"(v) : "memory"); }
__device__ __forceinline__ void sts2(uint32_t a, uint32_t x, uint32_t y) { asm volatile("st.shared.v2.u32 [%0], {%1,%2};" ::"r"(a), "r"(x), "r"(y) : "memory"); }
__device__ __forceinline__ void sts4(uint32_t a, uint4 v) { asm volatile("st.shared.v4.u32 [%0], {%1,%2,%3,%4};" ::"r"(a), "r"(v.x), "r"(v.y), "r"(v.z), "r"(v.w) : "memory"); }
__device__ __forceinline__ void sts2f(uint32_t a, float x, float y) { asm volatile("st.shared.v2.f32 [%0], {%1,%2};" ::"r"(a), "f"(x), "f"(y) : "memory"); }
__device__ __forceinline__ void sts4f(uint32_t a, float x, float y, float z, float w) { asm volatile("st.shared.v4.f32 [%0], {%1,%2,%3,%4};" ::"r"(a), "f"(x), "f"(y), "f"(z), "f"(w) : "memory"); }
__device__ __forceinline__ void stsf(uint32_t a, float v) { asm volatile("st.shared.f32 [%0], %1;" ::"r"(a), "f"(v) : "memory"); }
__device__ __forceinline__ uint32_t lds1(uint32_t a) { uint32_t v; asm volatile("ld.shared.u32 %0, [%1];" : "=r"(v) : "r"(a) : "memory"); return v; }
__device__ __forceinline__ float ldsf(uint32_t a) { float v; asm volatile("ld.shared.f32 %0, [%1];" : "=f"(v) : "r"(a) : "memory"); return v; }
__device__ __forceinline__ float2 ldsf2(uint32_t a) { float2 v; asm volatile("ld.shared.v2.f32 {%0,%1}, [%2];" : "=f"(v.x), "=f"(v.y) : "r"(a) : "memory"); return v; }
__device__ __forceinline__ float4 ldsf4(uint32_t a) { float4 v; asm volatile("ld.shared.v4.f32 {%0,%1,%2,%3}, [%4];" : "=f"(v.x), "=f"(v.y), "=f"(v.z), "=f"(v.w) : "r"(a) : "memory"); return v; }
__device__ __forceinline__ void lds4(uint32_t (&r)[4], uint32_t a) { asm volatile("ld.shared.v4.u32 {%0,%1,%2,%3}, [%4];" : "=r"(r[0]), "=r"(r[1]), "=r"(r[2]), "=r"(r[3]) : "r"(a) : "memory"); }

__device__ __forceinline__ void wg_fence() { asm volatile("wgmma.fence.sync.aligned;" ::: "memory"); }
__device__ __forceinline__ void wg_commit() { asm volatile("wgmma.commit_group.sync.aligned;" ::: "memory"); }
template <int N> __device__ __forceinline__ void wg_wait() { asm volatile("wgmma.wait_group.sync.aligned %0;" ::"n"(N) : "memory"); }
__host__ __device__ constexpr uint32_t desc_lo(uint32_t off) { return ((SB + off) >> 4) | 0x10000u; }
template <int TA, int ACC> __device__ __forceinline__ void wgmma_n16(float (&d)[8], uint32_t da, uint32_t db) {
  asm volatile("{\n.reg .b64 da, db;\nmov.b64 da, {%8, 0x40000040};\nmov.b64 db, {%9, 0x40000040};\n"
               "wgmma.mma_async.sync.aligned.m64n16k16.f32.bf16.bf16 {%0,%1,%2,%3,%4,%5,%6,%7}, da, db, %11, 1, 1, %10, 0;\n}"
               : "+f"(d[0]), "+f"(d[1]), "+f"(d[2]), "+f"(d[3]), "+f"(d[4]), "+f"(d[5]), "+f"(d[6]), "+f"(d[7])
               : "r"(da), "r"(db), "n"(TA), "n"(ACC));
}
__device__ __forceinline__ void wgmma_n16_ones(float (&d)[8], uint32_t one, uint32_t db) {
  asm volatile("{\n.reg .b64 db;\nmov.b64 db, {%9, 0x40000040};\n"
               "wgmma.mma_async.sync.aligned.m64n16k16.f32.bf16.bf16 {%0,%1,%2,%3,%4,%5,%6,%7}, {%8,%8,%8,%8}, db, 1, 1, 1, 0;\n}"
               : "+f"(d[0]), "+f"(d[1]), "+f"(d[2]), "+f"(d[3]), "+f"(d[4]), "+f"(d[5]), "+f"(d[6]), "+f"(d[7])
               : "r"(one), "r"(db));
}
__device__ __forceinline__ void acc_fence(float (&d)[8]) {
  asm volatile("" : "+f"(d[0]), "+f"(d[1]), "+f"(d[2]), "+f"(d[3]), "+f"(d[4]), "+f"(d[5]), "+f"(d[6]), "+f"(d[7]) :: "memory");
}

template <int N, int STRIDE> __device__ __forceinline__ void load_units(uint2 (&v)[N], const uint32_t* p) {
#pragma unroll
  for (int i = 0; i < N; i++) v[i] = ldg_u64(p + i * STRIDE);
}
template <int N, int STRIDE> __device__ __forceinline__ int check_units(uint2 (&v)[N], const uint32_t* p, int rb) {
  int it = 0;
  while (true) {
    uint32_t mn = v[0].y;
#pragma unroll
    for (int i = 1; i < N; i++) mn = min(mn, v[i].y);
    if (mn != 0) break;
    backoff(rb);
#pragma unroll
    for (int i = 0; i < N; i++) if (v[i].y == 0) v[i] = ldg_u64(p + i * STRIDE);
    if (++it > SPIN_LIMIT) __trap();
  }
  return it;
}
__device__ __forceinline__ void sum4_to_smem(const uint2 (&v)[4], uint32_t dst) {
  const float c0 = (bf_lo(v[0].x) + bf_lo(v[1].x)) + (bf_lo(v[2].x) + bf_lo(v[3].x));
  const float c1 = (bf_hi(v[0].x) + bf_hi(v[1].x)) + (bf_hi(v[2].x) + bf_hi(v[3].x));
  const float c2 = (bf_lo(v[0].y) + bf_lo(v[1].y)) + (bf_lo(v[2].y) + bf_lo(v[3].y));
  const float c3 = (bf_hi(v[0].y) + bf_hi(v[1].y)) + (bf_hi(v[2].y) + bf_hi(v[3].y));
  sts1(dst, pack_bf16(c0, c1));
  sts1(dst + 128, pack_bf16(c2, c3));
}
__device__ __forceinline__ void load_a_t(uint32_t (&a)[8][4], uint32_t wbase, int w, int lane) {
  const int mi = lane >> 3, r = lane & 7;
  const uint32_t base = wbase + (w >> 2) * 16384 + (8 * (mi >> 1) + r) * 128 + (((2 * (w & 3) + (mi & 1)) ^ r) << 4);
#pragma unroll
  for (int ks = 0; ks < 8; ks++) ldsm4t(a[ks], base + ks * 2048);
}
__device__ __forceinline__ void mma128(float (&d)[4], const uint32_t (&a)[8][4], const uint32_t (&b)[4][4]) {
  float e[4][4] = {{0.f, 0.f, 0.f, 0.f}, {0.f, 0.f, 0.f, 0.f}, {0.f, 0.f, 0.f, 0.f}, {0.f, 0.f, 0.f, 0.f}};
#pragma unroll
  for (int kk = 0; kk < 4; kk++) { mma16816(e[(2 * kk) & 3], a[2 * kk], b[kk][0], b[kk][1]); mma16816(e[(2 * kk + 1) & 3], a[2 * kk + 1], b[kk][2], b[kk][3]); }
#pragma unroll
  for (int i = 0; i < 4; i++) d[i] = (e[0][i] + e[1][i]) + (e[2][i] + e[3][i]);
}
template <int NP> __device__ __forceinline__ int sum_pieces(const uint32_t* p0, int g, int t, float& v0, float& v1, int rb) {
  constexpr int NL = NP / 8;
  uint32_t v[NL][4];
#pragma unroll
  for (int i = 0; i < NL; i++) { const uint4 x = ldg_2u64(p0 + i * 128); v[i][0] = x.x; v[i][1] = x.y; v[i][2] = x.z; v[i][3] = x.w; }
  int it = 0;
  while (true) {
    uint32_t mn = 0xffffffffu;
#pragma unroll
    for (int i = 0; i < NL; i++) mn = min(mn, min(v[i][1], v[i][3]));
    if (mn != 0) break;
    backoff(rb);
#pragma unroll
    for (int i = 0; i < NL; i++)
      if (v[i][1] == 0 || v[i][3] == 0) { const uint4 x = ldg_2u64(p0 + i * 128); v[i][0] = x.x; v[i][1] = x.y; v[i][2] = x.z; v[i][3] = x.w; }
    if (++it > SPIN_LIMIT) __trap();
  }
  __syncwarp();
  const uint32_t one = (g & 1) ? 0x3f800000u : 0x00003f80u;
  const uint32_t b0 = (g & 2) ? 0u : one, b1 = (g & 2) ? one : 0u;
  float d[4][4] = {{0.f, 0.f, 0.f, 0.f}, {0.f, 0.f, 0.f, 0.f}, {0.f, 0.f, 0.f, 0.f}, {0.f, 0.f, 0.f, 0.f}};
#pragma unroll
  for (int i = 0; i < NL; i++) mma16816(d[i & 3], v[i], b0, b1);
  const bool up = t & 2;
  const float x0 = up ? (d[0][2] + d[1][2]) + (d[2][2] + d[3][2]) : (d[0][0] + d[1][0]) + (d[2][0] + d[3][0]);
  const float x1 = up ? (d[0][3] + d[1][3]) + (d[2][3] + d[3][3]) : (d[0][1] + d[1][1]) + (d[2][1] + d[3][1]);
  v0 = x0 + __shfl_xor_sync(~0u, x0, 16);
  v1 = x1 + __shfl_xor_sync(~0u, x1, 16);
  return it;
}
template <typename F> __device__ __forceinline__ float reduce_g(const float (&x)[4], int lane, F f) {
  const bool u4 = lane & 16, u3 = lane & 8;
  const float a0 = f(u4 ? x[2] : x[0], __shfl_xor_sync(~0u, u4 ? x[0] : x[2], 16));
  const float a1 = f(u4 ? x[3] : x[1], __shfl_xor_sync(~0u, u4 ? x[1] : x[3], 16));
  const float b = f(u3 ? a1 : a0, __shfl_xor_sync(~0u, u3 ? a0 : a1, 8));
  return f(b, __shfl_xor_sync(~0u, b, 4));
}

__global__ void __launch_bounds__(NTHREADS, 1)
fused_decode_kernel(__nv_bfloat16* __restrict__ gout, Scratch* __restrict__ gs, const uint8_t* __restrict__ gwmod,
                    const uint8_t* __restrict__ gx, const uint8_t* __restrict__ gc,
                    const __grid_constant__ Params P) {
  constexpr Tune T{};
  extern __shared__ __align__(1024) uint8_t smem_raw[];
  const uint32_t sb = (uint32_t)__cvta_generic_to_shared(smem_raw);
  const int tid = threadIdx.x, lane = tid & 31;
  const int w = __shfl_sync(0xffffffffu, tid >> 5, 0);
  const int cta = blockIdx.x;
  const uint32_t bars = sb + OFF_BARS;
  auto BAR = [&](int i) { return bars + 8 * i; };
  const int g = lane >> 2, t = lane & 3;
  const int hI = cta >> 2, jI = cta & 3;
  const int bs = cta >> 1, hh = cta & 1;

  CLK_DECL;
  CLK(0);
  if (w == 8) {
    CLK(7);
    const uint32_t t_entry = gtime32();
    CLK(8);
    if (lane == 0) {
      if ((sb & 0xffffff) != SB) __trap();
      mbar_init(BAR(BAR_WQ), 1); mbar_init(BAR(BAR_WQ + 1), 1); mbar_init(BAR(BAR_XC), 1); mbar_init(BAR(BAR_C), 1);
      asm volatile("fence.mbarrier_init.release.cluster;" ::: "memory");
      asm volatile("prefetch.tensormap [%0];" ::"l"(&P.wq) : "memory");
      mbar_expect(BAR(BAR_XC), 8192); mbar_expect(BAR(BAR_C), 8192); mbar_expect(BAR(BAR_WQ), 16384); mbar_expect(BAR(BAR_WQ + 1), 16384);
      CLK(9);
    }
    __syncwarp();
    asm volatile("barrier.cta.arrive.aligned 0, %0;" ::"n"(NTHREADS) : "memory");
    CLK(10);
    uint32_t tn = t_entry + T.PC_T0 + ((bs * 37) & 63) * T.PC_STAG / 64;
    const int h = hI, j = jI;
    if (lane == 0) {
      uint64_t pol; asm volatile("createpolicy.fractional.L2::evict_first.b64 %0, 1.0;" : "=l"(pol));
#pragma unroll
      for (int u = 0; u < 4; u++) {
        until_ns(tn + u * T.PC_P1);
        if (u == 0) CLK(11);
        tma2d(sb + OFF_WQ + u * 8192, &P.wq, 128 * h + 64 * (u >> 1), 128 * j + 64 * (u & 1), BAR(BAR_WQ + (u >> 1)), pol);
        if (u == T.PC_XC) {
#pragma unroll
          for (int i = 0; i < 4; i++) { const int o = ((i + cta) & 3) * 2048; bulk_ld(sb + OFF_XS + o, gx + o, 2048, BAR(BAR_XC)); }
        }
        if (u == T.PC_C) {
#pragma unroll
          for (int i = 0; i < 4; i++) { const int o = ((i + cta) & 3) * 2048; bulk_ld(sb + OFF_CS + o, gc + o, 2048, BAR(BAR_C)); }
        }
        if (u == 0) {
          CLK(1);
          asm volatile("prefetch.tensormap [%0];" ::"l"(&P.wuk) : "memory");
          asm volatile("prefetch.tensormap [%0];" ::"l"(&P.wm2) : "memory");
          asm volatile("prefetch.tensormap [%0];" ::"l"(&P.ckv2) : "memory");
        }
      }
    }
    __syncwarp();
    tn += 4 * T.PC_P1;
    bar_sync(5, 64);
    if (lane == 0) {
      uint64_t pol; asm volatile("createpolicy.fractional.L2::evict_first.b64 %0, 1.0;" : "=l"(pol));
#pragma unroll
      for (int u = 0; u < 4; u++) {
        if ((u & 1) == (T.PC_W > 3) && T.PC_NW) mbar_wait(BAR(BAR_WQ + (u >> 1)));
        slot(tn, T.PC_SL);
        tma5d(sb + OFF_WUK + u * 8192, &P.wuk, 128 * h + 64 * (u >> 1), 0, 0, 0, 8 * j + 4 * (u & 1), BAR(BAR_WUK + (u >> 1)), pol);
        tn += T.PC_P1;
      }
#pragma unroll
      for (int u = 0; u < 2; u++) {
        if (u == (T.PC_W > 3) && T.PC_NW) mbar_wait(BAR(BAR_WUK));
        slot(tn, T.PC_SL);
        tma2d_nohint(sb + OFF_WM2 + u * 8192, &P.wm2, 1024 + 16 * cta, 256 * u, BAR(BAR_WM2));
        tn += T.PC_P1;
      }
      const int row0 = (bs >> 3) * 4096 + (bs & 7) * 64;
      uint32_t dst = sb + OFF_RING;
      const int p2 = T.PC_P2 + (32 - ((bs * 37) & 63)) * T.PC_DS / 1024;
#pragma unroll 1
      for (int n = 0; n < 31; n++) {
        if (n >= 4 && (n < 12 || (n & 3) == 0)) mbar_wait(BAR(n >= 12 ? BAR_EMPTY + (n >> 2) - 3 : n == 7 ? BAR_P0BD : (n == 8 || n == 9) ? BAR_P2D : BAR_P1D));
        if (n < T.PC_NW) {
          if (n >= T.PC_W) mbar_wait(BAR(BAR_FULL + n - T.PC_W));
          else if ((n & 1) == (T.PC_W > 3)) mbar_wait(BAR(n < 2 ? BAR_WUK + 1 : BAR_WM2));
        }
        slot(tn, T.PC_SL);
        tma3d(dst, &P.ckv2, 0, row0 + (n >> 2) * 512, 2 * (n & 3), BAR(BAR_FULL + n), pol);
        dst = (n == 11 || n == 23) ? sb + OFF_RING : dst + 16384;
        tn += n >= 15 ? p2 : T.PC_P2;
        if (n == 4) CLK(2);
        if (n == 12) CLK(3);
        if (n == 20) CLK(4);
        if (n == 28) CLK(5);
        if (n == 24) {
          asm volatile("prefetch.tensormap [%0];" ::"l"(&P.ckv1) : "memory");
          asm volatile("prefetch.tensormap [%0];" ::"l"(&P.wuv) : "memory");
          asm volatile("prefetch.tensormap [%0];" ::"l"(&P.wo) : "memory");
          asm volatile("prefetch.tensormap [%0];" ::"l"(&P.w1) : "memory");
          asm volatile("prefetch.tensormap [%0];" ::"l"(&P.w2) : "memory");
        }
      }
      slot(tn, T.PC_SL);
      tma3d(dst, &P.ckv1, 0, row0 + 7 * 512, 6, BAR(BAR_LAST + 3), pol);
      tma3d(dst + 8192, &P.ckv1, 0, row0 + 7 * 512, 7, BAR(BAR_LAST + 4), pol);
      tn += T.PC_P2;
      CLK(6);
      auto unit = [&](int u) {
        if (u < 4) tma5d(sb + OFF_WUV + u * 8192, &P.wuv, 128 * h + 64 * (u >> 1), 0, 4 * (j >> 1), 0, 2 * (j & 1) + (u & 1), BAR(BAR_WUV + (u >> 1)), pol);
        else if (u < 8) tma2d(sb + OFF_WO + (u - 4) * 8192, &P.wo, 128 * j + 64 * ((u - 4) >> 1), 128 * h + 64 * (u & 1), BAR(BAR_WO + ((u - 4) >> 1)), pol);
        else if (u < 10) { if (cta < NFF) tma2d_nohint(sb + OFF_W1 + (u - 8) * 16384, &P.w1, 32 * bs, 256 * (u - 8), BAR(BAR_W1)); }
        else if (cta < NFF) tma3d(sb + OFF_W2 + (u - 10) * 8192, &P.w2, 0, 32 * bs, 4 * hh + 2 * (u - 10), BAR(BAR_W2), pol);
      };
      mbar_wait(BAR(BAR_EMPTY + 5));
      if (T.PW_A >= 0) { mbar_wait(BAR(BAR_LAST + T.PW_A)); tn = gtime32(); }
      tn += T.PW_0 + ((cta * 37) & 127) * T.PW_ST / 128;
#pragma unroll
      for (int u = 0; u < 12; u++) {
        if (u == 8) mbar_wait(BAR(BAR_EMPTY + 6));
        until_ns(tn);
        unit(u);
        tn += u < 3 ? T.PW_UV : u == 3 ? T.PW_G : u < 8 ? T.PW_O : T.PW_F;
      }
      CLK_DUMP();
    }
    return;
  }

  if (w == 9) {
    if (lane == 0) {
#pragma unroll
      for (int i = 0; i < NBARS; i++) mbar_init(BAR(i), i >= BAR_P1D ? 8 : i >= BAR_EMPTY ? 4 : 1);
      asm volatile("fence.mbarrier_init.release.cluster;" ::: "memory");
    }
    __syncwarp();
    mbar_expect(BAR(lane), lane == BAR_LAST + 3 ? 8192 : 16384);
    if (lane < BAR_ALLCLR - 32) mbar_expect(BAR(32 + lane), lane == 0 ? 8192 : lane == BAR_W1 - 32 ? 32768 : 16384);
    CLK(9);
    asm volatile("barrier.cta.arrive.aligned 5, 64;" ::: "memory");
    asm volatile("barrier.cta.arrive.aligned 0, %0;" ::"n"(NTHREADS) : "memory");
  }
  const uint32_t epoch = ldg_rlx1(&gs->epoch);

  if (w == 9) {
    const int wd = 2 * (t & 1) + (t >> 1), bo = 2 * (g & 3) + (wd >> 1), mo = 16 * hI + 2 * jI + 8 * (wd & 1);
    const uint32_t xo = ldg_nc1(gx + (bo * 512 + mo) * 2);
    const int par = epoch & 1;
    until_ns(gtime32() + T.CLR_T0);
    {
      const uint4 z = make_uint4(0, 0, 0, 0);
      uint4* x1 = reinterpret_cast<uint4*>(gs->X1 + ((64 * hh + (lane >> 4)) * 64 + bs) * 64) + (lane & 15);
      constexpr int sx1 = 2 * 64 * 16, sx3 = 8 * 32 * 4, sx4 = 8 * NFG * 4;
      uint4* x3 = reinterpret_cast<uint4*>(gs->X3A + ((32 * jI + g) * 32 + hI) * 16) + t;
      uint4* x4 = reinterpret_cast<uint4*>(gs->X4 + ((64 * hh + g) * NFG + bs) * 16) + t;
#pragma unroll 1
      for (int i0 = 0; i0 < 32; i0 += 4) {
#pragma unroll
        for (int i = 0; i < 4; i++) stg4(x1 + (i0 + i) * sx1, z);
        backoff(T.CLR_CLK);
      }
#pragma unroll
      for (int i = 0; i < 4; i++) stg4(x3 + i * sx3, z);
      backoff(T.CLR_CLK);
#pragma unroll
      for (int i = 0; i < 4; i++) stg4(reinterpret_cast<uint4*>(gs->X2 + cta * 512) + i * 32 + lane, z);
      backoff(T.CLR_CLK);
      stg4(reinterpret_cast<uint4*>(gs->X3B + (lane >> 2) * 2048 + cta * 16) + (lane & 3), z);
      if (lane < 8) stg4(reinterpret_cast<uint4*>(gs->ML + cta * 32) + lane, z);
      if (cta < NFF) {
#pragma unroll
        for (int i = 0; i < 8; i++) { stg4(x4 + i * sx4, z); if ((i & 3) == 1) backoff(T.CLR_CLK); }
      }
      CLK(1);
      asm volatile("fence.acq_rel.gpu;" ::: "memory");
      CLK(2);
      __syncwarp();
      if (lane < NSYNC) asm volatile("red.relaxed.gpu.global.add.u32 [%0], 1;" ::"l"(&gs->sync[lane][0]) : "memory");
#pragma unroll
      for (int i = 0; i < 4; i++) stg4(reinterpret_cast<uint4*>(gs->QP[par ^ 1] + cta * 512) + i * 32 + lane, z);
      backoff(T.CLR_CLK);
#pragma unroll
      for (int i = 0; i < 4; i++) stg4(reinterpret_cast<uint4*>(gs->QX[par ^ 1] + cta * 512) + i * 32 + lane, z);
      stg4(reinterpret_cast<uint4*>(gs->MOD1[par ^ 1] + cta * 128) + lane, z);
      if (lane < 16) stg4(reinterpret_cast<uint4*>(gs->MOD2[par ^ 1] + cta * 64) + lane, z);
      if (lane == 0) {
        const uint32_t target = (epoch + 1) * NCTA;
        uint32_t c; int it = 0;
        do { backoff(T.CLR_CLK); asm volatile("ld.acquire.gpu.global.u32 %0, [%1];" : "=r"(c) : "l"(&gs->sync[cta % NSYNC][0]) : "memory"); if (++it > SPIN_LIMIT) __trap(); } while ((int)(c - target) < 0);
        mbar_arrive(BAR(BAR_ALLCLR));
      }
      __syncwarp();
    }
    CLK(3);
    uint2 gg[2];
    {
      const uint32_t* pg = gs->MOD2[par] + cta * 16 + bo * 2;
      load_units<2, 3 * 2048>(gg, pg);
      check_units<2, 3 * 2048>(gg, pg, T.RB);
    }
    const uint32_t ga2 = (wd & 1) ? gg[0].y : gg[0].x, gb2 = (wd & 1) ? gg[1].y : gg[1].x;
    uint32_t anchor;
    {
      mbar_wait(BAR(BAR_LAST + 4));
      unsigned long long now; asm volatile("mov.u64 %0, %%globaltimer;" : "=l"(now));
      if (lane < NSYNC) {
        asm volatile("red.relaxed.gpu.global.max.u64 [%0], %1;" ::"l"(&gs->sync[lane][2]), "l"(now) : "memory");
        asm volatile("red.relaxed.gpu.global.add.u32 [%0], 1;" ::"l"(&gs->sync[lane][1]) : "memory");
      }
      backoff(T.D_TS);
      const uint32_t target = (epoch + 1) * NCTA;
      uint4 v; int it = 0;
      do { v = ldg_2u64(gs->sync[cta % NSYNC]); if (++it > SPIN_LIMIT) __trap(); } while ((int)(v.y - target) < 0);
      const int age = min(max((int)(gtime32() - v.z), 0), 4000);
      anchor = clk32() - age * 7 / 4;
      if (lane == 0) { sts1(sb + OFF_TS, anchor); mbar_arrive(BAR(BAR_TS)); }
      CLK(10);
    }
    {
      const uint32_t* pm = pin(gs->ML + hI * 128 + lane * 4);
      wait_clk(anchor, T.A_M);
      uint4 ml = ldg_2u64(pm);
      int it = 0;
      while (ml.y == 0 || ml.w == 0) { ml = ldg_2u64(pm); if (++it > SPIN_LIMIT) __trap(); }
      __syncwarp();
      ITS(2, it);
      float M = fmaxf(__uint_as_float(ml.x), __uint_as_float(ml.z));
      M = fmaxf(M, __shfl_xor_sync(~0u, M, 1)); M = fmaxf(M, __shfl_xor_sync(~0u, M, 2));
      const float e0 = ex2(__uint_as_float(ml.x) - M), e1 = ex2(__uint_as_float(ml.z) - M);
      float l = e0 * __uint_as_float(ml.y) + e1 * __uint_as_float(ml.w);
      l += __shfl_xor_sync(~0u, l, 1); l += __shfl_xor_sync(~0u, l, 2);
      const float inv = __fdividef(1.f, l);
      sts2f(sb + OFF_WV + lane * 8, e0 * inv, e1 * inv);
      __syncwarp();
      if (lane == 0) mbar_arrive(BAR(BAR_WV));
      CLK(11);
    }
    float v0, v1;
    uint32_t* const x3o = pin(gs->X3B + (lane >> 2) * 2048 + cta * 16 + (lane & 3) * 4);
    uint32_t* const fo = pin(reinterpret_cast<uint32_t*>(gout) + (bo * 512 + mo) / 2);
    const int po = (4 * (g >> 2) + t) * 16 + (g & 3) * 4;
    const uint32_t* const p3 = pin(gs->X3A + cta * 512 + po);
    const uint32_t* const p4 = pin(gs->X4 + cta * NFG * 16 + po);
    mbar_wait(BAR(BAR_P5D));
    backoff(T.D_X3A);
    wait_clk(anchor, T.A_X3A);
    CLK(4);
    { const int it = sum_pieces<32>(p3, g, t, v0, v1, T.RB); ITS(0, it); }
    CLK(5);
    const uint32_t x2w = pack_bf16(bf_lo(xo) + bf_lo(ga2) * v0, bf_hi(xo) + bf_hi(ga2) * v1);
    {
      const int src = 4 * (lane & 3);
      uint4 o;
      o.x = __shfl_sync(~0u, x2w, src); o.y = __shfl_sync(~0u, x2w, src + 2); o.z = __shfl_sync(~0u, x2w, src + 1); o.w = __shfl_sync(~0u, x2w, src + 3);
      stg_2u64(x3o, o);
    }
    CLK(6);
    if (cta < NFF) { mbar_wait(BAR(BAR_P7D)); backoff(T.D_FIN); } else backoff(T.D_FIN2);
    CLK(7);
    { const int it = sum_pieces<NFG>(p4, g, t, v0, v1, T.RB); ITS(1, it); }
    if (g < 4) *fo = pack_bf16(bf_lo(x2w) + bf_lo(gb2) * v0, bf_hi(x2w) + bf_hi(gb2) * v1);
    CLK(8);
    CLK_DUMP();
    if (cta == 0 && lane == 0) stg1(&gs->epoch, epoch + 1);
    return;
  }

  const int wg = w >> 2, wq = w & 3;
  uint32_t tstore;
  {
    const uint8_t* pw = gwmod + (size_t)(128 * jI + 16 * w + 4 * (g >> 1) + (g & 1)) * 6144 + 64 * hI + 16 * t;
    const uint4 w0 = ldg_nc4(pw), w1 = ldg_nc4(pw + 2 * 6144);
    const uint2 cc = ldg_nc2(gc + g * 1024 + 256 * jI + 32 * w + 8 * t);
    CLK(40);
    const uint32_t a[4] = {silu2(cc.x), 0u, silu2(cc.y), 0u};
    float d[4][4] = {{0.f, 0.f, 0.f, 0.f}, {0.f, 0.f, 0.f, 0.f}, {0.f, 0.f, 0.f, 0.f}, {0.f, 0.f, 0.f, 0.f}};
    mma16816(d[0], a, movm(w0.x), movm(w1.x)); mma16816(d[1], a, movm(w0.y), movm(w1.y));
    mma16816(d[2], a, movm(w0.z), movm(w1.z)); mma16816(d[3], a, movm(w0.w), movm(w1.w));
    CLK(1);
    sts4f(sb + OFF_P0S + w * 1088 + lane * 16, d[0][0], d[0][1], d[1][0], d[1][1]);
    sts4f(sb + OFF_P0S + w * 1088 + 544 + lane * 16, d[2][0], d[2][1], d[3][0], d[3][1]);
    bar_sync(0, NTHREADS);
    if (tid < 128) {
      const uint32_t src = sb + OFF_P0S + ((tid >> 2) & 1) * 544 + (((tid >> 3) & 7) * 4 + 2 * (tid >> 6) + (tid & 1)) * 16 + ((tid >> 1) & 1) * 8;
      float2 v[8];
#pragma unroll
      for (int i = 0; i < 8; i++) v[i] = ldsf2(src + i * 1088);
      const float ax = ((v[0].x + v[1].x) + (v[2].x + v[3].x)) + ((v[4].x + v[5].x) + (v[6].x + v[7].x));
      const float ay = ((v[0].y + v[1].y) + (v[2].y + v[3].y)) + ((v[4].y + v[5].y) + (v[6].y + v[7].y));
      stg1(gs->MOD1[epoch & 1] + jI * 4096 + hI * 128 + tid, nz(pack_bf16(ax, ay)));
    }
    tstore = clk32();
  }
  CLK(2);
  const int par = epoch & 1;
  uint32_t cf[4][4];
  mbar_wait(BAR(BAR_XC));
  {
    uint32_t u[2][4];
    lds4(u[0], sb + OFF_XS + w * 1024 + lane * 16); lds4(u[1], sb + OFF_XS + w * 1024 + 512 + lane * 16);
    float v[16];
#pragma unroll
    for (int i = 0; i < 8; i++) { v[2 * i] = bf_lo(u[i >> 2][i & 3]); v[2 * i + 1] = bf_hi(u[i >> 2][i & 3]); }
    float s = 0.f;
#pragma unroll
    for (int i = 0; i < 16; i++) s += v[i];
#pragma unroll
    for (int o = 16; o; o >>= 1) s += __shfl_xor_sync(~0u, s, o);
    const float mu = s * (1.f / 512.f);
    float q = 0.f;
#pragma unroll
    for (int i = 0; i < 16; i++) { v[i] -= mu; q += v[i] * v[i]; }
#pragma unroll
    for (int o = 16; o; o >>= 1) q += __shfl_xor_sync(~0u, q, o);
    const float rs = rsqrtf(q * (1.f / 512.f) + 1e-5f);
    const bool hi = jI & 2;
    uint32_t o[4];
#pragma unroll
    for (int i = 0; i < 4; i++) o[i] = pack_bf16((hi ? v[8 + 2 * i] : v[2 * i]) * rs, (hi ? v[9 + 2 * i] : v[2 * i + 1]) * rs);
    if ((lane >> 4) == (jI & 1)) sts4(sb + OFF_XN + w * 272 + (lane & 15) * 16, make_uint4(o[0], o[1], o[2], o[3]));
  }
  CLK(3);
  uint32_t aw[8][4];
  {
    const uint32_t* pm = pin(gs->MOD1[par] + (8 * jI + w) * 64 + lane * 2);
    uint32_t* const qpo = pin(gs->QP[par] + (cta * 256 + tid) * 2);
    wait_clk(tstore, T.D_MOD);
    CLK(4);
    uint2 v[8];
    load_units<8, 2048>(v, pm);
    cbar();
    const uint32_t xn0 = lds1(sb + OFF_XN + g * 272 + w * 32 + t * 4), xn1 = lds1(sb + OFF_XN + g * 272 + w * 32 + 16 + t * 4);
    const bool early = __all_sync(~0u, mbar_test(BAR(BAR_WQ + wg)));
    if (early) load_a_t(aw, sb + OFF_WQ, w, lane);
    int it = 0;
    while (true) {
      uint32_t mn = 0xffffffffu;
#pragma unroll
      for (int i = 0; i < 8; i++) mn = min(mn, min(v[i].x, v[i].y));
      if (mn != 0) break;
#pragma unroll
      for (int i = 0; i < 8; i++) if (v[i].x == 0 || v[i].y == 0) v[i] = ldg_u64(pm + i * 2048);
      if (++it > SPIN_LIMIT) __trap();
    }
    CLK(5);
    ITS(0, it);
    float sc[2][4];
#pragma unroll
    for (int i = 0; i < 2; i++) {
      sc[i][0] = (bf_lo(v[i].x) + bf_lo(v[2 + i].x)) + (bf_lo(v[4 + i].x) + bf_lo(v[6 + i].x));
      sc[i][1] = (bf_hi(v[i].x) + bf_hi(v[2 + i].x)) + (bf_hi(v[4 + i].x) + bf_hi(v[6 + i].x));
      sc[i][2] = (bf_lo(v[i].y) + bf_lo(v[2 + i].y)) + (bf_lo(v[4 + i].y) + bf_lo(v[6 + i].y));
      sc[i][3] = (bf_hi(v[i].y) + bf_hi(v[2 + i].y)) + (bf_hi(v[4 + i].y) + bf_hi(v[6 + i].y));
    }
    sts2(sb + OFF_BS1 + (w >> 1) * 512 + lane * 16 + (w & 1) * 8,
         pack_bf16(bf_lo(xn0) * (1.f + sc[1][0]) + sc[0][0], bf_hi(xn0) * (1.f + sc[1][1]) + sc[0][1]),
         pack_bf16(bf_lo(xn1) * (1.f + sc[1][2]) + sc[0][2], bf_hi(xn1) * (1.f + sc[1][3]) + sc[0][3]));
    if (!early) { mbar_wait(BAR(BAR_WQ + wg)); load_a_t(aw, sb + OFF_WQ, w, lane); }
    CLK(6);
    cbar();
    uint32_t b[4][4];
#pragma unroll
    for (int kk = 0; kk < 4; kk++) lds4(b[kk], sb + OFF_BS1 + kk * 512 + lane * 16);
    float d[4];
    mma128(d, aw, b);
    stg_u64(qpo, pack_bf16(d[0], d[1]), pack_bf16(d[2], d[3]));
    tstore = clk32();
    CLK(7);
    if (wg) {
      mbar_wait(BAR(BAR_C));
#pragma unroll
      for (int i = 0; i < 4; i++) lds4(cf[i], sb + OFF_CS + g * 1024 + wq * 256 + i * 64 + t * 16);
#pragma unroll
      for (int i = 0; i < 16; i++) cf[i >> 2][i & 3] = silu2(cf[i >> 2][i & 3]);
    }
    __syncwarp();
    if (lane == 0) mbar_arrive(BAR(BAR_P1D));
  }
  {
    const uint32_t* pq = pin(gs->QP[par] + (hI * 4 * 256 + tid) * 2);
    uint32_t* const qxo = pin(gs->QX[par] + (g * 32 + hI) * 256 + 64 * jI + 8 * w + 2 * t);
    uint2 v[4];
    wait_clk(tstore, T.D_QP);
    CLK(8);
    load_units<4, 512>(v, pq);
    const uint32_t abase = sb + OFF_WUK + (16 * w + (lane & 15)) * 128;
    auto load_half = [&](int hf) {
#pragma unroll
      for (int ks = 0; ks < 4; ks++) ldsm4(aw[4 * hf + ks], abase + hf * 16384 + (((2 * ks + (lane >> 4)) ^ (lane & 7)) << 4));
    };
    mbar_wait(BAR(BAR_WUK));
    load_half(0);
    const bool early = __all_sync(~0u, mbar_test(BAR(BAR_WUK + 1)));
    if (early) load_half(1);
    const int it = check_units<4, 512>(v, pq, T.RB);
    CLK(9);
    ITS(1, it);
    sum4_to_smem(v, sb + OFF_BS2 + (16 * w + g) * 16 + t * 4);
    if (!early) { mbar_wait(BAR(BAR_WUK + 1)); load_half(1); }
    CLK(10);
    cbar();
    uint32_t b[4][4];
#pragma unroll
    for (int kk = 0; kk < 4; kk++) ldsm4t(b[kk], sb + OFF_BS2 + (32 * kk + lane) * 16);
    float d[4];
    mma128(d, aw, b);
    const float sc = 0.08838834764831845f * 1.4426950408889634f;
    stg_u64(qxo, movm(pack_bf16(d[0] * sc, d[1] * sc)), movm(pack_bf16(d[2] * sc, d[3] * sc)));
    tstore = clk32();
    CLK(11);
    if (lane == 0) mbar_arrive(BAR(BAR_P2D));
  }
  if (wg) {
    const int mi = lane >> 3, r = lane & 7;
    const uint32_t a0 = sb + OFF_WM2 + (8 * (r >> 1) + (r & 1) + 2 * (mi >> 1)) * 32 + (mi & 1) * 16;
    mbar_wait(BAR(BAR_WM2));
#pragma unroll
    for (int s = 0; s < 8; s++) ldsm4t(aw[s], a0 + (128 * wq + 32 * (s >> 1) + 4 * (s & 1)) * 32);
    float d[4];
    mma128(d, aw, cf);
    sts4f(sb + OFF_P0B + (tid - 128) * 16, d[0], d[1], d[2], d[3]);
    if (lane == 0) mbar_arrive(BAR(BAR_P0BD));
    bar_sync(3, 128);
    if (w == 4) {
      float4 v[4];
#pragma unroll
      for (int i = 0; i < 4; i++) v[i] = ldsf4(sb + OFF_P0B + (i * 32 + lane) * 16);
      stg_u64(gs->MOD2[par] + cta * 64 + t * 16 + g * 2, movm(pack_bf16((v[0].x + v[1].x) + (v[2].x + v[3].x), (v[0].y + v[1].y) + (v[2].y + v[3].y))),
              movm(pack_bf16((v[0].z + v[1].z) + (v[2].z + v[3].z), (v[0].w + v[1].w) + (v[2].w + v[3].w))));
    }
    CLK(15);
  }
  {
    const uint32_t* qx = pin(gs->QX[par] + ((bs >> 3) * 32 + 16 * hh) * 256 + tid * 4);
    const int ch = tid & 63, h0 = tid >> 6;
    const uint32_t dst = sb + OFF_Q + (ch >> 3) * 2048 + h0 * 128;
    wait_clk(tstore, T.D_QX);
    CLK(12);
    uint4 v[4];
#pragma unroll
    for (int i = 0; i < 4; i++) v[i] = ldg_2u64(qx + i * 1024);
    int it = 0;
    while (true) {
      uint32_t mn = 0xffffffffu;
#pragma unroll
      for (int i = 0; i < 4; i++) mn = min(mn, min(v[i].y, v[i].w));
      if (mn != 0) break;
#pragma unroll
      for (int i = 0; i < 4; i++) if (v[i].y == 0 || v[i].w == 0) v[i] = ldg_2u64(qx + i * 1024);
      if (++it > SPIN_LIMIT) __trap();
    }
    CLK(13);
    ITS(2, it);
#pragma unroll
    for (int i = 0; i < 4; i++) sts4(dst + i * 512 + (((ch & 7) ^ ((4 * i + h0) & 7)) << 4), v[i]);
    asm volatile("fence.proxy.async.shared::cta;" ::: "memory");
    CLK(14);
    cbar();
  }

  uint2 cbf[4], sbf[4];
  const uint32_t* const pcb = gs->MOD2[par] + 2048 + (16 * w + t) * 16 + g * 2;
  uint32_t thand, anchor;
  if (wg == 0) {
    float mh[4];
    float L[8];
#pragma unroll
    for (int i = 0; i < 4; i++) { L[2 * i] = L[2 * i + 1] = 0.f; mh[i] = -INFINITY; }
    constexpr uint32_t dq = desc_lo(OFF_Q);
    const uint32_t ptw = sb + OFF_PT + (8 * (lane >> 4) + (lane & 7)) * 128 + (((2 * wq + ((lane >> 3) & 1)) ^ (lane & 7)) << 4);
    float S[8];
    auto softmax = [&](int tl) {
      auto write_p = [&](const float (&x)[8]) {
        float p[8];
#pragma unroll
        for (int i = 0; i < 8; i++) p[i] = ex2(x[i]);
        stsm4t(ptw + (tl & 1) * 2048, pack_bf16(p[0], p[1]), pack_bf16(p[2], p[3]), pack_bf16(p[4], p[5]), pack_bf16(p[6], p[7]));
        asm volatile("fence.proxy.async.shared::cta;" ::: "memory");
      };
      float x[8];
#pragma unroll
      for (int i = 0; i < 8; i++) x[i] = S[i] - mh[2 * (i >> 2) + (i & 1)];
      if (tl) write_p(x);
      const float ex = fmaxf(fmaxf(fmaxf(x[0], x[1]), fmaxf(x[2], x[3])), fmaxf(fmaxf(x[4], x[5]), fmaxf(x[6], x[7])));
      if (tl == 0 || bar_over(ex)) {
        float mx[4];
#pragma unroll
        for (int i = 0; i < 4; i++) mx[i] = fmaxf(S[4 * (i >> 1) + (i & 1)], S[4 * (i >> 1) + 2 + (i & 1)]);
        const float a = reduce_g(mx, lane, [](float u, float v) { return fmaxf(u, v); });
        stsf(sb + OFF_RED + wq * 64 + (8 * (lane >> 4) + 2 * t + ((lane >> 3) & 1)) * 4, a);
        bar_sync(2, 128);
#pragma unroll
        for (int jn = 0; jn < 2; jn++) {
          float m0 = mh[2 * jn], m1 = mh[2 * jn + 1];
#pragma unroll
          for (int i = 0; i < 4; i++) { const float2 v = ldsf2(sb + OFF_RED + i * 64 + (8 * jn + 2 * t) * 4); m0 = fmaxf(m0, v.x); m1 = fmaxf(m1, v.y); }
          const float a0 = ex2(mh[2 * jn] - m0), a1 = ex2(mh[2 * jn + 1] - m1);
          mh[2 * jn] = m0; mh[2 * jn + 1] = m1;
          L[4 * jn] *= a0; L[4 * jn + 1] *= a1; L[4 * jn + 2] *= a0; L[4 * jn + 3] *= a1;
          if (tid < 4) sts2f(sb + OFF_ALPHA + (8 * jn + 2 * t) * 4, a0, a1);
        }
#pragma unroll
        for (int i = 0; i < 8; i++) x[i] = S[i] - mh[2 * (i >> 2) + (i & 1)];
        write_p(x);
        cbar();
      }
      const uint32_t dpt = __shfl_sync(~0u, desc_lo(OFF_PT) + (tl & 1) * 128, 0);
      wg_fence();
#pragma unroll
      for (int ks = 0; ks < 4; ks++) wgmma_n16_ones(L, ONE2, dpt + ks * 2);
      wg_commit();
    };
    uint32_t da = desc_lo(OFF_RING);
#pragma unroll 1
    for (int tl = 0; tl < 7; tl++) {
      uint32_t ok = 0;
#pragma unroll
      for (int u = 0; u < 4; u++) ok += mbar_test(BAR(BAR_FULL + 4 * tl + u));
      ok = __reduce_min_sync(~0u, ok);
      const uint32_t du = __shfl_sync(~0u, da, 0);
#pragma unroll
      for (int u = 0; u < 4; u++) {
        if (ok != 4) mbar_wait(BAR(BAR_FULL + 4 * tl + u));
        wg_fence();
#pragma unroll
        for (int k = 0; k < 8; k++) {
          const int i = 8 * u + k;
          if (i == 0) wgmma_n16<0, 0>(S, du, dq); else wgmma_n16<0, 1>(S, du + (i >> 2) * 512 + (i & 3) * 2, dq + (i >> 2) * 128 + (i & 3) * 2);
        }
        wg_commit();
      }
      wg_wait<0>();
      acc_fence(S); acc_fence(L);
      if (tl == 0) CLK(15);
      if (tl == 1) CLK(17);
      softmax(tl);
      if (tl == 0) CLK(16);
      if (tl == 1) CLK(18);
      if (tl == 3) CLK(19);
      if (tl == 6) CLK(20);
      da = (tl == 2 || tl == 5) ? da - 8192 : da + 4096;
    }
    if (cta < NFF) { load_units<4, 64>(sbf, pcb); load_units<4, 64>(cbf, pcb + 2048); }
    mbar_wait(BAR(BAR_ALLCLR));
    uint32_t* const mlo = pin(gs->ML + ((16 * hh + 4 * (g & 2) + 2 * t + (g & 1)) * 64 + bs) * 2);
#pragma unroll
    for (int i = 0; i < 32; i++) {
      if (i == 0 || i == 8 || i == 16 || i == 24 || i == 28) {
        if (i) wg_commit();
        mbar_wait(BAR(BAR_LAST + (i == 28 ? 4 : i >> 3)));
        if (i == 28) CLK(21);
        wg_fence();
      }
      if (i == 0) wgmma_n16<0, 0>(S, da, dq); else wgmma_n16<0, 1>(S, da + (i >> 2) * 512 + (i & 3) * 2, dq + (i >> 2) * 128 + (i & 3) * 2);
    }
    wg_commit();
    wg_wait<0>();
    acc_fence(S); acc_fence(L);
    CLK(22);
    softmax(7);
    CLK(23);
    thand = clk32();
    wg_wait<0>();
    acc_fence(L);
    if (tid < 16) stg_u64(mlo, __float_as_uint(g & 2 ? (g & 1 ? mh[3] : mh[2]) : (g & 1 ? mh[1] : mh[0])), __float_as_uint(g & 2 ? (g & 1 ? L[5] : L[4]) : (g & 1 ? L[1] : L[0])));
    CLK(24);
  } else {
    float O[8][8];
#pragma unroll
    for (int i = 0; i < 8; i++)
#pragma unroll
      for (int k = 0; k < 8; k++) O[i][k] = 0.f;
    constexpr uint32_t dp = desc_lo(OFF_PT);
    auto handover = [&](int tl) {
      if (tl == 0) { cbar(); return; }
      if (bar_over(0.f)) {
        cbar();
#pragma unroll
        for (int jn = 0; jn < 2; jn++) {
          const float2 a = ldsf2(sb + OFF_ALPHA + (8 * jn + 2 * t) * 4);
#pragma unroll
          for (int mb = 0; mb < 8; mb++) { O[mb][4 * jn] *= a.x; O[mb][4 * jn + 1] *= a.y; O[mb][4 * jn + 2] *= a.x; O[mb][4 * jn + 3] *= a.y; }
        }
      }
    };
    uint32_t da = desc_lo(OFF_RING);
#pragma unroll 1
    for (int tl = 0; tl < 7; tl++) {
      handover(tl);
      const uint32_t dpt = dp + (tl & 1) * 128;
      wg_fence();
#pragma unroll
      for (int i = 0; i < 32; i++) wgmma_n16<1, 1>(O[i >> 2], da + (i >> 2) * 512 + (i & 3) * 128, dpt + (i & 3) * 2);
      wg_commit();
      wg_wait<0>();
#pragma unroll
      for (int mb = 0; mb < 8; mb++) acc_fence(O[mb]);
      if (lane == 0) mbar_arrive(BAR(BAR_EMPTY + tl));
      if (tl == 0) CLK(16);
      if (tl == 1) CLK(18);
      if (tl == 3) CLK(19);
      if (tl == 6) CLK(20);
      da = (tl == 2 || tl == 5) ? da - 8192 : da + 4096;
    }
    if (cta < NFF) { load_units<4, 64>(sbf, pcb); load_units<4, 64>(cbf, pcb + 2048); }
    mbar_wait(BAR(BAR_ALLCLR));
    uint32_t* const x1o = pin(gs->X1 + (((16 * hh + 2 * t) * 4 + (wq >> 1)) * 64 + bs) * 64 + ((wq & 1) * 8 + g) * 4);
    handover(7);
    CLK(23);
    thand = clk32();
    auto pv = [&](int J) {
      wg_fence();
#pragma unroll
      for (int i = 0; i < 16; i++) wgmma_n16<1, 1>(O[4 * J + (i >> 2)], desc_lo(65536) + (4 * J + (i >> 2)) * 512 + (i & 3) * 128, dp + 128 + (i & 3) * 2);
      wg_commit();
    };
    auto publish = [&](int J) {
#pragma unroll
      for (int k = 0; k < 4; k++) acc_fence(O[4 * J + k]);
#pragma unroll
      for (int i = 0; i < 4; i++) {
        const int k = 4 * (i >> 1) + (i & 1);
        stg_2u64(x1o + ((8 * (i >> 1) + (i & 1)) * 4 + 2 * J) * 4096,
                 make_uint4(pack_bf16(O[4 * J][k], O[4 * J][k + 2]), pack_bf16(O[4 * J + 1][k], O[4 * J + 1][k + 2]),
                            pack_bf16(O[4 * J + 2][k], O[4 * J + 2][k + 2]), pack_bf16(O[4 * J + 3][k], O[4 * J + 3][k + 2])));
      }
    };
    pv(0); pv(1);
    wg_wait<1>(); publish(0);
    wg_wait<0>(); publish(1);
    CLK(24);
  }

  {
    const uint32_t* px = pin(gs->X1 + (cta * 64 + w * 8) * 64 + lane * 2);
    uint32_t* const x2o = pin(gs->X2 + (cta * 256 + tid) * 2);
    mbar_wait(BAR(BAR_TS));
    anchor = lds1(sb + OFF_TS);
    wait_clk(thand, T.D_X1);
    wait_clk(anchor, T.A_X1 + (jI >> 1) * T.A_X1J);
    CLK(25);
    uint2 v[8];
    load_units<8, 64>(v, px);
    const bool early = __all_sync(~0u, mbar_test(BAR(BAR_WUV + wg)));
    if (early) load_a_t(aw, sb + OFF_WUV, w, lane);
    mbar_wait(BAR(BAR_WV));
    const float4 wa = ldsf4(sb + OFF_WV + w * 32), wb = ldsf4(sb + OFF_WV + w * 32 + 16);
    const float wv[8] = {wa.x, wa.y, wa.z, wa.w, wb.x, wb.y, wb.z, wb.w};
    CLK(27);
    const int it = check_units<8, 64>(v, px, T.RB);
    CLK(28);
    ITS(4, it);
    float a0 = 0.f, a1 = 0.f, a2 = 0.f, a3 = 0.f;
#pragma unroll
    for (int i = 0; i < 8; i++) { a0 += wv[i] * bf_lo(v[i].x); a1 += wv[i] * bf_hi(v[i].x); a2 += wv[i] * bf_lo(v[i].y); a3 += wv[i] * bf_hi(v[i].y); }
    sts2(sb + OFF_BS4 + w * 272 + lane * 8, pack_bf16(a0, a1), pack_bf16(a2, a3));
    CLK(29);
    if (!early) { mbar_wait(BAR(BAR_WUV + wg)); load_a_t(aw, sb + OFF_WUV, w, lane); }
    cbar();
    uint32_t b[4][4];
#pragma unroll
    for (int kk = 0; kk < 4; kk++) ldsm4(b[kk], sb + OFF_BS4 + (lane & 7) * 272 + (4 * kk + (lane >> 3)) * 16);
    float d[4];
    mma128(d, aw, b);
    stg_u64(x2o, pack_bf16(d[0], d[1]), pack_bf16(d[2], d[3]));
    tstore = clk32();
    CLK(30);
  }
  {
    uint32_t* const o = pin(gs->X3A + ((4 * (8 * jI + w) + t) * 32 + hI) * 16 + g * 2);
    const uint32_t* const x2i = pin(gs->X2 + (hI * 4 * 256 + tid) * 2);
    wait_clk(tstore, T.D_X2);
    wait_clk(anchor, T.A_X2);
    uint2 v[4];
    load_units<4, 512>(v, x2i);
    mbar_wait(BAR(BAR_WO + wg));
    load_a_t(aw, sb + OFF_WO, w, lane);
    CLK(31);
    const int it = check_units<4, 512>(v, x2i, T.RB);
    CLK(32);
    ITS(5, it);
    sum4_to_smem(v, sb + OFF_BS5 + (16 * w + g) * 16 + t * 4);
    cbar();
    uint32_t b[4][4];
#pragma unroll
    for (int kk = 0; kk < 4; kk++) ldsm4t(b[kk], sb + OFF_BS5 + (32 * kk + lane) * 16);
    float d[4];
    mma128(d, aw, b);
    stg_u64(o, movm(pack_bf16(d[0], d[1])), movm(pack_bf16(d[2], d[3])));
    tstore = clk32();
    CLK(33);
    if (lane == 0) mbar_arrive(BAR(BAR_P5D));
  }
  if (cta < NFF) {
    const int mi = lane >> 3, r = lane & 7;
    uint32_t a1[2][4][4], a2[2][2][4];
    check_units<4, 64>(sbf, pcb, T.RB);
    check_units<4, 64>(cbf, pcb + 2048, T.RB);
    __syncwarp();
#pragma unroll
    for (int s = 0; s < 4; s++) { cbf[s].x = hadd2(cbf[s].x, ONE2); cbf[s].y = hadd2(cbf[s].y, ONE2); }
    mbar_wait(BAR(BAR_W1));
#pragma unroll
    for (int mt = 0; mt < 2; mt++) {
#pragma unroll
      for (int ks = 0; ks < 4; ks++) ldsm4t(a1[mt][ks], sb + OFF_W1 + (64 * w + 16 * ks + 8 * (mi >> 1) + r) * 64 + (((2 * mt + (mi & 1)) ^ (r >> 1)) << 4));
      float u[4] = {0.f, 0.f, 0.f, 0.f}, vv[4] = {0.f, 0.f, 0.f, 0.f};
#pragma unroll
      for (int s = 0; s < 4; s++) { mma16816(u, a1[mt][s], cbf[s].x, cbf[s].y); mma16816(vv, a1[mt][s], sbf[s].x, sbf[s].y); }
      sts4f(sb + OFF_REDU + w * 1024 + mt * 512 + lane * 16, u[0], u[1], u[2], u[3]);
      sts4f(sb + OFF_REDV + w * 1024 + mt * 512 + lane * 16, vv[0], vv[1], vv[2], vv[3]);
    }
    cbar();
    const int lp = (tid >> 2) & 31, kq = tid & 3;
    const int fo = 16 * wg + (lp >> 2) + 8 * (kq >> 1), bo = 2 * (lp & 3) + (kq & 1);
    float U = 0.f, V = 0.f;
#pragma unroll
    for (int i = 0; i < 8; i++) { U += ldsf(sb + OFF_REDU + i * 1024 + tid * 4); V += ldsf(sb + OFF_REDV + i * 1024 + tid * 4); }
    const uint32_t* xb = pin(gs->X3B + (cta & (NREP - 1)) * 2048 + (16 * w + t) * 16 + g * 2);
    uint32_t* const ox = pin(gs->X4 + ((64 * hh + 8 * w + t) * NFG + bs) * 16 + g * 2);
    CLK(34);
    wait_clk(tstore, T.D_X3B);
    uint2 x[4];
    load_units<4, 64>(x, xb);
    mbar_wait(BAR(BAR_W2));
#pragma unroll
    for (int i = 0; i < 4; i++)
      ldsm4t(a2[i >> 1][i & 1], sb + OFF_W2 + (w >> 1) * 4096 + (16 * (i & 1) + 8 * (mi >> 1) + r) * 128 + (((4 * (w & 1) + 2 * (i >> 1) + (mi & 1)) ^ r) << 4));
    CLK(35);
    const int it = check_units<4, 64>(x, xb, T.RB);
    __syncwarp();
    CLK(36);
    ITS(6, it);
    float G[2][2][4] = {}, S[2][4] = {};
#pragma unroll
    for (int s = 0; s < 4; s++) {
      const uint32_t sx[4] = {x[s].x, ONE2, x[s].y, ONE2};
      mma16816(S[s & 1], sx, x[s].x, x[s].y);
      const uint32_t y0 = hmul2(x[s].x, cbf[s].x), y1 = hmul2(x[s].y, cbf[s].y);
      mma16816(G[0][s & 1], a1[0][s], y0, y1);
      mma16816(G[1][s & 1], a1[1][s], y0, y1);
    }
    if (t == (g >> 1)) sts2f(sb + OFF_REDS + g * 80 + w * 8, (g & 1) ? S[0][3] + S[1][3] : S[0][2] + S[1][2], (g & 1) ? S[0][1] + S[1][1] : S[0][0] + S[1][0]);
#pragma unroll
    for (int mt = 0; mt < 2; mt++)
      sts4f(sb + OFF_REDG + w * 1024 + mt * 512 + lane * 16, G[mt][0][0] + G[mt][1][0], G[mt][0][1] + G[mt][1][1], G[mt][0][2] + G[mt][1][2], G[mt][0][3] + G[mt][1][3]);
    CLK(37);
    cbar();
    {
      float gv[8];
      float4 sv[4];
#pragma unroll
      for (int i = 0; i < 4; i++) sv[i] = ldsf4(sb + OFF_REDS + bo * 80 + i * 16);
#pragma unroll
      for (int i = 0; i < 8; i++) gv[i] = ldsf(sb + OFF_REDG + i * 1024 + tid * 4);
      const float s1 = ((sv[0].x + sv[0].z) + (sv[1].x + sv[1].z)) + ((sv[2].x + sv[2].z) + (sv[3].x + sv[3].z));
      const float s2 = ((sv[0].y + sv[0].w) + (sv[1].y + sv[1].w)) + ((sv[2].y + sv[2].w) + (sv[3].y + sv[3].w));
      const float gsum = ((gv[0] + gv[1]) + (gv[2] + gv[3])) + ((gv[4] + gv[5]) + (gv[6] + gv[7]));
      const float mu = s1 * (1.f / 512.f);
      const float rs = rsqrtf(fmaxf(s2 * (1.f / 512.f) - mu * mu, 0.f) + 1e-5f);
      const float hv = fmaxf(rs * (gsum - mu * U) + V, 0.f);
      asm volatile("st.shared.u16 [%0], %1;" ::"r"(sb + OFF_H1 + fo * 16 + bo * 2), "h"(__bfloat16_as_ushort(__float2bfloat16(hv))) : "memory");
    }
    CLK(38);
    cbar();
    uint32_t b[4];
    ldsm4t(b, sb + OFF_H1 + lane * 16);
    float o[2][2][4] = {};
#pragma unroll
    for (int i = 0; i < 4; i++) mma16816(o[i >> 1][i & 1], a2[i >> 1][i & 1], b[2 * (i & 1)], b[2 * (i & 1) + 1]);
#pragma unroll
    for (int mb = 0; mb < 2; mb++)
      stg_u64(ox + mb * 4 * NFG * 16, movm(pack_bf16(o[mb][0][0] + o[mb][1][0], o[mb][0][1] + o[mb][1][1])), movm(pack_bf16(o[mb][0][2] + o[mb][1][2], o[mb][0][3] + o[mb][1][3])));
    CLK(39);
    if (lane == 0) mbar_arrive(BAR(BAR_P7D));
  }
  CLK_DUMP();
}

typedef CUresult (*EncodeTiledFn)(CUtensorMap*, CUtensorMapDataType, cuuint32_t, void*, const cuuint64_t*, const cuuint64_t*,
                                  const cuuint32_t*, const cuuint32_t*, CUtensorMapInterleave, CUtensorMapSwizzle,
                                  CUtensorMapL2promotion, CUtensorMapFloatOOBfill);

struct Dim { uint64_t size, stride; uint32_t box; };
template <int R> void encode_map(EncodeTiledFn enc, CUtensorMap* m, const void* base, const Dim (&d)[R], CUtensorMapSwizzle sw, CUtensorMapL2promotion promo) {
  cuuint64_t dims[R], strides[R];
  cuuint32_t box[R], es[R];
  for (int i = 0; i < R; i++) { dims[i] = d[i].size; strides[i] = d[i].stride; box[i] = d[i].box; es[i] = 1; }
  enc(m, CU_TENSOR_MAP_DATA_TYPE_BFLOAT16, R, const_cast<void*>(base), dims, strides + 1, box, es, CU_TENSOR_MAP_INTERLEAVE_NONE, sw, promo,
      CU_TENSOR_MAP_FLOAT_OOB_FILL_NONE);
}

}

extern "C" void kernel_launch(void* const* d_in, const int* in_sizes, int n_in, void* d_out, int out_size) {
  (void)in_sizes; (void)n_in; (void)out_size;
  static EncodeTiledFn enc = nullptr;
  static Scratch* scratch = nullptr;
  if (!enc) {
    void* sp = nullptr;
    cudaGetSymbolAddress(&sp, g_s);
    scratch = (Scratch*)sp;
    void* fn = nullptr;
    cudaDriverEntryPointQueryResult q;
    cudaGetDriverEntryPoint("cuTensorMapEncodeTiled", &fn, cudaEnableDefault, &q);
    enc = (EncodeTiledFn)fn;
    cudaFuncSetAttribute(fused_decode_kernel, cudaFuncAttributeMaxDynamicSharedMemorySize, SMEM_BYTES);
  }
  const CUtensorMapSwizzle S128 = CU_TENSOR_MAP_SWIZZLE_128B, S0 = CU_TENSOR_MAP_SWIZZLE_NONE;
  const CUtensorMapL2promotion L0 = CU_TENSOR_MAP_L2_PROMOTION_NONE, L128 = CU_TENSOR_MAP_L2_PROMOTION_L2_128B;
  Params P;
  encode_map<2>(enc, &P.wq, d_in[2], {{4096, 2, 64}, {512, 8192, 64}}, S128, L0);
  encode_map<5>(enc, &P.wuk, d_in[3], {{4096, 2, 64}, {2, 8192, 2}, {4, 4 * 8192, 4}, {2, 2 * 8192, 2}, {32, 16 * 8192, 4}}, S128, L0);
  encode_map<2>(enc, &P.wm2, d_in[10], {{3072, 2, 16}, {512, 6144, 256}}, S0, L128);
  encode_map<3>(enc, &P.ckv2, d_in[1], {{64, 2, 64}, {8 * 4096, 1024, 64}, {8, 128, 2}}, S128, L0);
  encode_map<3>(enc, &P.ckv1, d_in[1], {{64, 2, 64}, {8 * 4096, 1024, 64}, {8, 128, 1}}, S128, L0);
  encode_map<5>(enc, &P.wuv, d_in[4], {{4096, 2, 64}, {2, 8 * 8192, 2}, {8, 64 * 8192, 4}, {8, 8192, 8}, {4, 16 * 8192, 1}}, S128, L0);
  encode_map<2>(enc, &P.wo, d_in[5], {{512, 2, 64}, {4096, 1024, 64}}, S128, L0);
  encode_map<2>(enc, &P.w1, d_in[7], {{1792, 2, 32}, {512, 3584, 256}}, CU_TENSOR_MAP_SWIZZLE_64B, L128);
  encode_map<3>(enc, &P.w2, d_in[8], {{64, 2, 64}, {1792, 1024, 32}, {8, 128, 2}}, S128, L0);
  cudaLaunchConfig_t cfg = {};
  cfg.gridDim = dim3(NCTA);
  cfg.blockDim = dim3(NTHREADS);
  cfg.dynamicSmemBytes = SMEM_BYTES;
  cfg.stream = cudaStreamPerThread;
  cudaLaunchAttribute at[1];
  at[0].id = cudaLaunchAttributeClusterDimension;
  at[0].val.clusterDim.x = 2; at[0].val.clusterDim.y = 1; at[0].val.clusterDim.z = 1;
  cfg.attrs = at;
  cfg.numAttrs = 0;
  cudaLaunchKernelEx(&cfg, fused_decode_kernel, (__nv_bfloat16*)d_out, scratch, (const uint8_t*)d_in[10], (const uint8_t*)d_in[0],
                     (const uint8_t*)d_in[9],
                     P);
}
```

```cpp
#include <cuda_runtime.h>
#include <cuda.h>
#include <cuda_bf16.h>
#include <stdint.h>
#define V4 1

namespace {

constexpr int NCTA = 128;
constexpr int NTHREADS = 320;
constexpr int NFG = 56;
constexpr int NFF = 2 * NFG;
constexpr int NSYNC = 4;
#define REPSEL 0
constexpr int NREP = 8;

constexpr uint32_t OFF_RING = 0;
constexpr uint32_t OFF_WUK = 131072;
constexpr uint32_t OFF_WQ = 131072 + 32768;
constexpr uint32_t OFF_WM2 = 65536 + 49152;
constexpr uint32_t OFF_WUV = 131072;
constexpr uint32_t OFF_WO = 131072 + 32768;
constexpr uint32_t OFF_W1 = 0;
constexpr uint32_t OFF_W2 = 32768;
constexpr uint32_t OFF_Q = 196608;
constexpr uint32_t OFF_PT = 212992;
constexpr uint32_t OFF_SCR = 217088;
constexpr uint32_t OFF_XS = 65536;
constexpr uint32_t OFF_CS = 65536 + 8192;
constexpr uint32_t OFF_P0S = 65536 + 16384;
constexpr uint32_t OFF_BS1 = OFF_SCR + 2048;
constexpr uint32_t OFF_BS2 = OFF_SCR + 4096;
constexpr uint32_t OFF_P0B = OFF_SCR + 6144;
constexpr uint32_t OFF_XN = OFF_SCR + 8192;
constexpr uint32_t OFF_RED = OFF_SCR + 10496;
constexpr uint32_t OFF_ALPHA = OFF_SCR + 11072;
constexpr uint32_t OFF_WV = OFF_SCR + 6144;
constexpr uint32_t OFF_TS = OFF_SCR + 11136;
constexpr uint32_t OFF_BARS = OFF_SCR + 11264;
constexpr uint32_t SMEM_BYTES = OFF_BARS + 512;
constexpr uint32_t OFF_BS4 = OFF_Q;
constexpr uint32_t OFF_H1 = OFF_Q + 2304;
constexpr uint32_t OFF_REDS = OFF_Q + 2816;
constexpr uint32_t OFF_BS5 = OFF_Q + 4096;
constexpr uint32_t OFF_REDG = OFF_Q + 8192;
constexpr uint32_t OFF_REDU = 65536;
constexpr uint32_t OFF_REDV = 65536 + 8192;

constexpr int BAR_FULL = 0;
constexpr int BAR_LAST = 28;
constexpr int BAR_WUK = 33, BAR_WM2 = 35, BAR_WUV = 36, BAR_WO = 38, BAR_W1 = 40, BAR_W2 = 41;
constexpr int BAR_ALLCLR = 42, BAR_TS = 43, BAR_WV = 44;
constexpr int BAR_EMPTY = 45;
constexpr int BAR_P0BD = 52;
constexpr int BAR_P1D = 53, BAR_P2D = 54;
constexpr int BAR_P5D = 55, BAR_P7D = 56;
constexpr int NBARS = 57;
constexpr int BAR_XC = 57, BAR_WQ = 58;
constexpr int BAR_C = 60, BAR_END = 61;
constexpr uint32_t SB = 1024;

#define TUNE_LIST(X) \
  X(PC_T0, 340) X(PC_XC, 0) X(PC_C, 0) X(PC_P1, 320) X(PC_P2, 322) X(PC_STAG, 390) X(PC_DS, 0) X(PC_SL, 500) X(PC_W, 4) X(PC_NW, 8) \
  X(PW_A, -1) X(PW_0, 200) X(PW_ST, 0) X(PW_UV, 345) X(PW_G, 560) X(PW_O, 345) X(PW_G2, 345) X(PW_G3, 385) X(PW_F, 385) X(CLR_T0, 5000) X(CLR_CLK, 400) \
  X(D_MOD, 1500) X(D_QP, 1300) X(D_QX, 1300) X(TS_P, 1) X(TS_O, 730) X(D_TS, 800) X(A_M, 2000) X(D_X1, 1400) X(A_X1, 2200) X(A_X1J, 60) \
  X(D_X2, 350) X(A_X2, 5250) X(D_X3A, 240) X(A_X3A, 0) X(D_X3B, 1640) X(D_FIN, 500) X(D_FIN2, 2300) X(RB, 0)
struct Tune {
#define X(n, v) static constexpr int n = v;
  TUNE_LIST(X)
#undef X
};

#define PFENCE 0
#define WSWAP 0
#define PVV 0
struct Scratch {
  uint32_t MOD1[2][4 * 64 * 64];
  uint32_t MOD2[2][128 * 64];
  uint32_t QP[2][128 * 256 * 2];
  uint32_t QX[2][8 * 32 * 256];
  uint32_t ML[32 * 64 * 2];
  uint32_t X1[128 * 64 * 64];
  uint32_t X2[128 * 256 * 2];
  uint32_t X3A[128 * 32 * 16];
  uint32_t X3B[NREP * 128 * 16];
  uint32_t X4[128 * NFG * 16];
  uint32_t epoch;
  uint32_t pad[31];
  uint32_t sync[NSYNC][32];
};
__device__ Scratch g_s;

#define CLK_DECL
#define CLK(i) do {} while (0)
#define CLK_DUMP() do {} while (0)
#define ITS(i, v) do {} while (0)

struct Params {
  CUtensorMap wq, wuk, wm2, ckv2, ckv1, wuv, wo, w1, w2;
};

__device__ __forceinline__ void mbar_init(uint32_t bar, int cnt) { asm volatile("mbarrier.init.shared::cta.b64 [%0], %1;" ::"r"(bar), "r"(cnt)); }
__device__ __forceinline__ void mbar_expect(uint32_t bar, uint32_t bytes) { asm volatile("mbarrier.arrive.expect_tx.shared::cta.b64 _, [%0], %1;" ::"r"(bar), "r"(bytes) : "memory"); }
__device__ __forceinline__ void mbar_arrive(uint32_t bar) { asm volatile("mbarrier.arrive.shared::cta.b64 _, [%0];" ::"r"(bar) : "memory"); }
__device__ __forceinline__ uint32_t clk32() { unsigned long long c; asm volatile("mov.u64 %0, %%clock64;" : "=l"(c) :: "memory"); return (uint32_t)c; }
__device__ __forceinline__ uint32_t gtime32() { uint32_t c; asm volatile("mov.u32 %0, %%globaltimer_lo;" : "=r"(c) :: "memory"); return c; }
__device__ __forceinline__ void wait_clk(uint32_t t0, int clocks) { while ((int)(clk32() - t0) < clocks) {} }
__device__ __forceinline__ void backoff(int clocks) { if (clocks > 0) wait_clk(clk32(), clocks); }
__device__ __forceinline__ void until_ns(uint32_t ns) { while ((int)(gtime32() - ns) < 0) {} }
__device__ __forceinline__ void slot(uint32_t& tn, int slack) {
  uint32_t now;
  do { now = gtime32(); } while ((int)(now - tn) < 0);
  if ((int)(now - tn) > slack) tn = now - slack;
}
template <typename T> __device__ __forceinline__ T* pin(T* p) { asm volatile("" : "+l"(p)); return p; }
constexpr int SPIN_LIMIT = 1 << 22;
__device__ __forceinline__ void mbar_wait(uint32_t bar) {
  asm volatile("{\n.reg .pred p;\n.reg .u32 c;\nmov.u32 c, 0;\n"
               "MW_LOOP:\nmbarrier.try_wait.parity.shared::cta.b64 p, [%0], 0;\n@p bra MW_DONE;\n"
               "add.u32 c, c, 1;\nsetp.lt.u32 p, c, 4194304;\n@p bra MW_LOOP;\ntrap;\nMW_DONE:\n}"
               ::"r"(bar) : "memory");
}
__device__ __forceinline__ bool mbar_test(uint32_t bar) {
  uint32_t ok;
  asm volatile("{\n.reg .pred p;\nmbarrier.test_wait.parity.shared::cta.b64 p, [%1], 0;\nselp.u32 %0,1,0,p;\n}" : "=r"(ok) : "r"(bar) : "memory");
  return ok;
}
__device__ __forceinline__ void tma2d(uint32_t dst, const CUtensorMap* m, int c0, int c1, uint32_t bar, uint64_t pol) {
  asm volatile("cp.async.bulk.tensor.2d.shared::cluster.global.mbarrier::complete_tx::bytes.L2::cache_hint [%0], [%1, {%3,%4}], [%2], %5;"
               ::"r"(dst), "l"(m), "r"(bar), "r"(c0), "r"(c1), "l"(pol) : "memory");
}
__device__ __forceinline__ void tma2d_nohint(uint32_t dst, const CUtensorMap* m, int c0, int c1, uint32_t bar) {
  asm volatile("cp.async.bulk.tensor.2d.shared::cluster.global.mbarrier::complete_tx::bytes [%0], [%1, {%3,%4}], [%2];"
               ::"r"(dst), "l"(m), "r"(bar), "r"(c0), "r"(c1) : "memory");
}
__device__ __forceinline__ void tma3d(uint32_t dst, const CUtensorMap* m, int c0, int c1, int c2, uint32_t bar, uint64_t pol) {
  asm volatile("cp.async.bulk.tensor.3d.shared::cluster.global.mbarrier::complete_tx::bytes.L2::cache_hint [%0], [%1, {%3,%4,%5}], [%2], %6;"
               ::"r"(dst), "l"(m), "r"(bar), "r"(c0), "r"(c1), "r"(c2), "l"(pol) : "memory");
}
__device__ __forceinline__ void tma5d(uint32_t dst, const CUtensorMap* m, int c0, int c1, int c2, int c3, int c4, uint32_t bar, uint64_t pol) {
  asm volatile("cp.async.bulk.tensor.5d.shared::cluster.global.mbarrier::complete_tx::bytes.L2::cache_hint [%0], [%1, {%3,%4,%5,%6,%7}], [%2], %8;"
               ::"r"(dst), "l"(m), "r"(bar), "r"(c0), "r"(c1), "r"(c2), "r"(c3), "r"(c4), "l"(pol) : "memory");
}
__device__ __forceinline__ void bulk_ld(uint32_t dst, const void* src, uint32_t bytes, uint32_t bar) {
  asm volatile("cp.async.bulk.shared::cluster.global.mbarrier::complete_tx::bytes [%0], [%1], %2, [%3];" ::"r"(dst), "l"(src), "r"(bytes), "r"(bar) : "memory");
}
__device__ __forceinline__ void bar_sync(int id, int n) { asm volatile("barrier.cta.sync.aligned %0, %1;" ::"r"(id), "r"(n) : "memory"); }
__device__ __forceinline__ void cbar() { asm volatile("barrier.cta.sync.aligned 1, 256;" ::: "memory"); }
__device__ __forceinline__ bool bar_over(float ex) {
  uint32_t over;
  asm volatile("{\n.reg .pred p, q;\nsetp.gtu.f32 p, %1, 0f41F00000;\nbarrier.cta.red.or.aligned.pred q, 4, 256, p;\nselp.u32 %0, 1, 0, q;\n}"
               : "=r"(over) : "f"(ex) : "memory");
  return over;
}

__device__ __forceinline__ uint32_t ldg_nc1(const void* p) { uint32_t v; asm volatile("ld.global.nc.L1::no_allocate.u32 %0, [%1];" : "=r"(v) : "l"(p)); return v; }
__device__ __forceinline__ uint2 ldg_nc2(const void* p) { uint2 v; asm volatile("ld.global.nc.v2.u32 {%0,%1}, [%2];" : "=r"(v.x), "=r"(v.y) : "l"(p)); return v; }
__device__ __forceinline__ uint4 ldg_nc4(const void* p) { uint4 v; asm volatile("ld.global.nc.L1::no_allocate.v4.u32 {%0,%1,%2,%3}, [%4];" : "=r"(v.x), "=r"(v.y), "=r"(v.z), "=r"(v.w) : "l"(p)); return v; }
__device__ __forceinline__ uint32_t ldg_rlx1(const void* p) { uint32_t v; asm volatile("ld.relaxed.gpu.global.u32 %0, [%1];" : "=r"(v) : "l"(p) : "memory"); return v; }
__device__ __forceinline__ void stg4(void* p, uint4 v) { asm volatile("st.relaxed.gpu.global.v4.u32 [%0], {%1,%2,%3,%4};" ::"l"(p), "r"(v.x), "r"(v.y), "r"(v.z), "r"(v.w) : "memory"); }
__device__ __forceinline__ void stg1(void* p, uint32_t a) { asm volatile("st.relaxed.gpu.global.u32 [%0], %1;" ::"l"(p), "r"(a) : "memory"); }
__device__ __forceinline__ uint32_t nz(uint32_t w) { return max(w, 1u); }
__device__ __forceinline__ uint2 ldg_u64(const void* p) {
  uint2 v; asm volatile("{\n.reg .b64 a;\nld.relaxed.gpu.global.b64 a, [%2];\nmov.b64 {%0,%1}, a;\n}" : "=r"(v.x), "=r"(v.y) : "l"(p) : "memory"); return v;
}
__device__ __forceinline__ uint4 ldg_2u64(const void* p) {
  uint4 v; asm volatile("{\n.reg .b64 a, b;\nld.relaxed.gpu.global.v2.b64 {a, b}, [%4];\nmov.b64 {%0,%1}, a;\nmov.b64 {%2,%3}, b;\n}" : "=r"(v.x), "=r"(v.y), "=r"(v.z), "=r"(v.w) : "l"(p) : "memory"); return v;
}
__device__ __forceinline__ void stg_u64(void* p, uint32_t x, uint32_t y) {
  asm volatile("{\n.reg .b32 y;\nmax.u32 y, %2, 1;\nst.relaxed.gpu.global.v2.b32 [%0], {%1, y};\n}" ::"l"(p), "r"(x), "r"(y) : "memory");
}
__device__ __forceinline__ void stg_2u64(void* p, uint4 v) {
  asm volatile("{\n.reg .b32 y, w;\nmax.u32 y, %2, 1;\nmax.u32 w, %4, 1;\nst.relaxed.gpu.global.v4.b32 [%0], {%1, y, %3, w};\n}" ::"l"(p), "r"(v.x), "r"(v.y), "r"(v.z), "r"(v.w) : "memory");
}

__device__ __forceinline__ void stg_cvt8(void* p, float a0, float a1, float b0, float b1, float c0, float c1, float d0, float d1) {
  asm volatile("{\n.reg .b32 x, y, z, w;\ncvt.rn.bf16x2.f32 x, %2, %1;\ncvt.rn.bf16x2.f32 y, %4, %3;\ncvt.rn.bf16x2.f32 z, %6, %5;\ncvt.rn.bf16x2.f32 w, %8, %7;\n"
               "max.u32 y, y, 1;\nmax.u32 w, w, 1;\nst.relaxed.gpu.global.v4.b32 [%0], {x, y, z, w};\n}"
               ::"l"(p), "f"(a0), "f"(a1), "f"(b0), "f"(b1), "f"(c0), "f"(c1), "f"(d0), "f"(d1) : "memory");
}
__device__ __forceinline__ uint32_t pack_bf16(float lo, float hi) { uint32_t r; asm("cvt.rn.bf16x2.f32 %0, %1, %2;" : "=r"(r) : "f"(hi), "f"(lo)); return r; }
__device__ __forceinline__ float bf_lo(uint32_t w) { return __uint_as_float(w << 16); }
__device__ __forceinline__ float bf_hi(uint32_t w) { return __uint_as_float(w & 0xffff0000u); }
__device__ __forceinline__ float ex2(float x) { float r; asm("ex2.approx.ftz.f32 %0, %1;" : "=f"(r) : "f"(x)); return r; }
__device__ __forceinline__ uint32_t hmul2(uint32_t a, uint32_t b) { uint32_t r; asm("mul.rn.bf16x2 %0, %1, %2;" : "=r"(r) : "r"(a), "r"(b)); return r; }
__device__ __forceinline__ uint32_t hadd2(uint32_t a, uint32_t b) { uint32_t r; asm("add.rn.bf16x2 %0, %1, %2;" : "=r"(r) : "r"(a), "r"(b)); return r; }
__device__ __forceinline__ uint32_t hfma2(uint32_t a, uint32_t b, uint32_t c) { uint32_t r; asm("fma.rn.bf16x2 %0, %1, %2, %3;" : "=r"(r) : "r"(a), "r"(b), "r"(c)); return r; }
__device__ __forceinline__ uint32_t silu2(uint32_t v) { const float a = bf_lo(v), b = bf_hi(v); return pack_bf16(__fdividef(a, 1.f + __expf(-a)), __fdividef(b, 1.f + __expf(-b))); }
constexpr uint32_t ONE2 = 0x3f803f80u;

__device__ __forceinline__ void ldsm4(uint32_t (&r)[4], uint32_t a) { asm volatile("ldmatrix.sync.aligned.m8n8.x4.shared.b16 {%0,%1,%2,%3}, [%4];" : "=r"(r[0]), "=r"(r[1]), "=r"(r[2]), "=r"(r[3]) : "r"(a) : "memory"); }
__device__ __forceinline__ void ldsm4t(uint32_t (&r)[4], uint32_t a) { asm volatile("ldmatrix.sync.aligned.m8n8.x4.trans.shared.b16 {%0,%1,%2,%3}, [%4];" : "=r"(r[0]), "=r"(r[1]), "=r"(r[2]), "=r"(r[3]) : "r"(a) : "memory"); }
__device__ __forceinline__ void ldsm2t(uint32_t& r0, uint32_t& r1, uint32_t a) { asm volatile("ldmatrix.sync.aligned.m8n8.x2.trans.shared.b16 {%0,%1}, [%2];" : "=r"(r0), "=r"(r1) : "r"(a) : "memory"); }
__device__ __forceinline__ void stsm4t(uint32_t a, uint32_t r0, uint32_t r1, uint32_t r2, uint32_t r3) { asm volatile("stmatrix.sync.aligned.m8n8.x4.trans.shared.b16 [%0], {%1,%2,%3,%4};" ::"r"(a), "r"(r0), "r"(r1), "r"(r2), "r"(r3) : "memory"); }
__device__ __forceinline__ uint32_t movm(uint32_t a) { uint32_t d; asm volatile("movmatrix.sync.aligned.m8n8.trans.b16 %0, %1;" : "=r"(d) : "r"(a)); return d; }
__device__ __forceinline__ void mma16816(float (&d)[4], const uint32_t (&a)[4], uint32_t b0, uint32_t b1) {
  asm volatile("mma.sync.aligned.m16n8k16.row.col.f32.bf16.bf16.f32 {%0,%1,%2,%3}, {%4,%5,%6,%7}, {%8,%9}, {%0,%1,%2,%3};"
               : "+f"(d[0]), "+f"(d[1]), "+f"(d[2]), "+f"(d[3]) : "r"(a[0]), "r"(a[1]), "r"(a[2]), "r"(a[3]), "r"(b0), "r"(b1));
}
__device__ __forceinline__ void sts1(uint32_t a, uint32_t v) { asm volatile("st.shared.u32 [%0], %1;" ::"r"(a), "r"(v) : "memory"); }
__device__ __forceinline__ void sts2(uint32_t a, uint32_t x, uint32_t y) { asm volatile("st.shared.v2.u32 [%0], {%1,%2};" ::"r"(a), "r"(x), "r"(y) : "memory"); }
__device__ __forceinline__ void sts4(uint32_t a, uint4 v) { asm volatile("st.shared.v4.u32 [%0], {%1,%2,%3,%4};" ::"r"(a), "r"(v.x), "r"(v.y), "r"(v.z), "r"(v.w) : "memory"); }
__device__ __forceinline__ void sts2f(uint32_t a, float x, float y) { asm volatile("st.shared.v2.f32 [%0], {%1,%2};" ::"r"(a), "f"(x), "f"(y) : "memory"); }
__device__ __forceinline__ void sts4f(uint32_t a, float x, float y, float z, float w) { asm volatile("st.shared.v4.f32 [%0], {%1,%2,%3,%4};" ::"r"(a), "f"(x), "f"(y), "f"(z), "f"(w) : "memory"); }
__device__ __forceinline__ void stsf(uint32_t a, float v) { asm volatile("st.shared.f32 [%0], %1;" ::"r"(a), "f"(v) : "memory"); }
__device__ __forceinline__ uint32_t lds1(uint32_t a) { uint32_t v; asm volatile("ld.shared.u32 %0, [%1];" : "=r"(v) : "r"(a) : "memory"); return v; }
__device__ __forceinline__ float ldsf(uint32_t a) { float v; asm volatile("ld.shared.f32 %0, [%1];" : "=f"(v) : "r"(a) : "memory"); return v; }
__device__ __forceinline__ float2 ldsf2(uint32_t a) { float2 v; asm volatile("ld.shared.v2.f32 {%0,%1}, [%2];" : "=f"(v.x), "=f"(v.y) : "r"(a) : "memory"); return v; }
__device__ __forceinline__ float4 ldsf4(uint32_t a) { float4 v; asm volatile("ld.shared.v4.f32 {%0,%1,%2,%3}, [%4];" : "=f"(v.x), "=f"(v.y), "=f"(v.z), "=f"(v.w) : "r"(a) : "memory"); return v; }
__device__ __forceinline__ void lds4(uint32_t (&r)[4], uint32_t a) { asm volatile("ld.shared.v4.u32 {%0,%1,%2,%3}, [%4];" : "=r"(r[0]), "=r"(r[1]), "=r"(r[2]), "=r"(r[3]) : "r"(a) : "memory"); }

__device__ __forceinline__ void wg_fence() { asm volatile("wgmma.fence.sync.aligned;" ::: "memory"); }
__device__ __forceinline__ void wg_commit() { asm volatile("wgmma.commit_group.sync.aligned;" ::: "memory"); }
template <int N> __device__ __forceinline__ void wg_wait() { asm volatile("wgmma.wait_group.sync.aligned %0;" ::"n"(N) : "memory"); }
__host__ __device__ constexpr uint32_t desc_lo(uint32_t off) { return ((SB + off) >> 4) | 0x10000u; }
template <int TA, int ACC> __device__ __forceinline__ void wgmma_n16(float (&d)[8], uint32_t da, uint32_t db) {
  asm volatile("{\n.reg .b64 da, db;\nmov.b64 da, {%8, 0x40000040};\nmov.b64 db, {%9, 0x40000040};\n"
               "wgmma.mma_async.sync.aligned.m64n16k16.f32.bf16.bf16 {%0,%1,%2,%3,%4,%5,%6,%7}, da, db, %11, 1, 1, %10, 0;\n}"
               : "+f"(d[0]), "+f"(d[1]), "+f"(d[2]), "+f"(d[3]), "+f"(d[4]), "+f"(d[5]), "+f"(d[6]), "+f"(d[7])
               : "r"(da), "r"(db), "n"(TA), "n"(ACC));
}
__device__ __forceinline__ void wgmma_n16_ones(float (&d)[8], uint32_t one, uint32_t db) {
  asm volatile("{\n.reg .b64 db;\nmov.b64 db, {%9, 0x40000040};\n"
               "wgmma.mma_async.sync.aligned.m64n16k16.f32.bf16.bf16 {%0,%1,%2,%3,%4,%5,%6,%7}, {%8,%8,%8,%8}, db, 1, 1, 1, 0;\n}"
               : "+f"(d[0]), "+f"(d[1]), "+f"(d[2]), "+f"(d[3]), "+f"(d[4]), "+f"(d[5]), "+f"(d[6]), "+f"(d[7])
               : "r"(one), "r"(db));
}
__device__ __forceinline__ void acc_fence(float (&d)[8]) {
  asm volatile("" : "+f"(d[0]), "+f"(d[1]), "+f"(d[2]), "+f"(d[3]), "+f"(d[4]), "+f"(d[5]), "+f"(d[6]), "+f"(d[7]) :: "memory");
}

template <int N, int STRIDE> __device__ __forceinline__ void load_units(uint2 (&v)[N], const uint32_t* p) {
#pragma unroll
  for (int i = 0; i < N; i++) v[i] = ldg_u64(p + i * STRIDE);
}
template <int N, int STRIDE> __device__ __forceinline__ int check_units(uint2 (&v)[N], const uint32_t* p, int rb) {
  int it = 0;
  while (true) {
    uint32_t mn = v[0].y;
#pragma unroll
    for (int i = 1; i < N; i++) mn = min(mn, v[i].y);
    if (mn != 0) break;
    backoff(rb);
#pragma unroll
    for (int i = 0; i < N; i++) if (v[i].y == 0) v[i] = ldg_u64(p + i * STRIDE);
    if (++it > SPIN_LIMIT) __trap();
  }
  return it;
}
__device__ __forceinline__ void sum4_to_smem(const uint2 (&v)[4], uint32_t dst) {
  const float c0 = (bf_lo(v[0].x) + bf_lo(v[1].x)) + (bf_lo(v[2].x) + bf_lo(v[3].x));
  const float c1 = (bf_hi(v[0].x) + bf_hi(v[1].x)) + (bf_hi(v[2].x) + bf_hi(v[3].x));
  const float c2 = (bf_lo(v[0].y) + bf_lo(v[1].y)) + (bf_lo(v[2].y) + bf_lo(v[3].y));
  const float c3 = (bf_hi(v[0].y) + bf_hi(v[1].y)) + (bf_hi(v[2].y) + bf_hi(v[3].y));
  sts1(dst, pack_bf16(c0, c1));
  sts1(dst + 128, pack_bf16(c2, c3));
}
__device__ __forceinline__ void load_a_t(uint32_t (&a)[8][4], uint32_t wbase, int w, int lane) {
  const int mi = lane >> 3, r = lane & 7;
  const uint32_t base = wbase + (w >> 2) * 16384 + (8 * (mi >> 1) + r) * 128 + (((2 * (w & 3) + (mi & 1)) ^ r) << 4);
#pragma unroll
  for (int ks = 0; ks < 8; ks++) ldsm4t(a[ks], base + ks * 2048);
}
__device__ __forceinline__ void mma128(float (&d)[4], const uint32_t (&a)[8][4], const uint32_t (&b)[4][4]) {
  float e[4][4] = {{0.f, 0.f, 0.f, 0.f}, {0.f, 0.f, 0.f, 0.f}, {0.f, 0.f, 0.f, 0.f}, {0.f, 0.f, 0.f, 0.f}};
#pragma unroll
  for (int kk = 0; kk < 4; kk++) { mma16816(e[(2 * kk) & 3], a[2 * kk], b[kk][0], b[kk][1]); mma16816(e[(2 * kk + 1) & 3], a[2 * kk + 1], b[kk][2], b[kk][3]); }
#pragma unroll
  for (int i = 0; i < 4; i++) d[i] = (e[0][i] + e[1][i]) + (e[2][i] + e[3][i]);
}
template <int NP> __device__ __forceinline__ int sum_pieces(const uint32_t* p0, int g, int t, float& v0, float& v1, int rb) {
  constexpr int NL = NP / 8;
  uint32_t v[NL][4];
#pragma unroll
  for (int i = 0; i < NL; i++) { const uint4 x = ldg_2u64(p0 + i * 128); v[i][0] = x.x; v[i][1] = x.y; v[i][2] = x.z; v[i][3] = x.w; }
  int it = 0;
  while (true) {
    uint32_t mn = 0xffffffffu;
#pragma unroll
    for (int i = 0; i < NL; i++) mn = min(mn, min(v[i][1], v[i][3]));
    if (mn != 0) break;
    backoff(rb);
#pragma unroll
    for (int i = 0; i < NL; i++)
      if (v[i][1] == 0 || v[i][3] == 0) { const uint4 x = ldg_2u64(p0 + i * 128); v[i][0] = x.x; v[i][1] = x.y; v[i][2] = x.z; v[i][3] = x.w; }
    if (++it > SPIN_LIMIT) __trap();
  }
  __syncwarp();
  const uint32_t one = (g & 1) ? 0x3f800000u : 0x00003f80u;
  const uint32_t b0 = (g & 2) ? 0u : one, b1 = (g & 2) ? one : 0u;
  float d[4][4] = {{0.f, 0.f, 0.f, 0.f}, {0.f, 0.f, 0.f, 0.f}, {0.f, 0.f, 0.f, 0.f}, {0.f, 0.f, 0.f, 0.f}};
#pragma unroll
  for (int i = 0; i < NL; i++) mma16816(d[i & 3], v[i], b0, b1);
  const bool up = t & 2;
  const float x0 = up ? (d[0][2] + d[1][2]) + (d[2][2] + d[3][2]) : (d[0][0] + d[1][0]) + (d[2][0] + d[3][0]);
  const float x1 = up ? (d[0][3] + d[1][3]) + (d[2][3] + d[3][3]) : (d[0][1] + d[1][1]) + (d[2][1] + d[3][1]);
  v0 = x0 + __shfl_xor_sync(~0u, x0, 16);
  v1 = x1 + __shfl_xor_sync(~0u, x1, 16);
  return it;
}
template <typename F> __device__ __forceinline__ float reduce_g(const float (&x)[4], int lane, F f) {
  const bool u4 = lane & 16, u3 = lane & 8;
  const float a0 = f(u4 ? x[2] : x[0], __shfl_xor_sync(~0u, u4 ? x[0] : x[2], 16));
  const float a1 = f(u4 ? x[3] : x[1], __shfl_xor_sync(~0u, u4 ? x[1] : x[3], 16));
  const float b = f(u3 ? a1 : a0, __shfl_xor_sync(~0u, u3 ? a0 : a1, 8));
  return f(b, __shfl_xor_sync(~0u, b, 4));
}

__global__ void __launch_bounds__(NTHREADS, 1)
fused_decode_kernel(__nv_bfloat16* __restrict__ gout, Scratch* __restrict__ gs, const uint8_t* __restrict__ gwmod,
                    const uint8_t* __restrict__ gx, const uint8_t* __restrict__ gc,
                    const __grid_constant__ Params P) {
  constexpr Tune T{};
  extern __shared__ __align__(1024) uint8_t smem_raw[];
  const uint32_t sb = (uint32_t)__cvta_generic_to_shared(smem_raw);
  const int tid = threadIdx.x, lane = tid & 31;
  const int w = __shfl_sync(0xffffffffu, tid >> 5, 0);
  const int cta = blockIdx.x;
  const uint32_t bars = sb + OFF_BARS;
  auto BAR = [&](int i) { return bars + 8 * i; };
  const int g = lane >> 2, t = lane & 3;
  const int hI = cta >> 2, jI = cta & 3;
  const int bs = cta >> 1, hh = cta & 1;

  CLK_DECL;
  CLK(0);
  if (w == 8) {
    CLK(7);
    const uint32_t t_entry = gtime32();
    CLK(8);
    if (lane == 0) {
      if ((sb & 0xffffff) != SB) __trap();
      mbar_init(BAR(BAR_WQ), 1); mbar_init(BAR(BAR_WQ + 1), 1); mbar_init(BAR(BAR_XC), 1); mbar_init(BAR(BAR_C), 1);
      asm volatile("fence.mbarrier_init.release.cluster;" ::: "memory");
      asm volatile("prefetch.tensormap [%0];" ::"l"(&P.wq) : "memory");
      mbar_expect(BAR(BAR_XC), 8192); mbar_expect(BAR(BAR_C), 8192); mbar_expect(BAR(BAR_WQ), 16384); mbar_expect(BAR(BAR_WQ + 1), 16384);
      CLK(9);
    }
    __syncwarp();
    asm volatile("barrier.cta.arrive.aligned 0, %0;" ::"n"(NTHREADS) : "memory");
    CLK(10);
    uint32_t tn = t_entry + T.PC_T0 + ((bs * 37) & 63) * T.PC_STAG / 64;
    const int h = hI, j = jI;
    if (lane == 0) {
      uint64_t pol; asm volatile("createpolicy.fractional.L2::evict_first.b64 %0, 1.0;" : "=l"(pol));
#pragma unroll
      for (int u = 0; u < 4; u++) {
        until_ns(tn + u * T.PC_P1);
        if (u == 0) CLK(11);
        tma2d(sb + OFF_WQ + u * 8192, &P.wq, 128 * h + 64 * (u >> 1), 128 * j + 64 * (u & 1), BAR(BAR_WQ + (u >> 1)), pol);
        if (u == T.PC_XC) {
#pragma unroll
          for (int i = 0; i < 4; i++) { const int o = ((i + cta) & 3) * 2048; bulk_ld(sb + OFF_XS + o, gx + o, 2048, BAR(BAR_XC)); }
        }
        if (u == T.PC_C) {
#pragma unroll
          for (int i = 0; i < 4; i++) { const int o = ((i + cta) & 3) * 2048; bulk_ld(sb + OFF_CS + o, gc + o, 2048, BAR(BAR_C)); }
        }
        if (u == 0) {
          CLK(1);
          asm volatile("prefetch.tensormap [%0];" ::"l"(&P.wuk) : "memory");
          asm volatile("prefetch.tensormap [%0];" ::"l"(&P.wm2) : "memory");
          asm volatile("prefetch.tensormap [%0];" ::"l"(&P.ckv2) : "memory");
        }
      }
    }
    __syncwarp();
    tn += 4 * T.PC_P1;
    bar_sync(5, 64);
    if (lane == 0) {
      uint64_t pol; asm volatile("createpolicy.fractional.L2::evict_first.b64 %0, 1.0;" : "=l"(pol));
#pragma unroll
      for (int u = 0; u < 4; u++) {
        if ((u & 1) == (T.PC_W > 3) && T.PC_NW) mbar_wait(BAR(BAR_WQ + (u >> 1)));
        slot(tn, T.PC_SL);
        tma5d(sb + OFF_WUK + u * 8192, &P.wuk, 128 * h + 64 * (u >> 1), 0, 0, 0, 8 * j + 4 * (u & 1), BAR(BAR_WUK + (u >> 1)), pol);
        tn += T.PC_P1;
      }
#pragma unroll
      for (int u = 0; u < 2; u++) {
        if (u == (T.PC_W > 3) && T.PC_NW) mbar_wait(BAR(BAR_WUK));
        slot(tn, T.PC_SL);
        tma2d_nohint(sb + OFF_WM2 + u * 8192, &P.wm2, 1024 + 16 * cta, 256 * u, BAR(BAR_WM2));
        tn += T.PC_P1;
      }
      const int row0 = (bs >> 3) * 4096 + (bs & 7) * 64;
      uint32_t dst = sb + OFF_RING;
      const int p2 = T.PC_P2 + (32 - ((bs * 37) & 63)) * T.PC_DS / 1024;
#pragma unroll 1
      for (int n = 0; n < 31; n++) {
        if (n >= 4 && (n < 12 || (n & 3) == 0)) mbar_wait(BAR(n >= 12 ? BAR_EMPTY + (n >> 2) - 3 : n == 7 ? BAR_P0BD : (n == 8 || n == 9) ? BAR_P2D : BAR_P1D));
        if (n < T.PC_NW) {
          if (n >= T.PC_W) mbar_wait(BAR(BAR_FULL + n - T.PC_W));
          else if ((n & 1) == (T.PC_W > 3)) mbar_wait(BAR(n < 2 ? BAR_WUK + 1 : BAR_WM2));
        }
        slot(tn, T.PC_SL);
        tma3d(dst, &P.ckv2, 0, row0 + (n >> 2) * 512, 2 * (n & 3), BAR(BAR_FULL + n), pol);
        dst = (n == 11 || n == 23) ? sb + OFF_RING : dst + 16384;
        tn += n >= 15 ? p2 : T.PC_P2;
        if (n == 4) CLK(2);
        if (n == 12) CLK(3);
        if (n == 20) CLK(4);
        if (n == 28) CLK(5);
        if (n == 24) {
          asm volatile("prefetch.tensormap [%0];" ::"l"(&P.ckv1) : "memory");
          asm volatile("prefetch.tensormap [%0];" ::"l"(&P.wuv) : "memory");
          asm volatile("prefetch.tensormap [%0];" ::"l"(&P.wo) : "memory");
          asm volatile("prefetch.tensormap [%0];" ::"l"(&P.w1) : "memory");
          asm volatile("prefetch.tensormap [%0];" ::"l"(&P.w2) : "memory");
        }
      }
      slot(tn, T.PC_SL);
      tma3d(dst, &P.ckv1, 0, row0 + 7 * 512, 6, BAR(BAR_LAST + 3), pol);
      tma3d(dst + 8192, &P.ckv1, 0, row0 + 7 * 512, 7, BAR(BAR_LAST + 4), pol);
      tn += T.PC_P2;
      CLK(6);
      auto unit = [&](int u) {
        if (u < 4) tma5d(sb + OFF_WUV + u * 8192, &P.wuv, 128 * h + 64 * (u >> 1), 0, 4 * (j >> 1), 0, 2 * (j & 1) + (u & 1), BAR(BAR_WUV + (u >> 1)), pol);
        else if (u < 8) tma2d(sb + OFF_WO + (u - 4) * 8192, &P.wo, 128 * j + 64 * ((u - 4) >> 1), 128 * h + 64 * (u & 1), BAR(BAR_WO + ((u - 4) >> 1)), pol);
        else if (u < 10) { if (cta < NFF) tma2d_nohint(sb + OFF_W1 + (u - 8) * 16384, &P.w1, 32 * bs, 256 * (u - 8), BAR(BAR_W1)); }
        else if (cta < NFF) tma3d(sb + OFF_W2 + (u - 10) * 8192, &P.w2, 0, 32 * bs, 4 * hh + 2 * (u - 10), BAR(BAR_W2), pol);
      };
      mbar_wait(BAR(BAR_EMPTY + 5));
      if (T.PW_A >= 0) { mbar_wait(BAR(BAR_LAST + T.PW_A)); tn = gtime32(); }
      tn += T.PW_0 + ((cta * 37) & 127) * T.PW_ST / 128;
#pragma unroll
      for (int u = 0; u < 12; u++) {
        if (u == 8) mbar_wait(BAR(BAR_EMPTY + 6));
        until_ns(tn);
        unit(WSWAP && u >= 8 ? (u ^ 2) : u);
        tn += u < 3 ? T.PW_UV : u == 3 ? T.PW_G : u < 7 ? T.PW_O : u == 7 ? T.PW_G2 : u == 9 ? T.PW_G3 : T.PW_F;
      }
      CLK_DUMP();
    }
    return;
  }

  if (w == 9) {
    if (lane == 0) {
#pragma unroll
      for (int i = 0; i < NBARS; i++) mbar_init(BAR(i), i >= BAR_P1D ? 8 : i >= BAR_EMPTY ? 4 : 1);
      asm volatile("fence.mbarrier_init.release.cluster;" ::: "memory");
    }
    __syncwarp();
    mbar_expect(BAR(lane), lane == BAR_LAST + 3 ? 8192 : 16384);
    if (lane < BAR_ALLCLR - 32) mbar_expect(BAR(32 + lane), lane == 0 ? 8192 : lane == BAR_W1 - 32 ? 32768 : 16384);
    CLK(9);
    asm volatile("barrier.cta.arrive.aligned 5, 64;" ::: "memory");
    asm volatile("barrier.cta.arrive.aligned 0, %0;" ::"n"(NTHREADS) : "memory");
  }
  const uint32_t epoch = ldg_rlx1(&gs->epoch);

  if (w == 9) {
    const int wd = 2 * (t & 1) + (t >> 1), bo = 2 * (g & 3) + (wd >> 1), mo = 16 * hI + 2 * jI + 8 * (wd & 1);
    const uint32_t xo = ldg_nc1(gx + (bo * 512 + mo) * 2);
    const int par = epoch & 1;
    until_ns(gtime32() + T.CLR_T0);
    {
      const uint4 z = make_uint4(0, 0, 0, 0);
      uint4* x1 = reinterpret_cast<uint4*>(gs->X1 + ((64 * hh + (lane >> 4)) * 64 + bs) * 64) + (lane & 15);
      constexpr int sx1 = 2 * 64 * 16, sx3 = 8 * 32 * 4, sx4 = 8 * NFG * 4;
      uint4* x3 = reinterpret_cast<uint4*>(gs->X3A + ((32 * jI + g) * 32 + hI) * 16) + t;
      uint4* x4 = reinterpret_cast<uint4*>(gs->X4 + ((64 * hh + g) * NFG + bs) * 16) + t;
#pragma unroll 1
      for (int i0 = 0; i0 < 32; i0 += 4) {
#pragma unroll
        for (int i = 0; i < 4; i++) stg4(x1 + (i0 + i) * sx1, z);
        backoff(T.CLR_CLK);
      }
#pragma unroll
      for (int i = 0; i < 4; i++) stg4(x3 + i * sx3, z);
      backoff(T.CLR_CLK);
#pragma unroll
      for (int i = 0; i < 4; i++) stg4(reinterpret_cast<uint4*>(gs->X2 + cta * 512) + i * 32 + lane, z);
      backoff(T.CLR_CLK);
      stg4(reinterpret_cast<uint4*>(gs->X3B + (lane >> 2) * 2048 + cta * 16) + (lane & 3), z);
      if (lane < 8) stg4(reinterpret_cast<uint4*>(gs->ML + cta * 32) + lane, z);
      if (cta < NFF) {
#pragma unroll
        for (int i = 0; i < 8; i++) { stg4(x4 + i * sx4, z); if ((i & 3) == 1) backoff(T.CLR_CLK); }
      }
      CLK(1);
      asm volatile("fence.acq_rel.gpu;" ::: "memory");
      CLK(2);
      __syncwarp();
      if (lane < NSYNC) asm volatile("red.relaxed.gpu.global.add.u32 [%0], 1;" ::"l"(&gs->sync[lane][0]) : "memory");
#pragma unroll
      for (int i = 0; i < 4; i++) stg4(reinterpret_cast<uint4*>(gs->QP[par ^ 1] + cta * 512) + i * 32 + lane, z);
      backoff(T.CLR_CLK);
#pragma unroll
      for (int i = 0; i < 4; i++) stg4(reinterpret_cast<uint4*>(gs->QX[par ^ 1] + cta * 512) + i * 32 + lane, z);
      stg4(reinterpret_cast<uint4*>(gs->MOD1[par ^ 1] + cta * 128) + lane, z);
      if (lane < 16) stg4(reinterpret_cast<uint4*>(gs->MOD2[par ^ 1] + cta * 64) + lane, z);
      if (lane == 0) {
        const uint32_t target = (epoch + 1) * NCTA;
        uint32_t c; int it = 0;
        do { backoff(T.CLR_CLK); asm volatile("ld.acquire.gpu.global.u32 %0, [%1];" : "=r"(c) : "l"(&gs->sync[cta % NSYNC][0]) : "memory"); if (++it > SPIN_LIMIT) __trap(); } while ((int)(c - target) < 0);
        mbar_arrive(BAR(BAR_ALLCLR));
      }
      __syncwarp();
    }
    CLK(3);
    uint2 gg[2];
    {
      const uint32_t* pg = gs->MOD2[par] + cta * 16 + bo * 2;
      load_units<2, 3 * 2048>(gg, pg);
      check_units<2, 3 * 2048>(gg, pg, T.RB);
    }
    const uint32_t ga2 = (wd & 1) ? gg[0].y : gg[0].x, gb2 = (wd & 1) ? gg[1].y : gg[1].x;
    uint32_t anchor;
    {
      mbar_wait(BAR(BAR_LAST + T.TS_P));
      unsigned long long now; asm volatile("mov.u64 %0, %%globaltimer;" : "=l"(now));
      if (lane < NSYNC) {
        asm volatile("red.relaxed.gpu.global.max.u64 [%0], %1;" ::"l"(&gs->sync[lane][2]), "l"(now) : "memory");
        asm volatile("red.relaxed.gpu.global.add.u32 [%0], 1;" ::"l"(&gs->sync[lane][1]) : "memory");
      }
      backoff(T.D_TS);
      const uint32_t target = (epoch + 1) * NCTA;
      uint4 v; int it = 0;
      do { v = ldg_2u64(gs->sync[cta % NSYNC]); if (++it > SPIN_LIMIT) __trap(); } while ((int)(v.y - target) < 0);
      const int age = min(max((int)(gtime32() - v.z), 0), 4000);
      anchor = clk32() - age * 7 / 4 + T.TS_O;
      if (lane == 0) { sts1(sb + OFF_TS, anchor); mbar_arrive(BAR(BAR_TS)); }
      CLK(10);
    }
    {
      const uint32_t* pm = pin(gs->ML + hI * 128 + lane * 4);
      wait_clk(anchor, T.A_M);
      uint4 ml = ldg_2u64(pm);
      int it = 0;
      while (ml.y == 0 || ml.w == 0) { ml = ldg_2u64(pm); if (++it > SPIN_LIMIT) __trap(); }
      __syncwarp();
      ITS(2, it);
      float M = fmaxf(__uint_as_float(ml.x), __uint_as_float(ml.z));
      M = fmaxf(M, __shfl_xor_sync(~0u, M, 1)); M = fmaxf(M, __shfl_xor_sync(~0u, M, 2));
      const float e0 = ex2(__uint_as_float(ml.x) - M), e1 = ex2(__uint_as_float(ml.z) - M);
      float l = e0 * __uint_as_float(ml.y) + e1 * __uint_as_float(ml.w);
      l += __shfl_xor_sync(~0u, l, 1); l += __shfl_xor_sync(~0u, l, 2);
      const float inv = __fdividef(1.f, l);
      sts2f(sb + OFF_WV + lane * 8, e0 * inv, e1 * inv);
      __syncwarp();
      if (lane == 0) mbar_arrive(BAR(BAR_WV));
      CLK(11);
    }
    float v0, v1;
    uint32_t* const x3o = pin(gs->X3B + (lane >> 2) * 2048 + cta * 16 + (lane & 3) * 4);
    uint32_t* const fo = pin(reinterpret_cast<uint32_t*>(gout) + (bo * 512 + mo) / 2);
    const int po = (4 * (g >> 2) + t) * 16 + (g & 3) * 4;
    const uint32_t* const p3 = pin(gs->X3A + cta * 512 + po);
    const uint32_t* const p4 = pin(gs->X4 + cta * NFG * 16 + po);
    mbar_wait(BAR(BAR_P5D));
    backoff(T.D_X3A);
    wait_clk(anchor, T.A_X3A);
    CLK(4);
    { const int it = sum_pieces<32>(p3, g, t, v0, v1, T.RB); ITS(0, it); }
    CLK(5);
    const uint32_t x2w = pack_bf16(bf_lo(xo) + bf_lo(ga2) * v0, bf_hi(xo) + bf_hi(ga2) * v1);
    {
      const int src = 4 * (lane & 3);
      uint4 o;
      o.x = __shfl_sync(~0u, x2w, src); o.y = __shfl_sync(~0u, x2w, src + 2); o.z = __shfl_sync(~0u, x2w, src + 1); o.w = __shfl_sync(~0u, x2w, src + 3);
      stg_2u64(x3o, o);
    }
    CLK(6);
    if (cta < NFF) { mbar_wait(BAR(BAR_P7D)); backoff(T.D_FIN); } else backoff(T.D_FIN2);
    CLK(7);
    { const int it = sum_pieces<NFG>(p4, g, t, v0, v1, T.RB); ITS(1, it); }
    if (g < 4) *fo = pack_bf16(bf_lo(x2w) + bf_lo(gb2) * v0, bf_hi(x2w) + bf_hi(gb2) * v1);
    CLK(8);
    CLK_DUMP();
    if (cta == 0 && lane == 0) stg1(&gs->epoch, epoch + 1);
    return;
  }

  const int wg = w >> 2, wq = w & 3;
  uint32_t tstore;
  {
    const uint8_t* pw = gwmod + (size_t)(128 * jI + 16 * w + 4 * (g >> 1) + (g & 1)) * 6144 + 64 * hI + 16 * t;
    const uint4 w0 = ldg_nc4(pw), w1 = ldg_nc4(pw + 2 * 6144);
    const uint2 cc = ldg_nc2(gc + g * 1024 + 256 * jI + 32 * w + 8 * t);
    CLK(40);
    const uint32_t a[4] = {silu2(cc.x), 0u, silu2(cc.y), 0u};
    float d[4][4] = {{0.f, 0.f, 0.f, 0.f}, {0.f, 0.f, 0.f, 0.f}, {0.f, 0.f, 0.f, 0.f}, {0.f, 0.f, 0.f, 0.f}};
    mma16816(d[0], a, movm(w0.x), movm(w1.x)); mma16816(d[1], a, movm(w0.y), movm(w1.y));
    mma16816(d[2], a, movm(w0.z), movm(w1.z)); mma16816(d[3], a, movm(w0.w), movm(w1.w));
    CLK(1);
    sts4f(sb + OFF_P0S + w * 1088 + lane * 16, d[0][0], d[0][1], d[1][0], d[1][1]);
    sts4f(sb + OFF_P0S + w * 1088 + 544 + lane * 16, d[2][0], d[2][1], d[3][0], d[3][1]);
    bar_sync(0, NTHREADS);
    if (tid < 128) {
      const uint32_t src = sb + OFF_P0S + ((tid >> 2) & 1) * 544 + (((tid >> 3) & 7) * 4 + 2 * (tid >> 6) + (tid & 1)) * 16 + ((tid >> 1) & 1) * 8;
      float2 v[8];
#pragma unroll
      for (int i = 0; i < 8; i++) v[i] = ldsf2(src + i * 1088);
      const float ax = ((v[0].x + v[1].x) + (v[2].x + v[3].x)) + ((v[4].x + v[5].x) + (v[6].x + v[7].x));
      const float ay = ((v[0].y + v[1].y) + (v[2].y + v[3].y)) + ((v[4].y + v[5].y) + (v[6].y + v[7].y));
      stg1(gs->MOD1[epoch & 1] + jI * 4096 + hI * 128 + tid, nz(pack_bf16(ax, ay)));
    }
    tstore = clk32();
  }
  CLK(2);
  const int par = epoch & 1;
  uint32_t cf[4][4];
  mbar_wait(BAR(BAR_XC));
  {
    uint32_t u[2][4];
    lds4(u[0], sb + OFF_XS + w * 1024 + lane * 16); lds4(u[1], sb + OFF_XS + w * 1024 + 512 + lane * 16);
    float v[16];
#pragma unroll
    for (int i = 0; i < 8; i++) { v[2 * i] = bf_lo(u[i >> 2][i & 3]); v[2 * i + 1] = bf_hi(u[i >> 2][i & 3]); }
    float s = 0.f;
#pragma unroll
    for (int i = 0; i < 16; i++) s += v[i];
#pragma unroll
    for (int o = 16; o; o >>= 1) s += __shfl_xor_sync(~0u, s, o);
    const float mu = s * (1.f / 512.f);
    float q = 0.f;
#pragma unroll
    for (int i = 0; i < 16; i++) { v[i] -= mu; q += v[i] * v[i]; }
#pragma unroll
    for (int o = 16; o; o >>= 1) q += __shfl_xor_sync(~0u, q, o);
    const float rs = rsqrtf(q * (1.f / 512.f) + 1e-5f);
    const bool hi = jI & 2;
    uint32_t o[4];
#pragma unroll
    for (int i = 0; i < 4; i++) o[i] = pack_bf16((hi ? v[8 + 2 * i] : v[2 * i]) * rs, (hi ? v[9 + 2 * i] : v[2 * i + 1]) * rs);
    if ((lane >> 4) == (jI & 1)) sts4(sb + OFF_XN + w * 272 + (lane & 15) * 16, make_uint4(o[0], o[1], o[2], o[3]));
  }
  CLK(3);
  uint32_t aw[8][4];
  {
    const uint32_t* pm = pin(gs->MOD1[par] + (8 * jI + w) * 64 + lane * 2);
    uint32_t* const qpo = pin(gs->QP[par] + (cta * 256 + tid) * 2);
    wait_clk(tstore, T.D_MOD);
    CLK(4);
    uint2 v[8];
    load_units<8, 2048>(v, pm);
    cbar();
    const uint32_t xn0 = lds1(sb + OFF_XN + g * 272 + w * 32 + t * 4), xn1 = lds1(sb + OFF_XN + g * 272 + w * 32 + 16 + t * 4);
    const bool early = __all_sync(~0u, mbar_test(BAR(BAR_WQ + wg)));
    if (early) load_a_t(aw, sb + OFF_WQ, w, lane);
    int it = 0;
    while (true) {
      uint32_t mn = 0xffffffffu;
#pragma unroll
      for (int i = 0; i < 8; i++) mn = min(mn, min(v[i].x, v[i].y));
      if (mn != 0) break;
#pragma unroll
      for (int i = 0; i < 8; i++) if (v[i].x == 0 || v[i].y == 0) v[i] = ldg_u64(pm + i * 2048);
      if (++it > SPIN_LIMIT) __trap();
    }
    CLK(5);
    ITS(0, it);
    float sc[2][4];
#pragma unroll
    for (int i = 0; i < 2; i++) {
      sc[i][0] = (bf_lo(v[i].x) + bf_lo(v[2 + i].x)) + (bf_lo(v[4 + i].x) + bf_lo(v[6 + i].x));
      sc[i][1] = (bf_hi(v[i].x) + bf_hi(v[2 + i].x)) + (bf_hi(v[4 + i].x) + bf_hi(v[6 + i].x));
      sc[i][2] = (bf_lo(v[i].y) + bf_lo(v[2 + i].y)) + (bf_lo(v[4 + i].y) + bf_lo(v[6 + i].y));
      sc[i][3] = (bf_hi(v[i].y) + bf_hi(v[2 + i].y)) + (bf_hi(v[4 + i].y) + bf_hi(v[6 + i].y));
    }
    sts2(sb + OFF_BS1 + (w >> 1) * 512 + lane * 16 + (w & 1) * 8,
         pack_bf16(bf_lo(xn0) * (1.f + sc[1][0]) + sc[0][0], bf_hi(xn0) * (1.f + sc[1][1]) + sc[0][1]),
         pack_bf16(bf_lo(xn1) * (1.f + sc[1][2]) + sc[0][2], bf_hi(xn1) * (1.f + sc[1][3]) + sc[0][3]));
    if (!early) { mbar_wait(BAR(BAR_WQ + wg)); load_a_t(aw, sb + OFF_WQ, w, lane); }
    CLK(6);
    cbar();
    uint32_t b[4][4];
#pragma unroll
    for (int kk = 0; kk < 4; kk++) lds4(b[kk], sb + OFF_BS1 + kk * 512 + lane * 16);
    float d[4];
    mma128(d, aw, b);
    stg_u64(qpo, pack_bf16(d[0], d[1]), pack_bf16(d[2], d[3]));
    tstore = clk32();
    CLK(7);
    if (wg) {
      mbar_wait(BAR(BAR_C));
#pragma unroll
      for (int i = 0; i < 4; i++) lds4(cf[i], sb + OFF_CS + g * 1024 + wq * 256 + i * 64 + t * 16);
#pragma unroll
      for (int i = 0; i < 16; i++) cf[i >> 2][i & 3] = silu2(cf[i >> 2][i & 3]);
    }
    __syncwarp();
    if (lane == 0) mbar_arrive(BAR(BAR_P1D));
  }
  {
    const uint32_t* pq = pin(gs->QP[par] + (hI * 4 * 256 + tid) * 2);
    uint32_t* const qxo = pin(gs->QX[par] + (g * 32 + hI) * 256 + 64 * jI + 8 * w + 2 * t);
    uint2 v[4];
    wait_clk(tstore, T.D_QP);
    CLK(8);
    load_units<4, 512>(v, pq);
    const uint32_t abase = sb + OFF_WUK + (16 * w + (lane & 15)) * 128;
    auto load_half = [&](int hf) {
#pragma unroll
      for (int ks = 0; ks < 4; ks++) ldsm4(aw[4 * hf + ks], abase + hf * 16384 + (((2 * ks + (lane >> 4)) ^ (lane & 7)) << 4));
    };
    mbar_wait(BAR(BAR_WUK));
    load_half(0);
    const bool early = __all_sync(~0u, mbar_test(BAR(BAR_WUK + 1)));
    if (early) load_half(1);
    const int it = check_units<4, 512>(v, pq, T.RB);
    CLK(9);
    ITS(1, it);
    sum4_to_smem(v, sb + OFF_BS2 + (16 * w + g) * 16 + t * 4);
    if (!early) { mbar_wait(BAR(BAR_WUK + 1)); load_half(1); }
    CLK(10);
    cbar();
    uint32_t b[4][4];
#pragma unroll
    for (int kk = 0; kk < 4; kk++) ldsm4t(b[kk], sb + OFF_BS2 + (32 * kk + lane) * 16);
    float d[4];
    mma128(d, aw, b);
    const float sc = 0.08838834764831845f * 1.4426950408889634f;
    stg_u64(qxo, movm(pack_bf16(d[0] * sc, d[1] * sc)), movm(pack_bf16(d[2] * sc, d[3] * sc)));
    tstore = clk32();
    CLK(11);
    if (lane == 0) mbar_arrive(BAR(BAR_P2D));
  }
  if (wg) {
    const int mi = lane >> 3, r = lane & 7;
    const uint32_t a0 = sb + OFF_WM2 + (8 * (r >> 1) + (r & 1) + 2 * (mi >> 1)) * 32 + (mi & 1) * 16;
    mbar_wait(BAR(BAR_WM2));
#pragma unroll
    for (int s = 0; s < 8; s++) ldsm4t(aw[s], a0 + (128 * wq + 32 * (s >> 1) + 4 * (s & 1)) * 32);
    float d[4];
    mma128(d, aw, cf);
    sts4f(sb + OFF_P0B + (tid - 128) * 16, d[0], d[1], d[2], d[3]);
    if (lane == 0) mbar_arrive(BAR(BAR_P0BD));
    bar_sync(3, 128);
    if (w == 4) {
      float4 v[4];
#pragma unroll
      for (int i = 0; i < 4; i++) v[i] = ldsf4(sb + OFF_P0B + (i * 32 + lane) * 16);
      stg_u64(gs->MOD2[par] + cta * 64 + t * 16 + g * 2, movm(pack_bf16((v[0].x + v[1].x) + (v[2].x + v[3].x), (v[0].y + v[1].y) + (v[2].y + v[3].y))),
              movm(pack_bf16((v[0].z + v[1].z) + (v[2].z + v[3].z), (v[0].w + v[1].w) + (v[2].w + v[3].w))));
    }
    CLK(15);
  }
  {
    const uint32_t* qx = pin(gs->QX[par] + ((bs >> 3) * 32 + 16 * hh) * 256 + tid * 4);
    const int ch = tid & 63, h0 = tid >> 6;
    const uint32_t dst = sb + OFF_Q + (ch >> 3) * 2048 + h0 * 128;
    wait_clk(tstore, T.D_QX);
    CLK(12);
    uint4 v[4];
#pragma unroll
    for (int i = 0; i < 4; i++) v[i] = ldg_2u64(qx + i * 1024);
    int it = 0;
    while (true) {
      uint32_t mn = 0xffffffffu;
#pragma unroll
      for (int i = 0; i < 4; i++) mn = min(mn, min(v[i].y, v[i].w));
      if (mn != 0) break;
#pragma unroll
      for (int i = 0; i < 4; i++) if (v[i].y == 0 || v[i].w == 0) v[i] = ldg_2u64(qx + i * 1024);
      if (++it > SPIN_LIMIT) __trap();
    }
    CLK(13);
    ITS(2, it);
#pragma unroll
    for (int i = 0; i < 4; i++) sts4(dst + i * 512 + (((ch & 7) ^ ((4 * i + h0) & 7)) << 4), v[i]);
    asm volatile("fence.proxy.async.shared::cta;" ::: "memory");
    CLK(14);
    cbar();
  }

  uint2 cbf[4], sbf[4];
  const uint32_t* const pcb = gs->MOD2[par] + 2048 + (16 * w + t) * 16 + g * 2;
  uint32_t thand, anchor;
  if (wg == 0) {
    float mh[4];
    float L[8];
#pragma unroll
    for (int i = 0; i < 4; i++) { L[2 * i] = L[2 * i + 1] = 0.f; mh[i] = -INFINITY; }
    constexpr uint32_t dq = desc_lo(OFF_Q);
    const uint32_t ptw = sb + OFF_PT + (8 * (lane >> 4) + (lane & 7)) * 128 + (((2 * wq + ((lane >> 3) & 1)) ^ (lane & 7)) << 4);
    float S[8];
    auto softmax = [&](int tl) {
      auto write_p = [&](const float (&x)[8]) {
        float p[8];
#pragma unroll
        for (int i = 0; i < 8; i++) p[i] = ex2(x[i]);
        stsm4t(ptw + (tl & 1) * 2048, pack_bf16(p[0], p[1]), pack_bf16(p[2], p[3]), pack_bf16(p[4], p[5]), pack_bf16(p[6], p[7]));
        asm volatile("fence.proxy.async.shared::cta;" ::: "memory");
      };
      float x[8];
#pragma unroll
      for (int i = 0; i < 8; i++) x[i] = S[i] - mh[2 * (i >> 2) + (i & 1)];
      if (tl) write_p(x);
      const float ex = fmaxf(fmaxf(fmaxf(x[0], x[1]), fmaxf(x[2], x[3])), fmaxf(fmaxf(x[4], x[5]), fmaxf(x[6], x[7])));
      if (tl == 0 || bar_over(ex)) {
        float mx[4];
#pragma unroll
        for (int i = 0; i < 4; i++) mx[i] = fmaxf(S[4 * (i >> 1) + (i & 1)], S[4 * (i >> 1) + 2 + (i & 1)]);
        const float a = reduce_g(mx, lane, [](float u, float v) { return fmaxf(u, v); });
        stsf(sb + OFF_RED + wq * 64 + (8 * (lane >> 4) + 2 * t + ((lane >> 3) & 1)) * 4, a);
        bar_sync(2, 128);
#pragma unroll
        for (int jn = 0; jn < 2; jn++) {
          float m0 = mh[2 * jn], m1 = mh[2 * jn + 1];
#pragma unroll
          for (int i = 0; i < 4; i++) { const float2 v = ldsf2(sb + OFF_RED + i * 64 + (8 * jn + 2 * t) * 4); m0 = fmaxf(m0, v.x); m1 = fmaxf(m1, v.y); }
          const float a0 = ex2(mh[2 * jn] - m0), a1 = ex2(mh[2 * jn + 1] - m1);
          mh[2 * jn] = m0; mh[2 * jn + 1] = m1;
          L[4 * jn] *= a0; L[4 * jn + 1] *= a1; L[4 * jn + 2] *= a0; L[4 * jn + 3] *= a1;
          if (tid < 4) sts2f(sb + OFF_ALPHA + (8 * jn + 2 * t) * 4, a0, a1);
        }
#pragma unroll
        for (int i = 0; i < 8; i++) x[i] = S[i] - mh[2 * (i >> 2) + (i & 1)];
        write_p(x);
        cbar();
      }
      const uint32_t dpt = __shfl_sync(~0u, desc_lo(OFF_PT) + (tl & 1) * 128, 0);
      wg_fence();
#pragma unroll
      for (int ks = 0; ks < 4; ks++) wgmma_n16_ones(L, ONE2, dpt + ks * 2);
      wg_commit();
    };
    uint32_t da = desc_lo(OFF_RING);
#pragma unroll 1
    for (int tl = 0; tl < 7; tl++) {
      uint32_t ok = 0;
#pragma unroll
      for (int u = 0; u < 4; u++) ok += mbar_test(BAR(BAR_FULL + 4 * tl + u));
      ok = __reduce_min_sync(~0u, ok);
      const uint32_t du = __shfl_sync(~0u, da, 0);
#pragma unroll
      for (int u = 0; u < 4; u++) {
        if (ok != 4) mbar_wait(BAR(BAR_FULL + 4 * tl + u));
        wg_fence();
#pragma unroll
        for (int k = 0; k < 8; k++) {
          const int i = 8 * u + k;
          if (i == 0) wgmma_n16<0, 0>(S, du, dq); else wgmma_n16<0, 1>(S, du + (i >> 2) * 512 + (i & 3) * 2, dq + (i >> 2) * 128 + (i & 3) * 2);
        }
        wg_commit();
      }
      wg_wait<0>();
      acc_fence(S); acc_fence(L);
      if (tl == 0) CLK(15);
      if (tl == 1) CLK(17);
      softmax(tl);
      if (tl == 0) CLK(16);
      if (tl == 1) CLK(18);
      if (tl == 3) CLK(19);
      if (tl == 6) CLK(20);
      da = (tl == 2 || tl == 5) ? da - 8192 : da + 4096;
    }
    if (cta < NFF) { load_units<4, 64>(sbf, pcb); load_units<4, 64>(cbf, pcb + 2048); }
    mbar_wait(BAR(BAR_ALLCLR));
    uint32_t* const mlo = pin(gs->ML + ((16 * hh + 4 * (g & 2) + 2 * t + (g & 1)) * 64 + bs) * 2);
#pragma unroll
    for (int i = 0; i < 32; i++) {
      if (i == 0 || i == 8 || i == 16 || i == 24 || i == 28) {
        if (i) wg_commit();
        mbar_wait(BAR(BAR_LAST + (i == 28 ? 4 : i >> 3)));
        if (i == 28) CLK(21);
        wg_fence();
      }
      if (i == 0) wgmma_n16<0, 0>(S, da, dq); else wgmma_n16<0, 1>(S, da + (i >> 2) * 512 + (i & 3) * 2, dq + (i >> 2) * 128 + (i & 3) * 2);
    }
    wg_commit();
    wg_wait<0>();
    acc_fence(S); acc_fence(L);
    CLK(22);
    softmax(7);
    CLK(23);
    thand = clk32();
    wg_wait<0>();
    acc_fence(L);
    if (tid < 16) stg_u64(mlo, __float_as_uint(g & 2 ? (g & 1 ? mh[3] : mh[2]) : (g & 1 ? mh[1] : mh[0])), __float_as_uint(g & 2 ? (g & 1 ? L[5] : L[4]) : (g & 1 ? L[1] : L[0])));
    CLK(24);
  } else {
    float O[8][8];
#pragma unroll
    for (int i = 0; i < 8; i++)
#pragma unroll
      for (int k = 0; k < 8; k++) O[i][k] = 0.f;
    constexpr uint32_t dp = desc_lo(OFF_PT);
    auto handover = [&](int tl) {
      if (tl == 0) { cbar(); return; }
      if (bar_over(0.f)) {
        cbar();
#pragma unroll
        for (int jn = 0; jn < 2; jn++) {
          const float2 a = ldsf2(sb + OFF_ALPHA + (8 * jn + 2 * t) * 4);
#pragma unroll
          for (int mb = 0; mb < 8; mb++) { O[mb][4 * jn] *= a.x; O[mb][4 * jn + 1] *= a.y; O[mb][4 * jn + 2] *= a.x; O[mb][4 * jn + 3] *= a.y; }
        }
      }
    };
    uint32_t da = desc_lo(OFF_RING);
#pragma unroll 1
    for (int tl = 0; tl < 7; tl++) {
      handover(tl);
      const uint32_t dpt = dp + (tl & 1) * 128;
      wg_fence();
#pragma unroll
      for (int i = 0; i < 32; i++) wgmma_n16<1, 1>(O[i >> 2], da + (i >> 2) * 512 + (i & 3) * 128, dpt + (i & 3) * 2);
      wg_commit();
      wg_wait<0>();
#pragma unroll
      for (int mb = 0; mb < 8; mb++) acc_fence(O[mb]);
      if (lane == 0) mbar_arrive(BAR(BAR_EMPTY + tl));
      if (tl == 0) CLK(16);
      if (tl == 1) CLK(18);
      if (tl == 3) CLK(19);
      if (tl == 6) CLK(20);
      da = (tl == 2 || tl == 5) ? da - 8192 : da + 4096;
    }
    if (cta < NFF) { load_units<4, 64>(sbf, pcb); load_units<4, 64>(cbf, pcb + 2048); }
    mbar_wait(BAR(BAR_ALLCLR));
    uint32_t* const x1o = pin(gs->X1 + (((16 * hh + 2 * t) * 4 + (wq >> 1)) * 64 + bs) * 64 + ((wq & 1) * 8 + g) * 4);
    handover(7);
    CLK(23);
    thand = clk32();
    auto pv = [&](int mb0, int n) {
      wg_fence();
#pragma unroll
      for (int i = 0; i < 16; i++)
        if (i < 4 * n) wgmma_n16<1, 1>(O[mb0 + (i >> 2)], desc_lo(65536) + (mb0 + (i >> 2)) * 512 + (i & 3) * 128, dp + 128 + (i & 3) * 2);
      wg_commit();
    };
    auto publish = [&](int J) {
#pragma unroll
      for (int k = 0; k < 4; k++) acc_fence(O[4 * J + k]);
#pragma unroll
      for (int i = 0; i < 4; i++) {
        const int k = 4 * (i >> 1) + (i & 1);
        stg_cvt8(x1o + ((8 * (i >> 1) + (i & 1)) * 4 + 2 * J) * 4096, O[4 * J][k], O[4 * J][k + 2], O[4 * J + 1][k], O[4 * J + 1][k + 2],
                 O[4 * J + 2][k], O[4 * J + 2][k + 2], O[4 * J + 3][k], O[4 * J + 3][k + 2]);
      }
    };
    pv(0, 4); pv(4, 4);
    wg_wait<1>(); publish(0);
    wg_wait<0>(); publish(1);
    CLK(24);
  }

  {
    const uint32_t* px = pin(gs->X1 + (cta * 64 + w * 8) * 64 + lane * 2);
    uint32_t* const x2o = pin(gs->X2 + (cta * 256 + tid) * 2);
    mbar_wait(BAR(BAR_TS));
    anchor = lds1(sb + OFF_TS);
    wait_clk(thand, T.D_X1);
    wait_clk(anchor, T.A_X1 + (jI >> 1) * T.A_X1J);
    CLK(25);
    uint2 v[8];
    load_units<8, 64>(v, px);
    const bool early = __all_sync(~0u, mbar_test(BAR(BAR_WUV + wg)));
    if (early) load_a_t(aw, sb + OFF_WUV, w, lane);
    mbar_wait(BAR(BAR_WV));
    const float4 wa = ldsf4(sb + OFF_WV + w * 32), wb = ldsf4(sb + OFF_WV + w * 32 + 16);
    const float wv[8] = {wa.x, wa.y, wa.z, wa.w, wb.x, wb.y, wb.z, wb.w};
    CLK(27);
    const int it = check_units<8, 64>(v, px, T.RB);
    CLK(28);
    ITS(4, it);
    float a0 = 0.f, a1 = 0.f, a2 = 0.f, a3 = 0.f;
#pragma unroll
    for (int i = 0; i < 8; i++) { a0 += wv[i] * bf_lo(v[i].x); a1 += wv[i] * bf_hi(v[i].x); a2 += wv[i] * bf_lo(v[i].y); a3 += wv[i] * bf_hi(v[i].y); }
    sts2(sb + OFF_BS4 + w * 272 + lane * 8, pack_bf16(a0, a1), pack_bf16(a2, a3));
    CLK(29);
    if (!early) { mbar_wait(BAR(BAR_WUV + wg)); load_a_t(aw, sb + OFF_WUV, w, lane); }
    cbar();
    uint32_t b[4][4];
#pragma unroll
    for (int kk = 0; kk < 4; kk++) ldsm4(b[kk], sb + OFF_BS4 + (lane & 7) * 272 + (4 * kk + (lane >> 3)) * 16);
    float d[4];
    mma128(d, aw, b);
    stg_u64(x2o, pack_bf16(d[0], d[1]), pack_bf16(d[2], d[3]));
    tstore = clk32();
    CLK(30);
  }
  {
    uint32_t* const o = pin(gs->X3A + ((4 * (8 * jI + w) + t) * 32 + hI) * 16 + g * 2);
    const uint32_t* const x2i = pin(gs->X2 + (hI * 4 * 256 + tid) * 2);
    wait_clk(tstore, T.D_X2);
    wait_clk(anchor, T.A_X2);
    uint2 v[4];
    load_units<4, 512>(v, x2i);
    mbar_wait(BAR(BAR_WO + wg));
    load_a_t(aw, sb + OFF_WO, w, lane);
    CLK(31);
    const int it = check_units<4, 512>(v, x2i, T.RB);
    CLK(32);
    ITS(5, it);
    sum4_to_smem(v, sb + OFF_BS5 + (16 * w + g) * 16 + t * 4);
    cbar();
    uint32_t b[4][4];
#pragma unroll
    for (int kk = 0; kk < 4; kk++) ldsm4t(b[kk], sb + OFF_BS5 + (32 * kk + lane) * 16);
    float d[4];
    mma128(d, aw, b);
    stg_u64(o, movm(pack_bf16(d[0], d[1])), movm(pack_bf16(d[2], d[3])));
    tstore = clk32();
    CLK(33);
    if (lane == 0) mbar_arrive(BAR(BAR_P5D));
  }
  if (cta < NFF) {
    const int mi = lane >> 3, r = lane & 7;
    uint32_t a1[2][4][4], a2[2][2][4];
    check_units<4, 64>(sbf, pcb, T.RB);
    check_units<4, 64>(cbf, pcb + 2048, T.RB);
    __syncwarp();
#pragma unroll
    for (int s = 0; s < 4; s++) { cbf[s].x = hadd2(cbf[s].x, ONE2); cbf[s].y = hadd2(cbf[s].y, ONE2); }
    mbar_wait(BAR(BAR_W1));
#pragma unroll
    for (int mt = 0; mt < 2; mt++) {
#pragma unroll
      for (int ks = 0; ks < 4; ks++) ldsm4t(a1[mt][ks], sb + OFF_W1 + (64 * w + 16 * ks + 8 * (mi >> 1) + r) * 64 + (((2 * mt + (mi & 1)) ^ (r >> 1)) << 4));
      float u[4] = {0.f, 0.f, 0.f, 0.f}, vv[4] = {0.f, 0.f, 0.f, 0.f};
#pragma unroll
      for (int s = 0; s < 4; s++) { mma16816(u, a1[mt][s], cbf[s].x, cbf[s].y); mma16816(vv, a1[mt][s], sbf[s].x, sbf[s].y); }
      sts4f(sb + OFF_REDU + w * 1024 + mt * 512 + lane * 16, u[0], u[1], u[2], u[3]);
      sts4f(sb + OFF_REDV + w * 1024 + mt * 512 + lane * 16, vv[0], vv[1], vv[2], vv[3]);
    }
    const uint32_t* xb = pin(gs->X3B + (((cta + 8 * (REPSEL != 0)) >> REPSEL) & (NREP - 1)) * 2048 + (16 * w + t) * 16 + g * 2);
    uint32_t* const ox = pin(gs->X4 + ((64 * hh + 8 * w + t) * NFG + bs) * 16 + g * 2);
    CLK(34);
    wait_clk(tstore, T.D_X3B);
    uint2 x[4];
    load_units<4, 64>(x, xb);
    cbar();
    const int lp = (tid >> 2) & 31, kq = tid & 3;
    const int fo = 16 * wg + (lp >> 2) + 8 * (kq >> 1), bo = 2 * (lp & 3) + (kq & 1);
    float U = 0.f, V = 0.f;
#pragma unroll
    for (int i = 0; i < 8; i++) { U += ldsf(sb + OFF_REDU + i * 1024 + tid * 4); V += ldsf(sb + OFF_REDV + i * 1024 + tid * 4); }
    mbar_wait(BAR(BAR_W2));
#pragma unroll
    for (int i = 0; i < 4; i++)
      ldsm4t(a2[i >> 1][i & 1], sb + OFF_W2 + (w >> 1) * 4096 + (16 * (i & 1) + 8 * (mi >> 1) + r) * 128 + (((4 * (w & 1) + 2 * (i >> 1) + (mi & 1)) ^ r) << 4));
    CLK(35);
    const int it = check_units<4, 64>(x, xb, T.RB);
    __syncwarp();
    CLK(36);
    ITS(6, it);
    float G[2][2][4] = {}, S[2][4] = {};
#pragma unroll
    for (int s = 0; s < 4; s++) {
      const uint32_t sx[4] = {x[s].x, ONE2, x[s].y, ONE2};
      mma16816(S[s & 1], sx, x[s].x, x[s].y);
      const uint32_t y0 = hmul2(x[s].x, cbf[s].x), y1 = hmul2(x[s].y, cbf[s].y);
      mma16816(G[0][s & 1], a1[0][s], y0, y1);
      mma16816(G[1][s & 1], a1[1][s], y0, y1);
    }
    if (t == (g >> 1)) sts2f(sb + OFF_REDS + g * 80 + w * 8, (g & 1) ? S[0][3] + S[1][3] : S[0][2] + S[1][2], (g & 1) ? S[0][1] + S[1][1] : S[0][0] + S[1][0]);
#pragma unroll
    for (int mt = 0; mt < 2; mt++)
      sts4f(sb + OFF_REDG + w * 1024 + mt * 512 + lane * 16, G[mt][0][0] + G[mt][1][0], G[mt][0][1] + G[mt][1][1], G[mt][0][2] + G[mt][1][2], G[mt][0][3] + G[mt][1][3]);
    CLK(37);
    cbar();
    {
      float gv[8];
      float4 sv[4];
#pragma unroll
      for (int i = 0; i < 4; i++) sv[i] = ldsf4(sb + OFF_REDS + bo * 80 + i * 16);
#pragma unroll
      for (int i = 0; i < 8; i++) gv[i] = ldsf(sb + OFF_REDG + i * 1024 + tid * 4);
      const float s1 = ((sv[0].x + sv[0].z) + (sv[1].x + sv[1].z)) + ((sv[2].x + sv[2].z) + (sv[3].x + sv[3].z));
      const float s2 = ((sv[0].y + sv[0].w) + (sv[1].y + sv[1].w)) + ((sv[2].y + sv[2].w) + (sv[3].y + sv[3].w));
      const float gsum = ((gv[0] + gv[1]) + (gv[2] + gv[3])) + ((gv[4] + gv[5]) + (gv[6] + gv[7]));
      const float mu = s1 * (1.f / 512.f);
      const float rs = rsqrtf(fmaxf(s2 * (1.f / 512.f) - mu * mu, 0.f) + 1e-5f);
      const float hv = fmaxf(rs * (gsum - mu * U) + V, 0.f);
      asm volatile("st.shared.u16 [%0], %1;" ::"r"(sb + OFF_H1 + fo * 16 + bo * 2), "h"(__bfloat16_as_ushort(__float2bfloat16(hv))) : "memory");
    }
    CLK(38);
    cbar();
    uint32_t b[4];
    ldsm4t(b, sb + OFF_H1 + lane * 16);
    float o[2][2][4] = {};
#pragma unroll
    for (int i = 0; i < 4; i++) mma16816(o[i >> 1][i & 1], a2[i >> 1][i & 1], b[2 * (i & 1)], b[2 * (i & 1) + 1]);
#pragma unroll
    for (int mb = 0; mb < 2; mb++)
      stg_u64(ox + mb * 4 * NFG * 16, movm(pack_bf16(o[mb][0][0] + o[mb][1][0], o[mb][0][1] + o[mb][1][1])), movm(pack_bf16(o[mb][0][2] + o[mb][1][2], o[mb][0][3] + o[mb][1][3])));
    CLK(39);
    if (lane == 0) mbar_arrive(BAR(BAR_P7D));
  }
  CLK_DUMP();
}

typedef CUresult (*EncodeTiledFn)(CUtensorMap*, CUtensorMapDataType, cuuint32_t, void*, const cuuint64_t*, const cuuint64_t*,
                                  const cuuint32_t*, const cuuint32_t*, CUtensorMapInterleave, CUtensorMapSwizzle,
                                  CUtensorMapL2promotion, CUtensorMapFloatOOBfill);

struct Dim { uint64_t size, stride; uint32_t box; };
template <int R> void encode_map(EncodeTiledFn enc, CUtensorMap* m, const void* base, const Dim (&d)[R], CUtensorMapSwizzle sw, CUtensorMapL2promotion promo) {
  cuuint64_t dims[R], strides[R];
  cuuint32_t box[R], es[R];
  for (int i = 0; i < R; i++) { dims[i] = d[i].size; strides[i] = d[i].stride; box[i] = d[i].box; es[i] = 1; }
  enc(m, CU_TENSOR_MAP_DATA_TYPE_BFLOAT16, R, const_cast<void*>(base), dims, strides + 1, box, es, CU_TENSOR_MAP_INTERLEAVE_NONE, sw, promo,
      CU_TENSOR_MAP_FLOAT_OOB_FILL_NONE);
}

}

extern "C" void kernel_launch(void* const* d_in, const int* in_sizes, int n_in, void* d_out, int out_size) {
  (void)in_sizes; (void)n_in; (void)out_size;
  static EncodeTiledFn enc = nullptr;
  static Scratch* scratch = nullptr;
  if (!enc) {
    void* sp = nullptr;
    cudaGetSymbolAddress(&sp, g_s);
    scratch = (Scratch*)sp;
    void* fn = nullptr;
    cudaDriverEntryPointQueryResult q;
    cudaGetDriverEntryPoint("cuTensorMapEncodeTiled", &fn, cudaEnableDefault, &q);
    enc = (EncodeTiledFn)fn;
    cudaFuncSetAttribute(fused_decode_kernel, cudaFuncAttributeMaxDynamicSharedMemorySize, SMEM_BYTES);
  }
  const CUtensorMapSwizzle S128 = CU_TENSOR_MAP_SWIZZLE_128B, S0 = CU_TENSOR_MAP_SWIZZLE_NONE;
  const CUtensorMapL2promotion L0 = CU_TENSOR_MAP_L2_PROMOTION_NONE, L128 = CU_TENSOR_MAP_L2_PROMOTION_L2_128B;
  Params P;
  encode_map<2>(enc, &P.wq, d_in[2], {{4096, 2, 64}, {512, 8192, 64}}, S128, L0);
  encode_map<5>(enc, &P.wuk, d_in[3], {{4096, 2, 64}, {2, 8192, 2}, {4, 4 * 8192, 4}, {2, 2 * 8192, 2}, {32, 16 * 8192, 4}}, S128, L0);
  encode_map<2>(enc, &P.wm2, d_in[10], {{3072, 2, 16}, {512, 6144, 256}}, S0, L128);
  encode_map<3>(enc, &P.ckv2, d_in[1], {{64, 2, 64}, {8 * 4096, 1024, 64}, {8, 128, 2}}, S128, L0);
  encode_map<3>(enc, &P.ckv1, d_in[1], {{64, 2, 64}, {8 * 4096, 1024, 64}, {8, 128, 1}}, S128, L0);
  encode_map<5>(enc, &P.wuv, d_in[4], {{4096, 2, 64}, {2, 8 * 8192, 2}, {8, 64 * 8192, 4}, {8, 8192, 8}, {4, 16 * 8192, 1}}, S128, L0);
  encode_map<2>(enc, &P.wo, d_in[5], {{512, 2, 64}, {4096, 1024, 64}}, S128, L0);
  encode_map<2>(enc, &P.w1, d_in[7], {{1792, 2, 32}, {512, 3584, 256}}, CU_TENSOR_MAP_SWIZZLE_64B, L128);
  encode_map<3>(enc, &P.w2, d_in[8], {{64, 2, 64}, {1792, 1024, 32}, {8, 128, 2}}, S128, L0);
  cudaLaunchConfig_t cfg = {};
  cfg.gridDim = dim3(NCTA);
  cfg.blockDim = dim3(NTHREADS);
  cfg.dynamicSmemBytes = SMEM_BYTES;
  cfg.stream = cudaStreamPerThread;
  cudaLaunchAttribute at[1];
  at[0].id = cudaLaunchAttributeClusterDimension;
  at[0].val.clusterDim.x = 2; at[0].val.clusterDim.y = 1; at[0].val.clusterDim.z = 1;
  cfg.attrs = at;
  cfg.numAttrs = 0;
  cudaLaunchKernelEx(&cfg, fused_decode_kernel, (__nv_bfloat16*)d_out, scratch, (const uint8_t*)d_in[10], (const uint8_t*)d_in[0],
                     (const uint8_t*)d_in[9],
                     P);
}
```

```cpp
#include <cuda_runtime.h>
#include <cuda.h>
#include <cuda_bf16.h>
#include <stdint.h>
#define V4 1

namespace {

constexpr int NCTA = 128;
constexpr int NTHREADS = 320;
constexpr int NFG = 56;
constexpr int NFF = 2 * NFG;
constexpr int NSYNC = 4;
#define NTS 8

constexpr uint32_t OFF_RING = 0;
constexpr uint32_t OFF_WUK = 131072;
constexpr uint32_t OFF_WQ = 131072 + 32768;
constexpr uint32_t OFF_WM2 = 65536 + 49152;
constexpr uint32_t OFF_WUV = 131072;
constexpr uint32_t OFF_WO = 131072 + 32768;
constexpr uint32_t OFF_W1 = 0;
constexpr uint32_t OFF_W2 = 32768;
constexpr uint32_t OFF_Q = 196608;
constexpr uint32_t OFF_PT = 212992;
constexpr uint32_t OFF_SCR = 217088;
constexpr uint32_t OFF_XS = 65536;
constexpr uint32_t OFF_CS = 65536 + 8192;
constexpr uint32_t OFF_P0S = 65536 + 16384;
constexpr uint32_t OFF_BS1 = OFF_SCR + 2048;
constexpr uint32_t OFF_BS2 = OFF_SCR + 4096;
constexpr uint32_t OFF_P0B = OFF_SCR + 6144;
constexpr uint32_t OFF_XN = OFF_SCR + 8192;
constexpr uint32_t OFF_RED = OFF_SCR + 10496;
constexpr uint32_t OFF_ALPHA = OFF_SCR + 11072;
constexpr uint32_t OFF_WV = OFF_SCR + 6144;
constexpr uint32_t OFF_SEL = OFF_SCR + 10752;
constexpr uint32_t OFF_TS = OFF_SCR + 11136;
constexpr uint32_t OFF_BARS = OFF_SCR + 11264;
constexpr uint32_t SMEM_BYTES = OFF_BARS + 512;
constexpr uint32_t OFF_BS4 = OFF_Q;
constexpr uint32_t OFF_H1 = OFF_Q + 2304;
constexpr uint32_t OFF_REDS = OFF_Q + 2816;
constexpr uint32_t OFF_BS5 = OFF_Q + 4096;
constexpr uint32_t OFF_REDG = OFF_Q + 8192;
constexpr uint32_t OFF_REDU = 65536;
constexpr uint32_t OFF_REDV = 65536 + 8192;

constexpr int BAR_FULL = 0;
constexpr int BAR_LAST = 28;
constexpr int BAR_WUK = 33, BAR_WM2 = 35, BAR_WUV = 36, BAR_WO = 38, BAR_W1 = 40, BAR_W2 = 41;
constexpr int BAR_ALLCLR = 42, BAR_TS = 43, BAR_WV = 44;
constexpr int BAR_EMPTY = 45;
constexpr int BAR_P0BD = 52;
constexpr int BAR_P1D = 53, BAR_P2D = 54;
constexpr int BAR_P5D = 55, BAR_P7D = 56;
constexpr int NBARS = 57;
constexpr int BAR_XC = 57, BAR_WQ = 58;
constexpr int BAR_C = 60, BAR_END = 61;
constexpr uint32_t SB = 1024;

#define TUNE_LIST(X) \
  X(PC_T0, 340) X(PC_XC, 0) X(PC_C, 0) X(PC_P1, 320) X(PC_P2, 322) X(PC_STAG, 390) X(PC_DS, 0) X(PC_SL, 500) X(PC_W, 4) X(PC_NW, 8) \
  X(PW_A, -1) X(PW_0, 260) X(PW_ST, 0) X(PW_UV, 300) X(PW_G, 470) X(PW_O, 385) X(PW_G2, 360) X(PW_G3, 480) X(PW_F, 300) \
  X(LOC, 0) X(PR_T0, 1000) X(PR_N, 4) X(CLR_T0, 3600) X(CLR_CLK, 230) \
  X(D_MOD, 1500) X(D_QP, 1300) X(D_QX, 1300) X(TS_P, 1) X(TS_O, 830) X(D_TS, 900) X(A_M, 2300) X(D_X1, 1400) X(A_X1, 2420) X(A_X1J, 200) \
  X(D_X2, 350) X(A_X2, 4850) X(D_X3A, 255) X(A_X3A, 0) X(D_X3B, 1550) X(D_FIN, 360) X(D_FIN2, 2050) X(RB, 0)
struct Tune {
#define X(n, v) static constexpr int n = v;
  TUNE_LIST(X)
#undef X
};

#define PFENCE 0
#define WSWAP 0
#define PVV 0
struct Scratch {
  uint32_t MOD1[2][4 * 64 * 64];
  uint32_t MOD2[2][128 * 64];
  uint32_t QP[2][128 * 256 * 2];
  uint32_t QX[2][8 * 32 * 256];
  uint32_t epoch;
  uint32_t pad[31];
  uint32_t sync[NSYNC][32];
};
__device__ Scratch g_s;
__device__ uint32_t g_in[129 * 16384];
__device__ __forceinline__ uint32_t blk(int c, int k, uint32_t sel) { return c * 16384 + k * 2048 + ((sel ^ k) & 1) * 1024; }

#define CLK_DECL
#define CLK(i) do {} while (0)
#define CLK_DUMP() do {} while (0)
#define ITS(i, v) do {} while (0)

struct Params {
  CUtensorMap wq, wuk, wm2, ckv2, ckv1, wuv, wo, w1, w2;
};

__device__ __forceinline__ void mbar_init(uint32_t bar, int cnt) { asm volatile("mbarrier.init.shared::cta.b64 [%0], %1;" ::"r"(bar), "r"(cnt)); }
__device__ __forceinline__ void mbar_expect(uint32_t bar, uint32_t bytes) { asm volatile("mbarrier.arrive.expect_tx.shared::cta.b64 _, [%0], %1;" ::"r"(bar), "r"(bytes) : "memory"); }
__device__ __forceinline__ void mbar_arrive(uint32_t bar) { asm volatile("mbarrier.arrive.shared::cta.b64 _, [%0];" ::"r"(bar) : "memory"); }
__device__ __forceinline__ uint32_t clk32() { unsigned long long c; asm volatile("mov.u64 %0, %%clock64;" : "=l"(c) :: "memory"); return (uint32_t)c; }
__device__ __forceinline__ uint32_t gtime32() { uint32_t c; asm volatile("mov.u32 %0, %%globaltimer_lo;" : "=r"(c) :: "memory"); return c; }
__device__ __forceinline__ void wait_clk(uint32_t t0, int clocks) { while ((int)(clk32() - t0) < clocks) {} }
__device__ __forceinline__ void backoff(int clocks) { if (clocks > 0) wait_clk(clk32(), clocks); }
__device__ __forceinline__ void until_ns(uint32_t ns) { while ((int)(gtime32() - ns) < 0) {} }
__device__ __forceinline__ void slot(uint32_t& tn, int slack) {
  uint32_t now;
  do { now = gtime32(); } while ((int)(now - tn) < 0);
  if ((int)(now - tn) > slack) tn = now - slack;
}
template <typename T> __device__ __forceinline__ T* pin(T* p) { asm volatile("" : "+l"(p)); return p; }
constexpr int SPIN_LIMIT = 1 << 22;
__device__ __forceinline__ void mbar_wait(uint32_t bar) {
  asm volatile("{\n.reg .pred p;\n.reg .u32 c;\nmov.u32 c, 0;\n"
               "MW_LOOP:\nmbarrier.try_wait.parity.shared::cta.b64 p, [%0], 0;\n@p bra MW_DONE;\n"
               "add.u32 c, c, 1;\nsetp.lt.u32 p, c, 4194304;\n@p bra MW_LOOP;\ntrap;\nMW_DONE:\n}"
               ::"r"(bar) : "memory");
}
__device__ __forceinline__ bool mbar_test(uint32_t bar) {
  uint32_t ok;
  asm volatile("{\n.reg .pred p;\nmbarrier.test_wait.parity.shared::cta.b64 p, [%1], 0;\nselp.u32 %0,1,0,p;\n}" : "=r"(ok) : "r"(bar) : "memory");
  return ok;
}
__device__ __forceinline__ void tma2d(uint32_t dst, const CUtensorMap* m, int c0, int c1, uint32_t bar, uint64_t pol) {
  asm volatile("cp.async.bulk.tensor.2d.shared::cluster.global.mbarrier::complete_tx::bytes.L2::cache_hint [%0], [%1, {%3,%4}], [%2], %5;"
               ::"r"(dst), "l"(m), "r"(bar), "r"(c0), "r"(c1), "l"(pol) : "memory");
}
__device__ __forceinline__ void tma2d_nohint(uint32_t dst, const CUtensorMap* m, int c0, int c1, uint32_t bar) {
  asm volatile("cp.async.bulk.tensor.2d.shared::cluster.global.mbarrier::complete_tx::bytes [%0], [%1, {%3,%4}], [%2];"
               ::"r"(dst), "l"(m), "r"(bar), "r"(c0), "r"(c1) : "memory");
}
__device__ __forceinline__ void tma3d(uint32_t dst, const CUtensorMap* m, int c0, int c1, int c2, uint32_t bar, uint64_t pol) {
  asm volatile("cp.async.bulk.tensor.3d.shared::cluster.global.mbarrier::complete_tx::bytes.L2::cache_hint [%0], [%1, {%3,%4,%5}], [%2], %6;"
               ::"r"(dst), "l"(m), "r"(bar), "r"(c0), "r"(c1), "r"(c2), "l"(pol) : "memory");
}
__device__ __forceinline__ void tma5d(uint32_t dst, const CUtensorMap* m, int c0, int c1, int c2, int c3, int c4, uint32_t bar, uint64_t pol) {
  asm volatile("cp.async.bulk.tensor.5d.shared::cluster.global.mbarrier::complete_tx::bytes.L2::cache_hint [%0], [%1, {%3,%4,%5,%6,%7}], [%2], %8;"
               ::"r"(dst), "l"(m), "r"(bar), "r"(c0), "r"(c1), "r"(c2), "r"(c3), "r"(c4), "l"(pol) : "memory");
}
__device__ __forceinline__ void bulk_ld(uint32_t dst, const void* src, uint32_t bytes, uint32_t bar) {
  asm volatile("cp.async.bulk.shared::cluster.global.mbarrier::complete_tx::bytes [%0], [%1], %2, [%3];" ::"r"(dst), "l"(src), "r"(bytes), "r"(bar) : "memory");
}
__device__ __forceinline__ void bar_sync(int id, int n) { asm volatile("barrier.cta.sync.aligned %0, %1;" ::"r"(id), "r"(n) : "memory"); }
__device__ __forceinline__ void cbar() { asm volatile("barrier.cta.sync.aligned 1, 256;" ::: "memory"); }
__device__ __forceinline__ bool bar_over(float ex) {
  uint32_t over;
  asm volatile("{\n.reg .pred p, q;\nsetp.gtu.f32 p, %1, 0f41F00000;\nbarrier.cta.red.or.aligned.pred q, 4, 256, p;\nselp.u32 %0, 1, 0, q;\n}"
               : "=r"(over) : "f"(ex) : "memory");
  return over;
}

__device__ __forceinline__ uint32_t ldg_nc1(const void* p) { uint32_t v; asm volatile("ld.global.nc.L1::no_allocate.u32 %0, [%1];" : "=r"(v) : "l"(p)); return v; }
__device__ __forceinline__ uint2 ldg_nc2(const void* p) { uint2 v; asm volatile("ld.global.nc.v2.u32 {%0,%1}, [%2];" : "=r"(v.x), "=r"(v.y) : "l"(p)); return v; }
__device__ __forceinline__ uint4 ldg_nc4(const void* p) { uint4 v; asm volatile("ld.global.nc.L1::no_allocate.v4.u32 {%0,%1,%2,%3}, [%4];" : "=r"(v.x), "=r"(v.y), "=r"(v.z), "=r"(v.w) : "l"(p)); return v; }
__device__ __forceinline__ uint32_t ldg_rlx1(const void* p) { uint32_t v; asm volatile("ld.relaxed.gpu.global.u32 %0, [%1];" : "=r"(v) : "l"(p) : "memory"); return v; }
__device__ __forceinline__ void stg4(void* p, uint4 v) { asm volatile("st.relaxed.gpu.global.v4.u32 [%0], {%1,%2,%3,%4};" ::"l"(p), "r"(v.x), "r"(v.y), "r"(v.z), "r"(v.w) : "memory"); }
__device__ __forceinline__ void stg1(void* p, uint32_t a) { asm volatile("st.relaxed.gpu.global.u32 [%0], %1;" ::"l"(p), "r"(a) : "memory"); }
__device__ __forceinline__ uint32_t nz(uint32_t w) { return max(w, 1u); }
__device__ __forceinline__ uint2 ldg_u64(const void* p) {
  uint2 v; asm volatile("{\n.reg .b64 a;\nld.relaxed.gpu.global.b64 a, [%2];\nmov.b64 {%0,%1}, a;\n}" : "=r"(v.x), "=r"(v.y) : "l"(p) : "memory"); return v;
}
__device__ __forceinline__ uint4 ldg_2u64(const void* p) {
  uint4 v; asm volatile("{\n.reg .b64 a, b;\nld.relaxed.gpu.global.v2.b64 {a, b}, [%4];\nmov.b64 {%0,%1}, a;\nmov.b64 {%2,%3}, b;\n}" : "=r"(v.x), "=r"(v.y), "=r"(v.z), "=r"(v.w) : "l"(p) : "memory"); return v;
}
__device__ __forceinline__ void stg_u64(void* p, uint32_t x, uint32_t y) {
  asm volatile("{\n.reg .b32 y;\nmax.u32 y, %2, 1;\nst.relaxed.gpu.global.v2.b32 [%0], {%1, y};\n}" ::"l"(p), "r"(x), "r"(y) : "memory");
}
__device__ __forceinline__ void stg_2u64(void* p, uint4 v) {
  asm volatile("{\n.reg .b32 y, w;\nmax.u32 y, %2, 1;\nmax.u32 w, %4, 1;\nst.relaxed.gpu.global.v4.b32 [%0], {%1, y, %3, w};\n}" ::"l"(p), "r"(v.x), "r"(v.y), "r"(v.z), "r"(v.w) : "memory");
}

__device__ __forceinline__ void stg_cvt8(void* p, float a0, float a1, float b0, float b1, float c0, float c1, float d0, float d1) {
  asm volatile("{\n.reg .b32 x, y, z, w;\ncvt.rn.bf16x2.f32 x, %2, %1;\ncvt.rn.bf16x2.f32 y, %4, %3;\ncvt.rn.bf16x2.f32 z, %6, %5;\ncvt.rn.bf16x2.f32 w, %8, %7;\n"
               "max.u32 y, y, 1;\nmax.u32 w, w, 1;\nst.relaxed.gpu.global.v4.b32 [%0], {x, y, z, w};\n}"
               ::"l"(p), "f"(a0), "f"(a1), "f"(b0), "f"(b1), "f"(c0), "f"(c1), "f"(d0), "f"(d1) : "memory");
}
__device__ __forceinline__ uint32_t pack_bf16(float lo, float hi) { uint32_t r; asm("cvt.rn.bf16x2.f32 %0, %1, %2;" : "=r"(r) : "f"(hi), "f"(lo)); return r; }
__device__ __forceinline__ float bf_lo(uint32_t w) { return __uint_as_float(w << 16); }
__device__ __forceinline__ float bf_hi(uint32_t w) { return __uint_as_float(w & 0xffff0000u); }
__device__ __forceinline__ float ex2(float x) { float r; asm("ex2.approx.ftz.f32 %0, %1;" : "=f"(r) : "f"(x)); return r; }
__device__ __forceinline__ uint32_t hmul2(uint32_t a, uint32_t b) { uint32_t r; asm("mul.rn.bf16x2 %0, %1, %2;" : "=r"(r) : "r"(a), "r"(b)); return r; }
__device__ __forceinline__ uint32_t hadd2(uint32_t a, uint32_t b) { uint32_t r; asm("add.rn.bf16x2 %0, %1, %2;" : "=r"(r) : "r"(a), "r"(b)); return r; }
__device__ __forceinline__ uint32_t hfma2(uint32_t a, uint32_t b, uint32_t c) { uint32_t r; asm("fma.rn.bf16x2 %0, %1, %2, %3;" : "=r"(r) : "r"(a), "r"(b), "r"(c)); return r; }
__device__ __forceinline__ uint32_t silu2(uint32_t v) { const float a = bf_lo(v), b = bf_hi(v); return pack_bf16(__fdividef(a, 1.f + __expf(-a)), __fdividef(b, 1.f + __expf(-b))); }
constexpr uint32_t ONE2 = 0x3f803f80u;

__device__ __forceinline__ void ldsm4(uint32_t (&r)[4], uint32_t a) { asm volatile("ldmatrix.sync.aligned.m8n8.x4.shared.b16 {%0,%1,%2,%3}, [%4];" : "=r"(r[0]), "=r"(r[1]), "=r"(r[2]), "=r"(r[3]) : "r"(a) : "memory"); }
__device__ __forceinline__ void ldsm4t(uint32_t (&r)[4], uint32_t a) { asm volatile("ldmatrix.sync.aligned.m8n8.x4.trans.shared.b16 {%0,%1,%2,%3}, [%4];" : "=r"(r[0]), "=r"(r[1]), "=r"(r[2]), "=r"(r[3]) : "r"(a) : "memory"); }
__device__ __forceinline__ void ldsm2t(uint32_t& r0, uint32_t& r1, uint32_t a) { asm volatile("ldmatrix.sync.aligned.m8n8.x2.trans.shared.b16 {%0,%1}, [%2];" : "=r"(r0), "=r"(r1) : "r"(a) : "memory"); }
__device__ __forceinline__ void stsm4t(uint32_t a, uint32_t r0, uint32_t r1, uint32_t r2, uint32_t r3) { asm volatile("stmatrix.sync.aligned.m8n8.x4.trans.shared.b16 [%0], {%1,%2,%3,%4};" ::"r"(a), "r"(r0), "r"(r1), "r"(r2), "r"(r3) : "memory"); }
__device__ __forceinline__ uint32_t movm(uint32_t a) { uint32_t d; asm volatile("movmatrix.sync.aligned.m8n8.trans.b16 %0, %1;" : "=r"(d) : "r"(a)); return d; }
__device__ __forceinline__ void mma16816(float (&d)[4], const uint32_t (&a)[4], uint32_t b0, uint32_t b1) {
  asm volatile("mma.sync.aligned.m16n8k16.row.col.f32.bf16.bf16.f32 {%0,%1,%2,%3}, {%4,%5,%6,%7}, {%8,%9}, {%0,%1,%2,%3};"
               : "+f"(d[0]), "+f"(d[1]), "+f"(d[2]), "+f"(d[3]) : "r"(a[0]), "r"(a[1]), "r"(a[2]), "r"(a[3]), "r"(b0), "r"(b1));
}
__device__ __forceinline__ void sts1(uint32_t a, uint32_t v) { asm volatile("st.shared.u32 [%0], %1;" ::"r"(a), "r"(v) : "memory"); }
__device__ __forceinline__ void sts2(uint32_t a, uint32_t x, uint32_t y) { asm volatile("st.shared.v2.u32 [%0], {%1,%2};" ::"r"(a), "r"(x), "r"(y) : "memory"); }
__device__ __forceinline__ void sts4(uint32_t a, uint4 v) { asm volatile("st.shared.v4.u32 [%0], {%1,%2,%3,%4};" ::"r"(a), "r"(v.x), "r"(v.y), "r"(v.z), "r"(v.w) : "memory"); }
__device__ __forceinline__ void sts2f(uint32_t a, float x, float y) { asm volatile("st.shared.v2.f32 [%0], {%1,%2};" ::"r"(a), "f"(x), "f"(y) : "memory"); }
__device__ __forceinline__ void sts4f(uint32_t a, float x, float y, float z, float w) { asm volatile("st.shared.v4.f32 [%0], {%1,%2,%3,%4};" ::"r"(a), "f"(x), "f"(y), "f"(z), "f"(w) : "memory"); }
__device__ __forceinline__ void stsf(uint32_t a, float v) { asm volatile("st.shared.f32 [%0], %1;" ::"r"(a), "f"(v) : "memory"); }
__device__ __forceinline__ uint32_t lds1(uint32_t a) { uint32_t v; asm volatile("ld.shared.u32 %0, [%1];" : "=r"(v) : "r"(a) : "memory"); return v; }
__device__ __forceinline__ float ldsf(uint32_t a) { float v; asm volatile("ld.shared.f32 %0, [%1];" : "=f"(v) : "r"(a) : "memory"); return v; }
__device__ __forceinline__ float2 ldsf2(uint32_t a) { float2 v; asm volatile("ld.shared.v2.f32 {%0,%1}, [%2];" : "=f"(v.x), "=f"(v.y) : "r"(a) : "memory"); return v; }
__device__ __forceinline__ float4 ldsf4(uint32_t a) { float4 v; asm volatile("ld.shared.v4.f32 {%0,%1,%2,%3}, [%4];" : "=f"(v.x), "=f"(v.y), "=f"(v.z), "=f"(v.w) : "r"(a) : "memory"); return v; }
__device__ __forceinline__ void lds4(uint32_t (&r)[4], uint32_t a) { asm volatile("ld.shared.v4.u32 {%0,%1,%2,%3}, [%4];" : "=r"(r[0]), "=r"(r[1]), "=r"(r[2]), "=r"(r[3]) : "r"(a) : "memory"); }

__device__ __forceinline__ void wg_fence() { asm volatile("wgmma.fence.sync.aligned;" ::: "memory"); }
__device__ __forceinline__ void wg_commit() { asm volatile("wgmma.commit_group.sync.aligned;" ::: "memory"); }
template <int N> __device__ __forceinline__ void wg_wait() { asm volatile("wgmma.wait_group.sync.aligned %0;" ::"n"(N) : "memory"); }
__host__ __device__ constexpr uint32_t desc_lo(uint32_t off) { return ((SB + off) >> 4) | 0x10000u; }
template <int TA, int ACC> __device__ __forceinline__ void wgmma_n16(float (&d)[8], uint32_t da, uint32_t db) {
  asm volatile("{\n.reg .b64 da, db;\nmov.b64 da, {%8, 0x40000040};\nmov.b64 db, {%9, 0x40000040};\n"
               "wgmma.mma_async.sync.aligned.m64n16k16.f32.bf16.bf16 {%0,%1,%2,%3,%4,%5,%6,%7}, da, db, %11, 1, 1, %10, 0;\n}"
               : "+f"(d[0]), "+f"(d[1]), "+f"(d[2]), "+f"(d[3]), "+f"(d[4]), "+f"(d[5]), "+f"(d[6]), "+f"(d[7])
               : "r"(da), "r"(db), "n"(TA), "n"(ACC));
}
__device__ __forceinline__ void wgmma_n16_ones(float (&d)[8], uint32_t one, uint32_t db) {
  asm volatile("{\n.reg .b64 db;\nmov.b64 db, {%9, 0x40000040};\n"
               "wgmma.mma_async.sync.aligned.m64n16k16.f32.bf16.bf16 {%0,%1,%2,%3,%4,%5,%6,%7}, {%8,%8,%8,%8}, db, 1, 1, 1, 0;\n}"
               : "+f"(d[0]), "+f"(d[1]), "+f"(d[2]), "+f"(d[3]), "+f"(d[4]), "+f"(d[5]), "+f"(d[6]), "+f"(d[7])
               : "r"(one), "r"(db));
}
__device__ __forceinline__ void acc_fence(float (&d)[8]) {
  asm volatile("" : "+f"(d[0]), "+f"(d[1]), "+f"(d[2]), "+f"(d[3]), "+f"(d[4]), "+f"(d[5]), "+f"(d[6]), "+f"(d[7]) :: "memory");
}

template <int N, int STRIDE> __device__ __forceinline__ void load_units(uint2 (&v)[N], const uint32_t* p) {
#pragma unroll
  for (int i = 0; i < N; i++) v[i] = ldg_u64(p + i * STRIDE);
}
template <int N, int STRIDE> __device__ __forceinline__ int check_units(uint2 (&v)[N], const uint32_t* p, int rb) {
  int it = 0;
  while (true) {
    uint32_t mn = v[0].y;
#pragma unroll
    for (int i = 1; i < N; i++) mn = min(mn, v[i].y);
    if (mn != 0) break;
    backoff(rb);
#pragma unroll
    for (int i = 0; i < N; i++) if (v[i].y == 0) v[i] = ldg_u64(p + i * STRIDE);
    if (++it > SPIN_LIMIT) __trap();
  }
  return it;
}
__device__ __forceinline__ void sum4_to_smem(const uint2 (&v)[4], uint32_t dst) {
  const float c0 = (bf_lo(v[0].x) + bf_lo(v[1].x)) + (bf_lo(v[2].x) + bf_lo(v[3].x));
  const float c1 = (bf_hi(v[0].x) + bf_hi(v[1].x)) + (bf_hi(v[2].x) + bf_hi(v[3].x));
  const float c2 = (bf_lo(v[0].y) + bf_lo(v[1].y)) + (bf_lo(v[2].y) + bf_lo(v[3].y));
  const float c3 = (bf_hi(v[0].y) + bf_hi(v[1].y)) + (bf_hi(v[2].y) + bf_hi(v[3].y));
  sts1(dst, pack_bf16(c0, c1));
  sts1(dst + 128, pack_bf16(c2, c3));
}
__device__ __forceinline__ void load_a_t(uint32_t (&a)[8][4], uint32_t wbase, int w, int lane) {
  const int mi = lane >> 3, r = lane & 7;
  const uint32_t base = wbase + (w >> 2) * 16384 + (8 * (mi >> 1) + r) * 128 + (((2 * (w & 3) + (mi & 1)) ^ r) << 4);
#pragma unroll
  for (int ks = 0; ks < 8; ks++) ldsm4t(a[ks], base + ks * 2048);
}
__device__ __forceinline__ void mma128(float (&d)[4], const uint32_t (&a)[8][4], const uint32_t (&b)[4][4]) {
  float e[4][4] = {{0.f, 0.f, 0.f, 0.f}, {0.f, 0.f, 0.f, 0.f}, {0.f, 0.f, 0.f, 0.f}, {0.f, 0.f, 0.f, 0.f}};
#pragma unroll
  for (int kk = 0; kk < 4; kk++) { mma16816(e[(2 * kk) & 3], a[2 * kk], b[kk][0], b[kk][1]); mma16816(e[(2 * kk + 1) & 3], a[2 * kk + 1], b[kk][2], b[kk][3]); }
#pragma unroll
  for (int i = 0; i < 4; i++) d[i] = (e[0][i] + e[1][i]) + (e[2][i] + e[3][i]);
}
template <int NP> __device__ __forceinline__ int sum_pieces(const uint32_t* p0, int g, int t, float& v0, float& v1, int rb) {
  constexpr int NL = NP / 8;
  uint32_t v[NL][4];
#pragma unroll
  for (int i = 0; i < NL; i++) { const uint4 x = ldg_2u64(p0 + i * 128); v[i][0] = x.x; v[i][1] = x.y; v[i][2] = x.z; v[i][3] = x.w; }
  int it = 0;
  while (true) {
    uint32_t mn = 0xffffffffu;
#pragma unroll
    for (int i = 0; i < NL; i++) mn = min(mn, min(v[i][1], v[i][3]));
    if (mn != 0) break;
    backoff(rb);
#pragma unroll
    for (int i = 0; i < NL; i++)
      if (v[i][1] == 0 || v[i][3] == 0) { const uint4 x = ldg_2u64(p0 + i * 128); v[i][0] = x.x; v[i][1] = x.y; v[i][2] = x.z; v[i][3] = x.w; }
    if (++it > SPIN_LIMIT) __trap();
  }
  __syncwarp();
  const uint32_t one = (g & 1) ? 0x3f800000u : 0x00003f80u;
  const uint32_t b0 = (g & 2) ? 0u : one, b1 = (g & 2) ? one : 0u;
  float d[4][4] = {{0.f, 0.f, 0.f, 0.f}, {0.f, 0.f, 0.f, 0.f}, {0.f, 0.f, 0.f, 0.f}, {0.f, 0.f, 0.f, 0.f}};
#pragma unroll
  for (int i = 0; i < NL; i++) mma16816(d[i & 3], v[i], b0, b1);
  const bool up = t & 2;
  const float x0 = up ? (d[0][2] + d[1][2]) + (d[2][2] + d[3][2]) : (d[0][0] + d[1][0]) + (d[2][0] + d[3][0]);
  const float x1 = up ? (d[0][3] + d[1][3]) + (d[2][3] + d[3][3]) : (d[0][1] + d[1][1]) + (d[2][1] + d[3][1]);
  v0 = x0 + __shfl_xor_sync(~0u, x0, 16);
  v1 = x1 + __shfl_xor_sync(~0u, x1, 16);
  return it;
}
template <typename F> __device__ __forceinline__ float reduce_g(const float (&x)[4], int lane, F f) {
  const bool u4 = lane & 16, u3 = lane & 8;
  const float a0 = f(u4 ? x[2] : x[0], __shfl_xor_sync(~0u, u4 ? x[0] : x[2], 16));
  const float a1 = f(u4 ? x[3] : x[1], __shfl_xor_sync(~0u, u4 ? x[1] : x[3], 16));
  const float b = f(u3 ? a1 : a0, __shfl_xor_sync(~0u, u3 ? a0 : a1, 8));
  return f(b, __shfl_xor_sync(~0u, b, 4));
}

__global__ void __launch_bounds__(NTHREADS, 1)
fused_decode_kernel(__nv_bfloat16* __restrict__ gout, Scratch* __restrict__ gs, const uint8_t* __restrict__ gwmod,
                    const uint8_t* __restrict__ gx, const uint8_t* __restrict__ gc, uint32_t* __restrict__ gin,
                    const __grid_constant__ Params P) {
  constexpr Tune T{};
  extern __shared__ __align__(1024) uint8_t smem_raw[];
  const uint32_t sb = (uint32_t)__cvta_generic_to_shared(smem_raw);
  const int tid = threadIdx.x, lane = tid & 31;
  const int w = __shfl_sync(0xffffffffu, tid >> 5, 0);
  const int cta = blockIdx.x;
  const uint32_t bars = sb + OFF_BARS;
  auto BAR = [&](int i) { return bars + 8 * i; };
  auto inbox = [&](int c, int k) { uint32_t v; asm volatile("ld.shared.u8 %0, [%1];" : "=r"(v) : "r"(sb + OFF_SEL + c) : "memory"); return gin + blk(c, k, v); };
  const int g = lane >> 2, t = lane & 3;
  const int hI = cta >> 2, jI = cta & 3;
  const int bs = cta >> 1, hh = cta & 1;

  CLK_DECL;
  CLK(0);
  if (w == 8) {
    CLK(7);
    const uint32_t t_entry = gtime32();
    CLK(8);
    if (lane == 0) {
      if ((sb & 0xffffff) != SB) __trap();
      mbar_init(BAR(BAR_WQ), 1); mbar_init(BAR(BAR_WQ + 1), 1); mbar_init(BAR(BAR_XC), 1); mbar_init(BAR(BAR_C), 1);
      asm volatile("fence.mbarrier_init.release.cluster;" ::: "memory");
      asm volatile("prefetch.tensormap [%0];" ::"l"(&P.wq) : "memory");
      mbar_expect(BAR(BAR_XC), 8192); mbar_expect(BAR(BAR_C), 8192); mbar_expect(BAR(BAR_WQ), 16384); mbar_expect(BAR(BAR_WQ + 1), 16384);
      CLK(9);
    }
    __syncwarp();
    asm volatile("barrier.cta.arrive.aligned 0, %0;" ::"n"(NTHREADS) : "memory");
    CLK(10);
    uint32_t tn = t_entry + T.PC_T0 + ((bs * 37) & 63) * T.PC_STAG / 64;
    const int h = hI, j = jI;
    if (lane == 0) {
      uint64_t pol; asm volatile("createpolicy.fractional.L2::evict_first.b64 %0, 1.0;" : "=l"(pol));
#pragma unroll
      for (int u = 0; u < 4; u++) {
        until_ns(tn + u * T.PC_P1);
        if (u == 0) CLK(11);
        tma2d(sb + OFF_WQ + u * 8192, &P.wq, 128 * h + 64 * (u >> 1), 128 * j + 64 * (u & 1), BAR(BAR_WQ + (u >> 1)), pol);
        if (u == T.PC_XC) {
#pragma unroll
          for (int i = 0; i < 4; i++) { const int o = ((i + cta) & 3) * 2048; bulk_ld(sb + OFF_XS + o, gx + o, 2048, BAR(BAR_XC)); }
        }
        if (u == T.PC_C) {
#pragma unroll
          for (int i = 0; i < 4; i++) { const int o = ((i + cta) & 3) * 2048; bulk_ld(sb + OFF_CS + o, gc + o, 2048, BAR(BAR_C)); }
        }
        if (u == 0) {
          CLK(1);
          asm volatile("prefetch.tensormap [%0];" ::"l"(&P.wuk) : "memory");
          asm volatile("prefetch.tensormap [%0];" ::"l"(&P.wm2) : "memory");
          asm volatile("prefetch.tensormap [%0];" ::"l"(&P.ckv2) : "memory");
        }
      }
    }
    __syncwarp();
    tn += 4 * T.PC_P1;
    bar_sync(5, 64);
    if (lane == 0) {
      uint64_t pol; asm volatile("createpolicy.fractional.L2::evict_first.b64 %0, 1.0;" : "=l"(pol));
#pragma unroll
      for (int u = 0; u < 4; u++) {
        if ((u & 1) == (T.PC_W > 3) && T.PC_NW) mbar_wait(BAR(BAR_WQ + (u >> 1)));
        slot(tn, T.PC_SL);
        tma5d(sb + OFF_WUK + u * 8192, &P.wuk, 128 * h + 64 * (u >> 1), 0, 0, 0, 8 * j + 4 * (u & 1), BAR(BAR_WUK + (u >> 1)), pol);
        tn += T.PC_P1;
      }
#pragma unroll
      for (int u = 0; u < 2; u++) {
        if (u == (T.PC_W > 3) && T.PC_NW) mbar_wait(BAR(BAR_WUK));
        slot(tn, T.PC_SL);
        tma2d_nohint(sb + OFF_WM2 + u * 8192, &P.wm2, 1024 + 16 * cta, 256 * u, BAR(BAR_WM2));
        tn += T.PC_P1;
      }
      const int row0 = (bs >> 3) * 4096 + (bs & 7) * 64;
      uint32_t dst = sb + OFF_RING;
      const int p2 = T.PC_P2 + (32 - ((bs * 37) & 63)) * T.PC_DS / 1024;
#pragma unroll 1
      for (int n = 0; n < 31; n++) {
        if (n >= 4 && (n < 12 || (n & 3) == 0)) mbar_wait(BAR(n >= 12 ? BAR_EMPTY + (n >> 2) - 3 : n == 7 ? BAR_P0BD : (n == 8 || n == 9) ? BAR_P2D : BAR_P1D));
        if (n < T.PC_NW) {
          if (n >= T.PC_W) mbar_wait(BAR(BAR_FULL + n - T.PC_W));
          else if ((n & 1) == (T.PC_W > 3)) mbar_wait(BAR(n < 2 ? BAR_WUK + 1 : BAR_WM2));
        }
        slot(tn, T.PC_SL);
        tma3d(dst, &P.ckv2, 0, row0 + (n >> 2) * 512, 2 * (n & 3), BAR(BAR_FULL + n), pol);
        dst = (n == 11 || n == 23) ? sb + OFF_RING : dst + 16384;
        tn += n >= 15 ? p2 : T.PC_P2;
        if (n == 4) CLK(2);
        if (n == 12) CLK(3);
        if (n == 20) CLK(4);
        if (n == 28) CLK(5);
        if (n == 24) {
          asm volatile("prefetch.tensormap [%0];" ::"l"(&P.ckv1) : "memory");
          asm volatile("prefetch.tensormap [%0];" ::"l"(&P.wuv) : "memory");
          asm volatile("prefetch.tensormap [%0];" ::"l"(&P.wo) : "memory");
          asm volatile("prefetch.tensormap [%0];" ::"l"(&P.w1) : "memory");
          asm volatile("prefetch.tensormap [%0];" ::"l"(&P.w2) : "memory");
        }
      }
      slot(tn, T.PC_SL);
      tma3d(dst, &P.ckv1, 0, row0 + 7 * 512, 6, BAR(BAR_LAST + 3), pol);
      tma3d(dst + 8192, &P.ckv1, 0, row0 + 7 * 512, 7, BAR(BAR_LAST + 4), pol);
      tn += T.PC_P2;
      CLK(6);
      auto unit = [&](int u) {
        if (u < 4) tma5d(sb + OFF_WUV + u * 8192, &P.wuv, 128 * h + 64 * (u >> 1), 0, 4 * (j >> 1), 0, 2 * (j & 1) + (u & 1), BAR(BAR_WUV + (u >> 1)), pol);
        else if (u < 8) tma2d(sb + OFF_WO + (u - 4) * 8192, &P.wo, 128 * j + 64 * ((u - 4) >> 1), 128 * h + 64 * (u & 1), BAR(BAR_WO + ((u - 4) >> 1)), pol);
        else if (u < 10) { if (cta < NFF) tma2d_nohint(sb + OFF_W1 + (u - 8) * 16384, &P.w1, 32 * bs, 256 * (u - 8), BAR(BAR_W1)); }
        else if (cta < NFF) tma3d(sb + OFF_W2 + (u - 10) * 8192, &P.w2, 0, 32 * bs, 4 * hh + 2 * (u - 10), BAR(BAR_W2), pol);
      };
      mbar_wait(BAR(BAR_EMPTY + 5));
      if (T.PW_A >= 0) { mbar_wait(BAR(BAR_LAST + T.PW_A)); tn = gtime32(); }
      tn += T.PW_0 + ((cta * 37) & 127) * T.PW_ST / 128;
#pragma unroll
      for (int u = 0; u < 12; u++) {
        if (u == 8) mbar_wait(BAR(BAR_EMPTY + 6));
        until_ns(tn);
        unit(WSWAP && u >= 8 ? (u ^ 2) : u);
        tn += u < 3 ? T.PW_UV : u == 3 ? T.PW_G : u < 7 ? T.PW_O : u == 7 ? T.PW_G2 : u == 9 ? T.PW_G3 : T.PW_F;
      }
      CLK_DUMP();
    }
    return;
  }

  if (w == 9) {
    if (lane == 0) {
#pragma unroll
      for (int i = 0; i < NBARS; i++) mbar_init(BAR(i), i >= BAR_P1D ? 8 : i >= BAR_EMPTY ? 4 : 1);
      asm volatile("fence.mbarrier_init.release.cluster;" ::: "memory");
    }
    __syncwarp();
    mbar_expect(BAR(lane), lane == BAR_LAST + 3 ? 8192 : 16384);
    if (lane < BAR_ALLCLR - 32) mbar_expect(BAR(32 + lane), lane == 0 ? 8192 : lane == BAR_W1 - 32 ? 32768 : 16384);
    CLK(9);
    asm volatile("barrier.cta.arrive.aligned 5, 64;" ::: "memory");
    asm volatile("barrier.cta.arrive.aligned 0, %0;" ::"n"(NTHREADS) : "memory");
  }
  const uint32_t epoch = ldg_rlx1(&gs->epoch);

  if (w == 9) {
    const int wd = 2 * (t & 1) + (t >> 1), bo = 2 * (g & 3) + (wd >> 1), mo = 16 * hI + 2 * jI + 8 * (wd & 1);
    const uint32_t xo = ldg_nc1(gx + (bo * 512 + mo) * 2);
    const int par = epoch & 1;
    const uint32_t t0 = gtime32();
    const uint4 z = make_uint4(0, 0, 0, 0);
    uint32_t sel;
    {
      uint32_t* pa = gin + blk(cta, 5, 0) + 960;
      uint32_t* pb = gin + blk(cta, 5, 1) + 960;
      until_ns(t0 + T.PR_T0);
      if (lane < 4) stg4(reinterpret_cast<uint4*>(lane & 2 ? pa : pb) + (lane & 1), z);
      uint32_t ma = 0xffffffffu, mb = 0xffffffffu;
      if (lane == 0) {
#pragma unroll 1
        for (int i = 0; i < 2 * T.PR_N; i++) {
          const uint32_t c0 = clk32();
          uint32_t v;
          asm volatile("atom.relaxed.gpu.global.add.u32 %0, [%1], 1;" : "=r"(v) : "l"(i & 1 ? pb : pa) : "memory");
          if (v == 0xffffffffu) __trap();
          const uint32_t d = clk32() - c0;
          if (i & 1) mb = min(mb, d); else ma = min(ma, d);
        }
      }
      sel = __shfl_sync(~0u, (uint32_t)(mb < ma), 0);
      if (T.LOC == 1) sel ^= 1;
      if (T.LOC == 2) sel ^= (cta ^ (cta >> 3)) & 1;
      if (lane < 2) stg4(reinterpret_cast<uint4*>(gin + blk(cta, 5, 1) + 896) + lane, make_uint4(sel, sel, sel, sel));
    }
    until_ns(t0 + T.CLR_T0);
    {
      const int nb = (cta & 7) == 0 ? 16 : 12;
#pragma unroll 1
      for (int i0 = 0; i0 < nb; i0++) {
        uint4* q = reinterpret_cast<uint4*>(gin + blk(cta, i0 >> 1, sel) + (i0 & 1) * 512) + lane;
#pragma unroll
        for (int i = 0; i < 4; i++) if (i0 != 11 || i < 3) stg4(q + i * 32, z);
        backoff(T.CLR_CLK);
      }
      if (jI == 1) stg4(reinterpret_cast<uint4*>(gin + blk(cta, 6, sel)) + lane, z);
      if (lane < 2) stg4(reinterpret_cast<uint4*>(gin + blk(cta, 5, sel) + 928) + lane, z);
      CLK(1);
      asm volatile("fence.acq_rel.gpu;" ::: "memory");
      CLK(2);
      __syncwarp();
      if (lane < NSYNC) asm volatile("red.relaxed.gpu.global.add.u32 [%0], 1;" ::"l"(&gs->sync[lane][0]) : "memory");
#pragma unroll
      for (int i = 0; i < 4; i++) stg4(reinterpret_cast<uint4*>(gs->QP[par ^ 1] + cta * 512) + i * 32 + lane, z);
      backoff(T.CLR_CLK);
#pragma unroll
      for (int i = 0; i < 4; i++) stg4(reinterpret_cast<uint4*>(gs->QX[par ^ 1] + cta * 512) + i * 32 + lane, z);
      stg4(reinterpret_cast<uint4*>(gs->MOD1[par ^ 1] + cta * 128) + lane, z);
      if (lane < 16) stg4(reinterpret_cast<uint4*>(gs->MOD2[par ^ 1] + cta * 64) + lane, z);
      if (lane == 0) {
        const uint32_t target = (epoch + 1) * NCTA;
        uint32_t c; int it = 0;
        do { backoff(T.CLR_CLK); asm volatile("ld.acquire.gpu.global.u32 %0, [%1];" : "=r"(c) : "l"(&gs->sync[cta % NSYNC][0]) : "memory"); if (++it > SPIN_LIMIT) __trap(); } while ((int)(c - target) < 0);
      }
      __syncwarp();
      uint32_t sv = 0;
#pragma unroll
      for (int i = 0; i < 4; i++) sv |= ldg_rlx1(gin + blk(4 * lane + i, 5, 1) + 896) << (8 * i);
      sts1(sb + OFF_SEL + lane * 4, sv);
      __syncwarp();
      if (lane == 0) mbar_arrive(BAR(BAR_ALLCLR));
    }
    CLK(3);
    uint2 gg[2];
    {
      const uint32_t* pg = gs->MOD2[par] + cta * 16 + bo * 2;
      load_units<2, 3 * 2048>(gg, pg);
      check_units<2, 3 * 2048>(gg, pg, T.RB);
    }
    const uint32_t ga2 = (wd & 1) ? gg[0].y : gg[0].x, gb2 = (wd & 1) ? gg[1].y : gg[1].x;
    uint32_t anchor;
    {
      uint32_t* const po = inbox(NTS * (lane & (128 / NTS - 1)), 5) + 928;
      const uint32_t* const pi = inbox(cta & ~(NTS - 1), 5) + 928;
      mbar_wait(BAR(BAR_LAST + T.TS_P));
      unsigned long long now; asm volatile("mov.u64 %0, %%globaltimer;" : "=l"(now));
      if (lane < 128 / NTS) {
        asm volatile("red.relaxed.gpu.global.max.u64 [%0], %1;" ::"l"(po + 2), "l"(now) : "memory");
        asm volatile("red.relaxed.gpu.global.add.u32 [%0], 1;" ::"l"(po + 1) : "memory");
      }
      backoff(T.D_TS);
      uint4 v; int it = 0;
      do { v = ldg_2u64(pi); if (++it > SPIN_LIMIT) __trap(); } while (v.y != NCTA);
      const int age = min(max((int)(gtime32() - v.z), 0), 4000);
      anchor = clk32() - age * 7 / 4 + T.TS_O;
      if (lane == 0) { sts1(sb + OFF_TS, anchor); mbar_arrive(BAR(BAR_TS)); }
      CLK(10);
    }
    {
      const uint32_t* pm = pin(inbox(4 * hI + 1, 6) + lane * 4);
      wait_clk(anchor, T.A_M);
      uint4 ml = ldg_2u64(pm);
      int it = 0;
      while (ml.y == 0 || ml.w == 0) { ml = ldg_2u64(pm); if (++it > SPIN_LIMIT) __trap(); }
      __syncwarp();
      ITS(2, it);
      float M = fmaxf(__uint_as_float(ml.x), __uint_as_float(ml.z));
      M = fmaxf(M, __shfl_xor_sync(~0u, M, 1)); M = fmaxf(M, __shfl_xor_sync(~0u, M, 2));
      const float e0 = ex2(__uint_as_float(ml.x) - M), e1 = ex2(__uint_as_float(ml.z) - M);
      float l = e0 * __uint_as_float(ml.y) + e1 * __uint_as_float(ml.w);
      l += __shfl_xor_sync(~0u, l, 1); l += __shfl_xor_sync(~0u, l, 2);
      const float inv = __fdividef(1.f, l);
      sts2f(sb + OFF_WV + lane * 8, e0 * inv, e1 * inv);
      __syncwarp();
      if (lane == 0) mbar_arrive(BAR(BAR_WV));
      CLK(11);
    }
    float v0, v1;
    uint32_t* const x3o = pin(inbox(8 * g, 6 + (cta >> 6)) + (cta & 63) * 16 + t * 4);
    uint32_t* const x3p = pin(inbox(64 + 8 * g, 6 + (cta >> 6)) + (cta & 63) * 16 + t * 4);
    uint32_t* const fo = pin(reinterpret_cast<uint32_t*>(gout) + (bo * 512 + mo) / 2);
    const int po = (4 * (g >> 2) + t) * 16 + (g & 3) * 4;
    const uint32_t* const p3 = pin(gin + blk(cta, 4, sel) + po);
    const uint32_t* const p4 = pin(gin + blk(cta, 5, sel) + po);
    mbar_wait(BAR(BAR_P5D));
    backoff(T.D_X3A);
    wait_clk(anchor, T.A_X3A);
    CLK(4);
    { const int it = sum_pieces<32>(p3, g, t, v0, v1, T.RB); ITS(0, it); }
    CLK(5);
    const uint32_t x2w = pack_bf16(bf_lo(xo) + bf_lo(ga2) * v0, bf_hi(xo) + bf_hi(ga2) * v1);
    {
      const int src = 4 * (lane & 3);
      uint4 o;
      o.x = __shfl_sync(~0u, x2w, src); o.y = __shfl_sync(~0u, x2w, src + 2); o.z = __shfl_sync(~0u, x2w, src + 1); o.w = __shfl_sync(~0u, x2w, src + 3);
      stg_2u64(x3o, o);
      if (g < NFF / 8 - 8) stg_2u64(x3p, o);
    }
    CLK(6);
    if (cta < NFF) { mbar_wait(BAR(BAR_P7D)); backoff(T.D_FIN); } else backoff(T.D_FIN2);
    CLK(7);
    { const int it = sum_pieces<NFG>(p4, g, t, v0, v1, T.RB); ITS(1, it); }
    if (g < 4) *fo = pack_bf16(bf_lo(x2w) + bf_lo(gb2) * v0, bf_hi(x2w) + bf_hi(gb2) * v1);
    CLK(8);
    CLK_DUMP();
    if (cta == 0 && lane == 0) stg1(&gs->epoch, epoch + 1);
    return;
  }

  const int wg = w >> 2, wq = w & 3;
  uint32_t tstore;
  {
    const uint8_t* pw = gwmod + (size_t)(128 * jI + 16 * w + 4 * (g >> 1) + (g & 1)) * 6144 + 64 * hI + 16 * t;
    const uint4 w0 = ldg_nc4(pw), w1 = ldg_nc4(pw + 2 * 6144);
    const uint2 cc = ldg_nc2(gc + g * 1024 + 256 * jI + 32 * w + 8 * t);
    CLK(40);
    const uint32_t a[4] = {silu2(cc.x), 0u, silu2(cc.y), 0u};
    float d[4][4] = {{0.f, 0.f, 0.f, 0.f}, {0.f, 0.f, 0.f, 0.f}, {0.f, 0.f, 0.f, 0.f}, {0.f, 0.f, 0.f, 0.f}};
    mma16816(d[0], a, movm(w0.x), movm(w1.x)); mma16816(d[1], a, movm(w0.y), movm(w1.y));
    mma16816(d[2], a, movm(w0.z), movm(w1.z)); mma16816(d[3], a, movm(w0.w), movm(w1.w));
    CLK(1);
    sts4f(sb + OFF_P0S + w * 1088 + lane * 16, d[0][0], d[0][1], d[1][0], d[1][1]);
    sts4f(sb + OFF_P0S + w * 1088 + 544 + lane * 16, d[2][0], d[2][1], d[3][0], d[3][1]);
    bar_sync(0, NTHREADS);
    if (tid < 128) {
      const uint32_t src = sb + OFF_P0S + ((tid >> 2) & 1) * 544 + (((tid >> 3) & 7) * 4 + 2 * (tid >> 6) + (tid & 1)) * 16 + ((tid >> 1) & 1) * 8;
      float2 v[8];
#pragma unroll
      for (int i = 0; i < 8; i++) v[i] = ldsf2(src + i * 1088);
      const float ax = ((v[0].x + v[1].x) + (v[2].x + v[3].x)) + ((v[4].x + v[5].x) + (v[6].x + v[7].x));
      const float ay = ((v[0].y + v[1].y) + (v[2].y + v[3].y)) + ((v[4].y + v[5].y) + (v[6].y + v[7].y));
      stg1(gs->MOD1[epoch & 1] + jI * 4096 + hI * 128 + tid, nz(pack_bf16(ax, ay)));
    }
    tstore = clk32();
  }
  CLK(2);
  const int par = epoch & 1;
  uint32_t cf[4][4];
  mbar_wait(BAR(BAR_XC));
  {
    uint32_t u[2][4];
    lds4(u[0], sb + OFF_XS + w * 1024 + lane * 16); lds4(u[1], sb + OFF_XS + w * 1024 + 512 + lane * 16);
    float v[16];
#pragma unroll
    for (int i = 0; i < 8; i++) { v[2 * i] = bf_lo(u[i >> 2][i & 3]); v[2 * i + 1] = bf_hi(u[i >> 2][i & 3]); }
    float s = 0.f;
#pragma unroll
    for (int i = 0; i < 16; i++) s += v[i];
#pragma unroll
    for (int o = 16; o; o >>= 1) s += __shfl_xor_sync(~0u, s, o);
    const float mu = s * (1.f / 512.f);
    float q = 0.f;
#pragma unroll
    for (int i = 0; i < 16; i++) { v[i] -= mu; q += v[i] * v[i]; }
#pragma unroll
    for (int o = 16; o; o >>= 1) q += __shfl_xor_sync(~0u, q, o);
    const float rs = rsqrtf(q * (1.f / 512.f) + 1e-5f);
    const bool hi = jI & 2;
    uint32_t o[4];
#pragma unroll
    for (int i = 0; i < 4; i++) o[i] = pack_bf16((hi ? v[8 + 2 * i] : v[2 * i]) * rs, (hi ? v[9 + 2 * i] : v[2 * i + 1]) * rs);
    if ((lane >> 4) == (jI & 1)) sts4(sb + OFF_XN + w * 272 + (lane & 15) * 16, make_uint4(o[0], o[1], o[2], o[3]));
  }
  CLK(3);
  uint32_t aw[8][4];
  {
    const uint32_t* pm = pin(gs->MOD1[par] + (8 * jI + w) * 64 + lane * 2);
    uint32_t* const qpo = pin(gs->QP[par] + (cta * 256 + tid) * 2);
    wait_clk(tstore, T.D_MOD);
    CLK(4);
    uint2 v[8];
    load_units<8, 2048>(v, pm);
    cbar();
    const uint32_t xn0 = lds1(sb + OFF_XN + g * 272 + w * 32 + t * 4), xn1 = lds1(sb + OFF_XN + g * 272 + w * 32 + 16 + t * 4);
    const bool early = __all_sync(~0u, mbar_test(BAR(BAR_WQ + wg)));
    if (early) load_a_t(aw, sb + OFF_WQ, w, lane);
    int it = 0;
    while (true) {
      uint32_t mn = 0xffffffffu;
#pragma unroll
      for (int i = 0; i < 8; i++) mn = min(mn, min(v[i].x, v[i].y));
      if (mn != 0) break;
#pragma unroll
      for (int i = 0; i < 8; i++) if (v[i].x == 0 || v[i].y == 0) v[i] = ldg_u64(pm + i * 2048);
      if (++it > SPIN_LIMIT) __trap();
    }
    CLK(5);
    ITS(0, it);
    float sc[2][4];
#pragma unroll
    for (int i = 0; i < 2; i++) {
      sc[i][0] = (bf_lo(v[i].x) + bf_lo(v[2 + i].x)) + (bf_lo(v[4 + i].x) + bf_lo(v[6 + i].x));
      sc[i][1] = (bf_hi(v[i].x) + bf_hi(v[2 + i].x)) + (bf_hi(v[4 + i].x) + bf_hi(v[6 + i].x));
      sc[i][2] = (bf_lo(v[i].y) + bf_lo(v[2 + i].y)) + (bf_lo(v[4 + i].y) + bf_lo(v[6 + i].y));
      sc[i][3] = (bf_hi(v[i].y) + bf_hi(v[2 + i].y)) + (bf_hi(v[4 + i].y) + bf_hi(v[6 + i].y));
    }
    sts2(sb + OFF_BS1 + (w >> 1) * 512 + lane * 16 + (w & 1) * 8,
         pack_bf16(bf_lo(xn0) * (1.f + sc[1][0]) + sc[0][0], bf_hi(xn0) * (1.f + sc[1][1]) + sc[0][1]),
         pack_bf16(bf_lo(xn1) * (1.f + sc[1][2]) + sc[0][2], bf_hi(xn1) * (1.f + sc[1][3]) + sc[0][3]));
    if (!early) { mbar_wait(BAR(BAR_WQ + wg)); load_a_t(aw, sb + OFF_WQ, w, lane); }
    CLK(6);
    cbar();
    uint32_t b[4][4];
#pragma unroll
    for (int kk = 0; kk < 4; kk++) lds4(b[kk], sb + OFF_BS1 + kk * 512 + lane * 16);
    float d[4];
    mma128(d, aw, b);
    stg_u64(qpo, pack_bf16(d[0], d[1]), pack_bf16(d[2], d[3]));
    tstore = clk32();
    CLK(7);
    if (wg) {
      mbar_wait(BAR(BAR_C));
#pragma unroll
      for (int i = 0; i < 4; i++) lds4(cf[i], sb + OFF_CS + g * 1024 + wq * 256 + i * 64 + t * 16);
#pragma unroll
      for (int i = 0; i < 16; i++) cf[i >> 2][i & 3] = silu2(cf[i >> 2][i & 3]);
    }
    __syncwarp();
    if (lane == 0) mbar_arrive(BAR(BAR_P1D));
  }
  {
    const uint32_t* pq = pin(gs->QP[par] + (hI * 4 * 256 + tid) * 2);
    uint32_t* const qxo = pin(gs->QX[par] + (g * 32 + hI) * 256 + 64 * jI + 8 * w + 2 * t);
    uint2 v[4];
    wait_clk(tstore, T.D_QP);
    CLK(8);
    load_units<4, 512>(v, pq);
    const uint32_t abase = sb + OFF_WUK + (16 * w + (lane & 15)) * 128;
    auto load_half = [&](int hf) {
#pragma unroll
      for (int ks = 0; ks < 4; ks++) ldsm4(aw[4 * hf + ks], abase + hf * 16384 + (((2 * ks + (lane >> 4)) ^ (lane & 7)) << 4));
    };
    mbar_wait(BAR(BAR_WUK));
    load_half(0);
    const bool early = __all_sync(~0u, mbar_test(BAR(BAR_WUK + 1)));
    if (early) load_half(1);
    const int it = check_units<4, 512>(v, pq, T.RB);
    CLK(9);
    ITS(1, it);
    sum4_to_smem(v, sb + OFF_BS2 + (16 * w + g) * 16 + t * 4);
    if (!early) { mbar_wait(BAR(BAR_WUK + 1)); load_half(1); }
    CLK(10);
    cbar();
    uint32_t b[4][4];
#pragma unroll
    for (int kk = 0; kk < 4; kk++) ldsm4t(b[kk], sb + OFF_BS2 + (32 * kk + lane) * 16);
    float d[4];
    mma128(d, aw, b);
    const float sc = 0.08838834764831845f * 1.4426950408889634f;
    stg_u64(qxo, movm(pack_bf16(d[0] * sc, d[1] * sc)), movm(pack_bf16(d[2] * sc, d[3] * sc)));
    tstore = clk32();
    CLK(11);
    if (lane == 0) mbar_arrive(BAR(BAR_P2D));
  }
  if (wg) {
    const int mi = lane >> 3, r = lane & 7;
    const uint32_t a0 = sb + OFF_WM2 + (8 * (r >> 1) + (r & 1) + 2 * (mi >> 1)) * 32 + (mi & 1) * 16;
    mbar_wait(BAR(BAR_WM2));
#pragma unroll
    for (int s = 0; s < 8; s++) ldsm4t(aw[s], a0 + (128 * wq + 32 * (s >> 1) + 4 * (s & 1)) * 32);
    float d[4];
    mma128(d, aw, cf);
    sts4f(sb + OFF_P0B + (tid - 128) * 16, d[0], d[1], d[2], d[3]);
    if (lane == 0) mbar_arrive(BAR(BAR_P0BD));
    bar_sync(3, 128);
    if (w == 4) {
      float4 v[4];
#pragma unroll
      for (int i = 0; i < 4; i++) v[i] = ldsf4(sb + OFF_P0B + (i * 32 + lane) * 16);
      stg_u64(gs->MOD2[par] + cta * 64 + t * 16 + g * 2, movm(pack_bf16((v[0].x + v[1].x) + (v[2].x + v[3].x), (v[0].y + v[1].y) + (v[2].y + v[3].y))),
              movm(pack_bf16((v[0].z + v[1].z) + (v[2].z + v[3].z), (v[0].w + v[1].w) + (v[2].w + v[3].w))));
    }
    CLK(15);
  }
  {
    const uint32_t* qx = pin(gs->QX[par] + ((bs >> 3) * 32 + 16 * hh) * 256 + tid * 4);
    const int ch = tid & 63, h0 = tid >> 6;
    const uint32_t dst = sb + OFF_Q + (ch >> 3) * 2048 + h0 * 128;
    wait_clk(tstore, T.D_QX);
    CLK(12);
    uint4 v[4];
#pragma unroll
    for (int i = 0; i < 4; i++) v[i] = ldg_2u64(qx + i * 1024);
    int it = 0;
    while (true) {
      uint32_t mn = 0xffffffffu;
#pragma unroll
      for (int i = 0; i < 4; i++) mn = min(mn, min(v[i].y, v[i].w));
      if (mn != 0) break;
#pragma unroll
      for (int i = 0; i < 4; i++) if (v[i].y == 0 || v[i].w == 0) v[i] = ldg_2u64(qx + i * 1024);
      if (++it > SPIN_LIMIT) __trap();
    }
    CLK(13);
    ITS(2, it);
#pragma unroll
    for (int i = 0; i < 4; i++) sts4(dst + i * 512 + (((ch & 7) ^ ((4 * i + h0) & 7)) << 4), v[i]);
    asm volatile("fence.proxy.async.shared::cta;" ::: "memory");
    CLK(14);
    cbar();
  }

  uint2 cbf[4], sbf[4];
  const uint32_t* const pcb = gs->MOD2[par] + 2048 + (16 * w + t) * 16 + g * 2;
  uint32_t thand, anchor;
  if (wg == 0) {
    float mh[4];
    float L[8];
#pragma unroll
    for (int i = 0; i < 4; i++) { L[2 * i] = L[2 * i + 1] = 0.f; mh[i] = -INFINITY; }
    constexpr uint32_t dq = desc_lo(OFF_Q);
    const uint32_t ptw = sb + OFF_PT + (8 * (lane >> 4) + (lane & 7)) * 128 + (((2 * wq + ((lane >> 3) & 1)) ^ (lane & 7)) << 4);
    float S[8];
    auto softmax = [&](int tl) {
      auto write_p = [&](const float (&x)[8]) {
        float p[8];
#pragma unroll
        for (int i = 0; i < 8; i++) p[i] = ex2(x[i]);
        stsm4t(ptw + (tl & 1) * 2048, pack_bf16(p[0], p[1]), pack_bf16(p[2], p[3]), pack_bf16(p[4], p[5]), pack_bf16(p[6], p[7]));
        asm volatile("fence.proxy.async.shared::cta;" ::: "memory");
      };
      float x[8];
#pragma unroll
      for (int i = 0; i < 8; i++) x[i] = S[i] - mh[2 * (i >> 2) + (i & 1)];
      if (tl) write_p(x);
      const float ex = fmaxf(fmaxf(fmaxf(x[0], x[1]), fmaxf(x[2], x[3])), fmaxf(fmaxf(x[4], x[5]), fmaxf(x[6], x[7])));
      if (tl == 0 || bar_over(ex)) {
        float mx[4];
#pragma unroll
        for (int i = 0; i < 4; i++) mx[i] = fmaxf(S[4 * (i >> 1) + (i & 1)], S[4 * (i >> 1) + 2 + (i & 1)]);
        const float a = reduce_g(mx, lane, [](float u, float v) { return fmaxf(u, v); });
        stsf(sb + OFF_RED + wq * 64 + (8 * (lane >> 4) + 2 * t + ((lane >> 3) & 1)) * 4, a);
        bar_sync(2, 128);
#pragma unroll
        for (int jn = 0; jn < 2; jn++) {
          float m0 = mh[2 * jn], m1 = mh[2 * jn + 1];
#pragma unroll
          for (int i = 0; i < 4; i++) { const float2 v = ldsf2(sb + OFF_RED + i * 64 + (8 * jn + 2 * t) * 4); m0 = fmaxf(m0, v.x); m1 = fmaxf(m1, v.y); }
          const float a0 = ex2(mh[2 * jn] - m0), a1 = ex2(mh[2 * jn + 1] - m1);
          mh[2 * jn] = m0; mh[2 * jn + 1] = m1;
          L[4 * jn] *= a0; L[4 * jn + 1] *= a1; L[4 * jn + 2] *= a0; L[4 * jn + 3] *= a1;
          if (tid < 4) sts2f(sb + OFF_ALPHA + (8 * jn + 2 * t) * 4, a0, a1);
        }
#pragma unroll
        for (int i = 0; i < 8; i++) x[i] = S[i] - mh[2 * (i >> 2) + (i & 1)];
        write_p(x);
        cbar();
      }
      const uint32_t dpt = __shfl_sync(~0u, desc_lo(OFF_PT) + (tl & 1) * 128, 0);
      wg_fence();
#pragma unroll
      for (int ks = 0; ks < 4; ks++) wgmma_n16_ones(L, ONE2, dpt + ks * 2);
      wg_commit();
    };
    uint32_t da = desc_lo(OFF_RING);
#pragma unroll 1
    for (int tl = 0; tl < 7; tl++) {
      uint32_t ok = 0;
#pragma unroll
      for (int u = 0; u < 4; u++) ok += mbar_test(BAR(BAR_FULL + 4 * tl + u));
      ok = __reduce_min_sync(~0u, ok);
      const uint32_t du = __shfl_sync(~0u, da, 0);
#pragma unroll
      for (int u = 0; u < 4; u++) {
        if (ok != 4) mbar_wait(BAR(BAR_FULL + 4 * tl + u));
        wg_fence();
#pragma unroll
        for (int k = 0; k < 8; k++) {
          const int i = 8 * u + k;
          if (i == 0) wgmma_n16<0, 0>(S, du, dq); else wgmma_n16<0, 1>(S, du + (i >> 2) * 512 + (i & 3) * 2, dq + (i >> 2) * 128 + (i & 3) * 2);
        }
        wg_commit();
      }
      wg_wait<0>();
      acc_fence(S); acc_fence(L);
      if (tl == 0) CLK(15);
      if (tl == 1) CLK(17);
      softmax(tl);
      if (tl == 0) CLK(16);
      if (tl == 1) CLK(18);
      if (tl == 3) CLK(19);
      if (tl == 6) CLK(20);
      da = (tl == 2 || tl == 5) ? da - 8192 : da + 4096;
    }
    if (cta < NFF) { load_units<4, 64>(sbf, pcb); load_units<4, 64>(cbf, pcb + 2048); }
    mbar_wait(BAR(BAR_ALLCLR));
    uint32_t* const mlo = pin(inbox(4 * (16 * hh + 4 * (g & 2) + 2 * t + (g & 1)) + 1, 6) + bs * 2);
#pragma unroll
    for (int i = 0; i < 32; i++) {
      if (i == 0 || i == 8 || i == 16 || i == 24 || i == 28) {
        if (i) wg_commit();
        mbar_wait(BAR(BAR_LAST + (i == 28 ? 4 : i >> 3)));
        if (i == 28) CLK(21);
        wg_fence();
      }
      if (i == 0) wgmma_n16<0, 0>(S, da, dq); else wgmma_n16<0, 1>(S, da + (i >> 2) * 512 + (i & 3) * 2, dq + (i >> 2) * 128 + (i & 3) * 2);
    }
    wg_commit();
    wg_wait<0>();
    acc_fence(S); acc_fence(L);
    CLK(22);
    softmax(7);
    CLK(23);
    thand = clk32();
    wg_wait<0>();
    acc_fence(L);
    if (tid < 16) stg_u64(mlo, __float_as_uint(g & 2 ? (g & 1 ? mh[3] : mh[2]) : (g & 1 ? mh[1] : mh[0])), __float_as_uint(g & 2 ? (g & 1 ? L[5] : L[4]) : (g & 1 ? L[1] : L[0])));
    CLK(24);
  } else {
    float O[8][8];
#pragma unroll
    for (int i = 0; i < 8; i++)
#pragma unroll
      for (int k = 0; k < 8; k++) O[i][k] = 0.f;
    constexpr uint32_t dp = desc_lo(OFF_PT);
    auto handover = [&](int tl) {
      if (tl == 0) { cbar(); return; }
      if (bar_over(0.f)) {
        cbar();
#pragma unroll
        for (int jn = 0; jn < 2; jn++) {
          const float2 a = ldsf2(sb + OFF_ALPHA + (8 * jn + 2 * t) * 4);
#pragma unroll
          for (int mb = 0; mb < 8; mb++) { O[mb][4 * jn] *= a.x; O[mb][4 * jn + 1] *= a.y; O[mb][4 * jn + 2] *= a.x; O[mb][4 * jn + 3] *= a.y; }
        }
      }
    };
    uint32_t da = desc_lo(OFF_RING);
#pragma unroll 1
    for (int tl = 0; tl < 7; tl++) {
      handover(tl);
      const uint32_t dpt = dp + (tl & 1) * 128;
      wg_fence();
#pragma unroll
      for (int i = 0; i < 32; i++) wgmma_n16<1, 1>(O[i >> 2], da + (i >> 2) * 512 + (i & 3) * 128, dpt + (i & 3) * 2);
      wg_commit();
      wg_wait<0>();
#pragma unroll
      for (int mb = 0; mb < 8; mb++) acc_fence(O[mb]);
      if (lane == 0) mbar_arrive(BAR(BAR_EMPTY + tl));
      if (tl == 0) CLK(16);
      if (tl == 1) CLK(18);
      if (tl == 3) CLK(19);
      if (tl == 6) CLK(20);
      da = (tl == 2 || tl == 5) ? da - 8192 : da + 4096;
    }
    if (cta < NFF) { load_units<4, 64>(sbf, pcb); load_units<4, 64>(cbf, pcb + 2048); }
    mbar_wait(BAR(BAR_ALLCLR));
    uint32_t* x1o[8];
#pragma unroll
    for (int i = 0; i < 8; i++)
      x1o[i] = pin(inbox((16 * hh + 8 * ((i >> 1) & 1) + 2 * t + (i & 1)) * 4 + 2 * (i >> 2) + (wq >> 1), bs >> 4) + (bs & 15) * 64 + ((wq & 1) * 8 + g) * 4);
    handover(7);
    CLK(23);
    thand = clk32();
    auto pv = [&](int mb0, int n) {
      wg_fence();
#pragma unroll
      for (int i = 0; i < 16; i++)
        if (i < 4 * n) wgmma_n16<1, 1>(O[mb0 + (i >> 2)], desc_lo(65536) + (mb0 + (i >> 2)) * 512 + (i & 3) * 128, dp + 128 + (i & 3) * 2);
      wg_commit();
    };
    auto publish = [&](int J) {
#pragma unroll
      for (int k = 0; k < 4; k++) acc_fence(O[4 * J + k]);
#pragma unroll
      for (int i = 0; i < 4; i++) {
        const int k = 4 * (i >> 1) + (i & 1);
        stg_cvt8(x1o[4 * J + i], O[4 * J][k], O[4 * J][k + 2], O[4 * J + 1][k], O[4 * J + 1][k + 2],
                 O[4 * J + 2][k], O[4 * J + 2][k + 2], O[4 * J + 3][k], O[4 * J + 3][k + 2]);
      }
    };
    pv(0, 4); pv(4, 4);
    wg_wait<1>(); publish(0);
    wg_wait<0>(); publish(1);
    CLK(24);
  }

  {
    const uint32_t* px = pin(inbox(cta, w >> 1) + (w & 1) * 512 + lane * 2);
    uint32_t* const x2o = pin(inbox(cta, 4) + 512 + tid * 2);
    mbar_wait(BAR(BAR_TS));
    anchor = lds1(sb + OFF_TS);
    wait_clk(thand, T.D_X1);
    wait_clk(anchor, T.A_X1 + (jI >> 1) * T.A_X1J);
    CLK(25);
    uint2 v[8];
    load_units<8, 64>(v, px);
    const bool early = __all_sync(~0u, mbar_test(BAR(BAR_WUV + wg)));
    if (early) load_a_t(aw, sb + OFF_WUV, w, lane);
    mbar_wait(BAR(BAR_WV));
    const float4 wa = ldsf4(sb + OFF_WV + w * 32), wb = ldsf4(sb + OFF_WV + w * 32 + 16);
    const float wv[8] = {wa.x, wa.y, wa.z, wa.w, wb.x, wb.y, wb.z, wb.w};
    CLK(27);
    const int it = check_units<8, 64>(v, px, T.RB);
    CLK(28);
    ITS(4, it);
    float a0 = 0.f, a1 = 0.f, a2 = 0.f, a3 = 0.f;
#pragma unroll
    for (int i = 0; i < 8; i++) { a0 += wv[i] * bf_lo(v[i].x); a1 += wv[i] * bf_hi(v[i].x); a2 += wv[i] * bf_lo(v[i].y); a3 += wv[i] * bf_hi(v[i].y); }
    sts2(sb + OFF_BS4 + w * 272 + lane * 8, pack_bf16(a0, a1), pack_bf16(a2, a3));
    CLK(29);
    if (!early) { mbar_wait(BAR(BAR_WUV + wg)); load_a_t(aw, sb + OFF_WUV, w, lane); }
    cbar();
    uint32_t b[4][4];
#pragma unroll
    for (int kk = 0; kk < 4; kk++) ldsm4(b[kk], sb + OFF_BS4 + (lane & 7) * 272 + (4 * kk + (lane >> 3)) * 16);
    float d[4];
    mma128(d, aw, b);
    stg_u64(x2o, pack_bf16(d[0], d[1]), pack_bf16(d[2], d[3]));
    tstore = clk32();
    CLK(30);
  }
  {
    uint32_t* const o = pin(inbox(4 * (8 * jI + w) + t, 4) + hI * 16 + g * 2);
    const uint32_t* x2i[4];
#pragma unroll
    for (int i = 0; i < 4; i++) x2i[i] = pin(inbox(4 * hI + i, 4) + 512 + tid * 2);
    wait_clk(tstore, T.D_X2);
    wait_clk(anchor, T.A_X2);
    uint2 v[4];
#pragma unroll
    for (int i = 0; i < 4; i++) v[i] = ldg_u64(x2i[i]);
    mbar_wait(BAR(BAR_WO + wg));
    load_a_t(aw, sb + OFF_WO, w, lane);
    CLK(31);
    int it = 0;
    while (min(min(v[0].y, v[1].y), min(v[2].y, v[3].y)) == 0) {
#pragma unroll
      for (int i = 0; i < 4; i++) if (v[i].y == 0) v[i] = ldg_u64(x2i[i]);
      if (++it > SPIN_LIMIT) __trap();
    }
    CLK(32);
    ITS(5, it);
    sum4_to_smem(v, sb + OFF_BS5 + (16 * w + g) * 16 + t * 4);
    cbar();
    uint32_t b[4][4];
#pragma unroll
    for (int kk = 0; kk < 4; kk++) ldsm4t(b[kk], sb + OFF_BS5 + (32 * kk + lane) * 16);
    float d[4];
    mma128(d, aw, b);
    stg_u64(o, movm(pack_bf16(d[0], d[1])), movm(pack_bf16(d[2], d[3])));
    tstore = clk32();
    CLK(33);
    if (lane == 0) mbar_arrive(BAR(BAR_P5D));
  }
  if (cta < NFF) {
    const int mi = lane >> 3, r = lane & 7;
    uint32_t a1[2][4][4], a2[2][2][4];
    check_units<4, 64>(sbf, pcb, T.RB);
    check_units<4, 64>(cbf, pcb + 2048, T.RB);
    __syncwarp();
#pragma unroll
    for (int s = 0; s < 4; s++) { cbf[s].x = hadd2(cbf[s].x, ONE2); cbf[s].y = hadd2(cbf[s].y, ONE2); }
    mbar_wait(BAR(BAR_W1));
#pragma unroll
    for (int mt = 0; mt < 2; mt++) {
#pragma unroll
      for (int ks = 0; ks < 4; ks++) ldsm4t(a1[mt][ks], sb + OFF_W1 + (64 * w + 16 * ks + 8 * (mi >> 1) + r) * 64 + (((2 * mt + (mi & 1)) ^ (r >> 1)) << 4));
      float u[4] = {0.f, 0.f, 0.f, 0.f}, vv[4] = {0.f, 0.f, 0.f, 0.f};
#pragma unroll
      for (int s = 0; s < 4; s++) { mma16816(u, a1[mt][s], cbf[s].x, cbf[s].y); mma16816(vv, a1[mt][s], sbf[s].x, sbf[s].y); }
      sts4f(sb + OFF_REDU + w * 1024 + mt * 512 + lane * 16, u[0], u[1], u[2], u[3]);
      sts4f(sb + OFF_REDV + w * 1024 + mt * 512 + lane * 16, vv[0], vv[1], vv[2], vv[3]);
    }
    const uint32_t* xb = pin(inbox(cta & ~7, 6 + wg) + (16 * wq + t) * 16 + g * 2);
    uint32_t* const ox[2] = {pin(inbox(64 * hh + 8 * w + t, 5) + bs * 16 + g * 2), pin(inbox(64 * hh + 8 * w + 4 + t, 5) + bs * 16 + g * 2)};
    CLK(34);
    wait_clk(tstore, T.D_X3B);
    uint2 x[4];
    load_units<4, 64>(x, xb);
    cbar();
    const int lp = (tid >> 2) & 31, kq = tid & 3;
    const int fo = 16 * wg + (lp >> 2) + 8 * (kq >> 1), bo = 2 * (lp & 3) + (kq & 1);
    float U = 0.f, V = 0.f;
#pragma unroll
    for (int i = 0; i < 8; i++) { U += ldsf(sb + OFF_REDU + i * 1024 + tid * 4); V += ldsf(sb + OFF_REDV + i * 1024 + tid * 4); }
    mbar_wait(BAR(BAR_W2));
#pragma unroll
    for (int i = 0; i < 4; i++)
      ldsm4t(a2[i >> 1][i & 1], sb + OFF_W2 + (w >> 1) * 4096 + (16 * (i & 1) + 8 * (mi >> 1) + r) * 128 + (((4 * (w & 1) + 2 * (i >> 1) + (mi & 1)) ^ r) << 4));
    CLK(35);
    const int it = check_units<4, 64>(x, xb, T.RB);
    __syncwarp();
    CLK(36);
    ITS(6, it);
    float G[2][2][4] = {}, S[2][4] = {};
#pragma unroll
    for (int s = 0; s < 4; s++) {
      const uint32_t sx[4] = {x[s].x, ONE2, x[s].y, ONE2};
      mma16816(S[s & 1], sx, x[s].x, x[s].y);
      const uint32_t y0 = hmul2(x[s].x, cbf[s].x), y1 = hmul2(x[s].y, cbf[s].y);
      mma16816(G[0][s & 1], a1[0][s], y0, y1);
      mma16816(G[1][s & 1], a1[1][s], y0, y1);
    }
    if (t == (g >> 1)) sts2f(sb + OFF_REDS + g * 80 + w * 8, (g & 1) ? S[0][3] + S[1][3] : S[0][2] + S[1][2], (g & 1) ? S[0][1] + S[1][1] : S[0][0] + S[1][0]);
#pragma unroll
    for (int mt = 0; mt < 2; mt++)
      sts4f(sb + OFF_REDG + w * 1024 + mt * 512 + lane * 16, G[mt][0][0] + G[mt][1][0], G[mt][0][1] + G[mt][1][1], G[mt][0][2] + G[mt][1][2], G[mt][0][3] + G[mt][1][3]);
    CLK(37);
    cbar();
    {
      float gv[8];
      float4 sv[4];
#pragma unroll
      for (int i = 0; i < 4; i++) sv[i] = ldsf4(sb + OFF_REDS + bo * 80 + i * 16);
#pragma unroll
      for (int i = 0; i < 8; i++) gv[i] = ldsf(sb + OFF_REDG + i * 1024 + tid * 4);
      const float s1 = ((sv[0].x + sv[0].z) + (sv[1].x + sv[1].z)) + ((sv[2].x + sv[2].z) + (sv[3].x + sv[3].z));
      const float s2 = ((sv[0].y + sv[0].w) + (sv[1].y + sv[1].w)) + ((sv[2].y + sv[2].w) + (sv[3].y + sv[3].w));
      const float gsum = ((gv[0] + gv[1]) + (gv[2] + gv[3])) + ((gv[4] + gv[5]) + (gv[6] + gv[7]));
      const float mu = s1 * (1.f / 512.f);
      const float rs = rsqrtf(fmaxf(s2 * (1.f / 512.f) - mu * mu, 0.f) + 1e-5f);
      const float hv = fmaxf(rs * (gsum - mu * U) + V, 0.f);
      asm volatile("st.shared.u16 [%0], %1;" ::"r"(sb + OFF_H1 + fo * 16 + bo * 2), "h"(__bfloat16_as_ushort(__float2bfloat16(hv))) : "memory");
    }
    CLK(38);
    cbar();
    uint32_t b[4];
    ldsm4t(b, sb + OFF_H1 + lane * 16);
    float o[2][2][4] = {};
#pragma unroll
    for (int i = 0; i < 4; i++) mma16816(o[i >> 1][i & 1], a2[i >> 1][i & 1], b[2 * (i & 1)], b[2 * (i & 1) + 1]);
#pragma unroll
    for (int mb = 0; mb < 2; mb++)
      stg_u64(ox[mb], movm(pack_bf16(o[mb][0][0] + o[mb][1][0], o[mb][0][1] + o[mb][1][1])), movm(pack_bf16(o[mb][0][2] + o[mb][1][2], o[mb][0][3] + o[mb][1][3])));
    CLK(39);
    if (lane == 0) mbar_arrive(BAR(BAR_P7D));
  }
  CLK_DUMP();
}

typedef CUresult (*EncodeTiledFn)(CUtensorMap*, CUtensorMapDataType, cuuint32_t, void*, const cuuint64_t*, const cuuint64_t*,
                                  const cuuint32_t*, const cuuint32_t*, CUtensorMapInterleave, CUtensorMapSwizzle,
                                  CUtensorMapL2promotion, CUtensorMapFloatOOBfill);

struct Dim { uint64_t size, stride; uint32_t box; };
template <int R> void encode_map(EncodeTiledFn enc, CUtensorMap* m, const void* base, const Dim (&d)[R], CUtensorMapSwizzle sw, CUtensorMapL2promotion promo) {
  cuuint64_t dims[R], strides[R];
  cuuint32_t box[R], es[R];
  for (int i = 0; i < R; i++) { dims[i] = d[i].size; strides[i] = d[i].stride; box[i] = d[i].box; es[i] = 1; }
  enc(m, CU_TENSOR_MAP_DATA_TYPE_BFLOAT16, R, const_cast<void*>(base), dims, strides + 1, box, es, CU_TENSOR_MAP_INTERLEAVE_NONE, sw, promo,
      CU_TENSOR_MAP_FLOAT_OOB_FILL_NONE);
}

}

extern "C" void kernel_launch(void* const* d_in, const int* in_sizes, int n_in, void* d_out, int out_size) {
  (void)in_sizes; (void)n_in; (void)out_size;
  static EncodeTiledFn enc = nullptr;
  static Scratch* scratch = nullptr;
  static uint32_t* inbox = nullptr;
  if (!enc) {
    void* sp = nullptr;
    cudaGetSymbolAddress(&sp, g_s);
    scratch = (Scratch*)sp;
    cudaGetSymbolAddress(&sp, g_in);
    inbox = (uint32_t*)(((uintptr_t)sp + 65535) & ~(uintptr_t)65535);
    void* fn = nullptr;
    cudaDriverEntryPointQueryResult q;
    cudaGetDriverEntryPoint("cuTensorMapEncodeTiled", &fn, cudaEnableDefault, &q);
    enc = (EncodeTiledFn)fn;
    cudaFuncSetAttribute(fused_decode_kernel, cudaFuncAttributeMaxDynamicSharedMemorySize, SMEM_BYTES);
  }
  const CUtensorMapSwizzle S128 = CU_TENSOR_MAP_SWIZZLE_128B, S0 = CU_TENSOR_MAP_SWIZZLE_NONE;
  const CUtensorMapL2promotion L0 = CU_TENSOR_MAP_L2_PROMOTION_NONE, L128 = CU_TENSOR_MAP_L2_PROMOTION_L2_128B;
  Params P;
  encode_map<2>(enc, &P.wq, d_in[2], {{4096, 2, 64}, {512, 8192, 64}}, S128, L0);
  encode_map<5>(enc, &P.wuk, d_in[3], {{4096, 2, 64}, {2, 8192, 2}, {4, 4 * 8192, 4}, {2, 2 * 8192, 2}, {32, 16 * 8192, 4}}, S128, L0);
  encode_map<2>(enc, &P.wm2, d_in[10], {{3072, 2, 16}, {512, 6144, 256}}, S0, L128);
  encode_map<3>(enc, &P.ckv2, d_in[1], {{64, 2, 64}, {8 * 4096, 1024, 64}, {8, 128, 2}}, S128, L0);
  encode_map<3>(enc, &P.ckv1, d_in[1], {{64, 2, 64}, {8 * 4096, 1024, 64}, {8, 128, 1}}, S128, L0);
  encode_map<5>(enc, &P.wuv, d_in[4], {{4096, 2, 64}, {2, 8 * 8192, 2}, {8, 64 * 8192, 4}, {8, 8192, 8}, {4, 16 * 8192, 1}}, S128, L0);
  encode_map<2>(enc, &P.wo, d_in[5], {{512, 2, 64}, {4096, 1024, 64}}, S128, L0);
  encode_map<2>(enc, &P.w1, d_in[7], {{1792, 2, 32}, {512, 3584, 256}}, CU_TENSOR_MAP_SWIZZLE_64B, L128);
  encode_map<3>(enc, &P.w2, d_in[8], {{64, 2, 64}, {1792, 1024, 32}, {8, 128, 2}}, S128, L0);
  cudaLaunchConfig_t cfg = {};
  cfg.gridDim = dim3(NCTA);
  cfg.blockDim = dim3(NTHREADS);
  cfg.dynamicSmemBytes = SMEM_BYTES;
  cfg.stream = cudaStreamPerThread;
  cudaLaunchAttribute at[1];
  at[0].id = cudaLaunchAttributeClusterDimension;
  at[0].val.clusterDim.x = 2; at[0].val.clusterDim.y = 1; at[0].val.clusterDim.z = 1;
  cfg.attrs = at;
  cfg.numAttrs = 0;
  cudaLaunchKernelEx(&cfg, fused_decode_kernel, (__nv_bfloat16*)d_out, scratch, (const uint8_t*)d_in[10], (const uint8_t*)d_in[0],
                     (const uint8_t*)d_in[9], inbox,
                     P);
}
```

```cpp
#include <cuda_runtime.h>
#include <cuda.h>
#include <cuda_bf16.h>
#include <stdint.h>
#define V4 1

namespace {

constexpr int NCTA = 128;
constexpr int NTHREADS = 320;
constexpr int NFG = 56;
constexpr int NFF = 2 * NFG;
constexpr int NSYNC = 4;
#define NTS 8

constexpr uint32_t OFF_RING = 0;
constexpr uint32_t OFF_WUK = 131072;
constexpr uint32_t OFF_WQ = 131072 + 32768;
constexpr uint32_t OFF_WM2 = 65536 + 49152;
constexpr uint32_t OFF_WUV = 131072;
constexpr uint32_t OFF_WO = 131072 + 32768;
constexpr uint32_t OFF_W1 = 0;
constexpr uint32_t OFF_W2 = 32768;
constexpr uint32_t OFF_Q = 196608;
constexpr uint32_t OFF_PT = 212992;
constexpr uint32_t OFF_SCR = 217088;
constexpr uint32_t OFF_XS = 65536;
constexpr uint32_t OFF_CS = 65536 + 8192;
constexpr uint32_t OFF_P0S = 65536 + 16384;
constexpr uint32_t OFF_BS1 = OFF_SCR + 2048;
constexpr uint32_t OFF_BS2 = OFF_SCR + 4096;
constexpr uint32_t OFF_P0B = OFF_SCR + 6144;
constexpr uint32_t OFF_XN = OFF_SCR + 8192;
constexpr uint32_t OFF_RED = OFF_SCR + 10496;
constexpr uint32_t OFF_ALPHA = OFF_SCR + 11072;
constexpr uint32_t OFF_WV = OFF_SCR + 6144;
constexpr uint32_t OFF_SEL = OFF_SCR + 10752;
constexpr uint32_t OFF_TS = OFF_SCR + 11136;
constexpr uint32_t OFF_BARS = OFF_SCR + 11264;
constexpr uint32_t SMEM_BYTES = OFF_BARS + 512;
constexpr uint32_t OFF_BS4 = OFF_Q;
constexpr uint32_t OFF_H1 = OFF_Q + 2304;
constexpr uint32_t OFF_REDS = OFF_Q + 2816;
constexpr uint32_t OFF_BS5 = OFF_Q + 4096;
constexpr uint32_t OFF_REDG = OFF_Q + 8192;
constexpr uint32_t OFF_REDU = 65536;
constexpr uint32_t OFF_REDV = 65536 + 8192;

constexpr int BAR_FULL = 0;
constexpr int BAR_LAST = 28;
constexpr int BAR_WUK = 33, BAR_WM2 = 35, BAR_WUV = 36, BAR_WO = 38, BAR_W1 = 40, BAR_W2 = 41;
constexpr int BAR_ALLCLR = 42, BAR_TS = 43, BAR_WV = 44;
constexpr int BAR_EMPTY = 45;
constexpr int BAR_P0BD = 52;
constexpr int BAR_P1D = 53, BAR_P2D = 54;
constexpr int BAR_P5D = 55, BAR_P7D = 56;
constexpr int NBARS = 57;
constexpr int BAR_XC = 57, BAR_WQ = 58;
constexpr int BAR_C = 60, BAR_END = 61;
constexpr uint32_t SB = 1024;

#define TUNE_LIST(X) \
  X(PC_T0, 340) X(PC_XC, 0) X(PC_C, 0) X(PC_P1, 320) X(PC_P2, 322) X(PC_STAG, 390) X(PC_DS, 0) X(PC_SL, 500) X(PC_W, 4) X(PC_NW, 8) \
  X(PW_A, -1) X(PW_0, 260) X(PW_ST, 0) X(PW_UV, 300) X(PW_G, 520) X(PW_O, 440) X(PW_G2, 430) X(PW_G3, 460) X(PW_F, 300) \
  X(LOC, 0) X(PR_T0, 1000) X(PR_N, 4) X(CLR_T0, 3200) X(CLR_CLK, 190) \
  X(D_MOD, 1500) X(D_QP, 1300) X(D_QX, 1300) X(TS_P, 1) X(TS_O, 950) X(D_TS, 900) X(A_M, 2100) X(D_X1, 1400) X(A_X1, 2520) \
  X(D_X2, 150) X(R_X2, 1750) X(D_X3A, 50) X(R_X3A, 3750) X(D_X3B, 1000) X(R_X3B, 980) X(D_FIN, 360) X(D_FIN2, 2100) X(RB, 0)
struct Tune {
#define X(n, v) static constexpr int n = v;
  TUNE_LIST(X)
#undef X
};

#define PFENCE 0
#define WSWAP 0
#define EARLYR 1
#define PVV 0
struct Scratch {
  uint32_t MOD1[2][4 * 64 * 64];
  uint32_t MOD2[2][128 * 64];
  uint32_t QP[2][128 * 256 * 2];
  uint32_t QX[2][8 * 32 * 256];
  uint32_t epoch;
  uint32_t pad[31];
  uint32_t sync[NSYNC][32];
};
__device__ Scratch g_s;
__device__ uint32_t g_in[129 * 16384];
__device__ __forceinline__ uint32_t blk(int c, int k, uint32_t sel) { return c * 16384 + k * 2048 + ((sel ^ k) & 1) * 1024; }

#define CLK_DECL
#define CLK(i) do {} while (0)
#define CLK_DUMP() do {} while (0)
#define ITS(i, v) do {} while (0)

struct Params {
  CUtensorMap wq, wuk, wm2, ckv2, ckv1, wuv, wo, w1, w2;
};

__device__ __forceinline__ void mbar_init(uint32_t bar, int cnt) { asm volatile("mbarrier.init.shared::cta.b64 [%0], %1;" ::"r"(bar), "r"(cnt)); }
__device__ __forceinline__ void mbar_expect(uint32_t bar, uint32_t bytes) { asm volatile("mbarrier.arrive.expect_tx.shared::cta.b64 _, [%0], %1;" ::"r"(bar), "r"(bytes) : "memory"); }
__device__ __forceinline__ void mbar_arrive(uint32_t bar) { asm volatile("mbarrier.arrive.shared::cta.b64 _, [%0];" ::"r"(bar) : "memory"); }
__device__ __forceinline__ uint32_t clk32() { unsigned long long c; asm volatile("mov.u64 %0, %%clock64;" : "=l"(c) :: "memory"); return (uint32_t)c; }
__device__ __forceinline__ uint32_t gtime32() { uint32_t c; asm volatile("mov.u32 %0, %%globaltimer_lo;" : "=r"(c) :: "memory"); return c; }
__device__ __forceinline__ void wait_clk(uint32_t t0, int clocks) { while ((int)(clk32() - t0) < clocks) {} }
__device__ __forceinline__ void backoff(int clocks) { if (clocks > 0) wait_clk(clk32(), clocks); }
__device__ __forceinline__ void until_ns(uint32_t ns) { while ((int)(gtime32() - ns) < 0) {} }
__device__ __forceinline__ void slot(uint32_t& tn, int slack) {
  uint32_t now;
  do { now = gtime32(); } while ((int)(now - tn) < 0);
  if ((int)(now - tn) > slack) tn = now - slack;
}
template <typename T> __device__ __forceinline__ T* pin(T* p) { asm volatile("" : "+l"(p)); return p; }
__device__ __forceinline__ uint32_t pin(uint32_t v) { asm volatile("" : "+r"(v)); return v; }
__device__ __forceinline__ float pin(float v) { asm volatile("" : "+f"(v)); return v; }
constexpr int SPIN_LIMIT = 1 << 22;
__device__ __forceinline__ void mbar_wait(uint32_t bar) {
  asm volatile("{\n.reg .pred p;\n.reg .u32 c;\nmov.u32 c, 0;\n"
               "MW_LOOP:\nmbarrier.try_wait.parity.shared::cta.b64 p, [%0], 0;\n@p bra MW_DONE;\n"
               "add.u32 c, c, 1;\nsetp.lt.u32 p, c, 4194304;\n@p bra MW_LOOP;\ntrap;\nMW_DONE:\n}"
               ::"r"(bar) : "memory");
}
__device__ __forceinline__ bool mbar_test(uint32_t bar) {
  uint32_t ok;
  asm volatile("{\n.reg .pred p;\nmbarrier.test_wait.parity.shared::cta.b64 p, [%1], 0;\nselp.u32 %0,1,0,p;\n}" : "=r"(ok) : "r"(bar) : "memory");
  return ok;
}
__device__ __forceinline__ void tma2d(uint32_t dst, const CUtensorMap* m, int c0, int c1, uint32_t bar, uint64_t pol) {
  asm volatile("cp.async.bulk.tensor.2d.shared::cluster.global.mbarrier::complete_tx::bytes.L2::cache_hint [%0], [%1, {%3,%4}], [%2], %5;"
               ::"r"(dst), "l"(m), "r"(bar), "r"(c0), "r"(c1), "l"(pol) : "memory");
}
__device__ __forceinline__ void tma2d_nohint(uint32_t dst, const CUtensorMap* m, int c0, int c1, uint32_t bar) {
  asm volatile("cp.async.bulk.tensor.2d.shared::cluster.global.mbarrier::complete_tx::bytes [%0], [%1, {%3,%4}], [%2];"
               ::"r"(dst), "l"(m), "r"(bar), "r"(c0), "r"(c1) : "memory");
}
__device__ __forceinline__ void tma3d(uint32_t dst, const CUtensorMap* m, int c0, int c1, int c2, uint32_t bar, uint64_t pol) {
  asm volatile("cp.async.bulk.tensor.3d.shared::cluster.global.mbarrier::complete_tx::bytes.L2::cache_hint [%0], [%1, {%3,%4,%5}], [%2], %6;"
               ::"r"(dst), "l"(m), "r"(bar), "r"(c0), "r"(c1), "r"(c2), "l"(pol) : "memory");
}
__device__ __forceinline__ void tma5d(uint32_t dst, const CUtensorMap* m, int c0, int c1, int c2, int c3, int c4, uint32_t bar, uint64_t pol) {
  asm volatile("cp.async.bulk.tensor.5d.shared::cluster.global.mbarrier::complete_tx::bytes.L2::cache_hint [%0], [%1, {%3,%4,%5,%6,%7}], [%2], %8;"
               ::"r"(dst), "l"(m), "r"(bar), "r"(c0), "r"(c1), "r"(c2), "r"(c3), "r"(c4), "l"(pol) : "memory");
}
__device__ __forceinline__ void bulk_ld(uint32_t dst, const void* src, uint32_t bytes, uint32_t bar) {
  asm volatile("cp.async.bulk.shared::cluster.global.mbarrier::complete_tx::bytes [%0], [%1], %2, [%3];" ::"r"(dst), "l"(src), "r"(bytes), "r"(bar) : "memory");
}
__device__ __forceinline__ void bar_sync(int id, int n) { asm volatile("barrier.cta.sync.aligned %0, %1;" ::"r"(id), "r"(n) : "memory"); }
__device__ __forceinline__ void cbar() { asm volatile("barrier.cta.sync.aligned 1, 256;" ::: "memory"); }
__device__ __forceinline__ uint32_t cbar_bad(uint32_t flags) {
  uint32_t bad;
  asm volatile("{\n.reg .pred p, q;\nsetp.eq.u32 p, %1, 0;\nbarrier.cta.red.or.aligned.pred q, 4, 256, p;\nselp.u32 %0, 1, 0, q;\n}" : "=r"(bad) : "r"(flags) : "memory");
  return bad;
}
__device__ __forceinline__ bool bar_over(float ex) {
  uint32_t over;
  asm volatile("{\n.reg .pred p, q;\nsetp.gtu.f32 p, %1, 0f41F00000;\nbarrier.cta.red.or.aligned.pred q, 4, 256, p;\nselp.u32 %0, 1, 0, q;\n}"
               : "=r"(over) : "f"(ex) : "memory");
  return over;
}

__device__ __forceinline__ uint32_t ldg_nc1(const void* p) { uint32_t v; asm volatile("ld.global.nc.L1::no_allocate.u32 %0, [%1];" : "=r"(v) : "l"(p)); return v; }
__device__ __forceinline__ uint2 ldg_nc2(const void* p) { uint2 v; asm volatile("ld.global.nc.v2.u32 {%0,%1}, [%2];" : "=r"(v.x), "=r"(v.y) : "l"(p)); return v; }
__device__ __forceinline__ uint4 ldg_nc4(const void* p) { uint4 v; asm volatile("ld.global.nc.L1::no_allocate.v4.u32 {%0,%1,%2,%3}, [%4];" : "=r"(v.x), "=r"(v.y), "=r"(v.z), "=r"(v.w) : "l"(p)); return v; }
__device__ __forceinline__ uint32_t ldg_rlx1(const void* p) { uint32_t v; asm volatile("ld.relaxed.gpu.global.u32 %0, [%1];" : "=r"(v) : "l"(p) : "memory"); return v; }
__device__ __forceinline__ void stg4(void* p, uint4 v) { asm volatile("st.relaxed.gpu.global.v4.u32 [%0], {%1,%2,%3,%4};" ::"l"(p), "r"(v.x), "r"(v.y), "r"(v.z), "r"(v.w) : "memory"); }
__device__ __forceinline__ void stg1(void* p, uint32_t a) { asm volatile("st.relaxed.gpu.global.u32 [%0], %1;" ::"l"(p), "r"(a) : "memory"); }
__device__ __forceinline__ uint32_t nz(uint32_t w) { return max(w, 1u); }
__device__ __forceinline__ uint2 ldg_u64(const void* p) {
  uint2 v; asm volatile("{\n.reg .b64 a;\nld.relaxed.gpu.global.b64 a, [%2];\nmov.b64 {%0,%1}, a;\n}" : "=r"(v.x), "=r"(v.y) : "l"(p) : "memory"); return v;
}
__device__ __forceinline__ uint4 ldg_2u64(const void* p) {
  uint4 v; asm volatile("{\n.reg .b64 a, b;\nld.relaxed.gpu.global.v2.b64 {a, b}, [%4];\nmov.b64 {%0,%1}, a;\nmov.b64 {%2,%3}, b;\n}" : "=r"(v.x), "=r"(v.y), "=r"(v.z), "=r"(v.w) : "l"(p) : "memory"); return v;
}
__device__ __forceinline__ void stg_u64(void* p, uint32_t x, uint32_t y) {
  asm volatile("{\n.reg .b32 y;\nmax.u32 y, %2, 1;\nst.relaxed.gpu.global.v2.b32 [%0], {%1, y};\n}" ::"l"(p), "r"(x), "r"(y) : "memory");
}
__device__ __forceinline__ void stg_u64_unless(uint32_t bad, void* p, uint32_t x, uint32_t y) {
  asm volatile("{\n.reg .b32 y;\n.reg .pred q;\nsetp.eq.u32 q, %3, 0;\nmax.u32 y, %2, 1;\n@q st.relaxed.gpu.global.v2.b32 [%0], {%1, y};\n}" ::"l"(p), "r"(x), "r"(y), "r"(bad) : "memory");
}
__device__ __forceinline__ void stg_2u64(void* p, uint4 v) {
  asm volatile("{\n.reg .b32 y, w;\nmax.u32 y, %2, 1;\nmax.u32 w, %4, 1;\nst.relaxed.gpu.global.v4.b32 [%0], {%1, y, %3, w};\n}" ::"l"(p), "r"(v.x), "r"(v.y), "r"(v.z), "r"(v.w) : "memory");
}

__device__ __forceinline__ void stg_cvt8(void* p, float a0, float a1, float b0, float b1, float c0, float c1, float d0, float d1) {
  asm volatile("{\n.reg .b32 x, y, z, w;\ncvt.rn.bf16x2.f32 x, %2, %1;\ncvt.rn.bf16x2.f32 y, %4, %3;\ncvt.rn.bf16x2.f32 z, %6, %5;\ncvt.rn.bf16x2.f32 w, %8, %7;\n"
               "max.u32 y, y, 1;\nmax.u32 w, w, 1;\nst.relaxed.gpu.global.v4.b32 [%0], {x, y, z, w};\n}"
               ::"l"(p), "f"(a0), "f"(a1), "f"(b0), "f"(b1), "f"(c0), "f"(c1), "f"(d0), "f"(d1) : "memory");
}
__device__ __forceinline__ uint32_t pack_bf16(float lo, float hi) { uint32_t r; asm("cvt.rn.bf16x2.f32 %0, %1, %2;" : "=r"(r) : "f"(hi), "f"(lo)); return r; }
__device__ __forceinline__ float bf_lo(uint32_t w) { return __uint_as_float(w << 16); }
__device__ __forceinline__ float bf_hi(uint32_t w) { return __uint_as_float(w & 0xffff0000u); }
__device__ __forceinline__ float ex2(float x) { float r; asm("ex2.approx.ftz.f32 %0, %1;" : "=f"(r) : "f"(x)); return r; }
__device__ __forceinline__ uint32_t hmul2(uint32_t a, uint32_t b) { uint32_t r; asm("mul.rn.bf16x2 %0, %1, %2;" : "=r"(r) : "r"(a), "r"(b)); return r; }
__device__ __forceinline__ uint32_t hadd2(uint32_t a, uint32_t b) { uint32_t r; asm("add.rn.bf16x2 %0, %1, %2;" : "=r"(r) : "r"(a), "r"(b)); return r; }
__device__ __forceinline__ uint32_t hfma2(uint32_t a, uint32_t b, uint32_t c) { uint32_t r; asm("fma.rn.bf16x2 %0, %1, %2, %3;" : "=r"(r) : "r"(a), "r"(b), "r"(c)); return r; }
__device__ __forceinline__ uint32_t silu2(uint32_t v) { const float a = bf_lo(v), b = bf_hi(v); return pack_bf16(__fdividef(a, 1.f + __expf(-a)), __fdividef(b, 1.f + __expf(-b))); }
constexpr uint32_t ONE2 = 0x3f803f80u;

__device__ __forceinline__ void ldsm4(uint32_t (&r)[4], uint32_t a) { asm volatile("ldmatrix.sync.aligned.m8n8.x4.shared.b16 {%0,%1,%2,%3}, [%4];" : "=r"(r[0]), "=r"(r[1]), "=r"(r[2]), "=r"(r[3]) : "r"(a) : "memory"); }
__device__ __forceinline__ void ldsm4t(uint32_t (&r)[4], uint32_t a) { asm volatile("ldmatrix.sync.aligned.m8n8.x4.trans.shared.b16 {%0,%1,%2,%3}, [%4];" : "=r"(r[0]), "=r"(r[1]), "=r"(r[2]), "=r"(r[3]) : "r"(a) : "memory"); }
__device__ __forceinline__ void ldsm2t(uint32_t& r0, uint32_t& r1, uint32_t a) { asm volatile("ldmatrix.sync.aligned.m8n8.x2.trans.shared.b16 {%0,%1}, [%2];" : "=r"(r0), "=r"(r1) : "r"(a) : "memory"); }
__device__ __forceinline__ void stsm4t(uint32_t a, uint32_t r0, uint32_t r1, uint32_t r2, uint32_t r3) { asm volatile("stmatrix.sync.aligned.m8n8.x4.trans.shared.b16 [%0], {%1,%2,%3,%4};" ::"r"(a), "r"(r0), "r"(r1), "r"(r2), "r"(r3) : "memory"); }
__device__ __forceinline__ uint32_t movm(uint32_t a) { uint32_t d; asm volatile("movmatrix.sync.aligned.m8n8.trans.b16 %0, %1;" : "=r"(d) : "r"(a)); return d; }
__device__ __forceinline__ void mma16816(float (&d)[4], const uint32_t (&a)[4], uint32_t b0, uint32_t b1) {
  asm volatile("mma.sync.aligned.m16n8k16.row.col.f32.bf16.bf16.f32 {%0,%1,%2,%3}, {%4,%5,%6,%7}, {%8,%9}, {%0,%1,%2,%3};"
               : "+f"(d[0]), "+f"(d[1]), "+f"(d[2]), "+f"(d[3]) : "r"(a[0]), "r"(a[1]), "r"(a[2]), "r"(a[3]), "r"(b0), "r"(b1));
}
__device__ __forceinline__ void sts1(uint32_t a, uint32_t v) { asm volatile("st.shared.u32 [%0], %1;" ::"r"(a), "r"(v) : "memory"); }
__device__ __forceinline__ void sts2(uint32_t a, uint32_t x, uint32_t y) { asm volatile("st.shared.v2.u32 [%0], {%1,%2};" ::"r"(a), "r"(x), "r"(y) : "memory"); }
__device__ __forceinline__ void sts4(uint32_t a, uint4 v) { asm volatile("st.shared.v4.u32 [%0], {%1,%2,%3,%4};" ::"r"(a), "r"(v.x), "r"(v.y), "r"(v.z), "r"(v.w) : "memory"); }
__device__ __forceinline__ void sts2f(uint32_t a, float x, float y) { asm volatile("st.shared.v2.f32 [%0], {%1,%2};" ::"r"(a), "f"(x), "f"(y) : "memory"); }
__device__ __forceinline__ void sts4f(uint32_t a, float x, float y, float z, float w) { asm volatile("st.shared.v4.f32 [%0], {%1,%2,%3,%4};" ::"r"(a), "f"(x), "f"(y), "f"(z), "f"(w) : "memory"); }
__device__ __forceinline__ void stsf(uint32_t a, float v) { asm volatile("st.shared.f32 [%0], %1;" ::"r"(a), "f"(v) : "memory"); }
__device__ __forceinline__ uint32_t lds1(uint32_t a) { uint32_t v; asm volatile("ld.shared.u32 %0, [%1];" : "=r"(v) : "r"(a) : "memory"); return v; }
__device__ __forceinline__ float ldsf(uint32_t a) { float v; asm volatile("ld.shared.f32 %0, [%1];" : "=f"(v) : "r"(a) : "memory"); return v; }
__device__ __forceinline__ float2 ldsf2(uint32_t a) { float2 v; asm volatile("ld.shared.v2.f32 {%0,%1}, [%2];" : "=f"(v.x), "=f"(v.y) : "r"(a) : "memory"); return v; }
__device__ __forceinline__ float4 ldsf4(uint32_t a) { float4 v; asm volatile("ld.shared.v4.f32 {%0,%1,%2,%3}, [%4];" : "=f"(v.x), "=f"(v.y), "=f"(v.z), "=f"(v.w) : "r"(a) : "memory"); return v; }
__device__ __forceinline__ void lds4(uint32_t (&r)[4], uint32_t a) { asm volatile("ld.shared.v4.u32 {%0,%1,%2,%3}, [%4];" : "=r"(r[0]), "=r"(r[1]), "=r"(r[2]), "=r"(r[3]) : "r"(a) : "memory"); }

__device__ __forceinline__ void wg_fence() { asm volatile("wgmma.fence.sync.aligned;" ::: "memory"); }
__device__ __forceinline__ void wg_commit() { asm volatile("wgmma.commit_group.sync.aligned;" ::: "memory"); }
template <int N> __device__ __forceinline__ void wg_wait() { asm volatile("wgmma.wait_group.sync.aligned %0;" ::"n"(N) : "memory"); }
__host__ __device__ constexpr uint32_t desc_lo(uint32_t off) { return ((SB + off) >> 4) | 0x10000u; }
template <int TA, int ACC> __device__ __forceinline__ void wgmma_n16(float (&d)[8], uint32_t da, uint32_t db) {
  asm volatile("{\n.reg .b64 da, db;\nmov.b64 da, {%8, 0x40000040};\nmov.b64 db, {%9, 0x40000040};\n"
               "wgmma.mma_async.sync.aligned.m64n16k16.f32.bf16.bf16 {%0,%1,%2,%3,%4,%5,%6,%7}, da, db, %11, 1, 1, %10, 0;\n}"
               : "+f"(d[0]), "+f"(d[1]), "+f"(d[2]), "+f"(d[3]), "+f"(d[4]), "+f"(d[5]), "+f"(d[6]), "+f"(d[7])
               : "r"(da), "r"(db), "n"(TA), "n"(ACC));
}
__device__ __forceinline__ void wgmma_n16_ones(float (&d)[8], uint32_t one, uint32_t db) {
  asm volatile("{\n.reg .b64 db;\nmov.b64 db, {%9, 0x40000040};\n"
               "wgmma.mma_async.sync.aligned.m64n16k16.f32.bf16.bf16 {%0,%1,%2,%3,%4,%5,%6,%7}, {%8,%8,%8,%8}, db, 1, 1, 1, 0;\n}"
               : "+f"(d[0]), "+f"(d[1]), "+f"(d[2]), "+f"(d[3]), "+f"(d[4]), "+f"(d[5]), "+f"(d[6]), "+f"(d[7])
               : "r"(one), "r"(db));
}
__device__ __forceinline__ void acc_fence(float (&d)[8]) {
  asm volatile("" : "+f"(d[0]), "+f"(d[1]), "+f"(d[2]), "+f"(d[3]), "+f"(d[4]), "+f"(d[5]), "+f"(d[6]), "+f"(d[7]) :: "memory");
}

template <int N, int STRIDE> __device__ __forceinline__ void load_units(uint2 (&v)[N], const uint32_t* p) {
#pragma unroll
  for (int i = 0; i < N; i++) v[i] = ldg_u64(p + i * STRIDE);
}
template <int N, int STRIDE> __device__ __forceinline__ int check_units(uint2 (&v)[N], const uint32_t* p, int rb) {
  int it = 0;
  while (true) {
    uint32_t mn = v[0].y;
#pragma unroll
    for (int i = 1; i < N; i++) mn = min(mn, v[i].y);
    if (mn != 0) break;
    backoff(rb);
#pragma unroll
    for (int i = 0; i < N; i++) if (v[i].y == 0) v[i] = ldg_u64(p + i * STRIDE);
    if (++it > SPIN_LIMIT) __trap();
  }
  return it;
}
__device__ __forceinline__ void reload_unit(uint2& v, const uint32_t* p) {
  asm volatile("{\n.reg .pred q;\nsetp.eq.u32 q, %1, 0;\n@q ld.relaxed.gpu.global.v2.b32 {%0, %1}, [%2];\n}" : "+r"(v.x), "+r"(v.y) : "l"(p) : "memory");
}
template <int N> __device__ __forceinline__ uint32_t min_flags(const uint2 (&v)[N]) {
  uint32_t a = v[0].y, b = v[1].y;
#pragma unroll
  for (int i = 2; i < N; i += 2) { a = min(a, v[i].y); b = min(b, v[i + 1].y); }
  return min(a, b);
}
__device__ __forceinline__ void sum4_to_smem(const uint2 (&v)[4], uint32_t dst) {
  const float c0 = (bf_lo(v[0].x) + bf_lo(v[1].x)) + (bf_lo(v[2].x) + bf_lo(v[3].x));
  const float c1 = (bf_hi(v[0].x) + bf_hi(v[1].x)) + (bf_hi(v[2].x) + bf_hi(v[3].x));
  const float c2 = (bf_lo(v[0].y) + bf_lo(v[1].y)) + (bf_lo(v[2].y) + bf_lo(v[3].y));
  const float c3 = (bf_hi(v[0].y) + bf_hi(v[1].y)) + (bf_hi(v[2].y) + bf_hi(v[3].y));
  sts1(dst, pack_bf16(c0, c1));
  sts1(dst + 128, pack_bf16(c2, c3));
}
__device__ __forceinline__ void load_a_t(uint32_t (&a)[8][4], uint32_t wbase, int w, int lane) {
  const int mi = lane >> 3, r = lane & 7;
  const uint32_t base = wbase + (w >> 2) * 16384 + (8 * (mi >> 1) + r) * 128 + (((2 * (w & 3) + (mi & 1)) ^ r) << 4);
#pragma unroll
  for (int ks = 0; ks < 8; ks++) ldsm4t(a[ks], base + ks * 2048);
}
__device__ __forceinline__ void mma128(float (&d)[4], const uint32_t (&a)[8][4], const uint32_t (&b)[4][4]) {
  float e[4][4] = {{0.f, 0.f, 0.f, 0.f}, {0.f, 0.f, 0.f, 0.f}, {0.f, 0.f, 0.f, 0.f}, {0.f, 0.f, 0.f, 0.f}};
#pragma unroll
  for (int kk = 0; kk < 4; kk++) { mma16816(e[(2 * kk) & 3], a[2 * kk], b[kk][0], b[kk][1]); mma16816(e[(2 * kk + 1) & 3], a[2 * kk + 1], b[kk][2], b[kk][3]); }
#pragma unroll
  for (int i = 0; i < 4; i++) d[i] = (e[0][i] + e[1][i]) + (e[2][i] + e[3][i]);
}
template <int NP> __device__ __forceinline__ bool sum_pieces(const uint32_t* p0, uint32_t one, float (&r)[4]) {
  uint2 v[NP / 4];
  load_units<NP / 4, 64>(v, p0);
  float d[4][4] = {};
#pragma unroll
  for (int i = 0; i < NP / 8; i++) { const uint32_t a[4] = {v[2 * i].x, v[2 * i].y, v[2 * i + 1].x, v[2 * i + 1].y}; mma16816(d[i & 3], a, one, one); }
  const bool ok = __all_sync(~0u, min_flags(v) != 0);
#pragma unroll
  for (int k = 0; k < 4; k++) r[k] = (d[0][k] + d[1][k]) + (d[2][k] + d[3][k]);
  return ok;
}
template <typename F> __device__ __forceinline__ float reduce_g(const float (&x)[4], int lane, F f) {
  const bool u4 = lane & 16, u3 = lane & 8;
  const float a0 = f(u4 ? x[2] : x[0], __shfl_xor_sync(~0u, u4 ? x[0] : x[2], 16));
  const float a1 = f(u4 ? x[3] : x[1], __shfl_xor_sync(~0u, u4 ? x[1] : x[3], 16));
  const float b = f(u3 ? a1 : a0, __shfl_xor_sync(~0u, u3 ? a0 : a1, 8));
  return f(b, __shfl_xor_sync(~0u, b, 4));
}

__global__ void __launch_bounds__(NTHREADS, 1)
fused_decode_kernel(__nv_bfloat16* __restrict__ gout, Scratch* __restrict__ gs, const uint8_t* __restrict__ gwmod,
                    const uint8_t* __restrict__ gx, const uint8_t* __restrict__ gc, uint32_t* __restrict__ gin,
                    const __grid_constant__ Params P) {
  constexpr Tune T{};
  extern __shared__ __align__(1024) uint8_t smem_raw[];
  const uint32_t sb = (uint32_t)__cvta_generic_to_shared(smem_raw);
  const int tid = threadIdx.x, lane = tid & 31;
  const int w = __shfl_sync(0xffffffffu, tid >> 5, 0);
  const int cta = blockIdx.x;
  const uint32_t bars = sb + OFF_BARS;
  auto BAR = [&](int i) { return bars + 8 * i; };
  auto inbox = [&](int c, int k) { uint32_t v; asm volatile("ld.shared.u8 %0, [%1];" : "=r"(v) : "r"(sb + OFF_SEL + c) : "memory"); return gin + blk(c, k, v); };
  const int g = lane >> 2, t = lane & 3;
  const int hI = cta >> 2, jI = cta & 3;
  const int bs = cta >> 1, hh = cta & 1;

  CLK_DECL;
  CLK(0);
  if (w == 8) {
    CLK(7);
    const uint32_t t_entry = gtime32();
    CLK(8);
    if (lane == 0) {
      if ((sb & 0xffffff) != SB) __trap();
      mbar_init(BAR(BAR_WQ), 1); mbar_init(BAR(BAR_WQ + 1), 1); mbar_init(BAR(BAR_XC), 1); mbar_init(BAR(BAR_C), 1);
      asm volatile("fence.mbarrier_init.release.cluster;" ::: "memory");
      asm volatile("prefetch.tensormap [%0];" ::"l"(&P.wq) : "memory");
      mbar_expect(BAR(BAR_XC), 8192); mbar_expect(BAR(BAR_C), 8192); mbar_expect(BAR(BAR_WQ), 16384); mbar_expect(BAR(BAR_WQ + 1), 16384);
      CLK(9);
    }
    __syncwarp();
    asm volatile("barrier.cta.arrive.aligned 0, %0;" ::"n"(NTHREADS) : "memory");
    CLK(10);
    uint32_t tn = t_entry + T.PC_T0 + ((bs * 37) & 63) * T.PC_STAG / 64;
    const int h = hI, j = jI;
    if (lane == 0) {
      uint64_t pol; asm volatile("createpolicy.fractional.L2::evict_first.b64 %0, 1.0;" : "=l"(pol));
#pragma unroll
      for (int u = 0; u < 4; u++) {
        until_ns(tn + u * T.PC_P1);
        if (u == 0) CLK(11);
        tma2d(sb + OFF_WQ + u * 8192, &P.wq, 128 * h + 64 * (u >> 1), 128 * j + 64 * (u & 1), BAR(BAR_WQ + (u >> 1)), pol);
        if (u == T.PC_XC) {
#pragma unroll
          for (int i = 0; i < 4; i++) { const int o = ((i + cta) & 3) * 2048; bulk_ld(sb + OFF_XS + o, gx + o, 2048, BAR(BAR_XC)); }
        }
        if (u == T.PC_C) {
#pragma unroll
          for (int i = 0; i < 4; i++) { const int o = ((i + cta) & 3) * 2048; bulk_ld(sb + OFF_CS + o, gc + o, 2048, BAR(BAR_C)); }
        }
        if (u == 0) {
          CLK(1);
          asm volatile("prefetch.tensormap [%0];" ::"l"(&P.wuk) : "memory");
          asm volatile("prefetch.tensormap [%0];" ::"l"(&P.wm2) : "memory");
          asm volatile("prefetch.tensormap [%0];" ::"l"(&P.ckv2) : "memory");
        }
      }
    }
    __syncwarp();
    tn += 4 * T.PC_P1;
    bar_sync(5, 64);
    if (lane == 0) {
      uint64_t pol; asm volatile("createpolicy.fractional.L2::evict_first.b64 %0, 1.0;" : "=l"(pol));
#pragma unroll
      for (int u = 0; u < 4; u++) {
        if ((u & 1) == (T.PC_W > 3) && T.PC_NW) mbar_wait(BAR(BAR_WQ + (u >> 1)));
        slot(tn, T.PC_SL);
        tma5d(sb + OFF_WUK + u * 8192, &P.wuk, 128 * h + 64 * (u >> 1), 0, 0, 0, 8 * j + 4 * (u & 1), BAR(BAR_WUK + (u >> 1)), pol);
        tn += T.PC_P1;
      }
#pragma unroll
      for (int u = 0; u < 2; u++) {
        if (u == (T.PC_W > 3) && T.PC_NW) mbar_wait(BAR(BAR_WUK));
        slot(tn, T.PC_SL);
        tma2d_nohint(sb + OFF_WM2 + u * 8192, &P.wm2, 1024 + 16 * cta, 256 * u, BAR(BAR_WM2));
        tn += T.PC_P1;
      }
      const int row0 = (bs >> 3) * 4096 + (bs & 7) * 64;
      uint32_t dst = sb + OFF_RING;
      const int p2 = T.PC_P2 + (32 - ((bs * 37) & 63)) * T.PC_DS / 1024;
#pragma unroll 1
      for (int n = 0; n < 31; n++) {
        if (n >= 4 && (n < 12 || (n & 3) == 0)) mbar_wait(BAR(n >= 12 ? BAR_EMPTY + (n >> 2) - 3 : n == 7 ? BAR_P0BD : (n == 8 || n == 9) ? BAR_P2D : BAR_P1D));
        if (n < T.PC_NW) {
          if (n >= T.PC_W) mbar_wait(BAR(BAR_FULL + n - T.PC_W));
          else if ((n & 1) == (T.PC_W > 3)) mbar_wait(BAR(n < 2 ? BAR_WUK + 1 : BAR_WM2));
        }
        slot(tn, T.PC_SL);
        tma3d(dst, &P.ckv2, 0, row0 + (n >> 2) * 512, 2 * (n & 3), BAR(BAR_FULL + n), pol);
        dst = (n == 11 || n == 23) ? sb + OFF_RING : dst + 16384;
        tn += n >= 15 ? p2 : T.PC_P2;
        if (n == 4) CLK(2);
        if (n == 12) CLK(3);
        if (n == 20) CLK(4);
        if (n == 28) CLK(5);
        if (n == 24) {
          asm volatile("prefetch.tensormap [%0];" ::"l"(&P.ckv1) : "memory");
          asm volatile("prefetch.tensormap [%0];" ::"l"(&P.wuv) : "memory");
          asm volatile("prefetch.tensormap [%0];" ::"l"(&P.wo) : "memory");
          asm volatile("prefetch.tensormap [%0];" ::"l"(&P.w1) : "memory");
          asm volatile("prefetch.tensormap [%0];" ::"l"(&P.w2) : "memory");
        }
      }
      slot(tn, T.PC_SL);
      tma3d(dst, &P.ckv1, 0, row0 + 7 * 512, 6, BAR(BAR_LAST + 3), pol);
      tma3d(dst + 8192, &P.ckv1, 0, row0 + 7 * 512, 7, BAR(BAR_LAST + 4), pol);
      tn += T.PC_P2;
      CLK(6);
      auto unit = [&](int u) {
        if (u < 4) tma5d(sb + OFF_WUV + u * 8192, &P.wuv, 128 * h + 64 * (u >> 1), 0, 4 * (j >> 1), 0, 2 * (j & 1) + (u & 1), BAR(BAR_WUV + (u >> 1)), pol);
        else if (u < 8) tma2d(sb + OFF_WO + (u - 4) * 8192, &P.wo, 128 * j + 64 * ((u - 4) >> 1), 128 * h + 64 * (u & 1), BAR(BAR_WO + ((u - 4) >> 1)), pol);
        else if (u < 10) { if (cta < NFF) tma2d_nohint(sb + OFF_W1 + (u - 8) * 16384, &P.w1, 32 * bs, 256 * (u - 8), BAR(BAR_W1)); }
        else if (cta < NFF) tma3d(sb + OFF_W2 + (u - 10) * 8192, &P.w2, 0, 32 * bs, 4 * hh + 2 * (u - 10), BAR(BAR_W2), pol);
      };
      mbar_wait(BAR(BAR_EMPTY + 5));
      if (T.PW_A >= 0) { mbar_wait(BAR(BAR_LAST + T.PW_A)); tn = gtime32(); }
      tn += T.PW_0 + ((cta * 37) & 127) * T.PW_ST / 128;
#pragma unroll
      for (int u = 0; u < 12; u++) {
        if (u == 8) mbar_wait(BAR(BAR_EMPTY + 6));
        until_ns(tn);
        unit(WSWAP && u >= 8 ? (u ^ 2) : u);
        tn += u < 3 ? T.PW_UV : u == 3 ? T.PW_G : u < 7 ? T.PW_O : u == 7 ? T.PW_G2 : u == 9 ? T.PW_G3 : T.PW_F;
      }
      CLK_DUMP();
    }
    return;
  }

  if (w == 9) {
    if (lane == 0) {
#pragma unroll
      for (int i = 0; i < NBARS; i++) mbar_init(BAR(i), i >= BAR_P1D ? 8 : i >= BAR_EMPTY ? 4 : 1);
      asm volatile("fence.mbarrier_init.release.cluster;" ::: "memory");
    }
    __syncwarp();
    mbar_expect(BAR(lane), lane == BAR_LAST + 3 ? 8192 : 16384);
    if (lane < BAR_ALLCLR - 32) mbar_expect(BAR(32 + lane), lane == 0 ? 8192 : lane == BAR_W1 - 32 ? 32768 : 16384);
    CLK(9);
    asm volatile("barrier.cta.arrive.aligned 5, 64;" ::: "memory");
    asm volatile("barrier.cta.arrive.aligned 0, %0;" ::"n"(NTHREADS) : "memory");
  }
  const uint32_t epoch = ldg_rlx1(&gs->epoch);

  if (w == 9) {
    const int mo = g * 512 + 16 * hI + 2 * jI;
    const uint32_t xo0 = ldg_nc1(gx + mo * 2), xo1 = ldg_nc1(gx + mo * 2 + 16);
    const int par = epoch & 1;
    const uint32_t t0 = gtime32();
    const uint4 z = make_uint4(0, 0, 0, 0);
    uint32_t sel;
    {
      uint32_t* pa = gin + blk(cta, 5, 0) + 960;
      uint32_t* pb = gin + blk(cta, 5, 1) + 960;
      until_ns(t0 + T.PR_T0);
      if (lane < 4) stg4(reinterpret_cast<uint4*>(lane & 2 ? pa : pb) + (lane & 1), z);
      uint32_t ma = 0xffffffffu, mb = 0xffffffffu;
      if (lane == 0) {
#pragma unroll 1
        for (int i = 0; i < 2 * T.PR_N; i++) {
          const uint32_t c0 = clk32();
          uint32_t v;
          asm volatile("atom.relaxed.gpu.global.add.u32 %0, [%1], 1;" : "=r"(v) : "l"(i & 1 ? pb : pa) : "memory");
          if (v == 0xffffffffu) __trap();
          const uint32_t d = clk32() - c0;
          if (i & 1) mb = min(mb, d); else ma = min(ma, d);
        }
      }
      sel = __shfl_sync(~0u, (uint32_t)(mb < ma), 0);
      if (T.LOC == 1) sel ^= 1;
      if (T.LOC == 2) sel ^= (cta ^ (cta >> 3)) & 1;
      const uint32_t sw = 2 * (epoch + 1) + sel;
      if (lane < 2) stg4(reinterpret_cast<uint4*>(gin + blk(cta, 5, 1) + 896) + lane, make_uint4(sw, sw, sw, sw));
    }
    until_ns(t0 + T.CLR_T0);
    {
      const int nb = (cta & 7) == 0 ? 16 : 12;
#pragma unroll 1
      for (int i0 = 0; i0 < nb; i0++) {
        uint4* q = reinterpret_cast<uint4*>(gin + blk(cta, i0 >> 1, sel) + (i0 & 1) * 512) + lane;
#pragma unroll
        for (int i = 0; i < 4; i++) if (i0 != 11 || i < 3) stg4(q + i * 32, z);
        backoff(T.CLR_CLK);
      }
      if (jI == 1) stg4(reinterpret_cast<uint4*>(gin + blk(cta, 6, sel)) + lane, z);
      if (lane < 2) stg4(reinterpret_cast<uint4*>(gin + blk(cta, 5, sel) + 928) + lane, z);
      CLK(1);
      {
        uint32_t sv = 0;
        uint32_t u[4];
#pragma unroll
        for (int i = 0; i < 4; i++) u[i] = ldg_rlx1(gin + blk(4 * lane + i, 5, 1) + 896);
#pragma unroll
        for (int i = 0; i < 4; i++) {
          int it = 0;
          while ((u[i] | 1) != 2 * (epoch + 1) + 1) { u[i] = ldg_rlx1(gin + blk(4 * lane + i, 5, 1) + 896); if (++it > SPIN_LIMIT) __trap(); }
          sv |= (u[i] & 1) << (8 * i);
        }
        sts1(sb + OFF_SEL + lane * 4, sv);
      }
      asm volatile("fence.acq_rel.gpu;" ::: "memory");
      CLK(2);
      __syncwarp();
      if (lane < NSYNC) asm volatile("red.relaxed.gpu.global.add.u32 [%0], 1;" ::"l"(&gs->sync[lane][0]) : "memory");
#pragma unroll
      for (int i = 0; i < 4; i++) stg4(reinterpret_cast<uint4*>(gs->QP[par ^ 1] + cta * 512) + i * 32 + lane, z);
      backoff(T.CLR_CLK);
#pragma unroll
      for (int i = 0; i < 4; i++) stg4(reinterpret_cast<uint4*>(gs->QX[par ^ 1] + cta * 512) + i * 32 + lane, z);
      stg4(reinterpret_cast<uint4*>(gs->MOD1[par ^ 1] + cta * 128) + lane, z);
      if (lane < 16) stg4(reinterpret_cast<uint4*>(gs->MOD2[par ^ 1] + cta * 64) + lane, z);
      if (lane == 0) {
        const uint32_t target = (epoch + 1) * NCTA;
        uint32_t c; int it = 0;
        do { backoff(T.CLR_CLK); asm volatile("ld.acquire.gpu.global.u32 %0, [%1];" : "=r"(c) : "l"(&gs->sync[cta % NSYNC][0]) : "memory"); if (++it > SPIN_LIMIT) __trap(); } while ((int)(c - target) < 0);
        mbar_arrive(BAR(BAR_ALLCLR));
      }
      __syncwarp();
    }
    CLK(3);
    uint2 gg[2];
    {
      const uint32_t* pg = gs->MOD2[par] + cta * 16 + g * 2;
      load_units<2, 3 * 2048>(gg, pg);
      check_units<2, 3 * 2048>(gg, pg, T.RB);
    }
    uint32_t anchor;
    {
      uint32_t* const po = inbox(NTS * (lane & (128 / NTS - 1)), 5) + 928;
      const uint32_t* const pi = inbox(cta & ~(NTS - 1), 5) + 928;
      mbar_wait(BAR(BAR_LAST + T.TS_P));
      unsigned long long now; asm volatile("mov.u64 %0, %%globaltimer;" : "=l"(now));
      if (lane < 128 / NTS) {
        asm volatile("red.relaxed.gpu.global.max.u64 [%0], %1;" ::"l"(po + 2), "l"(now) : "memory");
        asm volatile("red.relaxed.gpu.global.add.u32 [%0], 1;" ::"l"(po + 1) : "memory");
      }
      backoff(T.D_TS);
      uint4 v; int it = 0;
      do { v = ldg_2u64(pi); if (++it > SPIN_LIMIT) __trap(); } while (v.y != NCTA);
      const int age = min(max((int)(gtime32() - v.z), 0), 4000);
      anchor = clk32() - age * 7 / 4 + T.TS_O;
      if (lane == 0) { sts1(sb + OFF_TS, anchor); mbar_arrive(BAR(BAR_TS)); }
      CLK(10);
    }
    {
      const uint32_t* pm = pin(inbox(4 * hI + 1, 6) + lane * 4);
      wait_clk(anchor, T.A_M);
      uint4 ml = ldg_2u64(pm);
      int it = 0;
      while (ml.y == 0 || ml.w == 0) { ml = ldg_2u64(pm); if (++it > SPIN_LIMIT) __trap(); }
      __syncwarp();
      ITS(2, it);
      float M = fmaxf(__uint_as_float(ml.x), __uint_as_float(ml.z));
      M = fmaxf(M, __shfl_xor_sync(~0u, M, 1)); M = fmaxf(M, __shfl_xor_sync(~0u, M, 2));
      const float e0 = ex2(__uint_as_float(ml.x) - M), e1 = ex2(__uint_as_float(ml.z) - M);
      float l = e0 * __uint_as_float(ml.y) + e1 * __uint_as_float(ml.w);
      l += __shfl_xor_sync(~0u, l, 1); l += __shfl_xor_sync(~0u, l, 2);
      const float inv = __fdividef(1.f, l);
      sts2f(sb + OFF_WV + lane * 8, e0 * inv, e1 * inv);
      __syncwarp();
      if (lane == 0) mbar_arrive(BAR(BAR_WV));
      CLK(11);
    }
    uint32_t* x3o[4];
#pragma unroll
    for (int i = 0; i < 4; i++) x3o[i] = pin(inbox(32 * i + 8 * t, 6 + (cta >> 6)) + (cta & 63) * 16 + g * 2);
    uint32_t* const fo = pin(reinterpret_cast<uint32_t*>(gout) + mo / 2 + 4 * (t & 1));
    const uint32_t* const p3 = pin(gin + blk(cta, 4, sel) + t * 16 + g * 2);
    const uint32_t* const p4 = pin(gin + blk(cta, 5, sel) + t * 16 + g * 2);
    const uint32_t one = pin((g & 1) ? 0x3f800000u : 0x00003f80u);
    const float xf[4] = {pin(bf_lo(xo0)), pin(bf_hi(xo0)), pin(bf_lo(xo1)), pin(bf_hi(xo1))};
    const float ga[4] = {pin(bf_lo(gg[0].x)), pin(bf_hi(gg[0].x)), pin(bf_lo(gg[0].y)), pin(bf_hi(gg[0].y))};
    mbar_wait(BAR(BAR_P5D));
    backoff(T.D_X3A);
    wait_clk(anchor, T.A_X1 + T.R_X3A);
    CLK(4);
    float r[4];
    uint32_t x20, x21;
    int it = 0;
    bool ok;
    do {
      ok = sum_pieces<32>(p3, one, r);
      x20 = pack_bf16(xf[0] + ga[0] * r[0], xf[1] + ga[1] * r[1]); x21 = pack_bf16(xf[2] + ga[2] * r[2], xf[3] + ga[3] * r[3]);
#pragma unroll
      for (int i = 0; i < 4; i++) stg_u64_unless(!ok || (i == 3 && t >= 2), x3o[i], x20, x21);
    } while (!ok && ++it < SPIN_LIMIT);
    CLK(6);
    ITS(0, it);
    const uint32_t xw = (t & 1) ? x21 : x20, gw = (t & 1) ? gg[1].y : gg[1].x;
    const float xa = pin(bf_lo(xw)), xb = pin(bf_hi(xw)), gba = pin(bf_lo(gw)), gbb = pin(bf_hi(gw));
    if (cta < NFF) { mbar_wait(BAR(BAR_P7D)); backoff(T.D_FIN); } else backoff(T.D_FIN2);
    CLK(7);
    do {
      ok = sum_pieces<NFG>(p4, one, r);
      const uint32_t o = pack_bf16(xa + gba * ((t & 1) ? r[2] : r[0]), xb + gbb * ((t & 1) ? r[3] : r[1]));
      if (ok && t < 2) asm volatile("st.global.u32 [%0], %1;" ::"l"(fo), "r"(o) : "memory");
    } while (!ok && ++it < SPIN_LIMIT);
    if (!ok) __trap();
    ITS(1, it);
    CLK(8);
    CLK_DUMP();
    if (cta == 0 && lane == 0) stg1(&gs->epoch, epoch + 1);
    return;
  }

  const int wg = w >> 2, wq = w & 3;
  uint32_t tstore;
  {
    const uint8_t* pw = gwmod + (size_t)(128 * jI + 16 * w + 4 * (g >> 1) + (g & 1)) * 6144 + 64 * hI + 16 * t;
    const uint4 w0 = ldg_nc4(pw), w1 = ldg_nc4(pw + 2 * 6144);
    const uint2 cc = ldg_nc2(gc + g * 1024 + 256 * jI + 32 * w + 8 * t);
    CLK(40);
    const uint32_t a[4] = {silu2(cc.x), 0u, silu2(cc.y), 0u};
    float d[4][4] = {{0.f, 0.f, 0.f, 0.f}, {0.f, 0.f, 0.f, 0.f}, {0.f, 0.f, 0.f, 0.f}, {0.f, 0.f, 0.f, 0.f}};
    mma16816(d[0], a, movm(w0.x), movm(w1.x)); mma16816(d[1], a, movm(w0.y), movm(w1.y));
    mma16816(d[2], a, movm(w0.z), movm(w1.z)); mma16816(d[3], a, movm(w0.w), movm(w1.w));
    CLK(1);
    sts4f(sb + OFF_P0S + w * 1088 + lane * 16, d[0][0], d[0][1], d[1][0], d[1][1]);
    sts4f(sb + OFF_P0S + w * 1088 + 544 + lane * 16, d[2][0], d[2][1], d[3][0], d[3][1]);
    bar_sync(0, NTHREADS);
    if (tid < 128) {
      const uint32_t src = sb + OFF_P0S + ((tid >> 2) & 1) * 544 + (((tid >> 3) & 7) * 4 + 2 * (tid >> 6) + (tid & 1)) * 16 + ((tid >> 1) & 1) * 8;
      float2 v[8];
#pragma unroll
      for (int i = 0; i < 8; i++) v[i] = ldsf2(src + i * 1088);
      const float ax = ((v[0].x + v[1].x) + (v[2].x + v[3].x)) + ((v[4].x + v[5].x) + (v[6].x + v[7].x));
      const float ay = ((v[0].y + v[1].y) + (v[2].y + v[3].y)) + ((v[4].y + v[5].y) + (v[6].y + v[7].y));
      stg1(gs->MOD1[epoch & 1] + jI * 4096 + hI * 128 + tid, nz(pack_bf16(ax, ay)));
    }
    tstore = clk32();
  }
  CLK(2);
  const int par = epoch & 1;
  uint32_t cf[4][4];
  mbar_wait(BAR(BAR_XC));
  {
    uint32_t u[2][4];
    lds4(u[0], sb + OFF_XS + w * 1024 + lane * 16); lds4(u[1], sb + OFF_XS + w * 1024 + 512 + lane * 16);
    float v[16];
#pragma unroll
    for (int i = 0; i < 8; i++) { v[2 * i] = bf_lo(u[i >> 2][i & 3]); v[2 * i + 1] = bf_hi(u[i >> 2][i & 3]); }
    float s = 0.f;
#pragma unroll
    for (int i = 0; i < 16; i++) s += v[i];
#pragma unroll
    for (int o = 16; o; o >>= 1) s += __shfl_xor_sync(~0u, s, o);
    const float mu = s * (1.f / 512.f);
    float q = 0.f;
#pragma unroll
    for (int i = 0; i < 16; i++) { v[i] -= mu; q += v[i] * v[i]; }
#pragma unroll
    for (int o = 16; o; o >>= 1) q += __shfl_xor_sync(~0u, q, o);
    const float rs = rsqrtf(q * (1.f / 512.f) + 1e-5f);
    const bool hi = jI & 2;
    uint32_t o[4];
#pragma unroll
    for (int i = 0; i < 4; i++) o[i] = pack_bf16((hi ? v[8 + 2 * i] : v[2 * i]) * rs, (hi ? v[9 + 2 * i] : v[2 * i + 1]) * rs);
    if ((lane >> 4) == (jI & 1)) sts4(sb + OFF_XN + w * 272 + (lane & 15) * 16, make_uint4(o[0], o[1], o[2], o[3]));
  }
  CLK(3);
  uint32_t aw[8][4];
  {
    const uint32_t* pm = pin(gs->MOD1[par] + (8 * jI + w) * 64 + lane * 2);
    uint32_t* const qpo = pin(gs->QP[par] + (cta * 256 + tid) * 2);
    wait_clk(tstore, T.D_MOD);
    CLK(4);
    uint2 v[8];
    load_units<8, 2048>(v, pm);
    cbar();
    const uint32_t xn0 = lds1(sb + OFF_XN + g * 272 + w * 32 + t * 4), xn1 = lds1(sb + OFF_XN + g * 272 + w * 32 + 16 + t * 4);
    const bool early = __all_sync(~0u, mbar_test(BAR(BAR_WQ + wg)));
    if (early) load_a_t(aw, sb + OFF_WQ, w, lane);
    int it = 0;
    while (true) {
      uint32_t mn = 0xffffffffu;
#pragma unroll
      for (int i = 0; i < 8; i++) mn = min(mn, min(v[i].x, v[i].y));
      if (mn != 0) break;
#pragma unroll
      for (int i = 0; i < 8; i++) if (v[i].x == 0 || v[i].y == 0) v[i] = ldg_u64(pm + i * 2048);
      if (++it > SPIN_LIMIT) __trap();
    }
    CLK(5);
    ITS(0, it);
    float sc[2][4];
#pragma unroll
    for (int i = 0; i < 2; i++) {
      sc[i][0] = (bf_lo(v[i].x) + bf_lo(v[2 + i].x)) + (bf_lo(v[4 + i].x) + bf_lo(v[6 + i].x));
      sc[i][1] = (bf_hi(v[i].x) + bf_hi(v[2 + i].x)) + (bf_hi(v[4 + i].x) + bf_hi(v[6 + i].x));
      sc[i][2] = (bf_lo(v[i].y) + bf_lo(v[2 + i].y)) + (bf_lo(v[4 + i].y) + bf_lo(v[6 + i].y));
      sc[i][3] = (bf_hi(v[i].y) + bf_hi(v[2 + i].y)) + (bf_hi(v[4 + i].y) + bf_hi(v[6 + i].y));
    }
    sts2(sb + OFF_BS1 + (w >> 1) * 512 + lane * 16 + (w & 1) * 8,
         pack_bf16(bf_lo(xn0) * (1.f + sc[1][0]) + sc[0][0], bf_hi(xn0) * (1.f + sc[1][1]) + sc[0][1]),
         pack_bf16(bf_lo(xn1) * (1.f + sc[1][2]) + sc[0][2], bf_hi(xn1) * (1.f + sc[1][3]) + sc[0][3]));
    if (!early) { mbar_wait(BAR(BAR_WQ + wg)); load_a_t(aw, sb + OFF_WQ, w, lane); }
    CLK(6);
    cbar();
    uint32_t b[4][4];
#pragma unroll
    for (int kk = 0; kk < 4; kk++) lds4(b[kk], sb + OFF_BS1 + kk * 512 + lane * 16);
    float d[4];
    mma128(d, aw, b);
    stg_u64(qpo, pack_bf16(d[0], d[1]), pack_bf16(d[2], d[3]));
    tstore = clk32();
    CLK(7);
    if (wg) {
      mbar_wait(BAR(BAR_C));
#pragma unroll
      for (int i = 0; i < 4; i++) lds4(cf[i], sb + OFF_CS + g * 1024 + wq * 256 + i * 64 + t * 16);
#pragma unroll
      for (int i = 0; i < 16; i++) cf[i >> 2][i & 3] = silu2(cf[i >> 2][i & 3]);
    }
    __syncwarp();
    if (lane == 0) mbar_arrive(BAR(BAR_P1D));
  }
  {
    const uint32_t* pq = pin(gs->QP[par] + (hI * 4 * 256 + tid) * 2);
    uint32_t* const qxo = pin(gs->QX[par] + (g * 32 + hI) * 256 + 64 * jI + 8 * w + 2 * t);
    uint2 v[4];
    wait_clk(tstore, T.D_QP);
    CLK(8);
    load_units<4, 512>(v, pq);
    const uint32_t abase = sb + OFF_WUK + (16 * w + (lane & 15)) * 128;
    auto load_half = [&](int hf) {
#pragma unroll
      for (int ks = 0; ks < 4; ks++) ldsm4(aw[4 * hf + ks], abase + hf * 16384 + (((2 * ks + (lane >> 4)) ^ (lane & 7)) << 4));
    };
    mbar_wait(BAR(BAR_WUK));
    load_half(0);
    const bool early = __all_sync(~0u, mbar_test(BAR(BAR_WUK + 1)));
    if (early) load_half(1);
    const int it = check_units<4, 512>(v, pq, T.RB);
    CLK(9);
    ITS(1, it);
    sum4_to_smem(v, sb + OFF_BS2 + (16 * w + g) * 16 + t * 4);
    if (!early) { mbar_wait(BAR(BAR_WUK + 1)); load_half(1); }
    CLK(10);
    cbar();
    uint32_t b[4][4];
#pragma unroll
    for (int kk = 0; kk < 4; kk++) ldsm4t(b[kk], sb + OFF_BS2 + (32 * kk + lane) * 16);
    float d[4];
    mma128(d, aw, b);
    const float sc = 0.08838834764831845f * 1.4426950408889634f;
    stg_u64(qxo, movm(pack_bf16(d[0] * sc, d[1] * sc)), movm(pack_bf16(d[2] * sc, d[3] * sc)));
    tstore = clk32();
    CLK(11);
    if (lane == 0) mbar_arrive(BAR(BAR_P2D));
  }
  if (wg) {
    const int mi = lane >> 3, r = lane & 7;
    const uint32_t a0 = sb + OFF_WM2 + (8 * (r >> 1) + (r & 1) + 2 * (mi >> 1)) * 32 + (mi & 1) * 16;
    mbar_wait(BAR(BAR_WM2));
#pragma unroll
    for (int s = 0; s < 8; s++) ldsm4t(aw[s], a0 + (128 * wq + 32 * (s >> 1) + 4 * (s & 1)) * 32);
    float d[4];
    mma128(d, aw, cf);
    sts4f(sb + OFF_P0B + (tid - 128) * 16, d[0], d[1], d[2], d[3]);
    if (lane == 0) mbar_arrive(BAR(BAR_P0BD));
    bar_sync(3, 128);
    if (w == 4) {
      float4 v[4];
#pragma unroll
      for (int i = 0; i < 4; i++) v[i] = ldsf4(sb + OFF_P0B + (i * 32 + lane) * 16);
      stg_u64(gs->MOD2[par] + cta * 64 + t * 16 + g * 2, movm(pack_bf16((v[0].x + v[1].x) + (v[2].x + v[3].x), (v[0].y + v[1].y) + (v[2].y + v[3].y))),
              movm(pack_bf16((v[0].z + v[1].z) + (v[2].z + v[3].z), (v[0].w + v[1].w) + (v[2].w + v[3].w))));
    }
    CLK(15);
  }
  {
    const uint32_t* qx = pin(gs->QX[par] + ((bs >> 3) * 32 + 16 * hh) * 256 + tid * 4);
    const int ch = tid & 63, h0 = tid >> 6;
    const uint32_t dst = sb + OFF_Q + (ch >> 3) * 2048 + h0 * 128;
    wait_clk(tstore, T.D_QX);
    CLK(12);
    uint4 v[4];
#pragma unroll
    for (int i = 0; i < 4; i++) v[i] = ldg_2u64(qx + i * 1024);
    int it = 0;
    while (true) {
      uint32_t mn = 0xffffffffu;
#pragma unroll
      for (int i = 0; i < 4; i++) mn = min(mn, min(v[i].y, v[i].w));
      if (mn != 0) break;
#pragma unroll
      for (int i = 0; i < 4; i++) if (v[i].y == 0 || v[i].w == 0) v[i] = ldg_2u64(qx + i * 1024);
      if (++it > SPIN_LIMIT) __trap();
    }
    CLK(13);
    ITS(2, it);
#pragma unroll
    for (int i = 0; i < 4; i++) sts4(dst + i * 512 + (((ch & 7) ^ ((4 * i + h0) & 7)) << 4), v[i]);
    asm volatile("fence.proxy.async.shared::cta;" ::: "memory");
    CLK(14);
    cbar();
  }

  uint2 cbf[4], sbf[4];
  const uint32_t* const pcb = gs->MOD2[par] + 2048 + (16 * w + t) * 16 + g * 2;
  uint32_t thand, anchor;
  if (wg == 0) {
    float mh[4];
    float L[8];
#pragma unroll
    for (int i = 0; i < 4; i++) { L[2 * i] = L[2 * i + 1] = 0.f; mh[i] = -INFINITY; }
    constexpr uint32_t dq = desc_lo(OFF_Q);
    const uint32_t ptw = sb + OFF_PT + (8 * (lane >> 4) + (lane & 7)) * 128 + (((2 * wq + ((lane >> 3) & 1)) ^ (lane & 7)) << 4);
    float S[8];
    auto softmax = [&](int tl) {
      auto write_p = [&](const float (&x)[8]) {
        float p[8];
#pragma unroll
        for (int i = 0; i < 8; i++) p[i] = ex2(x[i]);
        stsm4t(ptw + (tl & 1) * 2048, pack_bf16(p[0], p[1]), pack_bf16(p[2], p[3]), pack_bf16(p[4], p[5]), pack_bf16(p[6], p[7]));
        asm volatile("fence.proxy.async.shared::cta;" ::: "memory");
      };
      float x[8];
#pragma unroll
      for (int i = 0; i < 8; i++) x[i] = S[i] - mh[2 * (i >> 2) + (i & 1)];
      if (tl) write_p(x);
      const float ex = fmaxf(fmaxf(fmaxf(x[0], x[1]), fmaxf(x[2], x[3])), fmaxf(fmaxf(x[4], x[5]), fmaxf(x[6], x[7])));
      if (tl == 0 || bar_over(ex)) {
        float mx[4];
#pragma unroll
        for (int i = 0; i < 4; i++) mx[i] = fmaxf(S[4 * (i >> 1) + (i & 1)], S[4 * (i >> 1) + 2 + (i & 1)]);
        const float a = reduce_g(mx, lane, [](float u, float v) { return fmaxf(u, v); });
        stsf(sb + OFF_RED + wq * 64 + (8 * (lane >> 4) + 2 * t + ((lane >> 3) & 1)) * 4, a);
        bar_sync(2, 128);
#pragma unroll
        for (int jn = 0; jn < 2; jn++) {
          float m0 = mh[2 * jn], m1 = mh[2 * jn + 1];
#pragma unroll
          for (int i = 0; i < 4; i++) { const float2 v = ldsf2(sb + OFF_RED + i * 64 + (8 * jn + 2 * t) * 4); m0 = fmaxf(m0, v.x); m1 = fmaxf(m1, v.y); }
          const float a0 = ex2(mh[2 * jn] - m0), a1 = ex2(mh[2 * jn + 1] - m1);
          mh[2 * jn] = m0; mh[2 * jn + 1] = m1;
          L[4 * jn] *= a0; L[4 * jn + 1] *= a1; L[4 * jn + 2] *= a0; L[4 * jn + 3] *= a1;
          if (tid < 4) sts2f(sb + OFF_ALPHA + (8 * jn + 2 * t) * 4, a0, a1);
        }
#pragma unroll
        for (int i = 0; i < 8; i++) x[i] = S[i] - mh[2 * (i >> 2) + (i & 1)];
        write_p(x);
        cbar();
      }
      const uint32_t dpt = __shfl_sync(~0u, desc_lo(OFF_PT) + (tl & 1) * 128, 0);
      wg_fence();
#pragma unroll
      for (int ks = 0; ks < 4; ks++) wgmma_n16_ones(L, ONE2, dpt + ks * 2);
      wg_commit();
    };
    uint32_t da = desc_lo(OFF_RING);
#pragma unroll 1
    for (int tl = 0; tl < 7; tl++) {
      uint32_t ok = 0;
#pragma unroll
      for (int u = 0; u < 4; u++) ok += mbar_test(BAR(BAR_FULL + 4 * tl + u));
      ok = __reduce_min_sync(~0u, ok);
      const uint32_t du = __shfl_sync(~0u, da, 0);
#pragma unroll
      for (int u = 0; u < 4; u++) {
        if (ok != 4) mbar_wait(BAR(BAR_FULL + 4 * tl + u));
        wg_fence();
#pragma unroll
        for (int k = 0; k < 8; k++) {
          const int i = 8 * u + k;
          if (i == 0) wgmma_n16<0, 0>(S, du, dq); else wgmma_n16<0, 1>(S, du + (i >> 2) * 512 + (i & 3) * 2, dq + (i >> 2) * 128 + (i & 3) * 2);
        }
        wg_commit();
      }
      wg_wait<0>();
      acc_fence(S); acc_fence(L);
      if (tl == 0) CLK(15);
      if (tl == 1) CLK(17);
      softmax(tl);
      if (tl == 0) CLK(16);
      if (tl == 1) CLK(18);
      if (tl == 3) CLK(19);
      if (tl == 6) CLK(20);
      da = (tl == 2 || tl == 5) ? da - 8192 : da + 4096;
    }
    if (cta < NFF) { load_units<4, 64>(sbf, pcb); load_units<4, 64>(cbf, pcb + 2048); }
    mbar_wait(BAR(BAR_ALLCLR));
    uint32_t* const mlo = pin(inbox(4 * (16 * hh + 4 * (g & 2) + 2 * t + (g & 1)) + 1, 6) + bs * 2);
#pragma unroll
    for (int i = 0; i < 32; i++) {
      if (i == 0 || i == 8 || i == 16 || i == 24 || i == 28) {
        if (i) wg_commit();
        mbar_wait(BAR(BAR_LAST + (i == 28 ? 4 : i >> 3)));
        if (i == 28) CLK(21);
        wg_fence();
      }
      if (i == 0) wgmma_n16<0, 0>(S, da, dq); else wgmma_n16<0, 1>(S, da + (i >> 2) * 512 + (i & 3) * 2, dq + (i >> 2) * 128 + (i & 3) * 2);
    }
    wg_commit();
    wg_wait<0>();
    acc_fence(S); acc_fence(L);
    CLK(22);
    softmax(7);
    CLK(23);
    thand = clk32();
    wg_wait<0>();
    acc_fence(L);
    if (tid < 16) stg_u64(mlo, __float_as_uint(g & 2 ? (g & 1 ? mh[3] : mh[2]) : (g & 1 ? mh[1] : mh[0])), __float_as_uint(g & 2 ? (g & 1 ? L[5] : L[4]) : (g & 1 ? L[1] : L[0])));
    CLK(24);
  } else {
    float O[8][8];
#pragma unroll
    for (int i = 0; i < 8; i++)
#pragma unroll
      for (int k = 0; k < 8; k++) O[i][k] = 0.f;
    constexpr uint32_t dp = desc_lo(OFF_PT);
    auto handover = [&](int tl) {
      if (tl == 0) { cbar(); return; }
      if (bar_over(0.f)) {
        cbar();
#pragma unroll
        for (int jn = 0; jn < 2; jn++) {
          const float2 a = ldsf2(sb + OFF_ALPHA + (8 * jn + 2 * t) * 4);
#pragma unroll
          for (int mb = 0; mb < 8; mb++) { O[mb][4 * jn] *= a.x; O[mb][4 * jn + 1] *= a.y; O[mb][4 * jn + 2] *= a.x; O[mb][4 * jn + 3] *= a.y; }
        }
      }
    };
    uint32_t da = desc_lo(OFF_RING);
#pragma unroll 1
    for (int tl = 0; tl < 7; tl++) {
      handover(tl);
      const uint32_t dpt = dp + (tl & 1) * 128;
      wg_fence();
#pragma unroll
      for (int i = 0; i < 32; i++) wgmma_n16<1, 1>(O[i >> 2], da + (i >> 2) * 512 + (i & 3) * 128, dpt + (i & 3) * 2);
      wg_commit();
      wg_wait<0>();
#pragma unroll
      for (int mb = 0; mb < 8; mb++) acc_fence(O[mb]);
      if (lane == 0) mbar_arrive(BAR(BAR_EMPTY + tl));
      if (tl == 0) CLK(16);
      if (tl == 1) CLK(18);
      if (tl == 3) CLK(19);
      if (tl == 6) CLK(20);
      da = (tl == 2 || tl == 5) ? da - 8192 : da + 4096;
    }
    if (cta < NFF) { load_units<4, 64>(sbf, pcb); load_units<4, 64>(cbf, pcb + 2048); }
    mbar_wait(BAR(BAR_ALLCLR));
    uint32_t* x1o[8];
#pragma unroll
    for (int i = 0; i < 8; i++)
      x1o[i] = pin(inbox((16 * hh + 8 * ((i >> 1) & 1) + 2 * t + (i & 1)) * 4 + 2 * (i >> 2) + (wq >> 1), bs >> 4) + (bs & 15) * 64 + ((wq & 1) * 8 + g) * 4);
    handover(7);
    CLK(23);
    thand = clk32();
    auto pv = [&](int mb0, int n) {
      wg_fence();
#pragma unroll
      for (int i = 0; i < 16; i++)
        if (i < 4 * n) wgmma_n16<1, 1>(O[mb0 + (i >> 2)], desc_lo(65536) + (mb0 + (i >> 2)) * 512 + (i & 3) * 128, dp + 128 + (i & 3) * 2);
      wg_commit();
    };
    auto publish = [&](int J) {
#pragma unroll
      for (int k = 0; k < 4; k++) acc_fence(O[4 * J + k]);
#pragma unroll
      for (int i = 0; i < 4; i++) {
        const int k = 4 * (i >> 1) + (i & 1);
        stg_cvt8(x1o[4 * J + i], O[4 * J][k], O[4 * J][k + 2], O[4 * J + 1][k], O[4 * J + 1][k + 2],
                 O[4 * J + 2][k], O[4 * J + 2][k + 2], O[4 * J + 3][k], O[4 * J + 3][k + 2]);
      }
    };
    pv(0, 4); pv(4, 4);
    wg_wait<1>(); publish(0);
    wg_wait<0>(); publish(1);
    CLK(24);
  }

  {
    const uint32_t* px = pin(inbox(cta, w >> 1) + (w & 1) * 512 + lane * 2);
    uint32_t* const x2o = pin(inbox(cta, 4) + 512 + tid * 2);
    mbar_wait(BAR(BAR_TS));
    anchor = lds1(sb + OFF_TS);
    const uint32_t sdst = pin(sb + OFF_BS4 + w * 272 + lane * 8), ssrc = pin(sb + OFF_BS4 + (lane & 7) * 272 + (lane >> 3) * 16);
    wait_clk(thand, T.D_X1);
    wait_clk(anchor, T.A_X1);
    CLK(25);
    uint2 v[8];
    load_units<8, 64>(v, px);
    bool early = __all_sync(~0u, mbar_test(BAR(BAR_WUV + wg)));
    if (early) load_a_t(aw, sb + OFF_WUV, w, lane);
    mbar_wait(BAR(BAR_WV));
    const float4 wa = ldsf4(sb + OFF_WV + w * 32), wb = ldsf4(sb + OFF_WV + w * 32 + 16);
    const float wv[8] = {wa.x, wa.y, wa.z, wa.w, wb.x, wb.y, wb.z, wb.w};
    CLK(27);
    int it = 0;
    while (true) {
      float a0 = 0.f, a1 = 0.f, a2 = 0.f, a3 = 0.f;
#pragma unroll
      for (int i = 0; i < 8; i++) { a0 += wv[i] * bf_lo(v[i].x); a1 += wv[i] * bf_hi(v[i].x); a2 += wv[i] * bf_lo(v[i].y); a3 += wv[i] * bf_hi(v[i].y); }
      sts2(sdst, pack_bf16(a0, a1), pack_bf16(a2, a3));
      CLK(29);
      const uint32_t bad = cbar_bad(min_flags(v));
      uint32_t b[4][4];
#pragma unroll
      for (int kk = 0; kk < 4; kk++) ldsm4(b[kk], ssrc + kk * 64);
#pragma unroll
      for (int i = 0; i < 8; i++) reload_unit(v[i], px + i * 64);
      if (__builtin_expect(!early, 0)) { mbar_wait(BAR(BAR_WUV + wg)); load_a_t(aw, sb + OFF_WUV, w, lane); early = true; }
      float d[4];
      mma128(d, aw, b);
      stg_u64_unless(bad, x2o, pack_bf16(d[0], d[1]), pack_bf16(d[2], d[3]));
      if (!bad) break;
      it += 1 + check_units<8, 64>(v, px, 0);
      cbar();
    }
    ITS(4, it);
    tstore = clk32();
    CLK(30);
  }
  {
    uint32_t* const o = pin(inbox(4 * (8 * jI + w) + t, 4) + hI * 16 + g * 2);
    const uint32_t* x2i[4];
#pragma unroll
    for (int i = 0; i < 4; i++) x2i[i] = pin(inbox(4 * hI + i, 4) + 512 + tid * 2);
    const uint32_t sdst = pin(sb + OFF_BS5 + (16 * w + g) * 16 + t * 4), ssrc = pin(sb + OFF_BS5 + lane * 16);
    wait_clk(tstore, T.D_X2);
    wait_clk(anchor, T.A_X1 + T.R_X2);
    uint2 v[4];
#pragma unroll
    for (int i = 0; i < 4; i++) v[i] = ldg_u64(x2i[i]);
    bool early = __all_sync(~0u, mbar_test(BAR(BAR_WO + wg)));
    if (early) load_a_t(aw, sb + OFF_WO, w, lane);
    CLK(31);
    int it = 0;
    while (true) {
      sum4_to_smem(v, sdst);
      CLK(32);
      const uint32_t bad = cbar_bad(min_flags(v));
      uint32_t b[4][4];
#pragma unroll
      for (int kk = 0; kk < 4; kk++) ldsm4t(b[kk], ssrc + kk * 512);
#pragma unroll
      for (int i = 0; i < 4; i++) reload_unit(v[i], x2i[i]);
      if (__builtin_expect(!early, 0)) { mbar_wait(BAR(BAR_WO + wg)); load_a_t(aw, sb + OFF_WO, w, lane); early = true; }
      float d[4];
      mma128(d, aw, b);
      stg_u64_unless(bad, o, movm(pack_bf16(d[0], d[1])), movm(pack_bf16(d[2], d[3])));
      if (!bad) break;
      it++;
      while (min_flags(v) == 0) {
#pragma unroll
        for (int i = 0; i < 4; i++) reload_unit(v[i], x2i[i]);
        if (++it > SPIN_LIMIT) __trap();
      }
      cbar();
    }
    ITS(5, it);
    tstore = clk32();
    CLK(33);
    if (lane == 0) mbar_arrive(BAR(BAR_P5D));
  }
  if (cta < NFF) {
    const int mi = lane >> 3, r = lane & 7;
    uint32_t a1[2][4][4], a2[2][2][4];
    check_units<4, 64>(sbf, pcb, T.RB);
    check_units<4, 64>(cbf, pcb + 2048, T.RB);
    __syncwarp();
#pragma unroll
    for (int s = 0; s < 4; s++) { cbf[s].x = hadd2(cbf[s].x, ONE2); cbf[s].y = hadd2(cbf[s].y, ONE2); }
    mbar_wait(BAR(BAR_W1));
#pragma unroll
    for (int mt = 0; mt < 2; mt++) {
#pragma unroll
      for (int ks = 0; ks < 4; ks++) ldsm4t(a1[mt][ks], sb + OFF_W1 + (64 * w + 16 * ks + 8 * (mi >> 1) + r) * 64 + (((2 * mt + (mi & 1)) ^ (r >> 1)) << 4));
      float u[4] = {0.f, 0.f, 0.f, 0.f}, vv[4] = {0.f, 0.f, 0.f, 0.f};
#pragma unroll
      for (int s = 0; s < 4; s++) { mma16816(u, a1[mt][s], cbf[s].x, cbf[s].y); mma16816(vv, a1[mt][s], sbf[s].x, sbf[s].y); }
      sts4f(sb + OFF_REDU + w * 1024 + mt * 512 + lane * 16, u[0], u[1], u[2], u[3]);
      sts4f(sb + OFF_REDV + w * 1024 + mt * 512 + lane * 16, vv[0], vv[1], vv[2], vv[3]);
    }
    const uint32_t* xb = pin(inbox(cta & ~7, 6 + wg) + (16 * wq + t) * 16 + g * 2);
    uint32_t* const ox[2] = {pin(inbox(64 * hh + 8 * w + t, 5) + bs * 16 + g * 2), pin(inbox(64 * hh + 8 * w + 4 + t, 5) + bs * 16 + g * 2)};
    cbar();
    const int lp = (tid >> 2) & 31, kq = tid & 3;
    const int fo = 16 * wg + (lp >> 2) + 8 * (kq >> 1), bo = 2 * (lp & 3) + (kq & 1);
    float U = 0.f, V = 0.f;
#pragma unroll
    for (int i = 0; i < 8; i++) { U += ldsf(sb + OFF_REDU + i * 1024 + tid * 4); V += ldsf(sb + OFF_REDV + i * 1024 + tid * 4); }
    U = pin(U); V = pin(V);
    const uint32_t s_g = pin(sb + OFF_REDG + w * 1024 + lane * 16), s_s = pin(sb + OFF_REDS + g * 80 + w * 8);
    const uint32_t l_g = pin(sb + OFF_REDG + tid * 4), l_s = pin(sb + OFF_REDS + bo * 80), s_h = pin(sb + OFF_H1 + fo * 16 + bo * 2);
    CLK(34);
    wait_clk(tstore, T.D_X3B);
    wait_clk(anchor, T.A_X1 + T.R_X3A + T.R_X3B);
    uint2 x[4];
    load_units<4, 64>(x, xb);
    mbar_wait(BAR(BAR_W2));
#pragma unroll
    for (int i = 0; i < 4; i++)
      ldsm4t(a2[i >> 1][i & 1], sb + OFF_W2 + (w >> 1) * 4096 + (16 * (i & 1) + 8 * (mi >> 1) + r) * 128 + (((4 * (w & 1) + 2 * (i >> 1) + (mi & 1)) ^ r) << 4));
    CLK(35);
    int it = 0;
    while (true) {
      float G[2][2][4] = {}, S[2][4] = {};
#pragma unroll
      for (int s = 0; s < 4; s++) {
        const uint32_t sx[4] = {x[s].x, ONE2, x[s].y, ONE2};
        mma16816(S[s & 1], sx, x[s].x, x[s].y);
        const uint32_t y0 = hmul2(x[s].x, cbf[s].x), y1 = hmul2(x[s].y, cbf[s].y);
        mma16816(G[0][s & 1], a1[0][s], y0, y1);
        mma16816(G[1][s & 1], a1[1][s], y0, y1);
      }
      const uint32_t fl = min_flags(x);
#pragma unroll
      for (int i = 0; i < 4; i++) reload_unit(x[i], xb + i * 64);
      if (t == (g >> 1)) sts2f(s_s, (g & 1) ? S[0][3] + S[1][3] : S[0][2] + S[1][2], (g & 1) ? S[0][1] + S[1][1] : S[0][0] + S[1][0]);
#pragma unroll
      for (int mt = 0; mt < 2; mt++)
        sts4f(s_g + mt * 512, G[mt][0][0] + G[mt][1][0], G[mt][0][1] + G[mt][1][1], G[mt][0][2] + G[mt][1][2], G[mt][0][3] + G[mt][1][3]);
      CLK(37);
      const uint32_t bad = cbar_bad(fl);
      float gv[8];
      float4 sv[4];
#pragma unroll
      for (int i = 0; i < 4; i++) sv[i] = ldsf4(l_s + i * 16);
#pragma unroll
      for (int i = 0; i < 8; i++) gv[i] = ldsf(l_g + i * 1024);
      const float s1 = ((sv[0].x + sv[0].z) + (sv[1].x + sv[1].z)) + ((sv[2].x + sv[2].z) + (sv[3].x + sv[3].z));
      const float s2 = ((sv[0].y + sv[0].w) + (sv[1].y + sv[1].w)) + ((sv[2].y + sv[2].w) + (sv[3].y + sv[3].w));
      const float gsum = ((gv[0] + gv[1]) + (gv[2] + gv[3])) + ((gv[4] + gv[5]) + (gv[6] + gv[7]));
      const float mu = s1 * (1.f / 512.f);
      float rs;
      asm("rsqrt.approx.ftz.f32 %0, %1;" : "=f"(rs) : "f"(fmaxf(s2 * (1.f / 512.f) - mu * mu, 0.f) + 1e-5f));
      const float hv = fmaxf(rs * (gsum - mu * U) + V, 0.f);
      asm volatile("st.shared.u16 [%0], %1;" ::"r"(s_h), "h"(__bfloat16_as_ushort(__float2bfloat16(hv))) : "memory");
      if (!bad) break;
      it += 1 + check_units<4, 64>(x, xb, 0);
      cbar();
    }
    ITS(6, it);
    CLK(38);
    cbar();
    uint32_t b[4];
    ldsm4t(b, sb + OFF_H1 + lane * 16);
    float o[2][2][4] = {};
#pragma unroll
    for (int i = 0; i < 4; i++) mma16816(o[i >> 1][i & 1], a2[i >> 1][i & 1], b[2 * (i & 1)], b[2 * (i & 1) + 1]);
#pragma unroll
    for (int mb = 0; mb < 2; mb++)
      stg_u64(ox[mb], movm(pack_bf16(o[mb][0][0] + o[mb][1][0], o[mb][0][1] + o[mb][1][1])), movm(pack_bf16(o[mb][0][2] + o[mb][1][2], o[mb][0][3] + o[mb][1][3])));
    CLK(39);
    if (lane == 0) mbar_arrive(BAR(BAR_P7D));
  }
  CLK_DUMP();
}

typedef CUresult (*EncodeTiledFn)(CUtensorMap*, CUtensorMapDataType, cuuint32_t, void*, const cuuint64_t*, const cuuint64_t*,
                                  const cuuint32_t*, const cuuint32_t*, CUtensorMapInterleave, CUtensorMapSwizzle,
                                  CUtensorMapL2promotion, CUtensorMapFloatOOBfill);

struct Dim { uint64_t size, stride; uint32_t box; };
template <int R> void encode_map(EncodeTiledFn enc, CUtensorMap* m, const void* base, const Dim (&d)[R], CUtensorMapSwizzle sw, CUtensorMapL2promotion promo) {
  cuuint64_t dims[R], strides[R];
  cuuint32_t box[R], es[R];
  for (int i = 0; i < R; i++) { dims[i] = d[i].size; strides[i] = d[i].stride; box[i] = d[i].box; es[i] = 1; }
  enc(m, CU_TENSOR_MAP_DATA_TYPE_BFLOAT16, R, const_cast<void*>(base), dims, strides + 1, box, es, CU_TENSOR_MAP_INTERLEAVE_NONE, sw, promo,
      CU_TENSOR_MAP_FLOAT_OOB_FILL_NONE);
}

}

extern "C" void kernel_launch(void* const* d_in, const int* in_sizes, int n_in, void* d_out, int out_size) {
  (void)in_sizes; (void)n_in; (void)out_size;
  static EncodeTiledFn enc = nullptr;
  static Scratch* scratch = nullptr;
  static uint32_t* inbox = nullptr;
  if (!enc) {
    void* sp = nullptr;
    cudaGetSymbolAddress(&sp, g_s);
    scratch = (Scratch*)sp;
    cudaGetSymbolAddress(&sp, g_in);
    inbox = (uint32_t*)(((uintptr_t)sp + 65535) & ~(uintptr_t)65535);
    void* fn = nullptr;
    cudaDriverEntryPointQueryResult q;
    cudaGetDriverEntryPoint("cuTensorMapEncodeTiled", &fn, cudaEnableDefault, &q);
    enc = (EncodeTiledFn)fn;
    cudaFuncSetAttribute(fused_decode_kernel, cudaFuncAttributeMaxDynamicSharedMemorySize, SMEM_BYTES);
  }
  const CUtensorMapSwizzle S128 = CU_TENSOR_MAP_SWIZZLE_128B, S0 = CU_TENSOR_MAP_SWIZZLE_NONE;
  const CUtensorMapL2promotion L0 = CU_TENSOR_MAP_L2_PROMOTION_NONE, L128 = CU_TENSOR_MAP_L2_PROMOTION_L2_128B;
  Params P;
  encode_map<2>(enc, &P.wq, d_in[2], {{4096, 2, 64}, {512, 8192, 64}}, S128, L0);
  encode_map<5>(enc, &P.wuk, d_in[3], {{4096, 2, 64}, {2, 8192, 2}, {4, 4 * 8192, 4}, {2, 2 * 8192, 2}, {32, 16 * 8192, 4}}, S128, L0);
  encode_map<2>(enc, &P.wm2, d_in[10], {{3072, 2, 16}, {512, 6144, 256}}, S0, L128);
  encode_map<3>(enc, &P.ckv2, d_in[1], {{64, 2, 64}, {8 * 4096, 1024, 64}, {8, 128, 2}}, S128, L0);
  encode_map<3>(enc, &P.ckv1, d_in[1], {{64, 2, 64}, {8 * 4096, 1024, 64}, {8, 128, 1}}, S128, L0);
  encode_map<5>(enc, &P.wuv, d_in[4], {{4096, 2, 64}, {2, 8 * 8192, 2}, {8, 64 * 8192, 4}, {8, 8192, 8}, {4, 16 * 8192, 1}}, S128, L0);
  encode_map<2>(enc, &P.wo, d_in[5], {{512, 2, 64}, {4096, 1024, 64}}, S128, L0);
  encode_map<2>(enc, &P.w1, d_in[7], {{1792, 2, 32}, {512, 3584, 256}}, CU_TENSOR_MAP_SWIZZLE_64B, L128);
  encode_map<3>(enc, &P.w2, d_in[8], {{64, 2, 64}, {1792, 1024, 32}, {8, 128, 2}}, S128, L0);
  cudaLaunchConfig_t cfg = {};
  cfg.gridDim = dim3(NCTA);
  cfg.blockDim = dim3(NTHREADS);
  cfg.dynamicSmemBytes = SMEM_BYTES;
  cfg.stream = cudaStreamPerThread;
  cudaLaunchAttribute at[1];
  at[0].id = cudaLaunchAttributeClusterDimension;
  at[0].val.clusterDim.x = 2; at[0].val.clusterDim.y = 1; at[0].val.clusterDim.z = 1;
  cfg.attrs = at;
  cfg.numAttrs = 0;
  cudaLaunchKernelEx(&cfg, fused_decode_kernel, (__nv_bfloat16*)d_out, scratch, (const uint8_t*)d_in[10], (const uint8_t*)d_in[0],
                     (const uint8_t*)d_in[9], inbox,
                     P);
}
```

```cpp
#include <cuda_runtime.h>
#include <cuda.h>
#include <cuda_bf16.h>
#include <stdint.h>
#define V4 1

namespace {

constexpr int NCTA = 128;
constexpr int NTHREADS = 320;
constexpr int NFG = 56;
constexpr int NFF = 2 * NFG;
constexpr int NSYNC = 4;
#define NTS 8

constexpr uint32_t OFF_RING = 0;
constexpr uint32_t OFF_WUK = 131072;
constexpr uint32_t OFF_WQ = 131072 + 32768;
constexpr uint32_t OFF_WM2 = 65536 + 49152;
constexpr uint32_t OFF_WUV = 131072;
constexpr uint32_t OFF_WO = 131072 + 32768;
constexpr uint32_t OFF_W1 = 0;
constexpr uint32_t OFF_W2 = 32768;
constexpr uint32_t OFF_Q = 196608;
constexpr uint32_t OFF_PT = 212992;
constexpr uint32_t OFF_SCR = 217088;
constexpr uint32_t OFF_XS = 65536;
constexpr uint32_t OFF_CS = 65536 + 8192;
constexpr uint32_t OFF_P0S = 65536 + 16384;
constexpr uint32_t OFF_BS1 = OFF_SCR + 2048;
constexpr uint32_t OFF_BS2 = OFF_SCR + 4096;
constexpr uint32_t OFF_P0B = OFF_SCR + 6144;
constexpr uint32_t OFF_XN = OFF_SCR + 8192;
constexpr uint32_t OFF_RED = OFF_SCR + 10496;
constexpr uint32_t OFF_ALPHA = OFF_SCR + 11072;
constexpr uint32_t OFF_WV = OFF_SCR + 6144;
constexpr uint32_t OFF_SEL = OFF_SCR + 10752;
constexpr uint32_t OFF_TS = OFF_SCR + 11136;
constexpr uint32_t OFF_BARS = OFF_SCR + 11264;
constexpr uint32_t SMEM_BYTES = OFF_BARS + 512;
constexpr uint32_t OFF_BS4 = OFF_Q;
constexpr uint32_t OFF_H1 = OFF_Q + 2304;
constexpr uint32_t OFF_REDS = OFF_Q + 2816;
constexpr uint32_t OFF_BS5 = OFF_Q + 4096;
constexpr uint32_t OFF_REDG = OFF_Q + 8192;
constexpr uint32_t OFF_REDU = 65536;
constexpr uint32_t OFF_REDV = 65536 + 8192;

constexpr int BAR_FULL = 0;
constexpr int BAR_LAST = 28;
constexpr int BAR_WUK = 33, BAR_WM2 = 35, BAR_WUV = 36, BAR_WO = 38, BAR_W1 = 40, BAR_W2 = 41;
constexpr int BAR_ALLCLR = 42, BAR_TS = 43, BAR_WV = 44;
constexpr int BAR_EMPTY = 45;
constexpr int BAR_P0BD = 52;
constexpr int BAR_P1D = 53, BAR_P2D = 54;
constexpr int BAR_P5D = 55, BAR_P7D = 56;
constexpr int NBARS = 57;
constexpr int BAR_XC = 57, BAR_WQ = 58;
constexpr int BAR_C = 60, BAR_END = 61;
constexpr uint32_t SB = 1024;

#define TUNE_LIST(X) \
  X(PC_T0, 340) X(PC_XC, 0) X(PC_C, 0) X(PC_P1, 320) X(PC_P2, 322) X(PC_STAG, 390) X(PC_DS, 0) X(PC_SL, 500) X(PC_W, 4) X(PC_NW, 8) \
  X(PW_A, -1) X(PW_0, 240) X(PW_ST, 0) X(PW_UV, 250) X(PW_G, 660) X(PW_O, 340) X(PW_G2, 480) X(PW_G3, 390) X(PW_F, 330) \
  X(LOC, 0) X(PR_T0, 1000) X(PR_N, 4) X(CLR_T0, 3200) X(CLR_CLK, 190) \
  X(D_MOD, 1500) X(D_QP, 1300) X(D_QX, 1300) X(TS_P, 1) X(TS_O, 950) X(D_TS, 900) X(A_M, 2050) X(D_X1, 1300) X(A_X1, 2400) \
  X(D_X2, 250) X(R_X2, 1550) X(D_X3A, 60) X(R_X3A, 3340) X(D_X3B, 800) X(R_X3B, 980) X(D_FIN, 320) X(R_FIN, 1520) X(RB, 0)
struct Tune {
#define X(n, v) static constexpr int n = v;
  TUNE_LIST(X)
#undef X
};

#define PFENCE 0
#define WSWAP 0
#define PVV 0
struct Scratch {
  uint32_t MOD1[2][4 * 64 * 64];
  uint32_t MOD2[2][128 * 64];
  uint32_t QP[2][128 * 256 * 2];
  uint32_t QX[2][8 * 32 * 256];
  uint32_t epoch;
  uint32_t pad[31];
  uint32_t sync[NSYNC][32];
};
__device__ Scratch g_s;
__device__ uint32_t g_in[129 * 16384];
__device__ __forceinline__ uint32_t blk(int c, int k, uint32_t sel) { return c * 16384 + k * 2048 + ((sel ^ k) & 1) * 1024; }

#define CLK_DECL
#define CLK(i) do {} while (0)
#define CLK_DUMP() do {} while (0)
#define ITS(i, v) do {} while (0)

struct Params {
  CUtensorMap wq, wuk, wm2, ckv2, ckv1, wuv, wo, w1, w2;
};

__device__ __forceinline__ void mbar_init(uint32_t bar, int cnt) { asm volatile("mbarrier.init.shared::cta.b64 [%0], %1;" ::"r"(bar), "r"(cnt)); }
__device__ __forceinline__ void mbar_expect(uint32_t bar, uint32_t bytes) { asm volatile("mbarrier.arrive.expect_tx.shared::cta.b64 _, [%0], %1;" ::"r"(bar), "r"(bytes) : "memory"); }
__device__ __forceinline__ void mbar_arrive(uint32_t bar) { asm volatile("mbarrier.arrive.shared::cta.b64 _, [%0];" ::"r"(bar) : "memory"); }
__device__ __forceinline__ uint32_t clk32() { unsigned long long c; asm volatile("mov.u64 %0, %%clock64;" : "=l"(c) :: "memory"); return (uint32_t)c; }
__device__ __forceinline__ uint32_t gtime32() { uint32_t c; asm volatile("mov.u32 %0, %%globaltimer_lo;" : "=r"(c) :: "memory"); return c; }
__device__ __forceinline__ void wait_clk(uint32_t t0, int clocks) { while ((int)(clk32() - t0) < clocks) {} }
__device__ __forceinline__ void backoff(int clocks) { if (clocks > 0) wait_clk(clk32(), clocks); }
__device__ __forceinline__ void until_ns(uint32_t ns) { while ((int)(gtime32() - ns) < 0) {} }
__device__ __forceinline__ void slot(uint32_t& tn, int slack) {
  uint32_t now;
  do { now = gtime32(); } while ((int)(now - tn) < 0);
  if ((int)(now - tn) > slack) tn = now - slack;
}
template <typename T> __device__ __forceinline__ T* pin(T* p) { asm volatile("" : "+l"(p)); return p; }
__device__ __forceinline__ uint32_t pin(uint32_t v) { asm volatile("" : "+r"(v)); return v; }
__device__ __forceinline__ float pin(float v) { asm volatile("" : "+f"(v)); return v; }
constexpr int SPIN_LIMIT = 1 << 22;
__device__ __forceinline__ void mbar_wait(uint32_t bar) {
  asm volatile("{\n.reg .pred p;\n.reg .u32 c;\nmov.u32 c, 0;\n"
               "MW_LOOP:\nmbarrier.try_wait.parity.shared::cta.b64 p, [%0], 0;\n@p bra MW_DONE;\n"
               "add.u32 c, c, 1;\nsetp.lt.u32 p, c, 4194304;\n@p bra MW_LOOP;\ntrap;\nMW_DONE:\n}"
               ::"r"(bar) : "memory");
}
__device__ __forceinline__ bool mbar_test(uint32_t bar) {
  uint32_t ok;
  asm volatile("{\n.reg .pred p;\nmbarrier.test_wait.parity.shared::cta.b64 p, [%1], 0;\nselp.u32 %0,1,0,p;\n}" : "=r"(ok) : "r"(bar) : "memory");
  return ok;
}
__device__ __forceinline__ void tma2d(uint32_t dst, const CUtensorMap* m, int c0, int c1, uint32_t bar, uint64_t pol) {
  asm volatile("cp.async.bulk.tensor.2d.shared::cluster.global.mbarrier::complete_tx::bytes.L2::cache_hint [%0], [%1, {%3,%4}], [%2], %5;"
               ::"r"(dst), "l"(m), "r"(bar), "r"(c0), "r"(c1), "l"(pol) : "memory");
}
__device__ __forceinline__ void tma2d_nohint(uint32_t dst, const CUtensorMap* m, int c0, int c1, uint32_t bar) {
  asm volatile("cp.async.bulk.tensor.2d.shared::cluster.global.mbarrier::complete_tx::bytes [%0], [%1, {%3,%4}], [%2];"
               ::"r"(dst), "l"(m), "r"(bar), "r"(c0), "r"(c1) : "memory");
}
__device__ __forceinline__ void tma3d(uint32_t dst, const CUtensorMap* m, int c0, int c1, int c2, uint32_t bar, uint64_t pol) {
  asm volatile("cp.async.bulk.tensor.3d.shared::cluster.global.mbarrier::complete_tx::bytes.L2::cache_hint [%0], [%1, {%3,%4,%5}], [%2], %6;"
               ::"r"(dst), "l"(m), "r"(bar), "r"(c0), "r"(c1), "r"(c2), "l"(pol) : "memory");
}
__device__ __forceinline__ void tma5d(uint32_t dst, const CUtensorMap* m, int c0, int c1, int c2, int c3, int c4, uint32_t bar, uint64_t pol) {
  asm volatile("cp.async.bulk.tensor.5d.shared::cluster.global.mbarrier::complete_tx::bytes.L2::cache_hint [%0], [%1, {%3,%4,%5,%6,%7}], [%2], %8;"
               ::"r"(dst), "l"(m), "r"(bar), "r"(c0), "r"(c1), "r"(c2), "r"(c3), "r"(c4), "l"(pol) : "memory");
}
__device__ __forceinline__ void bulk_ld(uint32_t dst, const void* src, uint32_t bytes, uint32_t bar) {
  asm volatile("cp.async.bulk.shared::cluster.global.mbarrier::complete_tx::bytes [%0], [%1], %2, [%3];" ::"r"(dst), "l"(src), "r"(bytes), "r"(bar) : "memory");
}
__device__ __forceinline__ void bar_sync(int id, int n) { asm volatile("barrier.cta.sync.aligned %0, %1;" ::"r"(id), "r"(n) : "memory"); }
__device__ __forceinline__ void cbar() { asm volatile("barrier.cta.sync.aligned 1, 256;" ::: "memory"); }
__device__ __forceinline__ bool bar_over(float ex) {
  uint32_t over;
  asm volatile("{\n.reg .pred p, q;\nsetp.gtu.f32 p, %1, 0f41F00000;\nbarrier.cta.red.or.aligned.pred q, 4, 256, p;\nselp.u32 %0, 1, 0, q;\n}"
               : "=r"(over) : "f"(ex) : "memory");
  return over;
}

__device__ __forceinline__ uint32_t ldg_nc1(const void* p) { uint32_t v; asm volatile("ld.global.nc.L1::no_allocate.u32 %0, [%1];" : "=r"(v) : "l"(p)); return v; }
__device__ __forceinline__ uint2 ldg_nc2(const void* p) { uint2 v; asm volatile("ld.global.nc.v2.u32 {%0,%1}, [%2];" : "=r"(v.x), "=r"(v.y) : "l"(p)); return v; }
__device__ __forceinline__ uint4 ldg_nc4(const void* p) { uint4 v; asm volatile("ld.global.nc.L1::no_allocate.v4.u32 {%0,%1,%2,%3}, [%4];" : "=r"(v.x), "=r"(v.y), "=r"(v.z), "=r"(v.w) : "l"(p)); return v; }
__device__ __forceinline__ uint32_t ldg_rlx1(const void* p) { uint32_t v; asm volatile("ld.relaxed.gpu.global.u32 %0, [%1];" : "=r"(v) : "l"(p) : "memory"); return v; }
__device__ __forceinline__ void stg4(void* p, uint4 v) { asm volatile("st.relaxed.gpu.global.v4.u32 [%0], {%1,%2,%3,%4};" ::"l"(p), "r"(v.x), "r"(v.y), "r"(v.z), "r"(v.w) : "memory"); }
__device__ __forceinline__ void stg1(void* p, uint32_t a) { asm volatile("st.relaxed.gpu.global.u32 [%0], %1;" ::"l"(p), "r"(a) : "memory"); }
__device__ __forceinline__ uint32_t nz(uint32_t w) { return max(w, 1u); }
__device__ __forceinline__ uint2 ldg_u64(const void* p) {
  uint2 v; asm volatile("{\n.reg .b64 a;\nld.relaxed.gpu.global.b64 a, [%2];\nmov.b64 {%0,%1}, a;\n}" : "=r"(v.x), "=r"(v.y) : "l"(p) : "memory"); return v;
}
__device__ __forceinline__ uint4 ldg_2u64(const void* p) {
  uint4 v; asm volatile("{\n.reg .b64 a, b;\nld.relaxed.gpu.global.v2.b64 {a, b}, [%4];\nmov.b64 {%0,%1}, a;\nmov.b64 {%2,%3}, b;\n}" : "=r"(v.x), "=r"(v.y), "=r"(v.z), "=r"(v.w) : "l"(p) : "memory"); return v;
}
__device__ __forceinline__ void stg_u64(void* p, uint32_t x, uint32_t y) {
  asm volatile("{\n.reg .b32 y;\nmax.u32 y, %2, 1;\nst.relaxed.gpu.global.v2.b32 [%0], {%1, y};\n}" ::"l"(p), "r"(x), "r"(y) : "memory");
}
__device__ __forceinline__ void stg_u64_unless(uint32_t bad, void* p, uint32_t x, uint32_t y) {
  asm volatile("{\n.reg .b32 y;\n.reg .pred q;\nsetp.eq.u32 q, %3, 0;\nmax.u32 y, %2, 1;\n@q st.relaxed.gpu.global.v2.b32 [%0], {%1, y};\n}" ::"l"(p), "r"(x), "r"(y), "r"(bad) : "memory");
}
__device__ __forceinline__ void stg_2u64(void* p, uint4 v) {
  asm volatile("{\n.reg .b32 y, w;\nmax.u32 y, %2, 1;\nmax.u32 w, %4, 1;\nst.relaxed.gpu.global.v4.b32 [%0], {%1, y, %3, w};\n}" ::"l"(p), "r"(v.x), "r"(v.y), "r"(v.z), "r"(v.w) : "memory");
}

__device__ __forceinline__ void stg_cvt8(void* p, float a0, float a1, float b0, float b1, float c0, float c1, float d0, float d1) {
  asm volatile("{\n.reg .b32 x, y, z, w;\ncvt.rn.bf16x2.f32 x, %2, %1;\ncvt.rn.bf16x2.f32 y, %4, %3;\ncvt.rn.bf16x2.f32 z, %6, %5;\ncvt.rn.bf16x2.f32 w, %8, %7;\n"
               "max.u32 y, y, 1;\nmax.u32 w, w, 1;\nst.relaxed.gpu.global.v4.b32 [%0], {x, y, z, w};\n}"
               ::"l"(p), "f"(a0), "f"(a1), "f"(b0), "f"(b1), "f"(c0), "f"(c1), "f"(d0), "f"(d1) : "memory");
}
__device__ __forceinline__ uint32_t pack_bf16(float lo, float hi) { uint32_t r; asm("cvt.rn.bf16x2.f32 %0, %1, %2;" : "=r"(r) : "f"(hi), "f"(lo)); return r; }
__device__ __forceinline__ float bf_lo(uint32_t w) { return __uint_as_float(w << 16); }
__device__ __forceinline__ float bf_hi(uint32_t w) { return __uint_as_float(w & 0xffff0000u); }
__device__ __forceinline__ float ex2(float x) { float r; asm("ex2.approx.ftz.f32 %0, %1;" : "=f"(r) : "f"(x)); return r; }
__device__ __forceinline__ uint32_t hmul2(uint32_t a, uint32_t b) { uint32_t r; asm("mul.rn.bf16x2 %0, %1, %2;" : "=r"(r) : "r"(a), "r"(b)); return r; }
__device__ __forceinline__ uint32_t hadd2(uint32_t a, uint32_t b) { uint32_t r; asm("add.rn.bf16x2 %0, %1, %2;" : "=r"(r) : "r"(a), "r"(b)); return r; }
__device__ __forceinline__ uint32_t hfma2(uint32_t a, uint32_t b, uint32_t c) { uint32_t r; asm("fma.rn.bf16x2 %0, %1, %2, %3;" : "=r"(r) : "r"(a), "r"(b), "r"(c)); return r; }
__device__ __forceinline__ uint32_t silu2(uint32_t v) { const float a = bf_lo(v), b = bf_hi(v); return pack_bf16(__fdividef(a, 1.f + __expf(-a)), __fdividef(b, 1.f + __expf(-b))); }
constexpr uint32_t ONE2 = 0x3f803f80u;

__device__ __forceinline__ void ldsm4(uint32_t (&r)[4], uint32_t a) { asm volatile("ldmatrix.sync.aligned.m8n8.x4.shared.b16 {%0,%1,%2,%3}, [%4];" : "=r"(r[0]), "=r"(r[1]), "=r"(r[2]), "=r"(r[3]) : "r"(a) : "memory"); }
__device__ __forceinline__ void ldsm4t(uint32_t (&r)[4], uint32_t a) { asm volatile("ldmatrix.sync.aligned.m8n8.x4.trans.shared.b16 {%0,%1,%2,%3}, [%4];" : "=r"(r[0]), "=r"(r[1]), "=r"(r[2]), "=r"(r[3]) : "r"(a) : "memory"); }
__device__ __forceinline__ void ldsm2t(uint32_t& r0, uint32_t& r1, uint32_t a) { asm volatile("ldmatrix.sync.aligned.m8n8.x2.trans.shared.b16 {%0,%1}, [%2];" : "=r"(r0), "=r"(r1) : "r"(a) : "memory"); }
__device__ __forceinline__ void stsm4t(uint32_t a, uint32_t r0, uint32_t r1, uint32_t r2, uint32_t r3) { asm volatile("stmatrix.sync.aligned.m8n8.x4.trans.shared.b16 [%0], {%1,%2,%3,%4};" ::"r"(a), "r"(r0), "r"(r1), "r"(r2), "r"(r3) : "memory"); }
__device__ __forceinline__ uint32_t movm(uint32_t a) { uint32_t d; asm volatile("movmatrix.sync.aligned.m8n8.trans.b16 %0, %1;" : "=r"(d) : "r"(a)); return d; }
__device__ __forceinline__ void mma16816(float (&d)[4], const uint32_t (&a)[4], uint32_t b0, uint32_t b1) {
  asm volatile("mma.sync.aligned.m16n8k16.row.col.f32.bf16.bf16.f32 {%0,%1,%2,%3}, {%4,%5,%6,%7}, {%8,%9}, {%0,%1,%2,%3};"
               : "+f"(d[0]), "+f"(d[1]), "+f"(d[2]), "+f"(d[3]) : "r"(a[0]), "r"(a[1]), "r"(a[2]), "r"(a[3]), "r"(b0), "r"(b1));
}
__device__ __forceinline__ void sts1(uint32_t a, uint32_t v) { asm volatile("st.shared.u32 [%0], %1;" ::"r"(a), "r"(v) : "memory"); }
__device__ __forceinline__ void sts2(uint32_t a, uint32_t x, uint32_t y) { asm volatile("st.shared.v2.u32 [%0], {%1,%2};" ::"r"(a), "r"(x), "r"(y) : "memory"); }
__device__ __forceinline__ void sts4(uint32_t a, uint4 v) { asm volatile("st.shared.v4.u32 [%0], {%1,%2,%3,%4};" ::"r"(a), "r"(v.x), "r"(v.y), "r"(v.z), "r"(v.w) : "memory"); }
__device__ __forceinline__ void sts2f(uint32_t a, float x, float y) { asm volatile("st.shared.v2.f32 [%0], {%1,%2};" ::"r"(a), "f"(x), "f"(y) : "memory"); }
__device__ __forceinline__ void sts4f(uint32_t a, float x, float y, float z, float w) { asm volatile("st.shared.v4.f32 [%0], {%1,%2,%3,%4};" ::"r"(a), "f"(x), "f"(y), "f"(z), "f"(w) : "memory"); }
__device__ __forceinline__ void stsf(uint32_t a, float v) { asm volatile("st.shared.f32 [%0], %1;" ::"r"(a), "f"(v) : "memory"); }
__device__ __forceinline__ uint32_t lds1(uint32_t a) { uint32_t v; asm volatile("ld.shared.u32 %0, [%1];" : "=r"(v) : "r"(a) : "memory"); return v; }
__device__ __forceinline__ float ldsf(uint32_t a) { float v; asm volatile("ld.shared.f32 %0, [%1];" : "=f"(v) : "r"(a) : "memory"); return v; }
__device__ __forceinline__ float2 ldsf2(uint32_t a) { float2 v; asm volatile("ld.shared.v2.f32 {%0,%1}, [%2];" : "=f"(v.x), "=f"(v.y) : "r"(a) : "memory"); return v; }
__device__ __forceinline__ float4 ldsf4(uint32_t a) { float4 v; asm volatile("ld.shared.v4.f32 {%0,%1,%2,%3}, [%4];" : "=f"(v.x), "=f"(v.y), "=f"(v.z), "=f"(v.w) : "r"(a) : "memory"); return v; }
__device__ __forceinline__ void lds4(uint32_t (&r)[4], uint32_t a) { asm volatile("ld.shared.v4.u32 {%0,%1,%2,%3}, [%4];" : "=r"(r[0]), "=r"(r[1]), "=r"(r[2]), "=r"(r[3]) : "r"(a) : "memory"); }

__device__ __forceinline__ void wg_fence() { asm volatile("wgmma.fence.sync.aligned;" ::: "memory"); }
__device__ __forceinline__ void wg_commit() { asm volatile("wgmma.commit_group.sync.aligned;" ::: "memory"); }
template <int N> __device__ __forceinline__ void wg_wait() { asm volatile("wgmma.wait_group.sync.aligned %0;" ::"n"(N) : "memory"); }
__host__ __device__ constexpr uint32_t desc_lo(uint32_t off) { return ((SB + off) >> 4) | 0x10000u; }
template <int TA, int ACC> __device__ __forceinline__ void wgmma_n16(float (&d)[8], uint32_t da, uint32_t db) {
  asm volatile("{\n.reg .b64 da, db;\nmov.b64 da, {%8, 0x40000040};\nmov.b64 db, {%9, 0x40000040};\n"
               "wgmma.mma_async.sync.aligned.m64n16k16.f32.bf16.bf16 {%0,%1,%2,%3,%4,%5,%6,%7}, da, db, %11, 1, 1, %10, 0;\n}"
               : "+f"(d[0]), "+f"(d[1]), "+f"(d[2]), "+f"(d[3]), "+f"(d[4]), "+f"(d[5]), "+f"(d[6]), "+f"(d[7])
               : "r"(da), "r"(db), "n"(TA), "n"(ACC));
}
__device__ __forceinline__ void wgmma_n16_ones(float (&d)[8], uint32_t one, uint32_t db) {
  asm volatile("{\n.reg .b64 db;\nmov.b64 db, {%9, 0x40000040};\n"
               "wgmma.mma_async.sync.aligned.m64n16k16.f32.bf16.bf16 {%0,%1,%2,%3,%4,%5,%6,%7}, {%8,%8,%8,%8}, db, 1, 1, 1, 0;\n}"
               : "+f"(d[0]), "+f"(d[1]), "+f"(d[2]), "+f"(d[3]), "+f"(d[4]), "+f"(d[5]), "+f"(d[6]), "+f"(d[7])
               : "r"(one), "r"(db));
}
__device__ __forceinline__ void acc_fence(float (&d)[8]) {
  asm volatile("" : "+f"(d[0]), "+f"(d[1]), "+f"(d[2]), "+f"(d[3]), "+f"(d[4]), "+f"(d[5]), "+f"(d[6]), "+f"(d[7]) :: "memory");
}

template <int N, int STRIDE> __device__ __forceinline__ void load_units(uint2 (&v)[N], const uint32_t* p) {
#pragma unroll
  for (int i = 0; i < N; i++) v[i] = ldg_u64(p + i * STRIDE);
}
template <int N, int STRIDE> __device__ __forceinline__ int check_units(uint2 (&v)[N], const uint32_t* p, int rb) {
  int it = 0;
  while (true) {
    uint32_t mn = v[0].y;
#pragma unroll
    for (int i = 1; i < N; i++) mn = min(mn, v[i].y);
    if (mn != 0) break;
    backoff(rb);
#pragma unroll
    for (int i = 0; i < N; i++) if (v[i].y == 0) v[i] = ldg_u64(p + i * STRIDE);
    if (++it > SPIN_LIMIT) __trap();
  }
  return it;
}
__device__ __forceinline__ void reload_unit(uint2& v, const uint32_t* p) {
  asm volatile("{\n.reg .pred q;\nsetp.eq.u32 q, %1, 0;\n@q ld.relaxed.gpu.global.v2.b32 {%0, %1}, [%2];\n}" : "+r"(v.x), "+r"(v.y) : "l"(p) : "memory");
}
template <int N> __device__ __forceinline__ uint32_t min_flags(const uint2 (&v)[N]) {
  uint32_t a = v[0].y, b = v[1].y;
#pragma unroll
  for (int i = 2; i < N; i += 2) { a = min(a, v[i].y); b = min(b, v[i + 1].y); }
  return min(a, b);
}
__device__ __forceinline__ void sum4_to_smem(const uint2 (&v)[4], uint32_t dst) {
  const float c0 = (bf_lo(v[0].x) + bf_lo(v[1].x)) + (bf_lo(v[2].x) + bf_lo(v[3].x));
  const float c1 = (bf_hi(v[0].x) + bf_hi(v[1].x)) + (bf_hi(v[2].x) + bf_hi(v[3].x));
  const float c2 = (bf_lo(v[0].y) + bf_lo(v[1].y)) + (bf_lo(v[2].y) + bf_lo(v[3].y));
  const float c3 = (bf_hi(v[0].y) + bf_hi(v[1].y)) + (bf_hi(v[2].y) + bf_hi(v[3].y));
  sts1(dst, pack_bf16(c0, c1));
  sts1(dst + 128, pack_bf16(c2, c3));
}
__device__ __forceinline__ void load_a_t(uint32_t (&a)[8][4], uint32_t wbase, int w, int lane) {
  const int mi = lane >> 3, r = lane & 7;
  const uint32_t base = wbase + (w >> 2) * 16384 + (8 * (mi >> 1) + r) * 128 + (((2 * (w & 3) + (mi & 1)) ^ r) << 4);
#pragma unroll
  for (int ks = 0; ks < 8; ks++) ldsm4t(a[ks], base + ks * 2048);
}
__device__ __forceinline__ void mma128(float (&d)[4], const uint32_t (&a)[8][4], const uint32_t (&b)[4][4]) {
  float e[4][4] = {{0.f, 0.f, 0.f, 0.f}, {0.f, 0.f, 0.f, 0.f}, {0.f, 0.f, 0.f, 0.f}, {0.f, 0.f, 0.f, 0.f}};
#pragma unroll
  for (int kk = 0; kk < 4; kk++) { mma16816(e[(2 * kk) & 3], a[2 * kk], b[kk][0], b[kk][1]); mma16816(e[(2 * kk + 1) & 3], a[2 * kk + 1], b[kk][2], b[kk][3]); }
#pragma unroll
  for (int i = 0; i < 4; i++) d[i] = (e[0][i] + e[1][i]) + (e[2][i] + e[3][i]);
}
template <int NP> __device__ __forceinline__ bool sum_pieces(const uint32_t* p0, uint32_t one, float (&r)[4]) {
  uint2 v[NP / 4];
  load_units<NP / 4, 64>(v, p0);
  float d[4][4] = {};
#pragma unroll
  for (int i = 0; i < NP / 8; i++) { const uint32_t a[4] = {v[2 * i].x, v[2 * i].y, v[2 * i + 1].x, v[2 * i + 1].y}; mma16816(d[i & 3], a, one, one); }
  const bool ok = __all_sync(~0u, min_flags(v) != 0);
#pragma unroll
  for (int k = 0; k < 4; k++) r[k] = (d[0][k] + d[1][k]) + (d[2][k] + d[3][k]);
  return ok;
}
template <typename F> __device__ __forceinline__ float reduce_g(const float (&x)[4], int lane, F f) {
  const bool u4 = lane & 16, u3 = lane & 8;
  const float a0 = f(u4 ? x[2] : x[0], __shfl_xor_sync(~0u, u4 ? x[0] : x[2], 16));
  const float a1 = f(u4 ? x[3] : x[1], __shfl_xor_sync(~0u, u4 ? x[1] : x[3], 16));
  const float b = f(u3 ? a1 : a0, __shfl_xor_sync(~0u, u3 ? a0 : a1, 8));
  return f(b, __shfl_xor_sync(~0u, b, 4));
}

__global__ void __launch_bounds__(NTHREADS, 1)
fused_decode_kernel(__nv_bfloat16* __restrict__ gout, Scratch* __restrict__ gs, const uint8_t* __restrict__ gwmod,
                    const uint8_t* __restrict__ gx, const uint8_t* __restrict__ gc, uint32_t* __restrict__ gin,
                    const __grid_constant__ Params P) {
  constexpr Tune T{};
  extern __shared__ __align__(1024) uint8_t smem_raw[];
  const uint32_t sb = (uint32_t)__cvta_generic_to_shared(smem_raw);
  const int tid = __shfl_xor_sync(0xffffffffu, threadIdx.x ^ 1, 1), lane = tid & 31;
  const int w = __shfl_sync(0xffffffffu, threadIdx.x >> 5, 0);
  const int cta = blockIdx.x;
  const uint32_t bars = sb + OFF_BARS;
  auto BAR = [&](int i) { return bars + 8 * i; };
  auto inbox = [&](int c, int k) { uint32_t v; asm volatile("ld.shared.u8 %0, [%1];" : "=r"(v) : "r"(sb + OFF_SEL + c) : "memory"); return gin + blk(c, k, v); };
  const int g = lane >> 2, t = lane & 3;
  const int hI = cta >> 2, jI = cta & 3;
  const int bs = cta >> 1, hh = cta & 1;

  CLK_DECL;
  CLK(0);
  if (w == 8) {
    CLK(7);
    const uint32_t t_entry = gtime32();
    CLK(8);
    if (lane == 0) {
      if ((sb & 0xffffff) != SB) __trap();
      mbar_init(BAR(BAR_WQ), 1); mbar_init(BAR(BAR_WQ + 1), 1); mbar_init(BAR(BAR_XC), 1); mbar_init(BAR(BAR_C), 1);
      asm volatile("fence.mbarrier_init.release.cluster;" ::: "memory");
      asm volatile("prefetch.tensormap [%0];" ::"l"(&P.wq) : "memory");
      mbar_expect(BAR(BAR_XC), 8192); mbar_expect(BAR(BAR_C), 8192); mbar_expect(BAR(BAR_WQ), 16384); mbar_expect(BAR(BAR_WQ + 1), 16384);
      CLK(9);
    }
    __syncwarp();
    asm volatile("barrier.cta.arrive.aligned 0, %0;" ::"n"(NTHREADS) : "memory");
    CLK(10);
    uint32_t tn = t_entry + T.PC_T0 + ((bs * 37) & 63) * T.PC_STAG / 64;
    const int h = hI, j = jI;
    if (lane == 0) {
      uint64_t pol; asm volatile("createpolicy.fractional.L2::evict_first.b64 %0, 1.0;" : "=l"(pol));
#pragma unroll
      for (int u = 0; u < 4; u++) {
        until_ns(tn + u * T.PC_P1);
        if (u == 0) CLK(11);
        tma2d(sb + OFF_WQ + u * 8192, &P.wq, 128 * h + 64 * (u >> 1), 128 * j + 64 * (u & 1), BAR(BAR_WQ + (u >> 1)), pol);
        if (u == T.PC_XC) {
#pragma unroll
          for (int i = 0; i < 4; i++) { const int o = ((i + cta) & 3) * 2048; bulk_ld(sb + OFF_XS + o, gx + o, 2048, BAR(BAR_XC)); }
        }
        if (u == T.PC_C) {
#pragma unroll
          for (int i = 0; i < 4; i++) { const int o = ((i + cta) & 3) * 2048; bulk_ld(sb + OFF_CS + o, gc + o, 2048, BAR(BAR_C)); }
        }
        if (u == 0) {
          CLK(1);
          asm volatile("prefetch.tensormap [%0];" ::"l"(&P.wuk) : "memory");
          asm volatile("prefetch.tensormap [%0];" ::"l"(&P.wm2) : "memory");
          asm volatile("prefetch.tensormap [%0];" ::"l"(&P.ckv2) : "memory");
        }
      }
    }
    __syncwarp();
    tn += 4 * T.PC_P1;
    bar_sync(5, 64);
    if (lane == 0) {
      uint64_t pol; asm volatile("createpolicy.fractional.L2::evict_first.b64 %0, 1.0;" : "=l"(pol));
#pragma unroll
      for (int u = 0; u < 4; u++) {
        if ((u & 1) == (T.PC_W > 3) && T.PC_NW) mbar_wait(BAR(BAR_WQ + (u >> 1)));
        slot(tn, T.PC_SL);
        tma5d(sb + OFF_WUK + u * 8192, &P.wuk, 128 * h + 64 * (u >> 1), 0, 0, 0, 8 * j + 4 * (u & 1), BAR(BAR_WUK + (u >> 1)), pol);
        tn += T.PC_P1;
      }
#pragma unroll
      for (int u = 0; u < 2; u++) {
        if (u == (T.PC_W > 3) && T.PC_NW) mbar_wait(BAR(BAR_WUK));
        slot(tn, T.PC_SL);
        tma2d_nohint(sb + OFF_WM2 + u * 8192, &P.wm2, 1024 + 16 * cta, 256 * u, BAR(BAR_WM2));
        tn += T.PC_P1;
      }
      const int row0 = (bs >> 3) * 4096 + (bs & 7) * 64;
      uint32_t dst = sb + OFF_RING;
      const int p2 = T.PC_P2 + (32 - ((bs * 37) & 63)) * T.PC_DS / 1024;
#pragma unroll 1
      for (int n = 0; n < 31; n++) {
        if (n >= 4 && (n < 12 || (n & 3) == 0)) mbar_wait(BAR(n >= 12 ? BAR_EMPTY + (n >> 2) - 3 : n == 7 ? BAR_P0BD : (n == 8 || n == 9) ? BAR_P2D : BAR_P1D));
        if (n < T.PC_NW) {
          if (n >= T.PC_W) mbar_wait(BAR(BAR_FULL + n - T.PC_W));
          else if ((n & 1) == (T.PC_W > 3)) mbar_wait(BAR(n < 2 ? BAR_WUK + 1 : BAR_WM2));
        }
        slot(tn, T.PC_SL);
        tma3d(dst, &P.ckv2, 0, row0 + (n >> 2) * 512, 2 * (n & 3), BAR(BAR_FULL + n), pol);
        dst = (n == 11 || n == 23) ? sb + OFF_RING : dst + 16384;
        tn += n >= 15 ? p2 : T.PC_P2;
        if (n == 4) CLK(2);
        if (n == 12) CLK(3);
        if (n == 20) CLK(4);
        if (n == 28) CLK(5);
        if (n == 24) {
          asm volatile("prefetch.tensormap [%0];" ::"l"(&P.ckv1) : "memory");
          asm volatile("prefetch.tensormap [%0];" ::"l"(&P.wuv) : "memory");
          asm volatile("prefetch.tensormap [%0];" ::"l"(&P.wo) : "memory");
          asm volatile("prefetch.tensormap [%0];" ::"l"(&P.w1) : "memory");
          asm volatile("prefetch.tensormap [%0];" ::"l"(&P.w2) : "memory");
        }
      }
      slot(tn, T.PC_SL);
      tma3d(dst, &P.ckv1, 0, row0 + 7 * 512, 6, BAR(BAR_LAST + 3), pol);
      tma3d(dst + 8192, &P.ckv1, 0, row0 + 7 * 512, 7, BAR(BAR_LAST + 4), pol);
      tn += T.PC_P2;
      CLK(6);
      auto unit = [&](int u) {
        if (u < 4) tma5d(sb + OFF_WUV + u * 8192, &P.wuv, 128 * h + 64 * (u >> 1), 0, 4 * (j >> 1), 0, 2 * (j & 1) + (u & 1), BAR(BAR_WUV + (u >> 1)), pol);
        else if (u < 8) tma2d(sb + OFF_WO + (u - 4) * 8192, &P.wo, 128 * j + 64 * ((u - 4) >> 1), 128 * h + 64 * (u & 1), BAR(BAR_WO + ((u - 4) >> 1)), pol);
        else if (u < 10) { if (cta < NFF) tma2d_nohint(sb + OFF_W1 + (u - 8) * 16384, &P.w1, 32 * bs, 256 * (u - 8), BAR(BAR_W1)); }
        else if (cta < NFF) tma3d(sb + OFF_W2 + (u - 10) * 8192, &P.w2, 0, 32 * bs, 4 * hh + 2 * (u - 10), BAR(BAR_W2), pol);
      };
      mbar_wait(BAR(BAR_EMPTY + 5));
      if (T.PW_A >= 0) { mbar_wait(BAR(BAR_LAST + T.PW_A)); tn = gtime32(); }
      tn += T.PW_0 + ((cta * 37) & 127) * T.PW_ST / 128;
#pragma unroll
      for (int u = 0; u < 12; u++) {
        if (u == 8) mbar_wait(BAR(BAR_EMPTY + 6));
        until_ns(tn);
        unit(WSWAP && u >= 8 ? (u ^ 2) : u);
        tn += u < 3 ? T.PW_UV : u == 3 ? T.PW_G : u < 7 ? T.PW_O : u == 7 ? T.PW_G2 : u == 9 ? T.PW_G3 : T.PW_F;
      }
      CLK_DUMP();
    }
    return;
  }

  if (w == 9) {
    if (lane == 0) {
#pragma unroll
      for (int i = 0; i < NBARS; i++) mbar_init(BAR(i), i >= BAR_P1D ? 8 : i >= BAR_EMPTY ? 4 : 1);
      asm volatile("fence.mbarrier_init.release.cluster;" ::: "memory");
    }
    __syncwarp();
    mbar_expect(BAR(lane), lane == BAR_LAST + 3 ? 8192 : 16384);
    if (lane < BAR_ALLCLR - 32) mbar_expect(BAR(32 + lane), lane == 0 ? 8192 : lane == BAR_W1 - 32 ? 32768 : 16384);
    CLK(9);
    asm volatile("barrier.cta.arrive.aligned 5, 64;" ::: "memory");
    asm volatile("barrier.cta.arrive.aligned 0, %0;" ::"n"(NTHREADS) : "memory");
  }
  const uint32_t epoch = ldg_rlx1(&gs->epoch);

  if (w == 9) {
    const int mo = g * 512 + 16 * hI + 2 * jI;
    const uint32_t xo0 = ldg_nc1(gx + mo * 2), xo1 = ldg_nc1(gx + mo * 2 + 16);
    const int par = epoch & 1;
    const uint32_t t0 = gtime32();
    const uint4 z = make_uint4(0, 0, 0, 0);
    uint32_t sel;
    {
      uint32_t* pa = gin + blk(cta, 5, 0) + 960;
      uint32_t* pb = gin + blk(cta, 5, 1) + 960;
      until_ns(t0 + T.PR_T0);
      if (lane < 4) stg4(reinterpret_cast<uint4*>(lane & 2 ? pa : pb) + (lane & 1), z);
      uint32_t ma = 0xffffffffu, mb = 0xffffffffu;
      if (lane == 0) {
#pragma unroll 1
        for (int i = 0; i < 2 * T.PR_N; i++) {
          const uint32_t c0 = clk32();
          uint32_t v;
          asm volatile("atom.relaxed.gpu.global.add.u32 %0, [%1], 1;" : "=r"(v) : "l"(i & 1 ? pb : pa) : "memory");
          if (v == 0xffffffffu) __trap();
          const uint32_t d = clk32() - c0;
          if (i & 1) mb = min(mb, d); else ma = min(ma, d);
        }
      }
      sel = __shfl_sync(~0u, (uint32_t)(mb < ma), 0);
      if (T.LOC == 1) sel ^= 1;
      if (T.LOC == 2) sel ^= (cta ^ (cta >> 3)) & 1;
      const uint32_t sw = 2 * (epoch + 1) + sel;
      if (lane < 2) stg4(reinterpret_cast<uint4*>(gin + blk(cta, 5, 1) + 896) + lane, make_uint4(sw, sw, sw, sw));
    }
    until_ns(t0 + T.CLR_T0);
    {
      const int nb = (cta & 7) == 0 ? 16 : 12;
#pragma unroll 1
      for (int i0 = 0; i0 < nb; i0++) {
        uint4* q = reinterpret_cast<uint4*>(gin + blk(cta, i0 >> 1, sel) + (i0 & 1) * 512) + lane;
#pragma unroll
        for (int i = 0; i < 4; i++) if (i0 != 11 || i < 3) stg4(q + i * 32, z);
        backoff(T.CLR_CLK);
      }
      if (jI == 1) stg4(reinterpret_cast<uint4*>(gin + blk(cta, 6, sel)) + lane, z);
      if (lane < 2) stg4(reinterpret_cast<uint4*>(gin + blk(cta, 5, sel) + 928) + lane, z);
      CLK(1);
      {
        uint32_t sv = 0;
        uint32_t u[4];
#pragma unroll
        for (int i = 0; i < 4; i++) u[i] = ldg_rlx1(gin + blk(4 * lane + i, 5, 1) + 896);
#pragma unroll
        for (int i = 0; i < 4; i++) {
          int it = 0;
          while ((u[i] | 1) != 2 * (epoch + 1) + 1) { u[i] = ldg_rlx1(gin + blk(4 * lane + i, 5, 1) + 896); if (++it > SPIN_LIMIT) __trap(); }
          sv |= (u[i] & 1) << (8 * i);
        }
        sts1(sb + OFF_SEL + lane * 4, sv);
      }
      asm volatile("fence.acq_rel.gpu;" ::: "memory");
      CLK(2);
      __syncwarp();
      if (lane < NSYNC) asm volatile("red.relaxed.gpu.global.add.u32 [%0], 1;" ::"l"(&gs->sync[lane][0]) : "memory");
#pragma unroll
      for (int i = 0; i < 4; i++) stg4(reinterpret_cast<uint4*>(gs->QP[par ^ 1] + cta * 512) + i * 32 + lane, z);
      backoff(T.CLR_CLK);
#pragma unroll
      for (int i = 0; i < 4; i++) stg4(reinterpret_cast<uint4*>(gs->QX[par ^ 1] + cta * 512) + i * 32 + lane, z);
      stg4(reinterpret_cast<uint4*>(gs->MOD1[par ^ 1] + cta * 128) + lane, z);
      if (lane < 16) stg4(reinterpret_cast<uint4*>(gs->MOD2[par ^ 1] + cta * 64) + lane, z);
      if (lane == 0) {
        const uint32_t target = (epoch + 1) * NCTA;
        uint32_t c; int it = 0;
        do { backoff(T.CLR_CLK); asm volatile("ld.acquire.gpu.global.u32 %0, [%1];" : "=r"(c) : "l"(&gs->sync[cta % NSYNC][0]) : "memory"); if (++it > SPIN_LIMIT) __trap(); } while ((int)(c - target) < 0);
        mbar_arrive(BAR(BAR_ALLCLR));
      }
      __syncwarp();
    }
    CLK(3);
    uint2 gg[2];
    {
      const uint32_t* pg = gs->MOD2[par] + cta * 16 + g * 2;
      load_units<2, 3 * 2048>(gg, pg);
      check_units<2, 3 * 2048>(gg, pg, T.RB);
    }
    uint32_t anchor;
    {
      uint32_t* const po = inbox(NTS * (lane & (128 / NTS - 1)), 5) + 928;
      const uint32_t* const pi = inbox(cta & ~(NTS - 1), 5) + 928;
      mbar_wait(BAR(BAR_LAST + T.TS_P));
      unsigned long long now; asm volatile("mov.u64 %0, %%globaltimer;" : "=l"(now));
      if (lane < 128 / NTS) {
        asm volatile("red.relaxed.gpu.global.max.u64 [%0], %1;" ::"l"(po + 2), "l"(now) : "memory");
        asm volatile("red.relaxed.gpu.global.add.u32 [%0], 1;" ::"l"(po + 1) : "memory");
      }
      backoff(T.D_TS);
      uint4 v; int it = 0;
      do { v = ldg_2u64(pi); if (++it > SPIN_LIMIT) __trap(); } while (v.y != NCTA);
      const int age = min(max((int)(gtime32() - v.z), 0), 4000);
      anchor = clk32() - age * 7 / 4 + T.TS_O;
      if (lane == 0) { sts1(sb + OFF_TS, anchor); mbar_arrive(BAR(BAR_TS)); }
      CLK(10);
    }
    {
      const uint32_t* pm = pin(inbox(4 * hI + 1, 6) + lane * 4);
      wait_clk(anchor, T.A_M);
      uint4 ml = ldg_2u64(pm);
      int it = 0;
      while (ml.y == 0 || ml.w == 0) { ml = ldg_2u64(pm); if (++it > SPIN_LIMIT) __trap(); }
      __syncwarp();
      ITS(2, it);
      float M = fmaxf(__uint_as_float(ml.x), __uint_as_float(ml.z));
      M = fmaxf(M, __shfl_xor_sync(~0u, M, 1)); M = fmaxf(M, __shfl_xor_sync(~0u, M, 2));
      const float e0 = ex2(__uint_as_float(ml.x) - M), e1 = ex2(__uint_as_float(ml.z) - M);
      float l = e0 * __uint_as_float(ml.y) + e1 * __uint_as_float(ml.w);
      l += __shfl_xor_sync(~0u, l, 1); l += __shfl_xor_sync(~0u, l, 2);
      const float inv = __fdividef(1.f, l);
      sts2f(sb + OFF_WV + lane * 8, e0 * inv, e1 * inv);
      __syncwarp();
      if (lane == 0) mbar_arrive(BAR(BAR_WV));
      CLK(11);
    }
    uint32_t* x3o[4];
#pragma unroll
    for (int i = 0; i < 4; i++) x3o[i] = pin(inbox(32 * i + 8 * t, 6 + (cta >> 6)) + (cta & 63) * 16 + g * 2);
    uint32_t* const fo = pin(reinterpret_cast<uint32_t*>(gout) + mo / 2 + 4 * (t & 1));
    const uint32_t* const p3 = pin(gin + blk(cta, 4, sel) + t * 16 + g * 2);
    const uint32_t* const p4 = pin(gin + blk(cta, 5, sel) + t * 16 + g * 2);
    const uint32_t one = pin((g & 1) ? 0x3f800000u : 0x00003f80u);
    const float xf[4] = {pin(bf_lo(xo0)), pin(bf_hi(xo0)), pin(bf_lo(xo1)), pin(bf_hi(xo1))};
    const float ga[4] = {pin(bf_lo(gg[0].x)), pin(bf_hi(gg[0].x)), pin(bf_lo(gg[0].y)), pin(bf_hi(gg[0].y))};
    mbar_wait(BAR(BAR_P5D));
    backoff(T.D_X3A);
    wait_clk(anchor, T.A_X1 + T.R_X3A);
    CLK(4);
    float r[4];
    uint32_t x20, x21;
    int it = 0;
    bool ok;
    do {
      ok = sum_pieces<32>(p3, one, r);
      x20 = pack_bf16(xf[0] + ga[0] * r[0], xf[1] + ga[1] * r[1]); x21 = pack_bf16(xf[2] + ga[2] * r[2], xf[3] + ga[3] * r[3]);
#pragma unroll
      for (int i = 0; i < 4; i++) stg_u64_unless(!ok || (i == 3 && t >= 2), x3o[i], x20, x21);
    } while (!ok && ++it < SPIN_LIMIT);
    CLK(6);
    ITS(0, it);
    const uint32_t xw = (t & 1) ? x21 : x20, gw = (t & 1) ? gg[1].y : gg[1].x;
    const float xa = pin(bf_lo(xw)), xb = pin(bf_hi(xw)), gba = pin(bf_lo(gw)), gbb = pin(bf_hi(gw));
    if (cta < NFF) { mbar_wait(BAR(BAR_P7D)); backoff(T.D_FIN); } else { backoff(1200); wait_clk(anchor, T.A_X1 + T.R_X3A + T.R_X3B + T.R_FIN); }
    CLK(7);
    do {
      ok = sum_pieces<NFG>(p4, one, r);
      const uint32_t o = pack_bf16(xa + gba * ((t & 1) ? r[2] : r[0]), xb + gbb * ((t & 1) ? r[3] : r[1]));
      if (ok && t < 2) asm volatile("st.global.u32 [%0], %1;" ::"l"(fo), "r"(o) : "memory");
    } while (!ok && ++it < SPIN_LIMIT);
    if (!ok) __trap();
    ITS(1, it);
    CLK(8);
    CLK_DUMP();
    if (cta == 0 && lane == 0) stg1(&gs->epoch, epoch + 1);
    return;
  }

  const int wg = w >> 2, wq = w & 3;
  uint32_t tstore;
  {
    const uint8_t* pw = gwmod + (size_t)(128 * jI + 16 * w + 4 * (g >> 1) + (g & 1)) * 6144 + 64 * hI + 16 * t;
    const uint4 w0 = ldg_nc4(pw), w1 = ldg_nc4(pw + 2 * 6144);
    const uint2 cc = ldg_nc2(gc + g * 1024 + 256 * jI + 32 * w + 8 * t);
    CLK(40);
    const uint32_t a[4] = {silu2(cc.x), 0u, silu2(cc.y), 0u};
    float d[4][4] = {{0.f, 0.f, 0.f, 0.f}, {0.f, 0.f, 0.f, 0.f}, {0.f, 0.f, 0.f, 0.f}, {0.f, 0.f, 0.f, 0.f}};
    mma16816(d[0], a, movm(w0.x), movm(w1.x)); mma16816(d[1], a, movm(w0.y), movm(w1.y));
    mma16816(d[2], a, movm(w0.z), movm(w1.z)); mma16816(d[3], a, movm(w0.w), movm(w1.w));
    CLK(1);
    sts4f(sb + OFF_P0S + w * 1088 + lane * 16, d[0][0], d[0][1], d[1][0], d[1][1]);
    sts4f(sb + OFF_P0S + w * 1088 + 544 + lane * 16, d[2][0], d[2][1], d[3][0], d[3][1]);
    bar_sync(0, NTHREADS);
    if (tid < 128) {
      const uint32_t src = sb + OFF_P0S + ((tid >> 2) & 1) * 544 + (((tid >> 3) & 7) * 4 + 2 * (tid >> 6) + (tid & 1)) * 16 + ((tid >> 1) & 1) * 8;
      float2 v[8];
#pragma unroll
      for (int i = 0; i < 8; i++) v[i] = ldsf2(src + i * 1088);
      const float ax = ((v[0].x + v[1].x) + (v[2].x + v[3].x)) + ((v[4].x + v[5].x) + (v[6].x + v[7].x));
      const float ay = ((v[0].y + v[1].y) + (v[2].y + v[3].y)) + ((v[4].y + v[5].y) + (v[6].y + v[7].y));
      stg1(gs->MOD1[epoch & 1] + jI * 4096 + hI * 128 + tid, nz(pack_bf16(ax, ay)));
    }
    tstore = clk32();
  }
  CLK(2);
  const int par = epoch & 1;
  uint32_t cf[4][4];
  mbar_wait(BAR(BAR_XC));
  {
    uint32_t u[2][4];
    lds4(u[0], sb + OFF_XS + w * 1024 + lane * 16); lds4(u[1], sb + OFF_XS + w * 1024 + 512 + lane * 16);
    float v[16];
#pragma unroll
    for (int i = 0; i < 8; i++) { v[2 * i] = bf_lo(u[i >> 2][i & 3]); v[2 * i + 1] = bf_hi(u[i >> 2][i & 3]); }
    float s = 0.f;
#pragma unroll
    for (int i = 0; i < 16; i++) s += v[i];
#pragma unroll
    for (int o = 16; o; o >>= 1) s += __shfl_xor_sync(~0u, s, o);
    const float mu = s * (1.f / 512.f);
    float q = 0.f;
#pragma unroll
    for (int i = 0; i < 16; i++) { v[i] -= mu; q += v[i] * v[i]; }
#pragma unroll
    for (int o = 16; o; o >>= 1) q += __shfl_xor_sync(~0u, q, o);
    const float rs = rsqrtf(q * (1.f / 512.f) + 1e-5f);
    const bool hi = jI & 2;
    uint32_t o[4];
#pragma unroll
    for (int i = 0; i < 4; i++) o[i] = pack_bf16((hi ? v[8 + 2 * i] : v[2 * i]) * rs, (hi ? v[9 + 2 * i] : v[2 * i + 1]) * rs);
    if ((lane >> 4) == (jI & 1)) sts4(sb + OFF_XN + w * 272 + (lane & 15) * 16, make_uint4(o[0], o[1], o[2], o[3]));
  }
  CLK(3);
  uint32_t aw[8][4];
  {
    const uint32_t* pm = pin(gs->MOD1[par] + (8 * jI + w) * 64 + lane * 2);
    uint32_t* const qpo = pin(gs->QP[par] + (cta * 256 + tid) * 2);
    wait_clk(tstore, T.D_MOD);
    CLK(4);
    uint2 v[8];
    load_units<8, 2048>(v, pm);
    cbar();
    const uint32_t xn0 = lds1(sb + OFF_XN + g * 272 + w * 32 + t * 4), xn1 = lds1(sb + OFF_XN + g * 272 + w * 32 + 16 + t * 4);
    const bool early = __all_sync(~0u, mbar_test(BAR(BAR_WQ + wg)));
    if (early) load_a_t(aw, sb + OFF_WQ, w, lane);
    int it = 0;
    while (true) {
      uint32_t mn = 0xffffffffu;
#pragma unroll
      for (int i = 0; i < 8; i++) mn = min(mn, min(v[i].x, v[i].y));
      if (mn != 0) break;
#pragma unroll
      for (int i = 0; i < 8; i++) if (v[i].x == 0 || v[i].y == 0) v[i] = ldg_u64(pm + i * 2048);
      if (++it > SPIN_LIMIT) __trap();
    }
    CLK(5);
    ITS(0, it);
    float sc[2][4];
#pragma unroll
    for (int i = 0; i < 2; i++) {
      sc[i][0] = (bf_lo(v[i].x) + bf_lo(v[2 + i].x)) + (bf_lo(v[4 + i].x) + bf_lo(v[6 + i].x));
      sc[i][1] = (bf_hi(v[i].x) + bf_hi(v[2 + i].x)) + (bf_hi(v[4 + i].x) + bf_hi(v[6 + i].x));
      sc[i][2] = (bf_lo(v[i].y) + bf_lo(v[2 + i].y)) + (bf_lo(v[4 + i].y) + bf_lo(v[6 + i].y));
      sc[i][3] = (bf_hi(v[i].y) + bf_hi(v[2 + i].y)) + (bf_hi(v[4 + i].y) + bf_hi(v[6 + i].y));
    }
    sts2(sb + OFF_BS1 + (w >> 1) * 512 + lane * 16 + (w & 1) * 8,
         pack_bf16(bf_lo(xn0) * (1.f + sc[1][0]) + sc[0][0], bf_hi(xn0) * (1.f + sc[1][1]) + sc[0][1]),
         pack_bf16(bf_lo(xn1) * (1.f + sc[1][2]) + sc[0][2], bf_hi(xn1) * (1.f + sc[1][3]) + sc[0][3]));
    if (!early) { mbar_wait(BAR(BAR_WQ + wg)); load_a_t(aw, sb + OFF_WQ, w, lane); }
    CLK(6);
    cbar();
    uint32_t b[4][4];
#pragma unroll
    for (int kk = 0; kk < 4; kk++) lds4(b[kk], sb + OFF_BS1 + kk * 512 + lane * 16);
    float d[4];
    mma128(d, aw, b);
    stg_u64(qpo, pack_bf16(d[0], d[1]), pack_bf16(d[2], d[3]));
    tstore = clk32();
    CLK(7);
    if (wg) {
      mbar_wait(BAR(BAR_C));
#pragma unroll
      for (int i = 0; i < 4; i++) lds4(cf[i], sb + OFF_CS + g * 1024 + wq * 256 + i * 64 + t * 16);
#pragma unroll
      for (int i = 0; i < 16; i++) cf[i >> 2][i & 3] = silu2(cf[i >> 2][i & 3]);
    }
    __syncwarp();
    if (lane == 0) mbar_arrive(BAR(BAR_P1D));
  }
  {
    const uint32_t* pq = pin(gs->QP[par] + (hI * 4 * 256 + tid) * 2);
    uint32_t* const qxo = pin(gs->QX[par] + (g * 32 + hI) * 256 + 64 * jI + 8 * w + 2 * t);
    uint2 v[4];
    wait_clk(tstore, T.D_QP);
    CLK(8);
    load_units<4, 512>(v, pq);
    const uint32_t abase = sb + OFF_WUK + (16 * w + (lane & 15)) * 128;
    auto load_half = [&](int hf) {
#pragma unroll
      for (int ks = 0; ks < 4; ks++) ldsm4(aw[4 * hf + ks], abase + hf * 16384 + (((2 * ks + (lane >> 4)) ^ (lane & 7)) << 4));
    };
    mbar_wait(BAR(BAR_WUK));
    load_half(0);
    const bool early = __all_sync(~0u, mbar_test(BAR(BAR_WUK + 1)));
    if (early) load_half(1);
    const int it = check_units<4, 512>(v, pq, T.RB);
    CLK(9);
    ITS(1, it);
    sum4_to_smem(v, sb + OFF_BS2 + (16 * w + g) * 16 + t * 4);
    if (!early) { mbar_wait(BAR(BAR_WUK + 1)); load_half(1); }
    CLK(10);
    cbar();
    uint32_t b[4][4];
#pragma unroll
    for (int kk = 0; kk < 4; kk++) ldsm4t(b[kk], sb + OFF_BS2 + (32 * kk + lane) * 16);
    float d[4];
    mma128(d, aw, b);
    const float sc = 0.08838834764831845f * 1.4426950408889634f;
    stg_u64(qxo, movm(pack_bf16(d[0] * sc, d[1] * sc)), movm(pack_bf16(d[2] * sc, d[3] * sc)));
    tstore = clk32();
    CLK(11);
    if (lane == 0) mbar_arrive(BAR(BAR_P2D));
  }
  if (wg) {
    const int mi = lane >> 3, r = lane & 7;
    const uint32_t a0 = sb + OFF_WM2 + (8 * (r >> 1) + (r & 1) + 2 * (mi >> 1)) * 32 + (mi & 1) * 16;
    mbar_wait(BAR(BAR_WM2));
#pragma unroll
    for (int s = 0; s < 8; s++) ldsm4t(aw[s], a0 + (128 * wq + 32 * (s >> 1) + 4 * (s & 1)) * 32);
    float d[4];
    mma128(d, aw, cf);
    sts4f(sb + OFF_P0B + (tid - 128) * 16, d[0], d[1], d[2], d[3]);
    if (lane == 0) mbar_arrive(BAR(BAR_P0BD));
    bar_sync(3, 128);
    if (w == 4) {
      float4 v[4];
#pragma unroll
      for (int i = 0; i < 4; i++) v[i] = ldsf4(sb + OFF_P0B + (i * 32 + lane) * 16);
      stg_u64(gs->MOD2[par] + cta * 64 + t * 16 + g * 2, movm(pack_bf16((v[0].x + v[1].x) + (v[2].x + v[3].x), (v[0].y + v[1].y) + (v[2].y + v[3].y))),
              movm(pack_bf16((v[0].z + v[1].z) + (v[2].z + v[3].z), (v[0].w + v[1].w) + (v[2].w + v[3].w))));
    }
    CLK(15);
  }
  {
    const uint32_t* qx = pin(gs->QX[par] + ((bs >> 3) * 32 + 16 * hh) * 256 + tid * 4);
    const int ch = tid & 63, h0 = tid >> 6;
    const uint32_t dst = sb + OFF_Q + (ch >> 3) * 2048 + h0 * 128;
    wait_clk(tstore, T.D_QX);
    CLK(12);
    uint4 v[4];
#pragma unroll
    for (int i = 0; i < 4; i++) v[i] = ldg_2u64(qx + i * 1024);
    int it = 0;
    while (true) {
      uint32_t mn = 0xffffffffu;
#pragma unroll
      for (int i = 0; i < 4; i++) mn = min(mn, min(v[i].y, v[i].w));
      if (mn != 0) break;
#pragma unroll
      for (int i = 0; i < 4; i++) if (v[i].y == 0 || v[i].w == 0) v[i] = ldg_2u64(qx + i * 1024);
      if (++it > SPIN_LIMIT) __trap();
    }
    CLK(13);
    ITS(2, it);
#pragma unroll
    for (int i = 0; i < 4; i++) sts4(dst + i * 512 + (((ch & 7) ^ ((4 * i + h0) & 7)) << 4), v[i]);
    asm volatile("fence.proxy.async.shared::cta;" ::: "memory");
    CLK(14);
    cbar();
  }

  uint2 cbf[4], sbf[4];
  const uint32_t* const pcb = gs->MOD2[par] + 2048 + (16 * w + t) * 16 + g * 2;
  uint32_t thand, anchor;
  if (wg == 0) {
    float mh[4];
    float L[8];
#pragma unroll
    for (int i = 0; i < 4; i++) { L[2 * i] = L[2 * i + 1] = 0.f; mh[i] = -INFINITY; }
    constexpr uint32_t dq = desc_lo(OFF_Q);
    const uint32_t ptw = sb + OFF_PT + (8 * (lane >> 4) + (lane & 7)) * 128 + (((2 * wq + ((lane >> 3) & 1)) ^ (lane & 7)) << 4);
    float S[8];
    auto softmax = [&](int tl) {
      auto write_p = [&](const float (&x)[8]) {
        float p[8];
#pragma unroll
        for (int i = 0; i < 8; i++) p[i] = ex2(x[i]);
        stsm4t(ptw + (tl & 1) * 2048, pack_bf16(p[0], p[1]), pack_bf16(p[2], p[3]), pack_bf16(p[4], p[5]), pack_bf16(p[6], p[7]));
        asm volatile("fence.proxy.async.shared::cta;" ::: "memory");
      };
      float x[8];
#pragma unroll
      for (int i = 0; i < 8; i++) x[i] = S[i] - mh[2 * (i >> 2) + (i & 1)];
      if (tl) write_p(x);
      const float ex = fmaxf(fmaxf(fmaxf(x[0], x[1]), fmaxf(x[2], x[3])), fmaxf(fmaxf(x[4], x[5]), fmaxf(x[6], x[7])));
      if (tl == 0 || bar_over(ex)) {
        float mx[4];
#pragma unroll
        for (int i = 0; i < 4; i++) mx[i] = fmaxf(S[4 * (i >> 1) + (i & 1)], S[4 * (i >> 1) + 2 + (i & 1)]);
        const float a = reduce_g(mx, lane, [](float u, float v) { return fmaxf(u, v); });
        stsf(sb + OFF_RED + wq * 64 + (8 * (lane >> 4) + 2 * t + ((lane >> 3) & 1)) * 4, a);
        bar_sync(2, 128);
#pragma unroll
        for (int jn = 0; jn < 2; jn++) {
          float m0 = mh[2 * jn], m1 = mh[2 * jn + 1];
#pragma unroll
          for (int i = 0; i < 4; i++) { const float2 v = ldsf2(sb + OFF_RED + i * 64 + (8 * jn + 2 * t) * 4); m0 = fmaxf(m0, v.x); m1 = fmaxf(m1, v.y); }
          const float a0 = ex2(mh[2 * jn] - m0), a1 = ex2(mh[2 * jn + 1] - m1);
          mh[2 * jn] = m0; mh[2 * jn + 1] = m1;
          L[4 * jn] *= a0; L[4 * jn + 1] *= a1; L[4 * jn + 2] *= a0; L[4 * jn + 3] *= a1;
          if (tid < 4) sts2f(sb + OFF_ALPHA + (8 * jn + 2 * t) * 4, a0, a1);
        }
#pragma unroll
        for (int i = 0; i < 8; i++) x[i] = S[i] - mh[2 * (i >> 2) + (i & 1)];
        write_p(x);
        cbar();
      }
      const uint32_t dpt = __shfl_sync(~0u, desc_lo(OFF_PT) + (tl & 1) * 128, 0);
      wg_fence();
#pragma unroll
      for (int ks = 0; ks < 4; ks++) wgmma_n16_ones(L, ONE2, dpt + ks * 2);
      wg_commit();
    };
    uint32_t da = desc_lo(OFF_RING);
#pragma unroll 1
    for (int tl = 0; tl < 7; tl++) {
      uint32_t ok = 0;
#pragma unroll
      for (int u = 0; u < 4; u++) ok += mbar_test(BAR(BAR_FULL + 4 * tl + u));
      ok = __reduce_min_sync(~0u, ok);
      const uint32_t du = __shfl_sync(~0u, da, 0);
#pragma unroll
      for (int u = 0; u < 4; u++) {
        if (ok != 4) mbar_wait(BAR(BAR_FULL + 4 * tl + u));
        wg_fence();
#pragma unroll
        for (int k = 0; k < 8; k++) {
          const int i = 8 * u + k;
          if (i == 0) wgmma_n16<0, 0>(S, du, dq); else wgmma_n16<0, 1>(S, du + (i >> 2) * 512 + (i & 3) * 2, dq + (i >> 2) * 128 + (i & 3) * 2);
        }
        wg_commit();
      }
      wg_wait<0>();
      acc_fence(S); acc_fence(L);
      if (tl == 0) CLK(15);
      if (tl == 1) CLK(17);
      softmax(tl);
      if (tl == 0) CLK(16);
      if (tl == 1) CLK(18);
      if (tl == 3) CLK(19);
      if (tl == 6) CLK(20);
      da = (tl == 2 || tl == 5) ? da - 8192 : da + 4096;
    }
    if (cta < NFF) { load_units<4, 64>(sbf, pcb); load_units<4, 64>(cbf, pcb + 2048); }
    mbar_wait(BAR(BAR_ALLCLR));
    uint32_t* const mlo = pin(inbox(4 * (16 * hh + 4 * (g & 2) + 2 * t + (g & 1)) + 1, 6) + bs * 2);
#pragma unroll
    for (int i = 0; i < 32; i++) {
      if (i == 0 || i == 8 || i == 16 || i == 24 || i == 28) {
        if (i) wg_commit();
        mbar_wait(BAR(BAR_LAST + (i == 28 ? 4 : i >> 3)));
        if (i == 28) CLK(21);
        wg_fence();
      }
      if (i == 0) wgmma_n16<0, 0>(S, da, dq); else wgmma_n16<0, 1>(S, da + (i >> 2) * 512 + (i & 3) * 2, dq + (i >> 2) * 128 + (i & 3) * 2);
    }
    wg_commit();
    wg_wait<0>();
    acc_fence(S); acc_fence(L);
    CLK(22);
    softmax(7);
    CLK(23);
    thand = clk32();
    wg_wait<0>();
    acc_fence(L);
    if (tid < 16) stg_u64(mlo, __float_as_uint(g & 2 ? (g & 1 ? mh[3] : mh[2]) : (g & 1 ? mh[1] : mh[0])), __float_as_uint(g & 2 ? (g & 1 ? L[5] : L[4]) : (g & 1 ? L[1] : L[0])));
    CLK(24);
  } else {
    float O[8][8];
#pragma unroll
    for (int i = 0; i < 8; i++)
#pragma unroll
      for (int k = 0; k < 8; k++) O[i][k] = 0.f;
    constexpr uint32_t dp = desc_lo(OFF_PT);
    auto handover = [&](int tl) {
      if (tl == 0) { cbar(); return; }
      if (bar_over(0.f)) {
        cbar();
#pragma unroll
        for (int jn = 0; jn < 2; jn++) {
          const float2 a = ldsf2(sb + OFF_ALPHA + (8 * jn + 2 * t) * 4);
#pragma unroll
          for (int mb = 0; mb < 8; mb++) { O[mb][4 * jn] *= a.x; O[mb][4 * jn + 1] *= a.y; O[mb][4 * jn + 2] *= a.x; O[mb][4 * jn + 3] *= a.y; }
        }
      }
    };
    uint32_t da = desc_lo(OFF_RING);
#pragma unroll 1
    for (int tl = 0; tl < 7; tl++) {
      handover(tl);
      const uint32_t dpt = dp + (tl & 1) * 128;
      wg_fence();
#pragma unroll
      for (int i = 0; i < 32; i++) wgmma_n16<1, 1>(O[i >> 2], da + (i >> 2) * 512 + (i & 3) * 128, dpt + (i & 3) * 2);
      wg_commit();
      wg_wait<0>();
#pragma unroll
      for (int mb = 0; mb < 8; mb++) acc_fence(O[mb]);
      if (lane == 0) mbar_arrive(BAR(BAR_EMPTY + tl));
      if (tl == 0) CLK(16);
      if (tl == 1) CLK(18);
      if (tl == 3) CLK(19);
      if (tl == 6) CLK(20);
      da = (tl == 2 || tl == 5) ? da - 8192 : da + 4096;
    }
    if (cta < NFF) { load_units<4, 64>(sbf, pcb); load_units<4, 64>(cbf, pcb + 2048); }
    mbar_wait(BAR(BAR_ALLCLR));
    uint32_t* x1o[8];
#pragma unroll
    for (int i = 0; i < 8; i++)
      x1o[i] = pin(inbox((16 * hh + 8 * ((i >> 1) & 1) + 2 * t + (i & 1)) * 4 + 2 * (i >> 2) + (wq >> 1), bs >> 4) + (bs & 15) * 64 + ((wq & 1) * 8 + g) * 4);
    handover(7);
    CLK(23);
    thand = clk32();
    auto pv = [&](int mb0, int n) {
      wg_fence();
#pragma unroll
      for (int i = 0; i < 16; i++)
        if (i < 4 * n) wgmma_n16<1, 1>(O[mb0 + (i >> 2)], desc_lo(65536) + (mb0 + (i >> 2)) * 512 + (i & 3) * 128, dp + 128 + (i & 3) * 2);
      wg_commit();
    };
    auto publish = [&](int J) {
#pragma unroll
      for (int k = 0; k < 4; k++) acc_fence(O[4 * J + k]);
#pragma unroll
      for (int i = 0; i < 4; i++) {
        const int k = 4 * (i >> 1) + (i & 1);
        stg_cvt8(x1o[4 * J + i], O[4 * J][k], O[4 * J][k + 2], O[4 * J + 1][k], O[4 * J + 1][k + 2],
                 O[4 * J + 2][k], O[4 * J + 2][k + 2], O[4 * J + 3][k], O[4 * J + 3][k + 2]);
      }
    };
    pv(0, 4); pv(4, 4);
    wg_wait<1>(); publish(0);
    wg_wait<0>(); publish(1);
    CLK(24);
  }

  {
    const uint32_t* px = pin(inbox(cta, w >> 1) + (w & 1) * 512 + lane * 2);
    uint32_t* const x2o = pin(inbox(cta, 4) + 512 + tid * 2);
    mbar_wait(BAR(BAR_TS));
    anchor = lds1(sb + OFF_TS);
    const uint32_t sdst = pin(sb + OFF_BS4 + w * 272 + lane * 8), ssrc = pin(sb + OFF_BS4 + (lane & 7) * 272 + (lane >> 3) * 16);
    wait_clk(thand, T.D_X1);
    wait_clk(anchor, T.A_X1);
    CLK(25);
    uint2 v[8];
    load_units<8, 64>(v, px);
    const bool early = __all_sync(~0u, mbar_test(BAR(BAR_WUV + wg)));
    if (early) load_a_t(aw, sb + OFF_WUV, w, lane);
    mbar_wait(BAR(BAR_WV));
    const float4 wa = ldsf4(sb + OFF_WV + w * 32), wb = ldsf4(sb + OFF_WV + w * 32 + 16);
    const float wv[8] = {wa.x, wa.y, wa.z, wa.w, wb.x, wb.y, wb.z, wb.w};
    CLK(27);
    int it = 0;
    while (true) {
      float a0 = 0.f, a1 = 0.f, a2 = 0.f, a3 = 0.f;
#pragma unroll
      for (int i = 0; i < 8; i++) { a0 += wv[i] * bf_lo(v[i].x); a1 += wv[i] * bf_hi(v[i].x); a2 += wv[i] * bf_lo(v[i].y); a3 += wv[i] * bf_hi(v[i].y); }
      const bool ok = __all_sync(~0u, min_flags(v) != 0);
      sts2(sdst, pack_bf16(a0, a1), pack_bf16(a2, a3));
      if (__builtin_expect(ok, 1)) break;
#pragma unroll
      for (int i = 0; i < 8; i++) reload_unit(v[i], px + i * 64);
      if (++it > SPIN_LIMIT) __trap();
    }
    CLK(29);
    cbar();
    uint32_t b[4][4];
#pragma unroll
    for (int kk = 0; kk < 4; kk++) ldsm4(b[kk], ssrc + kk * 64);
    if (__builtin_expect(!early, 0)) { mbar_wait(BAR(BAR_WUV + wg)); load_a_t(aw, sb + OFF_WUV, w, lane); }
    float d[4];
    mma128(d, aw, b);
    stg_u64(x2o, pack_bf16(d[0], d[1]), pack_bf16(d[2], d[3]));
    ITS(4, it);
    tstore = clk32();
    CLK(30);
  }
  {
    uint32_t* const o = pin(inbox(4 * (8 * jI + w) + t, 4) + hI * 16 + g * 2);
    const uint32_t* x2i[4];
#pragma unroll
    for (int i = 0; i < 4; i++) x2i[i] = pin(inbox(4 * hI + i, 4) + 512 + tid * 2);
    const uint32_t sdst = pin(sb + OFF_BS5 + (16 * w + g) * 16 + t * 4), ssrc = pin(sb + OFF_BS5 + lane * 16);
    wait_clk(tstore, T.D_X2);
    wait_clk(anchor, T.A_X1 + T.R_X2);
    uint2 v[4];
#pragma unroll
    for (int i = 0; i < 4; i++) v[i] = ldg_u64(x2i[i]);
    const bool early = __all_sync(~0u, mbar_test(BAR(BAR_WO + wg)));
    if (early) load_a_t(aw, sb + OFF_WO, w, lane);
    CLK(31);
    int it = 0;
    while (true) {
      const bool ok = __all_sync(~0u, min_flags(v) != 0);
      sum4_to_smem(v, sdst);
      if (__builtin_expect(ok, 1)) break;
#pragma unroll
      for (int i = 0; i < 4; i++) reload_unit(v[i], x2i[i]);
      if (++it > SPIN_LIMIT) __trap();
    }
    CLK(32);
    cbar();
    uint32_t b[4][4];
#pragma unroll
    for (int kk = 0; kk < 4; kk++) ldsm4t(b[kk], ssrc + kk * 512);
    if (__builtin_expect(!early, 0)) { mbar_wait(BAR(BAR_WO + wg)); load_a_t(aw, sb + OFF_WO, w, lane); }
    float d[4];
    mma128(d, aw, b);
    stg_u64(o, movm(pack_bf16(d[0], d[1])), movm(pack_bf16(d[2], d[3])));
    ITS(5, it);
    tstore = clk32();
    CLK(33);
    if (lane == 0) mbar_arrive(BAR(BAR_P5D));
  }
  if (cta < NFF) {
    const int mi = lane >> 3, r = lane & 7;
    uint32_t a1[2][4][4], a2[2][2][4];
    check_units<4, 64>(sbf, pcb, T.RB);
    check_units<4, 64>(cbf, pcb + 2048, T.RB);
    __syncwarp();
#pragma unroll
    for (int s = 0; s < 4; s++) { cbf[s].x = hadd2(cbf[s].x, ONE2); cbf[s].y = hadd2(cbf[s].y, ONE2); }
    mbar_wait(BAR(BAR_W1));
#pragma unroll
    for (int mt = 0; mt < 2; mt++) {
#pragma unroll
      for (int ks = 0; ks < 4; ks++) ldsm4t(a1[mt][ks], sb + OFF_W1 + (64 * w + 16 * ks + 8 * (mi >> 1) + r) * 64 + (((2 * mt + (mi & 1)) ^ (r >> 1)) << 4));
      float u[4] = {0.f, 0.f, 0.f, 0.f}, vv[4] = {0.f, 0.f, 0.f, 0.f};
#pragma unroll
      for (int s = 0; s < 4; s++) { mma16816(u, a1[mt][s], cbf[s].x, cbf[s].y); mma16816(vv, a1[mt][s], sbf[s].x, sbf[s].y); }
      sts4f(sb + OFF_REDU + w * 1024 + mt * 512 + lane * 16, u[0], u[1], u[2], u[3]);
      sts4f(sb + OFF_REDV + w * 1024 + mt * 512 + lane * 16, vv[0], vv[1], vv[2], vv[3]);
    }
    const uint32_t* xb = pin(inbox(cta & ~7, 6 + wg) + (16 * wq + t) * 16 + g * 2);
    uint32_t* const ox[2] = {pin(inbox(64 * hh + 8 * w + t, 5) + bs * 16 + g * 2), pin(inbox(64 * hh + 8 * w + 4 + t, 5) + bs * 16 + g * 2)};
    cbar();
    const int lp = (tid >> 2) & 31, kq = tid & 3;
    const int fo = 16 * wg + (lp >> 2) + 8 * (kq >> 1), bo = 2 * (lp & 3) + (kq & 1);
    float U = 0.f, V = 0.f;
#pragma unroll
    for (int i = 0; i < 8; i++) { U += ldsf(sb + OFF_REDU + i * 1024 + tid * 4); V += ldsf(sb + OFF_REDV + i * 1024 + tid * 4); }
    U = pin(U); V = pin(V);
    const uint32_t s_g = pin(sb + OFF_REDG + w * 1024 + lane * 16), s_s = pin(sb + OFF_REDS + g * 80 + w * 8);
    const uint32_t l_g = pin(sb + OFF_REDG + tid * 4), l_s = pin(sb + OFF_REDS + bo * 80), s_h = pin(sb + OFF_H1 + fo * 16 + bo * 2);
    CLK(34);
    wait_clk(tstore, T.D_X3B);
    wait_clk(anchor, T.A_X1 + T.R_X3A + T.R_X3B);
    uint2 x[4];
    load_units<4, 64>(x, xb);
    mbar_wait(BAR(BAR_W2));
#pragma unroll
    for (int i = 0; i < 4; i++)
      ldsm4t(a2[i >> 1][i & 1], sb + OFF_W2 + (w >> 1) * 4096 + (16 * (i & 1) + 8 * (mi >> 1) + r) * 128 + (((4 * (w & 1) + 2 * (i >> 1) + (mi & 1)) ^ r) << 4));
    CLK(35);
    int it = 0;
    float G[2][2][4], S[2][4];
    while (true) {
#pragma unroll
      for (int i = 0; i < 8; i++) { G[0][i >> 2][i & 3] = G[1][i >> 2][i & 3] = S[i >> 2][i & 3] = 0.f; }
#pragma unroll
      for (int s = 0; s < 4; s++) {
        const uint32_t sx[4] = {x[s].x, ONE2, x[s].y, ONE2};
        mma16816(S[s & 1], sx, x[s].x, x[s].y);
        const uint32_t y0 = hmul2(x[s].x, cbf[s].x), y1 = hmul2(x[s].y, cbf[s].y);
        mma16816(G[0][s & 1], a1[0][s], y0, y1);
        mma16816(G[1][s & 1], a1[1][s], y0, y1);
      }
      if (__builtin_expect(__all_sync(~0u, min_flags(x) != 0), 1)) break;
#pragma unroll
      for (int i = 0; i < 4; i++) reload_unit(x[i], xb + i * 64);
      if (++it > SPIN_LIMIT) __trap();
    }
    if (t == (g >> 1)) sts2f(s_s, (g & 1) ? S[0][3] + S[1][3] : S[0][2] + S[1][2], (g & 1) ? S[0][1] + S[1][1] : S[0][0] + S[1][0]);
#pragma unroll
    for (int mt = 0; mt < 2; mt++)
      sts4f(s_g + mt * 512, G[mt][0][0] + G[mt][1][0], G[mt][0][1] + G[mt][1][1], G[mt][0][2] + G[mt][1][2], G[mt][0][3] + G[mt][1][3]);
    CLK(37);
    cbar();
    {
      float gv[8];
      float4 sv[4];
#pragma unroll
      for (int i = 0; i < 4; i++) sv[i] = ldsf4(l_s + i * 16);
#pragma unroll
      for (int i = 0; i < 8; i++) gv[i] = ldsf(l_g + i * 1024);
      const float s1 = ((sv[0].x + sv[0].z) + (sv[1].x + sv[1].z)) + ((sv[2].x + sv[2].z) + (sv[3].x + sv[3].z));
      const float s2 = ((sv[0].y + sv[0].w) + (sv[1].y + sv[1].w)) + ((sv[2].y + sv[2].w) + (sv[3].y + sv[3].w));
      const float gsum = ((gv[0] + gv[1]) + (gv[2] + gv[3])) + ((gv[4] + gv[5]) + (gv[6] + gv[7]));
      const float mu = s1 * (1.f / 512.f);
      float rs;
      asm("rsqrt.approx.ftz.f32 %0, %1;" : "=f"(rs) : "f"(fmaxf(s2 * (1.f / 512.f) - mu * mu, 0.f) + 1e-5f));
      const float hv = fmaxf(rs * (gsum - mu * U) + V, 0.f);
      asm volatile("st.shared.u16 [%0], %1;" ::"r"(s_h), "h"(__bfloat16_as_ushort(__float2bfloat16(hv))) : "memory");
    }
    ITS(6, it);
    CLK(38);
    cbar();
    uint32_t b[4];
    ldsm4t(b, sb + OFF_H1 + lane * 16);
    float o[2][2][4] = {};
#pragma unroll
    for (int i = 0; i < 4; i++) mma16816(o[i >> 1][i & 1], a2[i >> 1][i & 1], b[2 * (i & 1)], b[2 * (i & 1) + 1]);
#pragma unroll
    for (int mb = 0; mb < 2; mb++)
      stg_u64(ox[mb], movm(pack_bf16(o[mb][0][0] + o[mb][1][0], o[mb][0][1] + o[mb][1][1])), movm(pack_bf16(o[mb][0][2] + o[mb][1][2], o[mb][0][3] + o[mb][1][3])));
    CLK(39);
    if (lane == 0) mbar_arrive(BAR(BAR_P7D));
  }
  CLK_DUMP();
}

typedef CUresult (*EncodeTiledFn)(CUtensorMap*, CUtensorMapDataType, cuuint32_t, void*, const cuuint64_t*, const cuuint64_t*,
                                  const cuuint32_t*, const cuuint32_t*, CUtensorMapInterleave, CUtensorMapSwizzle,
                                  CUtensorMapL2promotion, CUtensorMapFloatOOBfill);

struct Dim { uint64_t size, stride; uint32_t box; };
template <int R> void encode_map(EncodeTiledFn enc, CUtensorMap* m, const void* base, const Dim (&d)[R], CUtensorMapSwizzle sw, CUtensorMapL2promotion promo) {
  cuuint64_t dims[R], strides[R];
  cuuint32_t box[R], es[R];
  for (int i = 0; i < R; i++) { dims[i] = d[i].size; strides[i] = d[i].stride; box[i] = d[i].box; es[i] = 1; }
  enc(m, CU_TENSOR_MAP_DATA_TYPE_BFLOAT16, R, const_cast<void*>(base), dims, strides + 1, box, es, CU_TENSOR_MAP_INTERLEAVE_NONE, sw, promo,
      CU_TENSOR_MAP_FLOAT_OOB_FILL_NONE);
}

}

extern "C" void kernel_launch(void* const* d_in, const int* in_sizes, int n_in, void* d_out, int out_size) {
  (void)in_sizes; (void)n_in; (void)out_size;
  static EncodeTiledFn enc = nullptr;
  static Scratch* scratch = nullptr;
  static uint32_t* inbox = nullptr;
  if (!enc) {
    void* sp = nullptr;
    cudaGetSymbolAddress(&sp, g_s);
    scratch = (Scratch*)sp;
    cudaGetSymbolAddress(&sp, g_in);
    inbox = (uint32_t*)(((uintptr_t)sp + 65535) & ~(uintptr_t)65535);
    void* fn = nullptr;
    cudaDriverEntryPointQueryResult q;
    cudaGetDriverEntryPoint("cuTensorMapEncodeTiled", &fn, cudaEnableDefault, &q);
    enc = (EncodeTiledFn)fn;
    cudaFuncSetAttribute(fused_decode_kernel, cudaFuncAttributeMaxDynamicSharedMemorySize, SMEM_BYTES);
  }
  const CUtensorMapSwizzle S128 = CU_TENSOR_MAP_SWIZZLE_128B, S0 = CU_TENSOR_MAP_SWIZZLE_NONE;
  const CUtensorMapL2promotion L0 = CU_TENSOR_MAP_L2_PROMOTION_NONE, L128 = CU_TENSOR_MAP_L2_PROMOTION_L2_128B;
  Params P;
  encode_map<2>(enc, &P.wq, d_in[2], {{4096, 2, 64}, {512, 8192, 64}}, S128, L0);
  encode_map<5>(enc, &P.wuk, d_in[3], {{4096, 2, 64}, {2, 8192, 2}, {4, 4 * 8192, 4}, {2, 2 * 8192, 2}, {32, 16 * 8192, 4}}, S128, L0);
  encode_map<2>(enc, &P.wm2, d_in[10], {{3072, 2, 16}, {512, 6144, 256}}, S0, L128);
  encode_map<3>(enc, &P.ckv2, d_in[1], {{64, 2, 64}, {8 * 4096, 1024, 64}, {8, 128, 2}}, S128, L0);
  encode_map<3>(enc, &P.ckv1, d_in[1], {{64, 2, 64}, {8 * 4096, 1024, 64}, {8, 128, 1}}, S128, L0);
  encode_map<5>(enc, &P.wuv, d_in[4], {{4096, 2, 64}, {2, 8 * 8192, 2}, {8, 64 * 8192, 4}, {8, 8192, 8}, {4, 16 * 8192, 1}}, S128, L0);
  encode_map<2>(enc, &P.wo, d_in[5], {{512, 2, 64}, {4096, 1024, 64}}, S128, L0);
  encode_map<2>(enc, &P.w1, d_in[7], {{1792, 2, 32}, {512, 3584, 256}}, CU_TENSOR_MAP_SWIZZLE_64B, L128);
  encode_map<3>(enc, &P.w2, d_in[8], {{64, 2, 64}, {1792, 1024, 32}, {8, 128, 2}}, S128, L0);
  cudaLaunchConfig_t cfg = {};
  cfg.gridDim = dim3(NCTA);
  cfg.blockDim = dim3(NTHREADS);
  cfg.dynamicSmemBytes = SMEM_BYTES;
  cfg.stream = cudaStreamPerThread;
  cudaLaunchAttribute at[1];
  at[0].id = cudaLaunchAttributeClusterDimension;
  at[0].val.clusterDim.x = 2; at[0].val.clusterDim.y = 1; at[0].val.clusterDim.z = 1;
  cfg.attrs = at;
  cfg.numAttrs = 0;
  cudaLaunchKernelEx(&cfg, fused_decode_kernel, (__nv_bfloat16*)d_out, scratch, (const uint8_t*)d_in[10], (const uint8_t*)d_in[0],
                     (const uint8_t*)d_in[9], inbox,
                     P);
}
```

```cpp
#include <cuda_runtime.h>
#include <cuda.h>
#include <cuda_bf16.h>
#include <stdint.h>
#define V4 1

namespace {

constexpr int NCTA = 128;
constexpr int NTHREADS = 320;
constexpr int NFG = 56;
constexpr int NFF = 2 * NFG;
constexpr int NSYNC = 4;

constexpr uint32_t OFF_RING = 0;
constexpr uint32_t OFF_WUK = 131072;
constexpr uint32_t OFF_WQ = 131072 + 32768;
constexpr uint32_t OFF_WM2 = 65536 + 49152;
constexpr uint32_t OFF_WUV = 131072;
constexpr uint32_t OFF_WO = 131072 + 32768;
constexpr uint32_t OFF_W1 = 0;
constexpr uint32_t OFF_W2 = 32768;
constexpr uint32_t OFF_Q = 196608;
constexpr uint32_t OFF_PT = 212992;
constexpr uint32_t OFF_SCR = 217088;
constexpr uint32_t OFF_XS = 65536;
constexpr uint32_t OFF_CS = 65536 + 8192;
constexpr uint32_t OFF_P0S = 65536 + 16384;
constexpr uint32_t OFF_BS1 = OFF_SCR + 2048;
constexpr uint32_t OFF_BS2 = OFF_SCR + 4096;
constexpr uint32_t OFF_P0B = OFF_SCR + 6144;
constexpr uint32_t OFF_XN = OFF_SCR + 8192;
constexpr uint32_t OFF_RED = OFF_SCR + 10496;
constexpr uint32_t OFF_ALPHA = OFF_SCR + 11072;
constexpr uint32_t OFF_WV = OFF_SCR + 6144;
constexpr uint32_t OFF_SEL = OFF_SCR + 10752;
constexpr uint32_t OFF_TS = OFF_SCR + 11136;
constexpr uint32_t OFF_BARS = OFF_SCR + 11264;
constexpr uint32_t SMEM_BYTES = OFF_BARS + 512;
constexpr uint32_t OFF_BS4 = OFF_Q;
constexpr uint32_t OFF_H1 = OFF_Q + 2304;
constexpr uint32_t OFF_REDS = OFF_Q + 2816;
constexpr uint32_t OFF_BS5 = OFF_Q + 4096;
constexpr uint32_t OFF_REDG = OFF_Q + 8192;
constexpr uint32_t OFF_REDU = 65536;
constexpr uint32_t OFF_REDV = 65536 + 8192;

constexpr int BAR_FULL = 0;
constexpr int BAR_LAST = 28;
constexpr int BAR_WUK = 33, BAR_WM2 = 35, BAR_WUV = 36, BAR_WO = 38, BAR_W1 = 40, BAR_W2 = 41;
constexpr int BAR_ALLCLR = 42, BAR_TS = 43, BAR_WV = 44;
constexpr int BAR_EMPTY = 45;
constexpr int BAR_P0BD = 52;
constexpr int BAR_P1D = 53, BAR_P2D = 54;
constexpr int BAR_P5D = 55, BAR_P7D = 56;
constexpr int NBARS = 57;
constexpr int BAR_XC = 57, BAR_WQ = 58;
constexpr int BAR_C = 60, BAR_END = 61;
constexpr uint32_t SB = 1024;

#define TUNE_LIST(X) \
  X(PC_T0, 340) X(PC_XC, 0) X(PC_C, 0) X(PC_P1, 320) X(PC_P2, 322) X(PC_STAG, 390) X(PC_DS, 0) X(PC_SL, 500) X(PC_W, 4) X(PC_NW, 8) \
  X(PW_A, -1) X(PW_0, 240) X(PW_ST, 0) X(PW_UV, 250) X(PW_G, 660) X(PW_O, 340) X(PW_G2, 450) X(PW_G3, 390) X(PW_F, 330) \
  X(LOC, 0) X(PR_T0, 1000) X(PR_N, 4) X(CLR_T0, 3200) X(CLR_CLK, 190) \
  X(D_MOD, 1500) X(D_QP, 1300) X(D_QX, 1300) X(TS_P, 1) X(TS_O, 1000) X(D_TS, 900) X(A_M, 1800) X(D_X1, 1300) X(A_X1, 2400) \
  X(D_X2, 250) X(R_X2, 1550) X(D_X3A, 60) X(R_X3A, 3340) X(D_X3B, 800) X(R_X3B, 950) X(D_FIN, 295) X(R_FIN, 1520) X(RB, 0)
struct Tune {
#define X(n, v) static constexpr int n = v;
  TUNE_LIST(X)
#undef X
};

#define PFENCE 0
#define WSWAP 0
#define THRESH "0f42700000"
#define PVV 0
struct Scratch {
  uint32_t MOD1[2][4 * 64 * 64];
  uint32_t MOD2[2][128 * 64];
  uint32_t QP[2][128 * 256 * 2];
  uint32_t QX[2][8 * 32 * 256];
  uint32_t epoch;
  uint32_t pad[31];
  uint32_t sync[NSYNC][32];
};
__device__ Scratch g_s;
__device__ uint32_t g_in[(128 + 16) * 16384];
__device__ __forceinline__ uint32_t blk(int c, int k, uint32_t sel) { return c * 16384 + k * 2048 + ((sel ^ k) & 1) * 1024; }
__device__ __forceinline__ uint32_t flip(int c) { return c ^ (c >> 1) ^ (c >> 3); }

#define CLK_DECL
#define CLK(i) do {} while (0)
#define CLK_DUMP() do {} while (0)
#define ITS(i, v) do {} while (0)

struct Params {
  CUtensorMap wq, wuk, wm2, ckv2, ckv1, wuv, wo, w1, w2;
};

__device__ __forceinline__ void mbar_init(uint32_t bar, int cnt) { asm volatile("mbarrier.init.shared::cta.b64 [%0], %1;" ::"r"(bar), "r"(cnt)); }
__device__ __forceinline__ void mbar_expect(uint32_t bar, uint32_t bytes) { asm volatile("mbarrier.arrive.expect_tx.shared::cta.b64 _, [%0], %1;" ::"r"(bar), "r"(bytes) : "memory"); }
__device__ __forceinline__ void mbar_arrive(uint32_t bar) { asm volatile("mbarrier.arrive.shared::cta.b64 _, [%0];" ::"r"(bar) : "memory"); }
__device__ __forceinline__ uint32_t clk32() { unsigned long long c; asm volatile("mov.u64 %0, %%clock64;" : "=l"(c) :: "memory"); return (uint32_t)c; }
__device__ __forceinline__ uint32_t gtime32() { uint32_t c; asm volatile("mov.u32 %0, %%globaltimer_lo;" : "=r"(c) :: "memory"); return c; }
__device__ __forceinline__ void wait_clk(uint32_t t0, int clocks) { while ((int)(clk32() - t0) < clocks) {} }
__device__ __forceinline__ void backoff(int clocks) { if (clocks > 0) wait_clk(clk32(), clocks); }
__device__ __forceinline__ void until_ns(uint32_t ns) { while ((int)(gtime32() - ns) < 0) {} }
__device__ __forceinline__ void slot(uint32_t& tn, int slack) {
  uint32_t now;
  do { now = gtime32(); } while ((int)(now - tn) < 0);
  if ((int)(now - tn) > slack) tn = now - slack;
}
template <typename T> __device__ __forceinline__ T* pin(T* p) { asm volatile("" : "+l"(p)); return p; }
__device__ __forceinline__ uint32_t pin(uint32_t v) { asm volatile("" : "+r"(v)); return v; }
__device__ __forceinline__ float pin(float v) { asm volatile("" : "+f"(v)); return v; }
constexpr int SPIN_LIMIT = 1 << 22;
__device__ __forceinline__ void mbar_wait(uint32_t bar) {
  asm volatile("{\n.reg .pred p;\n.reg .u32 c;\nmov.u32 c, 0;\n"
               "MW_LOOP:\nmbarrier.try_wait.parity.shared::cta.b64 p, [%0], 0;\n@p bra MW_DONE;\n"
               "add.u32 c, c, 1;\nsetp.lt.u32 p, c, 4194304;\n@p bra MW_LOOP;\ntrap;\nMW_DONE:\n}"
               ::"r"(bar) : "memory");
}
__device__ __forceinline__ bool mbar_test(uint32_t bar) {
  uint32_t ok;
  asm volatile("{\n.reg .pred p;\nmbarrier.test_wait.parity.shared::cta.b64 p, [%1], 0;\nselp.u32 %0,1,0,p;\n}" : "=r"(ok) : "r"(bar) : "memory");
  return ok;
}
__device__ __forceinline__ void tma2d(uint32_t dst, const CUtensorMap* m, int c0, int c1, uint32_t bar, uint64_t pol) {
  asm volatile("cp.async.bulk.tensor.2d.shared::cluster.global.mbarrier::complete_tx::bytes.L2::cache_hint [%0], [%1, {%3,%4}], [%2], %5;"
               ::"r"(dst), "l"(m), "r"(bar), "r"(c0), "r"(c1), "l"(pol) : "memory");
}
__device__ __forceinline__ void tma2d_nohint(uint32_t dst, const CUtensorMap* m, int c0, int c1, uint32_t bar) {
  asm volatile("cp.async.bulk.tensor.2d.shared::cluster.global.mbarrier::complete_tx::bytes [%0], [%1, {%3,%4}], [%2];"
               ::"r"(dst), "l"(m), "r"(bar), "r"(c0), "r"(c1) : "memory");
}
__device__ __forceinline__ void tma3d(uint32_t dst, const CUtensorMap* m, int c0, int c1, int c2, uint32_t bar, uint64_t pol) {
  asm volatile("cp.async.bulk.tensor.3d.shared::cluster.global.mbarrier::complete_tx::bytes.L2::cache_hint [%0], [%1, {%3,%4,%5}], [%2], %6;"
               ::"r"(dst), "l"(m), "r"(bar), "r"(c0), "r"(c1), "r"(c2), "l"(pol) : "memory");
}
__device__ __forceinline__ void tma5d(uint32_t dst, const CUtensorMap* m, int c0, int c1, int c2, int c3, int c4, uint32_t bar, uint64_t pol) {
  asm volatile("cp.async.bulk.tensor.5d.shared::cluster.global.mbarrier::complete_tx::bytes.L2::cache_hint [%0], [%1, {%3,%4,%5,%6,%7}], [%2], %8;"
               ::"r"(dst), "l"(m), "r"(bar), "r"(c0), "r"(c1), "r"(c2), "r"(c3), "r"(c4), "l"(pol) : "memory");
}
__device__ __forceinline__ void bulk_ld(uint32_t dst, const void* src, uint32_t bytes, uint32_t bar) {
  asm volatile("cp.async.bulk.shared::cluster.global.mbarrier::complete_tx::bytes [%0], [%1], %2, [%3];" ::"r"(dst), "l"(src), "r"(bytes), "r"(bar) : "memory");
}
__device__ __forceinline__ void bar_sync(int id, int n) { asm volatile("barrier.cta.sync.aligned %0, %1;" ::"r"(id), "r"(n) : "memory"); }
__device__ __forceinline__ void cbar() { asm volatile("barrier.cta.sync.aligned 1, 256;" ::: "memory"); }
__device__ __forceinline__ bool bar_over(float ex) {
  uint32_t over;
  asm volatile("{\n.reg .pred p, q;\nsetp.gtu.f32 p, %1, " THRESH ";\nbarrier.cta.red.or.aligned.pred q, 4, 256, p;\nselp.u32 %0, 1, 0, q;\n}"
               : "=r"(over) : "f"(ex) : "memory");
  return over;
}

__device__ __forceinline__ uint32_t ldg_nc1(const void* p) { uint32_t v; asm volatile("ld.global.nc.L1::no_allocate.u32 %0, [%1];" : "=r"(v) : "l"(p)); return v; }
__device__ __forceinline__ uint2 ldg_nc2(const void* p) { uint2 v; asm volatile("ld.global.nc.v2.u32 {%0,%1}, [%2];" : "=r"(v.x), "=r"(v.y) : "l"(p)); return v; }
__device__ __forceinline__ uint4 ldg_nc4(const void* p) { uint4 v; asm volatile("ld.global.nc.L1::no_allocate.v4.u32 {%0,%1,%2,%3}, [%4];" : "=r"(v.x), "=r"(v.y), "=r"(v.z), "=r"(v.w) : "l"(p)); return v; }
__device__ __forceinline__ uint32_t ldg_rlx1(const void* p) { uint32_t v; asm volatile("ld.relaxed.gpu.global.u32 %0, [%1];" : "=r"(v) : "l"(p) : "memory"); return v; }
__device__ __forceinline__ void stg4(void* p, uint4 v) { asm volatile("st.relaxed.gpu.global.v4.u32 [%0], {%1,%2,%3,%4};" ::"l"(p), "r"(v.x), "r"(v.y), "r"(v.z), "r"(v.w) : "memory"); }
__device__ __forceinline__ void stg1(void* p, uint32_t a) { asm volatile("st.relaxed.gpu.global.u32 [%0], %1;" ::"l"(p), "r"(a) : "memory"); }
__device__ __forceinline__ uint32_t nz(uint32_t w) { return max(w, 1u); }
__device__ __forceinline__ uint2 ldg_u64(const void* p) {
  uint2 v; asm volatile("{\n.reg .b64 a;\nld.relaxed.gpu.global.b64 a, [%2];\nmov.b64 {%0,%1}, a;\n}" : "=r"(v.x), "=r"(v.y) : "l"(p) : "memory"); return v;
}
__device__ __forceinline__ uint4 ldg_2u64(const void* p) {
  uint4 v; asm volatile("{\n.reg .b64 a, b;\nld.relaxed.gpu.global.v2.b64 {a, b}, [%4];\nmov.b64 {%0,%1}, a;\nmov.b64 {%2,%3}, b;\n}" : "=r"(v.x), "=r"(v.y), "=r"(v.z), "=r"(v.w) : "l"(p) : "memory"); return v;
}
__device__ __forceinline__ void stg_u64(void* p, uint32_t x, uint32_t y) {
  asm volatile("{\n.reg .b32 y;\nmax.u32 y, %2, 1;\nst.relaxed.gpu.global.v2.b32 [%0], {%1, y};\n}" ::"l"(p), "r"(x), "r"(y) : "memory");
}
__device__ __forceinline__ void red_u64(void* p, uint32_t x, uint32_t y) {
  asm volatile("{\n.reg .b32 y;\n.reg .b64 a;\nmax.u32 y, %2, 1;\nmov.b64 a, {%1, y};\nred.relaxed.gpu.global.or.b64 [%0], a;\n}" ::"l"(p), "r"(x), "r"(y) : "memory");
}
__device__ __forceinline__ void red_u64_unless(uint32_t bad, void* p, uint32_t x, uint32_t y) {
  asm volatile("{\n.reg .b32 y;\n.reg .b64 a;\n.reg .pred q;\nsetp.eq.u32 q, %3, 0;\nmax.u32 y, %2, 1;\nmov.b64 a, {%1, y};\n@q red.relaxed.gpu.global.or.b64 [%0], a;\n}" ::"l"(p), "r"(x), "r"(y), "r"(bad) : "memory");
}
#define ST3A stg_u64
#define ST4 stg_u64
#define ST3B stg_u64_unless
#define MLST red_u64
__device__ __forceinline__ void stg_u64_unless(uint32_t bad, void* p, uint32_t x, uint32_t y) {
  asm volatile("{\n.reg .b32 y;\n.reg .pred q;\nsetp.eq.u32 q, %3, 0;\nmax.u32 y, %2, 1;\n@q st.relaxed.gpu.global.v2.b32 [%0], {%1, y};\n}" ::"l"(p), "r"(x), "r"(y), "r"(bad) : "memory");
}
__device__ __forceinline__ void stg_2u64(void* p, uint4 v) {
  asm volatile("{\n.reg .b32 y, w;\nmax.u32 y, %2, 1;\nmax.u32 w, %4, 1;\nst.relaxed.gpu.global.v4.b32 [%0], {%1, y, %3, w};\n}" ::"l"(p), "r"(v.x), "r"(v.y), "r"(v.z), "r"(v.w) : "memory");
}

__device__ __forceinline__ void stg_cvt8(void* p, float a0, float a1, float b0, float b1, float c0, float c1, float d0, float d1) {
  asm volatile("{\n.reg .b32 x, y, z, w;\ncvt.rn.bf16x2.f32 x, %2, %1;\ncvt.rn.bf16x2.f32 y, %4, %3;\ncvt.rn.bf16x2.f32 z, %6, %5;\ncvt.rn.bf16x2.f32 w, %8, %7;\n"
               "max.u32 y, y, 1;\nmax.u32 w, w, 1;\nst.relaxed.gpu.global.v4.b32 [%0], {x, y, z, w};\n}"
               ::"l"(p), "f"(a0), "f"(a1), "f"(b0), "f"(b1), "f"(c0), "f"(c1), "f"(d0), "f"(d1) : "memory");
}
__device__ __forceinline__ uint32_t pack_bf16(float lo, float hi) { uint32_t r; asm("cvt.rn.bf16x2.f32 %0, %1, %2;" : "=r"(r) : "f"(hi), "f"(lo)); return r; }
__device__ __forceinline__ float bf_lo(uint32_t w) { return __uint_as_float(w << 16); }
__device__ __forceinline__ float bf_hi(uint32_t w) { return __uint_as_float(w & 0xffff0000u); }
__device__ __forceinline__ float ex2(float x) { float r; asm("ex2.approx.ftz.f32 %0, %1;" : "=f"(r) : "f"(x)); return r; }
__device__ __forceinline__ uint32_t hmul2(uint32_t a, uint32_t b) { uint32_t r; asm("mul.rn.bf16x2 %0, %1, %2;" : "=r"(r) : "r"(a), "r"(b)); return r; }
__device__ __forceinline__ uint32_t hadd2(uint32_t a, uint32_t b) { uint32_t r; asm("add.rn.bf16x2 %0, %1, %2;" : "=r"(r) : "r"(a), "r"(b)); return r; }
__device__ __forceinline__ uint32_t hfma2(uint32_t a, uint32_t b, uint32_t c) { uint32_t r; asm("fma.rn.bf16x2 %0, %1, %2, %3;" : "=r"(r) : "r"(a), "r"(b), "r"(c)); return r; }
__device__ __forceinline__ uint32_t silu2(uint32_t v) { const float a = bf_lo(v), b = bf_hi(v); return pack_bf16(__fdividef(a, 1.f + __expf(-a)), __fdividef(b, 1.f + __expf(-b))); }
constexpr uint32_t ONE2 = 0x3f803f80u;

__device__ __forceinline__ void ldsm4(uint32_t (&r)[4], uint32_t a) { asm volatile("ldmatrix.sync.aligned.m8n8.x4.shared.b16 {%0,%1,%2,%3}, [%4];" : "=r"(r[0]), "=r"(r[1]), "=r"(r[2]), "=r"(r[3]) : "r"(a) : "memory"); }
__device__ __forceinline__ void ldsm4t(uint32_t (&r)[4], uint32_t a) { asm volatile("ldmatrix.sync.aligned.m8n8.x4.trans.shared.b16 {%0,%1,%2,%3}, [%4];" : "=r"(r[0]), "=r"(r[1]), "=r"(r[2]), "=r"(r[3]) : "r"(a) : "memory"); }
__device__ __forceinline__ void ldsm2t(uint32_t& r0, uint32_t& r1, uint32_t a) { asm volatile("ldmatrix.sync.aligned.m8n8.x2.trans.shared.b16 {%0,%1}, [%2];" : "=r"(r0), "=r"(r1) : "r"(a) : "memory"); }
__device__ __forceinline__ void stsm4t(uint32_t a, uint32_t r0, uint32_t r1, uint32_t r2, uint32_t r3) { asm volatile("stmatrix.sync.aligned.m8n8.x4.trans.shared.b16 [%0], {%1,%2,%3,%4};" ::"r"(a), "r"(r0), "r"(r1), "r"(r2), "r"(r3) : "memory"); }
__device__ __forceinline__ uint32_t movm(uint32_t a) { uint32_t d; asm volatile("movmatrix.sync.aligned.m8n8.trans.b16 %0, %1;" : "=r"(d) : "r"(a)); return d; }
__device__ __forceinline__ void mma16816(float (&d)[4], const uint32_t (&a)[4], uint32_t b0, uint32_t b1) {
  asm volatile("mma.sync.aligned.m16n8k16.row.col.f32.bf16.bf16.f32 {%0,%1,%2,%3}, {%4,%5,%6,%7}, {%8,%9}, {%0,%1,%2,%3};"
               : "+f"(d[0]), "+f"(d[1]), "+f"(d[2]), "+f"(d[3]) : "r"(a[0]), "r"(a[1]), "r"(a[2]), "r"(a[3]), "r"(b0), "r"(b1));
}
__device__ __forceinline__ void sts1(uint32_t a, uint32_t v) { asm volatile("st.shared.u32 [%0], %1;" ::"r"(a), "r"(v) : "memory"); }
__device__ __forceinline__ void sts2(uint32_t a, uint32_t x, uint32_t y) { asm volatile("st.shared.v2.u32 [%0], {%1,%2};" ::"r"(a), "r"(x), "r"(y) : "memory"); }
__device__ __forceinline__ void sts4(uint32_t a, uint4 v) { asm volatile("st.shared.v4.u32 [%0], {%1,%2,%3,%4};" ::"r"(a), "r"(v.x), "r"(v.y), "r"(v.z), "r"(v.w) : "memory"); }
__device__ __forceinline__ void sts2f(uint32_t a, float x, float y) { asm volatile("st.shared.v2.f32 [%0], {%1,%2};" ::"r"(a), "f"(x), "f"(y) : "memory"); }
__device__ __forceinline__ void sts4f(uint32_t a, float x, float y, float z, float w) { asm volatile("st.shared.v4.f32 [%0], {%1,%2,%3,%4};" ::"r"(a), "f"(x), "f"(y), "f"(z), "f"(w) : "memory"); }
__device__ __forceinline__ void stsf(uint32_t a, float v) { asm volatile("st.shared.f32 [%0], %1;" ::"r"(a), "f"(v) : "memory"); }
__device__ __forceinline__ uint32_t lds1(uint32_t a) { uint32_t v; asm volatile("ld.shared.u32 %0, [%1];" : "=r"(v) : "r"(a) : "memory"); return v; }
__device__ __forceinline__ float ldsf(uint32_t a) { float v; asm volatile("ld.shared.f32 %0, [%1];" : "=f"(v) : "r"(a) : "memory"); return v; }
__device__ __forceinline__ float2 ldsf2(uint32_t a) { float2 v; asm volatile("ld.shared.v2.f32 {%0,%1}, [%2];" : "=f"(v.x), "=f"(v.y) : "r"(a) : "memory"); return v; }
__device__ __forceinline__ float4 ldsf4(uint32_t a) { float4 v; asm volatile("ld.shared.v4.f32 {%0,%1,%2,%3}, [%4];" : "=f"(v.x), "=f"(v.y), "=f"(v.z), "=f"(v.w) : "r"(a) : "memory"); return v; }
__device__ __forceinline__ void lds4(uint32_t (&r)[4], uint32_t a) { asm volatile("ld.shared.v4.u32 {%0,%1,%2,%3}, [%4];" : "=r"(r[0]), "=r"(r[1]), "=r"(r[2]), "=r"(r[3]) : "r"(a) : "memory"); }

__device__ __forceinline__ void wg_fence() { asm volatile("wgmma.fence.sync.aligned;" ::: "memory"); }
__device__ __forceinline__ void wg_commit() { asm volatile("wgmma.commit_group.sync.aligned;" ::: "memory"); }
template <int N> __device__ __forceinline__ void wg_wait() { asm volatile("wgmma.wait_group.sync.aligned %0;" ::"n"(N) : "memory"); }
__host__ __device__ constexpr uint32_t desc_lo(uint32_t off) { return ((SB + off) >> 4) | 0x10000u; }
template <int TA, int ACC> __device__ __forceinline__ void wgmma_n16(float (&d)[8], uint32_t da, uint32_t db) {
  asm volatile("{\n.reg .b64 da, db;\nmov.b64 da, {%8, 0x40000040};\nmov.b64 db, {%9, 0x40000040};\n"
               "wgmma.mma_async.sync.aligned.m64n16k16.f32.bf16.bf16 {%0,%1,%2,%3,%4,%5,%6,%7}, da, db, %11, 1, 1, %10, 0;\n}"
               : "+f"(d[0]), "+f"(d[1]), "+f"(d[2]), "+f"(d[3]), "+f"(d[4]), "+f"(d[5]), "+f"(d[6]), "+f"(d[7])
               : "r"(da), "r"(db), "n"(TA), "n"(ACC));
}
__device__ __forceinline__ void wgmma_n16_ones(float (&d)[8], uint32_t one, uint32_t db) {
  asm volatile("{\n.reg .b64 db;\nmov.b64 db, {%9, 0x40000040};\n"
               "wgmma.mma_async.sync.aligned.m64n16k16.f32.bf16.bf16 {%0,%1,%2,%3,%4,%5,%6,%7}, {%8,%8,%8,%8}, db, 1, 1, 1, 0;\n}"
               : "+f"(d[0]), "+f"(d[1]), "+f"(d[2]), "+f"(d[3]), "+f"(d[4]), "+f"(d[5]), "+f"(d[6]), "+f"(d[7])
               : "r"(one), "r"(db));
}
__device__ __forceinline__ void acc_fence(float (&d)[8]) {
  asm volatile("" : "+f"(d[0]), "+f"(d[1]), "+f"(d[2]), "+f"(d[3]), "+f"(d[4]), "+f"(d[5]), "+f"(d[6]), "+f"(d[7]) :: "memory");
}

template <int N, int STRIDE> __device__ __forceinline__ void load_units(uint2 (&v)[N], const uint32_t* p) {
#pragma unroll
  for (int i = 0; i < N; i++) v[i] = ldg_u64(p + i * STRIDE);
}
template <int N, int STRIDE> __device__ __forceinline__ int check_units(uint2 (&v)[N], const uint32_t* p, int rb) {
  int it = 0;
  while (true) {
    uint32_t mn = v[0].y;
#pragma unroll
    for (int i = 1; i < N; i++) mn = min(mn, v[i].y);
    if (mn != 0) break;
    backoff(rb);
#pragma unroll
    for (int i = 0; i < N; i++) if (v[i].y == 0) v[i] = ldg_u64(p + i * STRIDE);
    if (++it > SPIN_LIMIT) __trap();
  }
  return it;
}
__device__ __forceinline__ void reload_unit(uint2& v, const uint32_t* p) {
  asm volatile("{\n.reg .pred q;\nsetp.eq.u32 q, %1, 0;\n@q ld.relaxed.gpu.global.v2.b32 {%0, %1}, [%2];\n}" : "+r"(v.x), "+r"(v.y) : "l"(p) : "memory");
}
template <int N> __device__ __forceinline__ uint32_t min_flags(const uint2 (&v)[N]) {
  uint32_t a = v[0].y, b = v[1].y;
#pragma unroll
  for (int i = 2; i < N; i += 2) { a = min(a, v[i].y); b = min(b, v[i + 1].y); }
  return min(a, b);
}
__device__ __forceinline__ void sum4_to_smem(const uint2 (&v)[4], uint32_t dst) {
  const float c0 = (bf_lo(v[0].x) + bf_lo(v[1].x)) + (bf_lo(v[2].x) + bf_lo(v[3].x));
  const float c1 = (bf_hi(v[0].x) + bf_hi(v[1].x)) + (bf_hi(v[2].x) + bf_hi(v[3].x));
  const float c2 = (bf_lo(v[0].y) + bf_lo(v[1].y)) + (bf_lo(v[2].y) + bf_lo(v[3].y));
  const float c3 = (bf_hi(v[0].y) + bf_hi(v[1].y)) + (bf_hi(v[2].y) + bf_hi(v[3].y));
  sts1(dst, pack_bf16(c0, c1));
  sts1(dst + 128, pack_bf16(c2, c3));
}
__device__ __forceinline__ void load_a_t(uint32_t (&a)[8][4], uint32_t wbase, int w, int lane) {
  const int mi = lane >> 3, r = lane & 7;
  const uint32_t base = wbase + (w >> 2) * 16384 + (8 * (mi >> 1) + r) * 128 + (((2 * (w & 3) + (mi & 1)) ^ r) << 4);
#pragma unroll
  for (int ks = 0; ks < 8; ks++) ldsm4t(a[ks], base + ks * 2048);
}
__device__ __forceinline__ void mma128(float (&d)[4], const uint32_t (&a)[8][4], const uint32_t (&b)[4][4]) {
  float e[4][4] = {{d[0], d[1], d[2], d[3]}, {0.f, 0.f, 0.f, 0.f}, {0.f, 0.f, 0.f, 0.f}, {0.f, 0.f, 0.f, 0.f}};
#pragma unroll
  for (int kk = 0; kk < 4; kk++) { mma16816(e[(2 * kk) & 3], a[2 * kk], b[kk][0], b[kk][1]); mma16816(e[(2 * kk + 1) & 3], a[2 * kk + 1], b[kk][2], b[kk][3]); }
#pragma unroll
  for (int i = 0; i < 4; i++) d[i] = (e[0][i] + e[1][i]) + (e[2][i] + e[3][i]);
}
template <int NP> __device__ __forceinline__ bool sum_pieces(const uint32_t* p0, uint32_t one, float (&r)[4]) {
  uint2 v[NP / 4];
  load_units<NP / 4, 64>(v, p0);
  float d[4][4] = {};
#pragma unroll
  for (int i = 0; i < NP / 8; i++) { const uint32_t a[4] = {v[2 * i].x, v[2 * i].y, v[2 * i + 1].x, v[2 * i + 1].y}; mma16816(d[i & 3], a, one, one); }
  const bool ok = __all_sync(~0u, min_flags(v) != 0);
#pragma unroll
  for (int k = 0; k < 4; k++) r[k] = (d[0][k] + d[1][k]) + (d[2][k] + d[3][k]);
  return ok;
}
template <typename F> __device__ __forceinline__ float reduce_g(const float (&x)[4], int lane, F f) {
  const bool u4 = lane & 16, u3 = lane & 8;
  const float a0 = f(u4 ? x[2] : x[0], __shfl_xor_sync(~0u, u4 ? x[0] : x[2], 16));
  const float a1 = f(u4 ? x[3] : x[1], __shfl_xor_sync(~0u, u4 ? x[1] : x[3], 16));
  const float b = f(u3 ? a1 : a0, __shfl_xor_sync(~0u, u3 ? a0 : a1, 8));
  return f(b, __shfl_xor_sync(~0u, b, 4));
}

__global__ void __launch_bounds__(NTHREADS, 1)
fused_decode_kernel(__nv_bfloat16* __restrict__ gout, Scratch* __restrict__ gs, const uint8_t* __restrict__ gwmod,
                    const uint8_t* __restrict__ gx, const uint8_t* __restrict__ gc, uint32_t* __restrict__ gin,
                    const __grid_constant__ Params P) {
  constexpr Tune T{};
  extern __shared__ __align__(1024) uint8_t smem_raw[];
  const uint32_t sb = (uint32_t)__cvta_generic_to_shared(smem_raw);
  const int tid = __shfl_xor_sync(0xffffffffu, threadIdx.x ^ 1, 1), lane = tid & 31;
  const int w = __shfl_sync(0xffffffffu, threadIdx.x >> 5, 0);
  const int cta = blockIdx.x;
  const uint32_t bars = sb + OFF_BARS;
  auto BAR = [&](int i) { return bars + 8 * i; };
  auto selector = [&](int c) { uint32_t v; asm volatile("ld.shared.u8 %0, [%1];" : "=r"(v) : "r"(sb + OFF_SEL + c) : "memory"); return v; };
  auto inbox = [&](int c, int k) { return gin + blk(c, k, selector(c)); };
  auto nearbox = [&](int c, int k) { return gin + blk(c, k, selector(cta) ^ flip((c ^ cta) & 15)); };
  const int g = lane >> 2, t = lane & 3;
  const int hI = cta >> 2, jI = cta & 3;
  const int bs = cta >> 1, hh = cta & 1;

  CLK_DECL;
  CLK(0);
  if (w == 8) {
    CLK(7);
    const uint32_t t_entry = gtime32();
    CLK(8);
    if (lane == 0) {
      if ((sb & 0xffffff) != SB) __trap();
      mbar_init(BAR(BAR_WQ), 1); mbar_init(BAR(BAR_WQ + 1), 1); mbar_init(BAR(BAR_XC), 1); mbar_init(BAR(BAR_C), 1);
      asm volatile("fence.mbarrier_init.release.cluster;" ::: "memory");
      asm volatile("prefetch.tensormap [%0];" ::"l"(&P.wq) : "memory");
      mbar_expect(BAR(BAR_XC), 8192); mbar_expect(BAR(BAR_C), 8192); mbar_expect(BAR(BAR_WQ), 16384); mbar_expect(BAR(BAR_WQ + 1), 16384);
      CLK(9);
    }
    __syncwarp();
    asm volatile("barrier.cta.arrive.aligned 0, %0;" ::"n"(NTHREADS) : "memory");
    CLK(10);
    uint32_t tn = t_entry + T.PC_T0 + ((bs * 37) & 63) * T.PC_STAG / 64;
    const int h = hI, j = jI;
    if (lane == 0) {
      uint64_t pol; asm volatile("createpolicy.fractional.L2::evict_first.b64 %0, 1.0;" : "=l"(pol));
#pragma unroll
      for (int u = 0; u < 4; u++) {
        until_ns(tn + u * T.PC_P1);
        if (u == 0) CLK(11);
        tma2d(sb + OFF_WQ + u * 8192, &P.wq, 128 * h + 64 * (u >> 1), 128 * j + 64 * (u & 1), BAR(BAR_WQ + (u >> 1)), pol);
        if (u == T.PC_XC) {
#pragma unroll
          for (int i = 0; i < 4; i++) { const int o = ((i + cta) & 3) * 2048; bulk_ld(sb + OFF_XS + o, gx + o, 2048, BAR(BAR_XC)); }
        }
        if (u == T.PC_C) {
#pragma unroll
          for (int i = 0; i < 4; i++) { const int o = ((i + cta) & 3) * 2048; bulk_ld(sb + OFF_CS + o, gc + o, 2048, BAR(BAR_C)); }
        }
        if (u == 0) {
          CLK(1);
          asm volatile("prefetch.tensormap [%0];" ::"l"(&P.wuk) : "memory");
          asm volatile("prefetch.tensormap [%0];" ::"l"(&P.wm2) : "memory");
          asm volatile("prefetch.tensormap [%0];" ::"l"(&P.ckv2) : "memory");
        }
      }
    }
    __syncwarp();
    tn += 4 * T.PC_P1;
    bar_sync(5, 64);
    if (lane == 0) {
      uint64_t pol; asm volatile("createpolicy.fractional.L2::evict_first.b64 %0, 1.0;" : "=l"(pol));
#pragma unroll
      for (int u = 0; u < 4; u++) {
        if ((u & 1) == (T.PC_W > 3) && T.PC_NW) mbar_wait(BAR(BAR_WQ + (u >> 1)));
        slot(tn, T.PC_SL);
        tma5d(sb + OFF_WUK + u * 8192, &P.wuk, 128 * h + 64 * (u >> 1), 0, 0, 0, 8 * j + 4 * (u & 1), BAR(BAR_WUK + (u >> 1)), pol);
        tn += T.PC_P1;
      }
#pragma unroll
      for (int u = 0; u < 2; u++) {
        if (u == (T.PC_W > 3) && T.PC_NW) mbar_wait(BAR(BAR_WUK));
        slot(tn, T.PC_SL);
        tma2d_nohint(sb + OFF_WM2 + u * 8192, &P.wm2, 1024 + 16 * cta, 256 * u, BAR(BAR_WM2));
        tn += T.PC_P1;
      }
      const int row0 = (bs >> 3) * 4096 + (bs & 7) * 64;
      uint32_t dst = sb + OFF_RING;
      const int p2 = T.PC_P2 + (32 - ((bs * 37) & 63)) * T.PC_DS / 1024;
#pragma unroll 1
      for (int n = 0; n < 31; n++) {
        if (n >= 4 && (n < 12 || (n & 3) == 0)) mbar_wait(BAR(n >= 12 ? BAR_EMPTY + (n >> 2) - 3 : n == 7 ? BAR_P0BD : (n == 8 || n == 9) ? BAR_P2D : BAR_P1D));
        if (n < T.PC_NW) {
          if (n >= T.PC_W) mbar_wait(BAR(BAR_FULL + n - T.PC_W));
          else if ((n & 1) == (T.PC_W > 3)) mbar_wait(BAR(n < 2 ? BAR_WUK + 1 : BAR_WM2));
        }
        slot(tn, T.PC_SL);
        tma3d(dst, &P.ckv2, 0, row0 + (n >> 2) * 512, 2 * (n & 3), BAR(BAR_FULL + n), pol);
        dst = (n == 11 || n == 23) ? sb + OFF_RING : dst + 16384;
        tn += n >= 15 ? p2 : T.PC_P2;
        if (n == 4) CLK(2);
        if (n == 12) CLK(3);
        if (n == 20) CLK(4);
        if (n == 28) CLK(5);
        if (n == 24) {
          asm volatile("prefetch.tensormap [%0];" ::"l"(&P.ckv1) : "memory");
          asm volatile("prefetch.tensormap [%0];" ::"l"(&P.wuv) : "memory");
          asm volatile("prefetch.tensormap [%0];" ::"l"(&P.wo) : "memory");
          asm volatile("prefetch.tensormap [%0];" ::"l"(&P.w1) : "memory");
          asm volatile("prefetch.tensormap [%0];" ::"l"(&P.w2) : "memory");
        }
      }
      slot(tn, T.PC_SL);
      tma3d(dst, &P.ckv1, 0, row0 + 7 * 512, 6, BAR(BAR_LAST + 3), pol);
      tma3d(dst + 8192, &P.ckv1, 0, row0 + 7 * 512, 7, BAR(BAR_LAST + 4), pol);
      tn += T.PC_P2;
      CLK(6);
      auto unit = [&](int u) {
        if (u < 4) tma5d(sb + OFF_WUV + u * 8192, &P.wuv, 128 * h + 64 * (u >> 1), 0, 4 * (j >> 1), 0, 2 * (j & 1) + (u & 1), BAR(BAR_WUV + (u >> 1)), pol);
        else if (u < 8) tma2d(sb + OFF_WO + (u - 4) * 8192, &P.wo, 128 * j + 64 * ((u - 4) >> 1), 128 * h + 64 * (u & 1), BAR(BAR_WO + ((u - 4) >> 1)), pol);
        else if (u < 10) { if (cta < NFF) tma2d_nohint(sb + OFF_W1 + (u - 8) * 16384, &P.w1, 32 * bs, 256 * (u - 8), BAR(BAR_W1)); }
        else if (cta < NFF) tma3d(sb + OFF_W2 + (u - 10) * 8192, &P.w2, 0, 32 * bs, 4 * hh + 2 * (u - 10), BAR(BAR_W2), pol);
      };
      mbar_wait(BAR(BAR_EMPTY + 5));
      if (T.PW_A >= 0) { mbar_wait(BAR(BAR_LAST + T.PW_A)); tn = gtime32(); }
      tn += T.PW_0 + ((cta * 37) & 127) * T.PW_ST / 128;
#pragma unroll
      for (int u = 0; u < 12; u++) {
        if (u == 8) mbar_wait(BAR(BAR_EMPTY + 6));
        until_ns(tn);
        unit(WSWAP && u >= 8 ? (u ^ 2) : u);
        tn += u < 3 ? T.PW_UV : u == 3 ? T.PW_G : u < 7 ? T.PW_O : u == 7 ? T.PW_G2 : u == 9 ? T.PW_G3 : T.PW_F;
      }
      CLK_DUMP();
    }
    return;
  }

  if (w == 9) {
    if (lane == 0) {
#pragma unroll
      for (int i = 0; i < NBARS; i++) mbar_init(BAR(i), i >= BAR_P1D ? 8 : i >= BAR_EMPTY ? 4 : 1);
      asm volatile("fence.mbarrier_init.release.cluster;" ::: "memory");
    }
    __syncwarp();
    mbar_expect(BAR(lane), lane == BAR_LAST + 3 ? 8192 : 16384);
    if (lane < BAR_ALLCLR - 32) mbar_expect(BAR(32 + lane), lane == 0 ? 8192 : lane == BAR_W1 - 32 ? 32768 : 16384);
    CLK(9);
    asm volatile("barrier.cta.arrive.aligned 5, 64;" ::: "memory");
    asm volatile("barrier.cta.arrive.aligned 0, %0;" ::"n"(NTHREADS) : "memory");
  }
  const uint32_t epoch = ldg_rlx1(&gs->epoch);

  if (w == 9) {
    const int mo = g * 512 + 16 * hI + 2 * jI;
    const uint32_t xo0 = ldg_nc1(gx + mo * 2), xo1 = ldg_nc1(gx + mo * 2 + 16);
    const int par = epoch & 1;
    const uint32_t t0 = gtime32();
    const uint4 z = make_uint4(0, 0, 0, 0);
    uint32_t sel;
    {
      uint32_t* pa = gin + blk(cta, 5, 0) + 960;
      uint32_t* pb = gin + blk(cta, 5, 1) + 960;
      until_ns(t0 + T.PR_T0);
      if (lane < 4) stg4(reinterpret_cast<uint4*>(lane & 2 ? pa : pb) + (lane & 1), z);
      uint32_t ma = 0xffffffffu, mb = 0xffffffffu;
      if (lane == 0) {
#pragma unroll 1
        for (int i = 0; i < 2 * T.PR_N; i++) {
          const uint32_t c0 = clk32();
          uint32_t v;
          asm volatile("atom.relaxed.gpu.global.add.u32 %0, [%1], 1;" : "=r"(v) : "l"(i & 1 ? pb : pa) : "memory");
          if (v == 0xffffffffu) __trap();
          const uint32_t d = clk32() - c0;
          if (i & 1) mb = min(mb, d); else ma = min(ma, d);
        }
      }
      sel = __shfl_sync(~0u, (uint32_t)(mb < ma), 0);
      if (T.LOC == 1) sel ^= 1;
      if (T.LOC == 2) sel ^= (cta ^ (cta >> 3)) & 1;
      const uint32_t sw = 2 * (epoch + 1) + sel;
      if (lane < 2) stg4(reinterpret_cast<uint4*>(gin + blk(cta, 5, 1) + 896) + lane, make_uint4(sw, sw, sw, sw));
    }
    until_ns(t0 + T.CLR_T0);
    {
#pragma unroll 1
      for (int i0 = 0; i0 < 13; i0++) {
        uint4* q = reinterpret_cast<uint4*>(gin + (i0 < 12 ? blk(cta, i0 >> 1, sel) + (i0 & 1) * 512 : blk(cta, 4, sel ^ 1) + 512)) + lane;
#pragma unroll
        for (int i = 0; i < 4; i++) if (i0 != 11 || i < 3) stg4(q + i * 32, z);
        backoff(T.CLR_CLK);
      }
#pragma unroll
      for (int i = 0; i < 2; i++) {
        if (jI == 1) stg4(reinterpret_cast<uint4*>(gin + blk(cta, 6, i)) + lane, z);
        if (lane < 2) stg4(reinterpret_cast<uint4*>(gin + blk(cta, 5, i) + 928) + lane, z);
        stg4(reinterpret_cast<uint4*>(gin + blk(16 * g, 6 + (cta >> 6), i) + (cta & 63) * 16) + t, z);
      }
      CLK(1);
      {
        uint32_t sv = 0;
        uint32_t u[4];
#pragma unroll
        for (int i = 0; i < 4; i++) u[i] = ldg_rlx1(gin + blk(4 * lane + i, 5, 1) + 896);
#pragma unroll
        for (int i = 0; i < 4; i++) {
          int it = 0;
          while ((u[i] | 1) != 2 * (epoch + 1) + 1) { u[i] = ldg_rlx1(gin + blk(4 * lane + i, 5, 1) + 896); if (++it > SPIN_LIMIT) __trap(); }
          sv |= (u[i] & 1) << (8 * i);
        }
        sts1(sb + OFF_SEL + lane * 4, sv);
      }
      asm volatile("fence.acq_rel.gpu;" ::: "memory");
      CLK(2);
      __syncwarp();
      if (lane < NSYNC) asm volatile("red.relaxed.gpu.global.add.u32 [%0], 1;" ::"l"(&gs->sync[lane][0]) : "memory");
#pragma unroll
      for (int i = 0; i < 4; i++) stg4(reinterpret_cast<uint4*>(gs->QP[par ^ 1] + cta * 512) + i * 32 + lane, z);
      backoff(T.CLR_CLK);
#pragma unroll
      for (int i = 0; i < 4; i++) stg4(reinterpret_cast<uint4*>(gs->QX[par ^ 1] + cta * 512) + i * 32 + lane, z);
      stg4(reinterpret_cast<uint4*>(gs->MOD1[par ^ 1] + cta * 128) + lane, z);
      if (lane < 16) stg4(reinterpret_cast<uint4*>(gs->MOD2[par ^ 1] + cta * 64) + lane, z);
      if (lane == 0) {
        const uint32_t target = (epoch + 1) * NCTA;
        uint32_t c; int it = 0;
        do { backoff(T.CLR_CLK); asm volatile("ld.acquire.gpu.global.u32 %0, [%1];" : "=r"(c) : "l"(&gs->sync[cta % NSYNC][0]) : "memory"); if (++it > SPIN_LIMIT) __trap(); } while ((int)(c - target) < 0);
        mbar_arrive(BAR(BAR_ALLCLR));
      }
      __syncwarp();
    }
    CLK(3);
    uint2 gg[2];
    {
      const uint32_t* pg = gs->MOD2[par] + cta * 16 + g * 2;
      load_units<2, 3 * 2048>(gg, pg);
      check_units<2, 3 * 2048>(gg, pg, T.RB);
    }
    uint32_t anchor;
    {
      uint32_t* const po = gin + blk(16 * (lane & 7), 5, lane >> 3) + 928;
      const uint32_t* const pi = nearbox(cta & ~15, 5) + 928;
      mbar_wait(BAR(BAR_LAST + T.TS_P));
      unsigned long long now; asm volatile("mov.u64 %0, %%globaltimer;" : "=l"(now));
      if (lane < 16) {
        asm volatile("red.relaxed.gpu.global.max.u64 [%0], %1;" ::"l"(po + 2), "l"(now) : "memory");
        asm volatile("red.relaxed.gpu.global.add.u32 [%0], 1;" ::"l"(po + 1) : "memory");
      }
      backoff(T.D_TS);
      uint4 v; int it = 0;
      do { v = ldg_2u64(pi); if (++it > SPIN_LIMIT) __trap(); } while (v.y != NCTA);
      const int age = min(max((int)(gtime32() - v.z), 0), 4000);
      anchor = clk32() - age * 7 / 4 + T.TS_O;
      if (lane == 0) { sts1(sb + OFF_TS, anchor); mbar_arrive(BAR(BAR_TS)); }
      CLK(10);
    }
    {
      const uint32_t* pm = pin(nearbox(4 * hI + 1, 6) + lane * 4);
      wait_clk(anchor, T.A_M);
      uint4 ml = ldg_2u64(pm);
      int it = 0;
      while (ml.y == 0 || ml.w == 0) { ml = ldg_2u64(pm); if (++it > SPIN_LIMIT) __trap(); }
      __syncwarp();
      ITS(2, it);
      float M = fmaxf(__uint_as_float(ml.x), __uint_as_float(ml.z));
      M = fmaxf(M, __shfl_xor_sync(~0u, M, 1)); M = fmaxf(M, __shfl_xor_sync(~0u, M, 2));
      const float e0 = ex2(__uint_as_float(ml.x) - M), e1 = ex2(__uint_as_float(ml.z) - M);
      float l = e0 * __uint_as_float(ml.y) + e1 * __uint_as_float(ml.w);
      l += __shfl_xor_sync(~0u, l, 1); l += __shfl_xor_sync(~0u, l, 2);
      const float inv = __fdividef(1.f, l);
      sts2f(sb + OFF_WV + lane * 8, e0 * inv, e1 * inv);
      __syncwarp();
      if (lane == 0) mbar_arrive(BAR(BAR_WV));
      CLK(11);
    }
    uint32_t* x3o[4];
#pragma unroll
    for (int i = 0; i < 4; i++) x3o[i] = pin(gin + blk(32 * i + 16 * (t >> 1), 6 + (cta >> 6), t) + (cta & 63) * 16 + g * 2);
    uint32_t* const fo = pin(reinterpret_cast<uint32_t*>(gout) + mo / 2 + 4 * (t & 1));
    const uint32_t* const p3 = pin(gin + blk(cta, 4, sel) + t * 16 + g * 2);
    const uint32_t* const p4 = pin(gin + blk(cta, 5, sel) + t * 16 + g * 2);
    const uint32_t one = pin((g & 1) ? 0x3f800000u : 0x00003f80u);
    const float xf[4] = {pin(bf_lo(xo0)), pin(bf_hi(xo0)), pin(bf_lo(xo1)), pin(bf_hi(xo1))};
    const float ga[4] = {pin(bf_lo(gg[0].x)), pin(bf_hi(gg[0].x)), pin(bf_lo(gg[0].y)), pin(bf_hi(gg[0].y))};
    mbar_wait(BAR(BAR_P5D));
    backoff(T.D_X3A);
    wait_clk(anchor, T.A_X1 + T.R_X3A);
    CLK(4);
    float r[4];
    uint32_t x20, x21;
    int it = 0;
    bool ok;
    do {
      ok = sum_pieces<32>(p3, one, r);
      x20 = pack_bf16(xf[0] + ga[0] * r[0], xf[1] + ga[1] * r[1]); x21 = pack_bf16(xf[2] + ga[2] * r[2], xf[3] + ga[3] * r[3]);
#pragma unroll
      for (int i = 0; i < 4; i++) ST3B(!ok || (i == 3 && t >= 2), x3o[i], x20, x21);
    } while (!ok && ++it < SPIN_LIMIT);
    CLK(6);
    ITS(0, it);
    const uint32_t xw = (t & 1) ? x21 : x20, gw = (t & 1) ? gg[1].y : gg[1].x;
    const float xa = pin(bf_lo(xw)), xb = pin(bf_hi(xw)), gba = pin(bf_lo(gw)), gbb = pin(bf_hi(gw));
    if (cta < NFF) { mbar_wait(BAR(BAR_P7D)); backoff(T.D_FIN); } else { backoff(1200); wait_clk(anchor, T.A_X1 + T.R_X3A + T.R_X3B + T.R_FIN); }
    CLK(7);
    do {
      ok = sum_pieces<NFG>(p4, one, r);
      const uint32_t o = pack_bf16(xa + gba * ((t & 1) ? r[2] : r[0]), xb + gbb * ((t & 1) ? r[3] : r[1]));
      if (ok && t < 2) asm volatile("st.global.u32 [%0], %1;" ::"l"(fo), "r"(o) : "memory");
    } while (!ok && ++it < SPIN_LIMIT);
    if (!ok) __trap();
    ITS(1, it);
    CLK(8);
    CLK_DUMP();
    if (cta == 0 && lane == 0) stg1(&gs->epoch, epoch + 1);
    return;
  }

  const int wg = w >> 2, wq = w & 3;
  uint32_t tstore;
  {
    const uint8_t* pw = gwmod + (size_t)(128 * jI + 16 * w + 4 * (g >> 1) + (g & 1)) * 6144 + 64 * hI + 16 * t;
    const uint4 w0 = ldg_nc4(pw), w1 = ldg_nc4(pw + 2 * 6144);
    const uint2 cc = ldg_nc2(gc + g * 1024 + 256 * jI + 32 * w + 8 * t);
    CLK(40);
    const uint32_t a[4] = {silu2(cc.x), 0u, silu2(cc.y), 0u};
    float d[4][4] = {{0.f, 0.f, 0.f, 0.f}, {0.f, 0.f, 0.f, 0.f}, {0.f, 0.f, 0.f, 0.f}, {0.f, 0.f, 0.f, 0.f}};
    mma16816(d[0], a, movm(w0.x), movm(w1.x)); mma16816(d[1], a, movm(w0.y), movm(w1.y));
    mma16816(d[2], a, movm(w0.z), movm(w1.z)); mma16816(d[3], a, movm(w0.w), movm(w1.w));
    CLK(1);
    sts4f(sb + OFF_P0S + w * 1088 + lane * 16, d[0][0], d[0][1], d[1][0], d[1][1]);
    sts4f(sb + OFF_P0S + w * 1088 + 544 + lane * 16, d[2][0], d[2][1], d[3][0], d[3][1]);
    bar_sync(0, NTHREADS);
    if (tid < 128) {
      const uint32_t src = sb + OFF_P0S + ((tid >> 2) & 1) * 544 + (((tid >> 3) & 7) * 4 + 2 * (tid >> 6) + (tid & 1)) * 16 + ((tid >> 1) & 1) * 8;
      float2 v[8];
#pragma unroll
      for (int i = 0; i < 8; i++) v[i] = ldsf2(src + i * 1088);
      const float ax = ((v[0].x + v[1].x) + (v[2].x + v[3].x)) + ((v[4].x + v[5].x) + (v[6].x + v[7].x));
      const float ay = ((v[0].y + v[1].y) + (v[2].y + v[3].y)) + ((v[4].y + v[5].y) + (v[6].y + v[7].y));
      stg1(gs->MOD1[epoch & 1] + jI * 4096 + hI * 128 + tid, nz(pack_bf16(ax, ay)));
    }
    tstore = clk32();
  }
  CLK(2);
  const int par = epoch & 1;
  uint32_t cf[4][4];
  mbar_wait(BAR(BAR_XC));
  {
    uint32_t u[2][4];
    lds4(u[0], sb + OFF_XS + w * 1024 + lane * 16); lds4(u[1], sb + OFF_XS + w * 1024 + 512 + lane * 16);
    float v[16];
#pragma unroll
    for (int i = 0; i < 8; i++) { v[2 * i] = bf_lo(u[i >> 2][i & 3]); v[2 * i + 1] = bf_hi(u[i >> 2][i & 3]); }
    float s = 0.f;
#pragma unroll
    for (int i = 0; i < 16; i++) s += v[i];
#pragma unroll
    for (int o = 16; o; o >>= 1) s += __shfl_xor_sync(~0u, s, o);
    const float mu = s * (1.f / 512.f);
    float q = 0.f;
#pragma unroll
    for (int i = 0; i < 16; i++) { v[i] -= mu; q += v[i] * v[i]; }
#pragma unroll
    for (int o = 16; o; o >>= 1) q += __shfl_xor_sync(~0u, q, o);
    const float rs = rsqrtf(q * (1.f / 512.f) + 1e-5f);
    const bool hi = jI & 2;
    uint32_t o[4];
#pragma unroll
    for (int i = 0; i < 4; i++) o[i] = pack_bf16((hi ? v[8 + 2 * i] : v[2 * i]) * rs, (hi ? v[9 + 2 * i] : v[2 * i + 1]) * rs);
    if ((lane >> 4) == (jI & 1)) sts4(sb + OFF_XN + w * 272 + (lane & 15) * 16, make_uint4(o[0], o[1], o[2], o[3]));
  }
  CLK(3);
  uint32_t aw[8][4];
  {
    const uint32_t* pm = pin(gs->MOD1[par] + (8 * jI + w) * 64 + lane * 2);
    uint32_t* const qpo = pin(gs->QP[par] + (cta * 256 + tid) * 2);
    float d[4] = {0.f, 0.f, 0.f, 0.f};
    wait_clk(tstore, T.D_MOD);
    CLK(4);
    uint2 v[8];
    load_units<8, 2048>(v, pm);
    cbar();
    const uint32_t xn0 = lds1(sb + OFF_XN + g * 272 + w * 32 + t * 4), xn1 = lds1(sb + OFF_XN + g * 272 + w * 32 + 16 + t * 4);
    const bool early = __all_sync(~0u, mbar_test(BAR(BAR_WQ + wg)));
    if (early) load_a_t(aw, sb + OFF_WQ, w, lane);
    int it = 0;
    while (true) {
      uint32_t mn = 0xffffffffu;
#pragma unroll
      for (int i = 0; i < 8; i++) mn = min(mn, min(v[i].x, v[i].y));
      if (mn != 0) break;
#pragma unroll
      for (int i = 0; i < 8; i++) if (v[i].x == 0 || v[i].y == 0) v[i] = ldg_u64(pm + i * 2048);
      if (++it > SPIN_LIMIT) __trap();
    }
    CLK(5);
    ITS(0, it);
    float sc[2][4];
#pragma unroll
    for (int i = 0; i < 2; i++) {
      sc[i][0] = (bf_lo(v[i].x) + bf_lo(v[2 + i].x)) + (bf_lo(v[4 + i].x) + bf_lo(v[6 + i].x));
      sc[i][1] = (bf_hi(v[i].x) + bf_hi(v[2 + i].x)) + (bf_hi(v[4 + i].x) + bf_hi(v[6 + i].x));
      sc[i][2] = (bf_lo(v[i].y) + bf_lo(v[2 + i].y)) + (bf_lo(v[4 + i].y) + bf_lo(v[6 + i].y));
      sc[i][3] = (bf_hi(v[i].y) + bf_hi(v[2 + i].y)) + (bf_hi(v[4 + i].y) + bf_hi(v[6 + i].y));
    }
    sts2(sb + OFF_BS1 + (w >> 1) * 512 + lane * 16 + (w & 1) * 8,
         pack_bf16(bf_lo(xn0) * (1.f + sc[1][0]) + sc[0][0], bf_hi(xn0) * (1.f + sc[1][1]) + sc[0][1]),
         pack_bf16(bf_lo(xn1) * (1.f + sc[1][2]) + sc[0][2], bf_hi(xn1) * (1.f + sc[1][3]) + sc[0][3]));
    if (!early) { mbar_wait(BAR(BAR_WQ + wg)); load_a_t(aw, sb + OFF_WQ, w, lane); }
    CLK(6);
    cbar();
    uint32_t b[4][4];
#pragma unroll
    for (int kk = 0; kk < 4; kk++) lds4(b[kk], sb + OFF_BS1 + kk * 512 + lane * 16);
    mma128(d, aw, b);
    stg_u64(qpo, pack_bf16(d[0], d[1]), pack_bf16(d[2], d[3]));
    tstore = clk32();
    CLK(7);
    if (wg) {
      mbar_wait(BAR(BAR_C));
#pragma unroll
      for (int i = 0; i < 4; i++) lds4(cf[i], sb + OFF_CS + g * 1024 + wq * 256 + i * 64 + t * 16);
#pragma unroll
      for (int i = 0; i < 16; i++) cf[i >> 2][i & 3] = silu2(cf[i >> 2][i & 3]);
    }
    __syncwarp();
    if (lane == 0) mbar_arrive(BAR(BAR_P1D));
  }
  {
    const uint32_t* pq = pin(gs->QP[par] + (hI * 4 * 256 + tid) * 2);
    uint32_t* const qxo = pin(gs->QX[par] + (g * 32 + hI) * 256 + 64 * jI + 8 * w + 2 * t);
    uint2 v[4];
    float d[4] = {0.f, 0.f, 0.f, 0.f};
    wait_clk(tstore, T.D_QP);
    CLK(8);
    load_units<4, 512>(v, pq);
    const uint32_t abase = sb + OFF_WUK + (16 * w + (lane & 15)) * 128;
    auto load_half = [&](int hf) {
#pragma unroll
      for (int ks = 0; ks < 4; ks++) ldsm4(aw[4 * hf + ks], abase + hf * 16384 + (((2 * ks + (lane >> 4)) ^ (lane & 7)) << 4));
    };
    mbar_wait(BAR(BAR_WUK));
    load_half(0);
    const bool early = __all_sync(~0u, mbar_test(BAR(BAR_WUK + 1)));
    if (early) load_half(1);
    const int it = check_units<4, 512>(v, pq, T.RB);
    CLK(9);
    ITS(1, it);
    sum4_to_smem(v, sb + OFF_BS2 + (16 * w + g) * 16 + t * 4);
    if (!early) { mbar_wait(BAR(BAR_WUK + 1)); load_half(1); }
    CLK(10);
    cbar();
    uint32_t b[4][4];
#pragma unroll
    for (int kk = 0; kk < 4; kk++) ldsm4t(b[kk], sb + OFF_BS2 + (32 * kk + lane) * 16);
    mma128(d, aw, b);
    const float sc = 0.08838834764831845f * 1.4426950408889634f;
    stg_u64(qxo, movm(pack_bf16(d[0] * sc, d[1] * sc)), movm(pack_bf16(d[2] * sc, d[3] * sc)));
    tstore = clk32();
    CLK(11);
    if (lane == 0) mbar_arrive(BAR(BAR_P2D));
  }
  if (wg) {
    const int mi = lane >> 3, r = lane & 7;
    const uint32_t a0 = sb + OFF_WM2 + (8 * (r >> 1) + (r & 1) + 2 * (mi >> 1)) * 32 + (mi & 1) * 16;
    mbar_wait(BAR(BAR_WM2));
#pragma unroll
    for (int s = 0; s < 8; s++) ldsm4t(aw[s], a0 + (128 * wq + 32 * (s >> 1) + 4 * (s & 1)) * 32);
    float d[4] = {0.f, 0.f, 0.f, 0.f};
    mma128(d, aw, cf);
    sts4f(sb + OFF_P0B + (tid - 128) * 16, d[0], d[1], d[2], d[3]);
    if (lane == 0) mbar_arrive(BAR(BAR_P0BD));
    bar_sync(3, 128);
    if (w == 4) {
      float4 v[4];
#pragma unroll
      for (int i = 0; i < 4; i++) v[i] = ldsf4(sb + OFF_P0B + (i * 32 + lane) * 16);
      stg_u64(gs->MOD2[par] + cta * 64 + t * 16 + g * 2, movm(pack_bf16((v[0].x + v[1].x) + (v[2].x + v[3].x), (v[0].y + v[1].y) + (v[2].y + v[3].y))),
              movm(pack_bf16((v[0].z + v[1].z) + (v[2].z + v[3].z), (v[0].w + v[1].w) + (v[2].w + v[3].w))));
    }
    CLK(15);
  }
  {
    const uint32_t* qx = pin(gs->QX[par] + ((bs >> 3) * 32 + 16 * hh) * 256 + tid * 4);
    const int ch = tid & 63, h0 = tid >> 6;
    const uint32_t dst = sb + OFF_Q + (ch >> 3) * 2048 + h0 * 128;
    wait_clk(tstore, T.D_QX);
    CLK(12);
    uint4 v[4];
#pragma unroll
    for (int i = 0; i < 4; i++) v[i] = ldg_2u64(qx + i * 1024);
    int it = 0;
    while (true) {
      uint32_t mn = 0xffffffffu;
#pragma unroll
      for (int i = 0; i < 4; i++) mn = min(mn, min(v[i].y, v[i].w));
      if (mn != 0) break;
#pragma unroll
      for (int i = 0; i < 4; i++) if (v[i].y == 0 || v[i].w == 0) v[i] = ldg_2u64(qx + i * 1024);
      if (++it > SPIN_LIMIT) __trap();
    }
    CLK(13);
    ITS(2, it);
#pragma unroll
    for (int i = 0; i < 4; i++) sts4(dst + i * 512 + (((ch & 7) ^ ((4 * i + h0) & 7)) << 4), v[i]);
    asm volatile("fence.proxy.async.shared::cta;" ::: "memory");
    CLK(14);
    cbar();
  }

  uint2 cbf[4], sbf[4];
  const uint32_t* const pcb = gs->MOD2[par] + 2048 + (16 * w + t) * 16 + g * 2;
  uint32_t thand, anchor;
  if (wg == 0) {
    float mh[4];
    float L[8];
#pragma unroll
    for (int i = 0; i < 4; i++) { L[2 * i] = L[2 * i + 1] = 0.f; mh[i] = -INFINITY; }
    constexpr uint32_t dq = desc_lo(OFF_Q);
    const uint32_t ptw = sb + OFF_PT + (8 * (lane >> 4) + (lane & 7)) * 128 + (((2 * wq + ((lane >> 3) & 1)) ^ (lane & 7)) << 4);
    float S[8];
    auto softmax = [&](int tl) {
      auto write_p = [&](const float (&x)[8]) {
        float p[8];
#pragma unroll
        for (int i = 0; i < 8; i++) p[i] = ex2(x[i]);
        stsm4t(ptw + (tl & 1) * 2048, pack_bf16(p[0], p[1]), pack_bf16(p[2], p[3]), pack_bf16(p[4], p[5]), pack_bf16(p[6], p[7]));
        asm volatile("fence.proxy.async.shared::cta;" ::: "memory");
      };
      float x[8];
#pragma unroll
      for (int i = 0; i < 8; i++) x[i] = S[i] - mh[2 * (i >> 2) + (i & 1)];
      if (tl) write_p(x);
      const float ex = fmaxf(fmaxf(fmaxf(x[0], x[1]), fmaxf(x[2], x[3])), fmaxf(fmaxf(x[4], x[5]), fmaxf(x[6], x[7])));
      if (tl == 0 || bar_over(ex)) {
        float mx[4];
#pragma unroll
        for (int i = 0; i < 4; i++) mx[i] = fmaxf(S[4 * (i >> 1) + (i & 1)], S[4 * (i >> 1) + 2 + (i & 1)]);
        const float a = reduce_g(mx, lane, [](float u, float v) { return fmaxf(u, v); });
        stsf(sb + OFF_RED + wq * 64 + (8 * (lane >> 4) + 2 * t + ((lane >> 3) & 1)) * 4, a);
        bar_sync(2, 128);
#pragma unroll
        for (int jn = 0; jn < 2; jn++) {
          float m0 = mh[2 * jn], m1 = mh[2 * jn + 1];
#pragma unroll
          for (int i = 0; i < 4; i++) { const float2 v = ldsf2(sb + OFF_RED + i * 64 + (8 * jn + 2 * t) * 4); m0 = fmaxf(m0, v.x); m1 = fmaxf(m1, v.y); }
          const float a0 = ex2(mh[2 * jn] - m0), a1 = ex2(mh[2 * jn + 1] - m1);
          mh[2 * jn] = m0; mh[2 * jn + 1] = m1;
          L[4 * jn] *= a0; L[4 * jn + 1] *= a1; L[4 * jn + 2] *= a0; L[4 * jn + 3] *= a1;
          if (tid < 4) sts2f(sb + OFF_ALPHA + (8 * jn + 2 * t) * 4, a0, a1);
        }
#pragma unroll
        for (int i = 0; i < 8; i++) x[i] = S[i] - mh[2 * (i >> 2) + (i & 1)];
        write_p(x);
        cbar();
      }
      const uint32_t dpt = __shfl_sync(~0u, desc_lo(OFF_PT) + (tl & 1) * 128, 0);
      wg_fence();
#pragma unroll
      for (int ks = 0; ks < 4; ks++) wgmma_n16_ones(L, ONE2, dpt + ks * 2);
      wg_commit();
    };
    uint32_t da = desc_lo(OFF_RING);
#pragma unroll 1
    for (int tl = 0; tl < 7; tl++) {
      uint32_t ok = 0;
#pragma unroll
      for (int u = 0; u < 4; u++) ok += mbar_test(BAR(BAR_FULL + 4 * tl + u));
      ok = __reduce_min_sync(~0u, ok);
      const uint32_t du = __shfl_sync(~0u, da, 0);
#pragma unroll
      for (int u = 0; u < 4; u++) {
        if (ok != 4) mbar_wait(BAR(BAR_FULL + 4 * tl + u));
        wg_fence();
#pragma unroll
        for (int k = 0; k < 8; k++) {
          const int i = 8 * u + k;
          if (i == 0) wgmma_n16<0, 0>(S, du, dq); else wgmma_n16<0, 1>(S, du + (i >> 2) * 512 + (i & 3) * 2, dq + (i >> 2) * 128 + (i & 3) * 2);
        }
        wg_commit();
      }
      wg_wait<0>();
      acc_fence(S); acc_fence(L);
      if (tl == 0) CLK(15);
      if (tl == 1) CLK(17);
      softmax(tl);
      if (tl == 0) CLK(16);
      if (tl == 1) CLK(18);
      if (tl == 3) CLK(19);
      if (tl == 6) CLK(20);
      da = (tl == 2 || tl == 5) ? da - 8192 : da + 4096;
    }
    if (cta < NFF) { load_units<4, 64>(sbf, pcb); load_units<4, 64>(cbf, pcb + 2048); }
    mbar_wait(BAR(BAR_ALLCLR));
    uint32_t* const mlo = pin(gin + blk(4 * (16 * hh + 4 * (g & 2) + 2 * t + (g & 1)) + 1, 6, g >> 2) + bs * 2);
#pragma unroll
    for (int i = 0; i < 32; i++) {
      if (i == 0 || i == 8 || i == 16 || i == 24 || i == 28) {
        if (i) wg_commit();
        mbar_wait(BAR(BAR_LAST + (i == 28 ? 4 : i >> 3)));
        if (i == 28) CLK(21);
        wg_fence();
      }
      if (i == 0) wgmma_n16<0, 0>(S, da, dq); else wgmma_n16<0, 1>(S, da + (i >> 2) * 512 + (i & 3) * 2, dq + (i >> 2) * 128 + (i & 3) * 2);
    }
    wg_commit();
    wg_wait<0>();
    acc_fence(S); acc_fence(L);
    CLK(22);
    softmax(7);
    CLK(23);
    thand = clk32();
    wg_wait<0>();
    acc_fence(L);
    if (tid < 32) MLST(mlo, __float_as_uint(g & 2 ? (g & 1 ? mh[3] : mh[2]) : (g & 1 ? mh[1] : mh[0])), __float_as_uint(g & 2 ? (g & 1 ? L[5] : L[4]) : (g & 1 ? L[1] : L[0])));
    CLK(24);
  } else {
    float O[8][8];
#pragma unroll
    for (int i = 0; i < 8; i++)
#pragma unroll
      for (int k = 0; k < 8; k++) O[i][k] = 0.f;
    constexpr uint32_t dp = desc_lo(OFF_PT);
    auto handover = [&](int tl) {
      if (tl == 0) { cbar(); return; }
      if (bar_over(0.f)) {
        cbar();
#pragma unroll
        for (int jn = 0; jn < 2; jn++) {
          const float2 a = ldsf2(sb + OFF_ALPHA + (8 * jn + 2 * t) * 4);
#pragma unroll
          for (int mb = 0; mb < 8; mb++) { O[mb][4 * jn] *= a.x; O[mb][4 * jn + 1] *= a.y; O[mb][4 * jn + 2] *= a.x; O[mb][4 * jn + 3] *= a.y; }
        }
      }
    };
    uint32_t da = desc_lo(OFF_RING);
#pragma unroll 1
    for (int tl = 0; tl < 7; tl++) {
      handover(tl);
      const uint32_t dpt = dp + (tl & 1) * 128;
      wg_fence();
#pragma unroll
      for (int i = 0; i < 32; i++) wgmma_n16<1, 1>(O[i >> 2], da + (i >> 2) * 512 + (i & 3) * 128, dpt + (i & 3) * 2);
      wg_commit();
      wg_wait<0>();
#pragma unroll
      for (int mb = 0; mb < 8; mb++) acc_fence(O[mb]);
      if (lane == 0) mbar_arrive(BAR(BAR_EMPTY + tl));
      if (tl == 0) CLK(16);
      if (tl == 1) CLK(18);
      if (tl == 3) CLK(19);
      if (tl == 6) CLK(20);
      da = (tl == 2 || tl == 5) ? da - 8192 : da + 4096;
    }
    if (cta < NFF) { load_units<4, 64>(sbf, pcb); load_units<4, 64>(cbf, pcb + 2048); }
    mbar_wait(BAR(BAR_ALLCLR));
    uint32_t* x1o[8];
#pragma unroll
    for (int i = 0; i < 8; i++)
      x1o[i] = pin(inbox((16 * hh + 8 * ((i >> 1) & 1) + 2 * t + (i & 1)) * 4 + 2 * (i >> 2) + (wq >> 1), bs >> 4) + (bs & 15) * 64 + ((wq & 1) * 8 + g) * 4);
    handover(7);
    CLK(23);
    thand = clk32();
    auto pv = [&](int mb0, int n) {
      wg_fence();
#pragma unroll
      for (int i = 0; i < 16; i++)
        if (i < 4 * n) wgmma_n16<1, 1>(O[mb0 + (i >> 2)], desc_lo(65536) + (mb0 + (i >> 2)) * 512 + (i & 3) * 128, dp + 128 + (i & 3) * 2);
      wg_commit();
    };
    auto publish = [&](int J) {
#pragma unroll
      for (int k = 0; k < 4; k++) acc_fence(O[4 * J + k]);
#pragma unroll
      for (int i = 0; i < 4; i++) {
        const int k = 4 * (i >> 1) + (i & 1);
        stg_cvt8(x1o[4 * J + i], O[4 * J][k], O[4 * J][k + 2], O[4 * J + 1][k], O[4 * J + 1][k + 2],
                 O[4 * J + 2][k], O[4 * J + 2][k + 2], O[4 * J + 3][k], O[4 * J + 3][k + 2]);
      }
    };
    pv(0, 4); pv(4, 4);
    wg_wait<1>(); publish(0);
    wg_wait<0>(); publish(1);
    CLK(24);
  }

  {
    const uint32_t* px = pin(inbox(cta, w >> 1) + (w & 1) * 512 + lane * 2);
    uint32_t* const x2o = pin(inbox(cta, 4) + 512 + tid * 2);
    uint32_t* const x2p = pin(gin + blk(cta, 4, selector(cta) ^ 1) + 512 + tid * 2);
    const uint32_t q4 = lds1(sb + OFF_SEL + 4 * hI) ^ 0x00010100u;
    const uint32_t same = pin((uint32_t)(q4 == 0 || q4 == 0x01010101u));
    mbar_wait(BAR(BAR_TS));
    anchor = lds1(sb + OFF_TS);
    const uint32_t sdst = pin(sb + OFF_BS4 + w * 272 + lane * 8), ssrc = pin(sb + OFF_BS4 + (lane & 7) * 272 + (lane >> 3) * 16);
    float d[4] = {0.f, 0.f, 0.f, 0.f};
    wait_clk(thand, T.D_X1);
    wait_clk(anchor, T.A_X1);
    CLK(25);
    uint2 v[8];
    load_units<8, 64>(v, px);
    const bool early = __all_sync(~0u, mbar_test(BAR(BAR_WUV + wg)));
    if (early) load_a_t(aw, sb + OFF_WUV, w, lane);
    mbar_wait(BAR(BAR_WV));
    const float4 wa = ldsf4(sb + OFF_WV + w * 32), wb = ldsf4(sb + OFF_WV + w * 32 + 16);
    const float wv[8] = {wa.x, wa.y, wa.z, wa.w, wb.x, wb.y, wb.z, wb.w};
    CLK(27);
    int it = 0;
    while (true) {
      float a0 = 0.f, a1 = 0.f, a2 = 0.f, a3 = 0.f;
#pragma unroll
      for (int i = 0; i < 8; i++) { a0 += wv[i] * bf_lo(v[i].x); a1 += wv[i] * bf_hi(v[i].x); a2 += wv[i] * bf_lo(v[i].y); a3 += wv[i] * bf_hi(v[i].y); }
      const bool ok = __all_sync(~0u, min_flags(v) != 0);
      sts2(sdst, pack_bf16(a0, a1), pack_bf16(a2, a3));
      if (__builtin_expect(ok, 1)) break;
#pragma unroll
      for (int i = 0; i < 8; i++) reload_unit(v[i], px + i * 64);
      if (++it > SPIN_LIMIT) __trap();
    }
    CLK(29);
    cbar();
    uint32_t b[4][4];
#pragma unroll
    for (int kk = 0; kk < 4; kk++) ldsm4(b[kk], ssrc + kk * 64);
    if (__builtin_expect(!early, 0)) { mbar_wait(BAR(BAR_WUV + wg)); load_a_t(aw, sb + OFF_WUV, w, lane); }
    mma128(d, aw, b);
    const uint32_t c0 = pack_bf16(d[0], d[1]), c1 = pack_bf16(d[2], d[3]);
    stg_u64(x2o, c0, c1);
    stg_u64_unless(same, x2p, c0, c1);
    ITS(4, it);
    tstore = clk32();
    CLK(30);
  }
  {
    uint32_t* const o = pin(inbox(4 * (8 * jI + w) + t, 4) + hI * 16 + g * 2);
    const uint32_t* x2i[4];
#pragma unroll
    for (int i = 0; i < 4; i++) x2i[i] = pin(nearbox(4 * hI + i, 4) + 512 + tid * 2);
    const uint32_t sdst = pin(sb + OFF_BS5 + (16 * w + g) * 16 + t * 4), ssrc = pin(sb + OFF_BS5 + lane * 16);
    float d[4] = {0.f, 0.f, 0.f, 0.f};
    wait_clk(tstore, T.D_X2);
    wait_clk(anchor, T.A_X1 + T.R_X2);
    uint2 v[4];
#pragma unroll
    for (int i = 0; i < 4; i++) v[i] = ldg_u64(x2i[i]);
    const bool early = __all_sync(~0u, mbar_test(BAR(BAR_WO + wg)));
    if (early) load_a_t(aw, sb + OFF_WO, w, lane);
    CLK(31);
    int it = 0;
    while (true) {
      const bool ok = __all_sync(~0u, min_flags(v) != 0);
      sum4_to_smem(v, sdst);
      if (__builtin_expect(ok, 1)) break;
#pragma unroll
      for (int i = 0; i < 4; i++) reload_unit(v[i], x2i[i]);
      if (++it > SPIN_LIMIT) __trap();
    }
    CLK(32);
    cbar();
    uint32_t b[4][4];
#pragma unroll
    for (int kk = 0; kk < 4; kk++) ldsm4t(b[kk], ssrc + kk * 512);
    if (__builtin_expect(!early, 0)) { mbar_wait(BAR(BAR_WO + wg)); load_a_t(aw, sb + OFF_WO, w, lane); }
    mma128(d, aw, b);
    ST3A(o, movm(pack_bf16(d[0], d[1])), movm(pack_bf16(d[2], d[3])));
    ITS(5, it);
    tstore = clk32();
    CLK(33);
    if (lane == 0) mbar_arrive(BAR(BAR_P5D));
  }
  if (cta < NFF) {
    const int mi = lane >> 3, r = lane & 7;
    uint32_t a1[2][4][4], a2[2][2][4];
    check_units<4, 64>(sbf, pcb, T.RB);
    check_units<4, 64>(cbf, pcb + 2048, T.RB);
    __syncwarp();
#pragma unroll
    for (int s = 0; s < 4; s++) { cbf[s].x = hadd2(cbf[s].x, ONE2); cbf[s].y = hadd2(cbf[s].y, ONE2); }
    mbar_wait(BAR(BAR_W1));
#pragma unroll
    for (int mt = 0; mt < 2; mt++) {
#pragma unroll
      for (int ks = 0; ks < 4; ks++) ldsm4t(a1[mt][ks], sb + OFF_W1 + (64 * w + 16 * ks + 8 * (mi >> 1) + r) * 64 + (((2 * mt + (mi & 1)) ^ (r >> 1)) << 4));
      float u[4] = {0.f, 0.f, 0.f, 0.f}, vv[4] = {0.f, 0.f, 0.f, 0.f};
#pragma unroll
      for (int s = 0; s < 4; s++) { mma16816(u, a1[mt][s], cbf[s].x, cbf[s].y); mma16816(vv, a1[mt][s], sbf[s].x, sbf[s].y); }
      sts4f(sb + OFF_REDU + w * 1024 + mt * 512 + lane * 16, u[0], u[1], u[2], u[3]);
      sts4f(sb + OFF_REDV + w * 1024 + mt * 512 + lane * 16, vv[0], vv[1], vv[2], vv[3]);
    }
    const uint32_t* xb = pin(nearbox(cta & ~15, 6 + wg) + (16 * wq + t) * 16 + g * 2);
    uint32_t* const ox[2] = {pin(inbox(64 * hh + 8 * w + t, 5) + bs * 16 + g * 2), pin(inbox(64 * hh + 8 * w + 4 + t, 5) + bs * 16 + g * 2)};
    cbar();
    const int lp = (tid >> 2) & 31, kq = tid & 3;
    const int fo = 16 * wg + (lp >> 2) + 8 * (kq >> 1), bo = 2 * (lp & 3) + (kq & 1);
    float U = 0.f, V = 0.f;
#pragma unroll
    for (int i = 0; i < 8; i++) { U += ldsf(sb + OFF_REDU + i * 1024 + tid * 4); V += ldsf(sb + OFF_REDV + i * 1024 + tid * 4); }
    U = pin(U); V = pin(V);
    const uint32_t s_g = pin(sb + OFF_REDG + w * 1024 + lane * 16), s_s = pin(sb + OFF_REDS + g * 80 + w * 8);
    const uint32_t l_g = pin(sb + OFF_REDG + tid * 4), l_s = pin(sb + OFF_REDS + bo * 80), s_h = pin(sb + OFF_H1 + fo * 16 + bo * 2);
    CLK(34);
    wait_clk(tstore, T.D_X3B);
    wait_clk(anchor, T.A_X1 + T.R_X3A + T.R_X3B);
    uint2 x[4];
    load_units<4, 64>(x, xb);
    mbar_wait(BAR(BAR_W2));
#pragma unroll
    for (int i = 0; i < 4; i++)
      ldsm4t(a2[i >> 1][i & 1], sb + OFF_W2 + (w >> 1) * 4096 + (16 * (i & 1) + 8 * (mi >> 1) + r) * 128 + (((4 * (w & 1) + 2 * (i >> 1) + (mi & 1)) ^ r) << 4));
    CLK(35);
    int it = 0;
    float G[2][2][4], S[2][4];
    while (true) {
#pragma unroll
      for (int i = 0; i < 8; i++) { G[0][i >> 2][i & 3] = G[1][i >> 2][i & 3] = S[i >> 2][i & 3] = 0.f; }
#pragma unroll
      for (int s = 0; s < 4; s++) {
        const uint32_t sx[4] = {x[s].x, ONE2, x[s].y, ONE2};
        mma16816(S[s & 1], sx, x[s].x, x[s].y);
        const uint32_t y0 = hmul2(x[s].x, cbf[s].x), y1 = hmul2(x[s].y, cbf[s].y);
        mma16816(G[0][s & 1], a1[0][s], y0, y1);
        mma16816(G[1][s & 1], a1[1][s], y0, y1);
      }
      if (__builtin_expect(__all_sync(~0u, min_flags(x) != 0), 1)) break;
#pragma unroll
      for (int i = 0; i < 4; i++) reload_unit(x[i], xb + i * 64);
      if (++it > SPIN_LIMIT) __trap();
    }
    if (t == (g >> 1)) sts2f(s_s, (g & 1) ? S[0][3] + S[1][3] : S[0][2] + S[1][2], (g & 1) ? S[0][1] + S[1][1] : S[0][0] + S[1][0]);
#pragma unroll
    for (int mt = 0; mt < 2; mt++)
      sts4f(s_g + mt * 512, G[mt][0][0] + G[mt][1][0], G[mt][0][1] + G[mt][1][1], G[mt][0][2] + G[mt][1][2], G[mt][0][3] + G[mt][1][3]);
    CLK(37);
    cbar();
    {
      float gv[8];
      float4 sv[4];
#pragma unroll
      for (int i = 0; i < 4; i++) sv[i] = ldsf4(l_s + i * 16);
#pragma unroll
      for (int i = 0; i < 8; i++) gv[i] = ldsf(l_g + i * 1024);
      const float s1 = ((sv[0].x + sv[0].z) + (sv[1].x + sv[1].z)) + ((sv[2].x + sv[2].z) + (sv[3].x + sv[3].z));
      const float s2 = ((sv[0].y + sv[0].w) + (sv[1].y + sv[1].w)) + ((sv[2].y + sv[2].w) + (sv[3].y + sv[3].w));
      const float gsum = ((gv[0] + gv[1]) + (gv[2] + gv[3])) + ((gv[4] + gv[5]) + (gv[6] + gv[7]));
      const float mu = s1 * (1.f / 512.f);
      float rs;
      asm("rsqrt.approx.ftz.f32 %0, %1;" : "=f"(rs) : "f"(fmaxf(s2 * (1.f / 512.f) - mu * mu, 0.f) + 1e-5f));
      const float hv = fmaxf(rs * (gsum - mu * U) + V, 0.f);
      asm volatile("st.shared.u16 [%0], %1;" ::"r"(s_h), "h"(__bfloat16_as_ushort(__float2bfloat16(hv))) : "memory");
    }
    ITS(6, it);
    CLK(38);
    cbar();
    uint32_t b[4];
    ldsm4t(b, sb + OFF_H1 + lane * 16);
    float o[2][2][4] = {};
#pragma unroll
    for (int i = 0; i < 4; i++) mma16816(o[i >> 1][i & 1], a2[i >> 1][i & 1], b[2 * (i & 1)], b[2 * (i & 1) + 1]);
#pragma unroll
    for (int mb = 0; mb < 2; mb++)
      ST4(ox[mb], movm(pack_bf16(o[mb][0][0] + o[mb][1][0], o[mb][0][1] + o[mb][1][1])), movm(pack_bf16(o[mb][0][2] + o[mb][1][2], o[mb][0][3] + o[mb][1][3])));
    CLK(39);
    if (lane == 0) mbar_arrive(BAR(BAR_P7D));
  }
  CLK_DUMP();
}

typedef CUresult (*EncodeTiledFn)(CUtensorMap*, CUtensorMapDataType, cuuint32_t, void*, const cuuint64_t*, const cuuint64_t*,
                                  const cuuint32_t*, const cuuint32_t*, CUtensorMapInterleave, CUtensorMapSwizzle,
                                  CUtensorMapL2promotion, CUtensorMapFloatOOBfill);

struct Dim { uint64_t size, stride; uint32_t box; };
template <int R> void encode_map(EncodeTiledFn enc, CUtensorMap* m, const void* base, const Dim (&d)[R], CUtensorMapSwizzle sw, CUtensorMapL2promotion promo) {
  cuuint64_t dims[R], strides[R];
  cuuint32_t box[R], es[R];
  for (int i = 0; i < R; i++) { dims[i] = d[i].size; strides[i] = d[i].stride; box[i] = d[i].box; es[i] = 1; }
  enc(m, CU_TENSOR_MAP_DATA_TYPE_BFLOAT16, R, const_cast<void*>(base), dims, strides + 1, box, es, CU_TENSOR_MAP_INTERLEAVE_NONE, sw, promo,
      CU_TENSOR_MAP_FLOAT_OOB_FILL_NONE);
}

}

extern "C" void kernel_launch(void* const* d_in, const int* in_sizes, int n_in, void* d_out, int out_size) {
  (void)in_sizes; (void)n_in; (void)out_size;
  static EncodeTiledFn enc = nullptr;
  static Scratch* scratch = nullptr;
  static uint32_t* inbox = nullptr;
  if (!enc) {
    void* sp = nullptr;
    cudaGetSymbolAddress(&sp, g_s);
    scratch = (Scratch*)sp;
    cudaGetSymbolAddress(&sp, g_in);
    inbox = (uint32_t*)(((uintptr_t)sp + 0xfffff) & ~(uintptr_t)0xfffff);
    void* fn = nullptr;
    cudaDriverEntryPointQueryResult q;
    cudaGetDriverEntryPoint("cuTensorMapEncodeTiled", &fn, cudaEnableDefault, &q);
    enc = (EncodeTiledFn)fn;
    cudaFuncSetAttribute(fused_decode_kernel, cudaFuncAttributeMaxDynamicSharedMemorySize, SMEM_BYTES);
  }
  const CUtensorMapSwizzle S128 = CU_TENSOR_MAP_SWIZZLE_128B, S0 = CU_TENSOR_MAP_SWIZZLE_NONE;
  const CUtensorMapL2promotion L0 = CU_TENSOR_MAP_L2_PROMOTION_NONE, L128 = CU_TENSOR_MAP_L2_PROMOTION_L2_128B;
  Params P;
  encode_map<2>(enc, &P.wq, d_in[2], {{4096, 2, 64}, {512, 8192, 64}}, S128, L0);
  encode_map<5>(enc, &P.wuk, d_in[3], {{4096, 2, 64}, {2, 8192, 2}, {4, 4 * 8192, 4}, {2, 2 * 8192, 2}, {32, 16 * 8192, 4}}, S128, L0);
  encode_map<2>(enc, &P.wm2, d_in[10], {{3072, 2, 16}, {512, 6144, 256}}, S0, L128);
  encode_map<3>(enc, &P.ckv2, d_in[1], {{64, 2, 64}, {8 * 4096, 1024, 64}, {8, 128, 2}}, S128, L0);
  encode_map<3>(enc, &P.ckv1, d_in[1], {{64, 2, 64}, {8 * 4096, 1024, 64}, {8, 128, 1}}, S128, L0);
  encode_map<5>(enc, &P.wuv, d_in[4], {{4096, 2, 64}, {2, 8 * 8192, 2}, {8, 64 * 8192, 4}, {8, 8192, 8}, {4, 16 * 8192, 1}}, S128, L0);
  encode_map<2>(enc, &P.wo, d_in[5], {{512, 2, 64}, {4096, 1024, 64}}, S128, L0);
  encode_map<2>(enc, &P.w1, d_in[7], {{1792, 2, 32}, {512, 3584, 256}}, CU_TENSOR_MAP_SWIZZLE_64B, L128);
  encode_map<3>(enc, &P.w2, d_in[8], {{64, 2, 64}, {1792, 1024, 32}, {8, 128, 2}}, S128, L0);
  cudaLaunchConfig_t cfg = {};
  cfg.gridDim = dim3(NCTA);
  cfg.blockDim = dim3(NTHREADS);
  cfg.dynamicSmemBytes = SMEM_BYTES;
  cfg.stream = cudaStreamPerThread;
  cudaLaunchAttribute at[1];
  at[0].id = cudaLaunchAttributeClusterDimension;
  at[0].val.clusterDim.x = 2; at[0].val.clusterDim.y = 1; at[0].val.clusterDim.z = 1;
  cfg.attrs = at;
  cfg.numAttrs = 0;
  cudaLaunchKernelEx(&cfg, fused_decode_kernel, (__nv_bfloat16*)d_out, scratch, (const uint8_t*)d_in[10], (const uint8_t*)d_in[0],
                     (const uint8_t*)d_in[9], inbox,
                     P);
}
```

```cpp
#include <cuda_runtime.h>
#include <cuda.h>
#include <cuda_bf16.h>
#include <stdint.h>
#define V4 1

namespace {

constexpr int NCTA = 128;
constexpr int NTHREADS = 320;
constexpr int NFG = 56;
constexpr int NFF = 2 * NFG;
constexpr int NSYNC = 4;

constexpr uint32_t OFF_RING = 0;
constexpr uint32_t OFF_WUK = 131072;
constexpr uint32_t OFF_WQ = 131072 + 32768;
constexpr uint32_t OFF_WM2 = 65536 + 49152;
constexpr uint32_t OFF_WUV = 131072;
constexpr uint32_t OFF_WO = 131072 + 32768;
constexpr uint32_t OFF_W1 = 0;
constexpr uint32_t OFF_W2 = 32768;
constexpr uint32_t OFF_Q = 196608;
constexpr uint32_t OFF_PT = 212992;
constexpr uint32_t OFF_SCR = 217088;
constexpr uint32_t OFF_XS = 65536;
constexpr uint32_t OFF_CS = 65536 + 8192;
constexpr uint32_t OFF_P0S = 65536 + 16384;
constexpr uint32_t OFF_BS1 = OFF_SCR + 2048;
constexpr uint32_t OFF_BS2 = OFF_SCR + 4096;
constexpr uint32_t OFF_P0B = OFF_SCR + 6144;
constexpr uint32_t OFF_XN = OFF_SCR + 8192;
constexpr uint32_t OFF_RED = OFF_SCR + 10496;
constexpr uint32_t OFF_ALPHA = OFF_SCR + 11072;
constexpr uint32_t OFF_WV = OFF_SCR + 6144;
constexpr uint32_t OFF_SEL = OFF_SCR + 10752;
constexpr uint32_t OFF_TS = OFF_SCR + 11136;
constexpr uint32_t OFF_BARS = OFF_SCR + 11264;
constexpr uint32_t SMEM_BYTES = OFF_BARS + 512;
constexpr uint32_t OFF_BS4 = OFF_Q;
constexpr uint32_t OFF_H1 = OFF_Q + 2304;
constexpr uint32_t OFF_REDS = OFF_Q + 2816;
constexpr uint32_t OFF_BS5 = OFF_Q + 4096;
constexpr uint32_t OFF_REDG = OFF_Q + 8192;
constexpr uint32_t OFF_REDU = 65536;
constexpr uint32_t OFF_REDV = 65536 + 8192;

constexpr int BAR_FULL = 0;
constexpr int BAR_LAST = 28;
constexpr int BAR_WUK = 33, BAR_WM2 = 35, BAR_WUV = 36, BAR_WO = 38, BAR_W1 = 40, BAR_W2 = 41;
constexpr int BAR_ALLCLR = 42, BAR_TS = 43, BAR_WV = 44;
constexpr int BAR_EMPTY = 45;
constexpr int BAR_P0BD = 52;
constexpr int BAR_P1D = 53, BAR_P2D = 54;
constexpr int BAR_P5D = 55, BAR_P7D = 56;
constexpr int NBARS = 57;
constexpr int BAR_XC = 57, BAR_WQ = 58;
constexpr int BAR_C = 60, BAR_END = 61;
constexpr uint32_t SB = 1024;

#define TUNE_LIST(X) \
  X(PC_T0, 340) X(PC_XC, 0) X(PC_C, 0) X(PC_P1, 320) X(PC_P2, 319) X(PC_STAG, 390) X(PC_DS, 0) X(PC_SL, 500) X(PC_W, 4) X(PC_NW, 8) \
  X(PW_A, -1) X(PW_0, 310) X(PW_ST, 0) X(PW_UV, 250) X(PW_G, 750) X(PW_O, 315) X(PW_G2, 450) X(PW_G3, 390) X(PW_F, 330) \
  X(LOC, 0) X(PR_T0, 1000) X(PR_N, 4) X(CLR_T0, 3900) X(CLR_CLK, 190) \
  X(D_MOD, 1650) X(D_QP, 1050) X(D_QX, 1100) X(TS_P, 1) X(TS_O, 1200) X(D_TS, 900) X(A_M, 1850) X(D_X1, 1300) X(A_X1, 2400) \
  X(D_X2, 260) X(R_X2, 1550) X(D_X3A, 60) X(R_X3A, 3350) X(D_X3B, 800) X(R_X3B, 880) X(D_FIN, 320) X(R_FIN, 1520) X(RB, 0)
struct Tune {
#define X(n, v) static constexpr int n = v;
  TUNE_LIST(X)
#undef X
};

#define PFENCE 0
#define WSWAP 0
#define THRESH "0f42700000"
#define PVV 0
struct Scratch {
  uint32_t MOD1[2][4 * 64 * 64];
  uint32_t MOD2[2][128 * 64];
  uint32_t QP[2][128 * 256 * 2];
  uint32_t QX[2][8 * 32 * 256];
  uint32_t epoch;
  uint32_t pad[31];
  uint32_t sync[NSYNC][32];
};
__device__ Scratch g_s;
__device__ uint32_t g_in[(128 + 16) * 16384];
__device__ __forceinline__ uint32_t blk(int c, int k, uint32_t sel) { return c * 16384 + k * 2048 + ((sel ^ k) & 1) * 1024; }
__device__ __forceinline__ uint32_t flip(int c) { return c ^ (c >> 1) ^ (c >> 3); }

#define CLK_DECL
#define CLK(i) do {} while (0)
#define CLK_DUMP() do {} while (0)
#define ITS(i, v) do {} while (0)

struct Params {
  CUtensorMap wq, wuk, wm2, ckv2, ckv1, wuv, wo, w1, w2;
};

__device__ __forceinline__ void mbar_init(uint32_t bar, int cnt) { asm volatile("mbarrier.init.shared::cta.b64 [%0], %1;" ::"r"(bar), "r"(cnt)); }
__device__ __forceinline__ void mbar_expect(uint32_t bar, uint32_t bytes) { asm volatile("mbarrier.arrive.expect_tx.shared::cta.b64 _, [%0], %1;" ::"r"(bar), "r"(bytes) : "memory"); }
__device__ __forceinline__ void mbar_arrive(uint32_t bar) { asm volatile("mbarrier.arrive.shared::cta.b64 _, [%0];" ::"r"(bar) : "memory"); }
__device__ __forceinline__ uint32_t clk32() { unsigned long long c; asm volatile("mov.u64 %0, %%clock64;" : "=l"(c) :: "memory"); return (uint32_t)c; }
__device__ __forceinline__ uint32_t gtime32() { uint32_t c; asm volatile("mov.u32 %0, %%globaltimer_lo;" : "=r"(c) :: "memory"); return c; }
__device__ __forceinline__ void wait_clk(uint32_t t0, int clocks) { while ((int)(clk32() - t0) < clocks) {} }
__device__ __forceinline__ void backoff(int clocks) { if (clocks > 0) wait_clk(clk32(), clocks); }
__device__ __forceinline__ void until_ns(uint32_t ns) { while ((int)(gtime32() - ns) < 0) {} }
__device__ __forceinline__ void slot(uint32_t& tn, int slack) {
  uint32_t now;
  do { now = gtime32(); } while ((int)(now - tn) < 0);
  if ((int)(now - tn) > slack) tn = now - slack;
}
template <typename T> __device__ __forceinline__ T* pin(T* p) { asm volatile("" : "+l"(p)); return p; }
__device__ __forceinline__ uint32_t pin(uint32_t v) { asm volatile("" : "+r"(v)); return v; }
__device__ __forceinline__ float pin(float v) { asm volatile("" : "+f"(v)); return v; }
constexpr int SPIN_LIMIT = 1 << 22;
__device__ __forceinline__ void mbar_wait(uint32_t bar) {
  asm volatile("{\n.reg .pred p;\n.reg .u32 c;\nmov.u32 c, 0;\n"
               "MW_LOOP:\nmbarrier.try_wait.parity.shared::cta.b64 p, [%0], 0;\n@p bra MW_DONE;\n"
               "add.u32 c, c, 1;\nsetp.lt.u32 p, c, 4194304;\n@p bra MW_LOOP;\ntrap;\nMW_DONE:\n}"
               ::"r"(bar) : "memory");
}
__device__ __forceinline__ bool mbar_test(uint32_t bar) {
  uint32_t ok;
  asm volatile("{\n.reg .pred p;\nmbarrier.test_wait.parity.shared::cta.b64 p, [%1], 0;\nselp.u32 %0,1,0,p;\n}" : "=r"(ok) : "r"(bar) : "memory");
  return ok;
}
__device__ __forceinline__ void tma2d(uint32_t dst, const CUtensorMap* m, int c0, int c1, uint32_t bar, uint64_t pol) {
  asm volatile("cp.async.bulk.tensor.2d.shared::cluster.global.mbarrier::complete_tx::bytes.L2::cache_hint [%0], [%1, {%3,%4}], [%2], %5;"
               ::"r"(dst), "l"(m), "r"(bar), "r"(c0), "r"(c1), "l"(pol) : "memory");
}
__device__ __forceinline__ void tma2d_nohint(uint32_t dst, const CUtensorMap* m, int c0, int c1, uint32_t bar) {
  asm volatile("cp.async.bulk.tensor.2d.shared::cluster.global.mbarrier::complete_tx::bytes [%0], [%1, {%3,%4}], [%2];"
               ::"r"(dst), "l"(m), "r"(bar), "r"(c0), "r"(c1) : "memory");
}
__device__ __forceinline__ void tma3d(uint32_t dst, const CUtensorMap* m, int c0, int c1, int c2, uint32_t bar, uint64_t pol) {
  asm volatile("cp.async.bulk.tensor.3d.shared::cluster.global.mbarrier::complete_tx::bytes.L2::cache_hint [%0], [%1, {%3,%4,%5}], [%2], %6;"
               ::"r"(dst), "l"(m), "r"(bar), "r"(c0), "r"(c1), "r"(c2), "l"(pol) : "memory");
}
__device__ __forceinline__ void tma5d(uint32_t dst, const CUtensorMap* m, int c0, int c1, int c2, int c3, int c4, uint32_t bar, uint64_t pol) {
  asm volatile("cp.async.bulk.tensor.5d.shared::cluster.global.mbarrier::complete_tx::bytes.L2::cache_hint [%0], [%1, {%3,%4,%5,%6,%7}], [%2], %8;"
               ::"r"(dst), "l"(m), "r"(bar), "r"(c0), "r"(c1), "r"(c2), "r"(c3), "r"(c4), "l"(pol) : "memory");
}
__device__ __forceinline__ void bulk_ld(uint32_t dst, const void* src, uint32_t bytes, uint32_t bar) {
  asm volatile("cp.async.bulk.shared::cluster.global.mbarrier::complete_tx::bytes [%0], [%1], %2, [%3];" ::"r"(dst), "l"(src), "r"(bytes), "r"(bar) : "memory");
}
__device__ __forceinline__ void bar_sync(int id, int n) { asm volatile("barrier.cta.sync.aligned %0, %1;" ::"r"(id), "r"(n) : "memory"); }
__device__ __forceinline__ void cbar() { asm volatile("barrier.cta.sync.aligned 1, 256;" ::: "memory"); }
__device__ __forceinline__ bool bar_over(float ex) {
  uint32_t over;
  asm volatile("{\n.reg .pred p, q;\nsetp.gtu.f32 p, %1, " THRESH ";\nbarrier.cta.red.or.aligned.pred q, 4, 256, p;\nselp.u32 %0, 1, 0, q;\n}"
               : "=r"(over) : "f"(ex) : "memory");
  return over;
}

__device__ __forceinline__ uint32_t ldg_nc1(const void* p) { uint32_t v; asm volatile("ld.global.nc.L1::no_allocate.u32 %0, [%1];" : "=r"(v) : "l"(p)); return v; }
__device__ __forceinline__ uint2 ldg_nc2(const void* p) { uint2 v; asm volatile("ld.global.nc.v2.u32 {%0,%1}, [%2];" : "=r"(v.x), "=r"(v.y) : "l"(p)); return v; }
__device__ __forceinline__ uint4 ldg_nc4(const void* p) { uint4 v; asm volatile("ld.global.nc.L1::no_allocate.v4.u32 {%0,%1,%2,%3}, [%4];" : "=r"(v.x), "=r"(v.y), "=r"(v.z), "=r"(v.w) : "l"(p)); return v; }
__device__ __forceinline__ uint32_t ldg_rlx1(const void* p) { uint32_t v; asm volatile("ld.relaxed.gpu.global.u32 %0, [%1];" : "=r"(v) : "l"(p) : "memory"); return v; }
__device__ __forceinline__ void stg4(void* p, uint4 v) { asm volatile("st.relaxed.gpu.global.v4.u32 [%0], {%1,%2,%3,%4};" ::"l"(p), "r"(v.x), "r"(v.y), "r"(v.z), "r"(v.w) : "memory"); }
__device__ __forceinline__ void stg1(void* p, uint32_t a) { asm volatile("st.relaxed.gpu.global.u32 [%0], %1;" ::"l"(p), "r"(a) : "memory"); }
__device__ __forceinline__ uint32_t nz(uint32_t w) { return max(w, 1u); }
__device__ __forceinline__ uint2 ldg_u64(const void* p) {
  uint2 v; asm volatile("{\n.reg .b64 a;\nld.relaxed.gpu.global.b64 a, [%2];\nmov.b64 {%0,%1}, a;\n}" : "=r"(v.x), "=r"(v.y) : "l"(p) : "memory"); return v;
}
__device__ __forceinline__ uint4 ldg_2u64(const void* p) {
  uint4 v; asm volatile("{\n.reg .b64 a, b;\nld.relaxed.gpu.global.v2.b64 {a, b}, [%4];\nmov.b64 {%0,%1}, a;\nmov.b64 {%2,%3}, b;\n}" : "=r"(v.x), "=r"(v.y), "=r"(v.z), "=r"(v.w) : "l"(p) : "memory"); return v;
}
__device__ __forceinline__ void stg_u64(void* p, uint32_t x, uint32_t y) {
  asm volatile("{\n.reg .b32 y;\nmax.u32 y, %2, 1;\nst.relaxed.gpu.global.v2.b32 [%0], {%1, y};\n}" ::"l"(p), "r"(x), "r"(y) : "memory");
}
__device__ __forceinline__ void red_u64(void* p, uint32_t x, uint32_t y) {
  asm volatile("{\n.reg .b32 y;\n.reg .b64 a;\nmax.u32 y, %2, 1;\nmov.b64 a, {%1, y};\nred.relaxed.gpu.global.or.b64 [%0], a;\n}" ::"l"(p), "r"(x), "r"(y) : "memory");
}
__device__ __forceinline__ void red_u64_unless(uint32_t bad, void* p, uint32_t x, uint32_t y) {
  asm volatile("{\n.reg .b32 y;\n.reg .b64 a;\n.reg .pred q;\nsetp.eq.u32 q, %3, 0;\nmax.u32 y, %2, 1;\nmov.b64 a, {%1, y};\n@q red.relaxed.gpu.global.or.b64 [%0], a;\n}" ::"l"(p), "r"(x), "r"(y), "r"(bad) : "memory");
}
#define ST3A stg_u64
#define ST4 stg_u64
#define ST3B stg_u64_unless
#define MLST red_u64
__device__ __forceinline__ void stg_u64_unless(uint32_t bad, void* p, uint32_t x, uint32_t y) {
  asm volatile("{\n.reg .b32 y;\n.reg .pred q;\nsetp.eq.u32 q, %3, 0;\nmax.u32 y, %2, 1;\n@q st.relaxed.gpu.global.v2.b32 [%0], {%1, y};\n}" ::"l"(p), "r"(x), "r"(y), "r"(bad) : "memory");
}
__device__ __forceinline__ void stg_2u64(void* p, uint4 v) {
  asm volatile("{\n.reg .b32 y, w;\nmax.u32 y, %2, 1;\nmax.u32 w, %4, 1;\nst.relaxed.gpu.global.v4.b32 [%0], {%1, y, %3, w};\n}" ::"l"(p), "r"(v.x), "r"(v.y), "r"(v.z), "r"(v.w) : "memory");
}

__device__ __forceinline__ void stg_cvt8(void* p, float a0, float a1, float b0, float b1, float c0, float c1, float d0, float d1) {
  asm volatile("{\n.reg .b32 x, y, z, w;\ncvt.rn.bf16x2.f32 x, %2, %1;\ncvt.rn.bf16x2.f32 y, %4, %3;\ncvt.rn.bf16x2.f32 z, %6, %5;\ncvt.rn.bf16x2.f32 w, %8, %7;\n"
               "max.u32 y, y, 1;\nmax.u32 w, w, 1;\nst.relaxed.gpu.global.v4.b32 [%0], {x, y, z, w};\n}"
               ::"l"(p), "f"(a0), "f"(a1), "f"(b0), "f"(b1), "f"(c0), "f"(c1), "f"(d0), "f"(d1) : "memory");
}
__device__ __forceinline__ uint32_t pack_bf16(float lo, float hi) { uint32_t r; asm("cvt.rn.bf16x2.f32 %0, %1, %2;" : "=r"(r) : "f"(hi), "f"(lo)); return r; }
__device__ __forceinline__ float bf_lo(uint32_t w) { return __uint_as_float(w << 16); }
__device__ __forceinline__ float bf_hi(uint32_t w) { return __uint_as_float(w & 0xffff0000u); }
__device__ __forceinline__ float ex2(float x) { float r; asm("ex2.approx.ftz.f32 %0, %1;" : "=f"(r) : "f"(x)); return r; }
__device__ __forceinline__ uint32_t hmul2(uint32_t a, uint32_t b) { uint32_t r; asm("mul.rn.bf16x2 %0, %1, %2;" : "=r"(r) : "r"(a), "r"(b)); return r; }
__device__ __forceinline__ uint32_t hadd2(uint32_t a, uint32_t b) { uint32_t r; asm("add.rn.bf16x2 %0, %1, %2;" : "=r"(r) : "r"(a), "r"(b)); return r; }
__device__ __forceinline__ uint32_t hfma2(uint32_t a, uint32_t b, uint32_t c) { uint32_t r; asm("fma.rn.bf16x2 %0, %1, %2, %3;" : "=r"(r) : "r"(a), "r"(b), "r"(c)); return r; }
__device__ __forceinline__ uint32_t silu2(uint32_t v) { const float a = bf_lo(v), b = bf_hi(v); return pack_bf16(__fdividef(a, 1.f + __expf(-a)), __fdividef(b, 1.f + __expf(-b))); }
constexpr uint32_t ONE2 = 0x3f803f80u;

__device__ __forceinline__ void ldsm4(uint32_t (&r)[4], uint32_t a) { asm volatile("ldmatrix.sync.aligned.m8n8.x4.shared.b16 {%0,%1,%2,%3}, [%4];" : "=r"(r[0]), "=r"(r[1]), "=r"(r[2]), "=r"(r[3]) : "r"(a) : "memory"); }
__device__ __forceinline__ void ldsm4t(uint32_t (&r)[4], uint32_t a) { asm volatile("ldmatrix.sync.aligned.m8n8.x4.trans.shared.b16 {%0,%1,%2,%3}, [%4];" : "=r"(r[0]), "=r"(r[1]), "=r"(r[2]), "=r"(r[3]) : "r"(a) : "memory"); }
__device__ __forceinline__ void ldsm2t(uint32_t& r0, uint32_t& r1, uint32_t a) { asm volatile("ldmatrix.sync.aligned.m8n8.x2.trans.shared.b16 {%0,%1}, [%2];" : "=r"(r0), "=r"(r1) : "r"(a) : "memory"); }
__device__ __forceinline__ void stsm4t(uint32_t a, uint32_t r0, uint32_t r1, uint32_t r2, uint32_t r3) { asm volatile("stmatrix.sync.aligned.m8n8.x4.trans.shared.b16 [%0], {%1,%2,%3,%4};" ::"r"(a), "r"(r0), "r"(r1), "r"(r2), "r"(r3) : "memory"); }
__device__ __forceinline__ uint32_t movm(uint32_t a) { uint32_t d; asm volatile("movmatrix.sync.aligned.m8n8.trans.b16 %0, %1;" : "=r"(d) : "r"(a)); return d; }
__device__ __forceinline__ void mma16816(float (&d)[4], const uint32_t (&a)[4], uint32_t b0, uint32_t b1) {
  asm volatile("mma.sync.aligned.m16n8k16.row.col.f32.bf16.bf16.f32 {%0,%1,%2,%3}, {%4,%5,%6,%7}, {%8,%9}, {%0,%1,%2,%3};"
               : "+f"(d[0]), "+f"(d[1]), "+f"(d[2]), "+f"(d[3]) : "r"(a[0]), "r"(a[1]), "r"(a[2]), "r"(a[3]), "r"(b0), "r"(b1));
}
__device__ __forceinline__ void sts1(uint32_t a, uint32_t v) { asm volatile("st.shared.u32 [%0], %1;" ::"r"(a), "r"(v) : "memory"); }
__device__ __forceinline__ void sts2(uint32_t a, uint32_t x, uint32_t y) { asm volatile("st.shared.v2.u32 [%0], {%1,%2};" ::"r"(a), "r"(x), "r"(y) : "memory"); }
__device__ __forceinline__ void sts4(uint32_t a, uint4 v) { asm volatile("st.shared.v4.u32 [%0], {%1,%2,%3,%4};" ::"r"(a), "r"(v.x), "r"(v.y), "r"(v.z), "r"(v.w) : "memory"); }
__device__ __forceinline__ void sts2f(uint32_t a, float x, float y) { asm volatile("st.shared.v2.f32 [%0], {%1,%2};" ::"r"(a), "f"(x), "f"(y) : "memory"); }
__device__ __forceinline__ void sts4f(uint32_t a, float x, float y, float z, float w) { asm volatile("st.shared.v4.f32 [%0], {%1,%2,%3,%4};" ::"r"(a), "f"(x), "f"(y), "f"(z), "f"(w) : "memory"); }
__device__ __forceinline__ void stsf(uint32_t a, float v) { asm volatile("st.shared.f32 [%0], %1;" ::"r"(a), "f"(v) : "memory"); }
__device__ __forceinline__ uint32_t lds1(uint32_t a) { uint32_t v; asm volatile("ld.shared.u32 %0, [%1];" : "=r"(v) : "r"(a) : "memory"); return v; }
__device__ __forceinline__ float ldsf(uint32_t a) { float v; asm volatile("ld.shared.f32 %0, [%1];" : "=f"(v) : "r"(a) : "memory"); return v; }
__device__ __forceinline__ float2 ldsf2(uint32_t a) { float2 v; asm volatile("ld.shared.v2.f32 {%0,%1}, [%2];" : "=f"(v.x), "=f"(v.y) : "r"(a) : "memory"); return v; }
__device__ __forceinline__ float4 ldsf4(uint32_t a) { float4 v; asm volatile("ld.shared.v4.f32 {%0,%1,%2,%3}, [%4];" : "=f"(v.x), "=f"(v.y), "=f"(v.z), "=f"(v.w) : "r"(a) : "memory"); return v; }
__device__ __forceinline__ void lds4(uint32_t (&r)[4], uint32_t a) { asm volatile("ld.shared.v4.u32 {%0,%1,%2,%3}, [%4];" : "=r"(r[0]), "=r"(r[1]), "=r"(r[2]), "=r"(r[3]) : "r"(a) : "memory"); }

__device__ __forceinline__ void wg_fence() { asm volatile("wgmma.fence.sync.aligned;" ::: "memory"); }
__device__ __forceinline__ void wg_commit() { asm volatile("wgmma.commit_group.sync.aligned;" ::: "memory"); }
template <int N> __device__ __forceinline__ void wg_wait() { asm volatile("wgmma.wait_group.sync.aligned %0;" ::"n"(N) : "memory"); }
__host__ __device__ constexpr uint32_t desc_lo(uint32_t off) { return ((SB + off) >> 4) | 0x10000u; }
template <int TA, int ACC> __device__ __forceinline__ void wgmma_n16(float (&d)[8], uint32_t da, uint32_t db) {
  asm volatile("{\n.reg .b64 da, db;\nmov.b64 da, {%8, 0x40000040};\nmov.b64 db, {%9, 0x40000040};\n"
               "wgmma.mma_async.sync.aligned.m64n16k16.f32.bf16.bf16 {%0,%1,%2,%3,%4,%5,%6,%7}, da, db, %11, 1, 1, %10, 0;\n}"
               : "+f"(d[0]), "+f"(d[1]), "+f"(d[2]), "+f"(d[3]), "+f"(d[4]), "+f"(d[5]), "+f"(d[6]), "+f"(d[7])
               : "r"(da), "r"(db), "n"(TA), "n"(ACC));
}
__device__ __forceinline__ void wgmma_n16_ones(float (&d)[8], uint32_t one, uint32_t db) {
  asm volatile("{\n.reg .b64 db;\nmov.b64 db, {%9, 0x40000040};\n"
               "wgmma.mma_async.sync.aligned.m64n16k16.f32.bf16.bf16 {%0,%1,%2,%3,%4,%5,%6,%7}, {%8,%8,%8,%8}, db, 1, 1, 1, 0;\n}"
               : "+f"(d[0]), "+f"(d[1]), "+f"(d[2]), "+f"(d[3]), "+f"(d[4]), "+f"(d[5]), "+f"(d[6]), "+f"(d[7])
               : "r"(one), "r"(db));
}
__device__ __forceinline__ void acc_fence(float (&d)[8]) {
  asm volatile("" : "+f"(d[0]), "+f"(d[1]), "+f"(d[2]), "+f"(d[3]), "+f"(d[4]), "+f"(d[5]), "+f"(d[6]), "+f"(d[7]) :: "memory");
}

template <int N, int STRIDE> __device__ __forceinline__ void load_units(uint2 (&v)[N], const uint32_t* p) {
#pragma unroll
  for (int i = 0; i < N; i++) v[i] = ldg_u64(p + i * STRIDE);
}
template <int N, int STRIDE> __device__ __forceinline__ int check_units(uint2 (&v)[N], const uint32_t* p, int rb) {
  int it = 0;
  while (true) {
    uint32_t mn = v[0].y;
#pragma unroll
    for (int i = 1; i < N; i++) mn = min(mn, v[i].y);
    if (mn != 0) break;
    backoff(rb);
#pragma unroll
    for (int i = 0; i < N; i++) if (v[i].y == 0) v[i] = ldg_u64(p + i * STRIDE);
    if (++it > SPIN_LIMIT) __trap();
  }
  return it;
}
__device__ __forceinline__ void reload_unit(uint2& v, const uint32_t* p) {
  asm volatile("{\n.reg .pred q;\nsetp.eq.u32 q, %1, 0;\n@q ld.relaxed.gpu.global.v2.b32 {%0, %1}, [%2];\n}" : "+r"(v.x), "+r"(v.y) : "l"(p) : "memory");
}
template <int N> __device__ __forceinline__ uint32_t min_flags(const uint2 (&v)[N]) {
  uint32_t a = v[0].y, b = v[1].y;
#pragma unroll
  for (int i = 2; i < N; i += 2) { a = min(a, v[i].y); b = min(b, v[i + 1].y); }
  return min(a, b);
}
__device__ __forceinline__ void sum4_to_smem(const uint2 (&v)[4], uint32_t dst) {
  const float c0 = (bf_lo(v[0].x) + bf_lo(v[1].x)) + (bf_lo(v[2].x) + bf_lo(v[3].x));
  const float c1 = (bf_hi(v[0].x) + bf_hi(v[1].x)) + (bf_hi(v[2].x) + bf_hi(v[3].x));
  const float c2 = (bf_lo(v[0].y) + bf_lo(v[1].y)) + (bf_lo(v[2].y) + bf_lo(v[3].y));
  const float c3 = (bf_hi(v[0].y) + bf_hi(v[1].y)) + (bf_hi(v[2].y) + bf_hi(v[3].y));
  sts1(dst, pack_bf16(c0, c1));
  sts1(dst + 128, pack_bf16(c2, c3));
}
__device__ __forceinline__ void load_a_t(uint32_t (&a)[8][4], uint32_t wbase, int w, int lane) {
  const int mi = lane >> 3, r = lane & 7;
  const uint32_t base = wbase + (w >> 2) * 16384 + (8 * (mi >> 1) + r) * 128 + (((2 * (w & 3) + (mi & 1)) ^ r) << 4);
#pragma unroll
  for (int ks = 0; ks < 8; ks++) ldsm4t(a[ks], base + ks * 2048);
}
__device__ __forceinline__ void mma128(float (&d)[4], const uint32_t (&a)[8][4], const uint32_t (&b)[4][4]) {
  float e[4][4] = {{d[0], d[1], d[2], d[3]}, {0.f, 0.f, 0.f, 0.f}, {0.f, 0.f, 0.f, 0.f}, {0.f, 0.f, 0.f, 0.f}};
#pragma unroll
  for (int kk = 0; kk < 4; kk++) { mma16816(e[(2 * kk) & 3], a[2 * kk], b[kk][0], b[kk][1]); mma16816(e[(2 * kk + 1) & 3], a[2 * kk + 1], b[kk][2], b[kk][3]); }
#pragma unroll
  for (int i = 0; i < 4; i++) d[i] = (e[0][i] + e[1][i]) + (e[2][i] + e[3][i]);
}
template <int NP> __device__ __forceinline__ bool sum_pieces(const uint32_t* p0, uint32_t one, float (&r)[4]) {
  uint2 v[NP / 4];
  load_units<NP / 4, 64>(v, p0);
  float d[4][4] = {};
#pragma unroll
  for (int i = 0; i < NP / 8; i++) { const uint32_t a[4] = {v[2 * i].x, v[2 * i].y, v[2 * i + 1].x, v[2 * i + 1].y}; mma16816(d[i & 3], a, one, one); }
  const bool ok = __all_sync(~0u, min_flags(v) != 0);
#pragma unroll
  for (int k = 0; k < 4; k++) r[k] = (d[0][k] + d[1][k]) + (d[2][k] + d[3][k]);
  return ok;
}
template <typename F> __device__ __forceinline__ float reduce_g(const float (&x)[4], int lane, F f) {
  const bool u4 = lane & 16, u3 = lane & 8;
  const float a0 = f(u4 ? x[2] : x[0], __shfl_xor_sync(~0u, u4 ? x[0] : x[2], 16));
  const float a1 = f(u4 ? x[3] : x[1], __shfl_xor_sync(~0u, u4 ? x[1] : x[3], 16));
  const float b = f(u3 ? a1 : a0, __shfl_xor_sync(~0u, u3 ? a0 : a1, 8));
  return f(b, __shfl_xor_sync(~0u, b, 4));
}

__global__ void __launch_bounds__(NTHREADS, 1)
fused_decode_kernel(__nv_bfloat16* __restrict__ gout, Scratch* __restrict__ gs, const uint8_t* __restrict__ gwmod,
                    const uint8_t* __restrict__ gx, const uint8_t* __restrict__ gc, uint32_t* __restrict__ gin,
                    const __grid_constant__ Params P) {
  constexpr Tune T{};
  extern __shared__ __align__(1024) uint8_t smem_raw[];
  const uint32_t sb = (uint32_t)__cvta_generic_to_shared(smem_raw);
  const int tid = __shfl_xor_sync(0xffffffffu, threadIdx.x ^ 1, 1), lane = tid & 31;
  const int w = __shfl_sync(0xffffffffu, threadIdx.x >> 5, 0);
  const int cta = blockIdx.x;
  const uint32_t bars = sb + OFF_BARS;
  auto BAR = [&](int i) { return bars + 8 * i; };
  auto selector = [&](int c) { uint32_t v; asm volatile("ld.shared.u8 %0, [%1];" : "=r"(v) : "r"(sb + OFF_SEL + c) : "memory"); return v; };
  auto inbox = [&](int c, int k) { return gin + blk(c, k, selector(c)); };
  auto nearbox = [&](int c, int k) { return gin + blk(c, k, selector(cta) ^ flip((c ^ cta) & 15)); };
  const int g = lane >> 2, t = lane & 3;
  const int hI = cta >> 2, jI = cta & 3;
  const int bs = cta >> 1, hh = cta & 1;

  CLK_DECL;
  CLK(0);
  if (w == 8) {
    CLK(7);
    const uint32_t t_entry = gtime32();
    CLK(8);
    if (lane == 0) {
      if ((sb & 0xffffff) != SB) __trap();
      mbar_init(BAR(BAR_WQ), 1); mbar_init(BAR(BAR_WQ + 1), 1); mbar_init(BAR(BAR_XC), 1); mbar_init(BAR(BAR_C), 1);
      asm volatile("fence.mbarrier_init.release.cluster;" ::: "memory");
      asm volatile("prefetch.tensormap [%0];" ::"l"(&P.wq) : "memory");
      mbar_expect(BAR(BAR_XC), 8192); mbar_expect(BAR(BAR_C), 8192); mbar_expect(BAR(BAR_WQ), 16384); mbar_expect(BAR(BAR_WQ + 1), 16384);
      CLK(9);
    }
    __syncwarp();
    asm volatile("barrier.cta.arrive.aligned 0, %0;" ::"n"(NTHREADS) : "memory");
    CLK(10);
    uint32_t tn = t_entry + T.PC_T0 + ((bs * 37) & 63) * T.PC_STAG / 64;
    const int h = hI, j = jI;
    if (lane == 0) {
      uint64_t pol; asm volatile("createpolicy.fractional.L2::evict_first.b64 %0, 1.0;" : "=l"(pol));
#pragma unroll
      for (int u = 0; u < 4; u++) {
        until_ns(tn + u * T.PC_P1);
        if (u == 0) CLK(11);
        tma2d(sb + OFF_WQ + u * 8192, &P.wq, 128 * h + 64 * (u >> 1), 128 * j + 64 * (u & 1), BAR(BAR_WQ + (u >> 1)), pol);
        if (u == T.PC_XC) {
#pragma unroll
          for (int i = 0; i < 4; i++) { const int o = ((i + cta) & 3) * 2048; bulk_ld(sb + OFF_XS + o, gx + o, 2048, BAR(BAR_XC)); }
        }
        if (u == T.PC_C) {
#pragma unroll
          for (int i = 0; i < 4; i++) { const int o = ((i + cta) & 3) * 2048; bulk_ld(sb + OFF_CS + o, gc + o, 2048, BAR(BAR_C)); }
        }
        if (u == 0) {
          CLK(1);
          asm volatile("prefetch.tensormap [%0];" ::"l"(&P.wuk) : "memory");
          asm volatile("prefetch.tensormap [%0];" ::"l"(&P.wm2) : "memory");
          asm volatile("prefetch.tensormap [%0];" ::"l"(&P.ckv2) : "memory");
        }
      }
    }
    __syncwarp();
    tn += 4 * T.PC_P1;
    bar_sync(5, 64);
    if (lane == 0) {
      uint64_t pol; asm volatile("createpolicy.fractional.L2::evict_first.b64 %0, 1.0;" : "=l"(pol));
#pragma unroll
      for (int u = 0; u < 4; u++) {
        if ((u & 1) == (T.PC_W > 3) && T.PC_NW) mbar_wait(BAR(BAR_WQ + (u >> 1)));
        slot(tn, T.PC_SL);
        tma5d(sb + OFF_WUK + u * 8192, &P.wuk, 128 * h + 64 * (u >> 1), 0, 0, 0, 8 * j + 4 * (u & 1), BAR(BAR_WUK + (u >> 1)), pol);
        tn += T.PC_P1;
      }
#pragma unroll
      for (int u = 0; u < 2; u++) {
        if (u == (T.PC_W > 3) && T.PC_NW) mbar_wait(BAR(BAR_WUK));
        slot(tn, T.PC_SL);
        tma2d_nohint(sb + OFF_WM2 + u * 8192, &P.wm2, 1024 + 16 * cta, 256 * u, BAR(BAR_WM2));
        tn += T.PC_P1;
      }
      const int row0 = (bs >> 3) * 4096 + (bs & 7) * 64;
      uint32_t dst = sb + OFF_RING;
      const int p2 = T.PC_P2 + (32 - ((bs * 37) & 63)) * T.PC_DS / 1024;
#pragma unroll 1
      for (int n = 0; n < 31; n++) {
        if (n >= 4 && (n < 12 || (n & 3) == 0)) mbar_wait(BAR(n >= 12 ? BAR_EMPTY + (n >> 2) - 3 : n == 7 ? BAR_P0BD : (n == 8 || n == 9) ? BAR_P2D : BAR_P1D));
        if (n < T.PC_NW) {
          if (n >= T.PC_W) mbar_wait(BAR(BAR_FULL + n - T.PC_W));
          else if ((n & 1) == (T.PC_W > 3)) mbar_wait(BAR(n < 2 ? BAR_WUK + 1 : BAR_WM2));
        }
        slot(tn, T.PC_SL);
        tma3d(dst, &P.ckv2, 0, row0 + (n >> 2) * 512, 2 * (n & 3), BAR(BAR_FULL + n), pol);
        dst = (n == 11 || n == 23) ? sb + OFF_RING : dst + 16384;
        tn += n >= 15 ? p2 : T.PC_P2;
        if (n == 4) CLK(2);
        if (n == 12) CLK(3);
        if (n == 20) CLK(4);
        if (n == 28) CLK(5);
        if (n == 24) {
          asm volatile("prefetch.tensormap [%0];" ::"l"(&P.ckv1) : "memory");
          asm volatile("prefetch.tensormap [%0];" ::"l"(&P.wuv) : "memory");
          asm volatile("prefetch.tensormap [%0];" ::"l"(&P.wo) : "memory");
          asm volatile("prefetch.tensormap [%0];" ::"l"(&P.w1) : "memory");
          asm volatile("prefetch.tensormap [%0];" ::"l"(&P.w2) : "memory");
        }
      }
      slot(tn, T.PC_SL);
      tma3d(dst, &P.ckv1, 0, row0 + 7 * 512, 6, BAR(BAR_LAST + 3), pol);
      tma3d(dst + 8192, &P.ckv1, 0, row0 + 7 * 512, 7, BAR(BAR_LAST + 4), pol);
      tn += T.PC_P2;
      CLK(6);
      auto unit = [&](int u) {
        if (u < 4) tma5d(sb + OFF_WUV + u * 8192, &P.wuv, 128 * h + 64 * (u >> 1), 0, 4 * (j >> 1), 0, 2 * (j & 1) + (u & 1), BAR(BAR_WUV + (u >> 1)), pol);
        else if (u < 8) tma2d(sb + OFF_WO + (u - 4) * 8192, &P.wo, 128 * j + 64 * ((u - 4) >> 1), 128 * h + 64 * (u & 1), BAR(BAR_WO + ((u - 4) >> 1)), pol);
        else if (u < 10) { if (cta < NFF) tma2d_nohint(sb + OFF_W1 + (u - 8) * 16384, &P.w1, 32 * bs, 256 * (u - 8), BAR(BAR_W1)); }
        else if (cta < NFF) tma3d(sb + OFF_W2 + (u - 10) * 8192, &P.w2, 0, 32 * bs, 4 * hh + 2 * (u - 10), BAR(BAR_W2), pol);
      };
      mbar_wait(BAR(BAR_EMPTY + 5));
      if (T.PW_A >= 0) { mbar_wait(BAR(BAR_LAST + T.PW_A)); tn = gtime32(); }
      tn += T.PW_0 + ((cta * 37) & 127) * T.PW_ST / 128;
#pragma unroll
      for (int u = 0; u < 12; u++) {
        if (u == 8) mbar_wait(BAR(BAR_EMPTY + 6));
        until_ns(tn);
        unit(WSWAP && u >= 8 ? (u ^ 2) : u);
        tn += u < 3 ? T.PW_UV : u == 3 ? T.PW_G : u < 7 ? T.PW_O : u == 7 ? T.PW_G2 : u == 9 ? T.PW_G3 : T.PW_F;
      }
      CLK_DUMP();
    }
    return;
  }

  if (w == 9) {
    if (lane == 0) {
#pragma unroll
      for (int i = 0; i < NBARS; i++) mbar_init(BAR(i), i >= BAR_P1D ? 8 : i >= BAR_EMPTY ? 4 : 1);
      asm volatile("fence.mbarrier_init.release.cluster;" ::: "memory");
    }
    __syncwarp();
    mbar_expect(BAR(lane), lane == BAR_LAST + 3 ? 8192 : 16384);
    if (lane < BAR_ALLCLR - 32) mbar_expect(BAR(32 + lane), lane == 0 ? 8192 : lane == BAR_W1 - 32 ? 32768 : 16384);
    CLK(9);
    asm volatile("barrier.cta.arrive.aligned 5, 64;" ::: "memory");
    asm volatile("barrier.cta.arrive.aligned 0, %0;" ::"n"(NTHREADS) : "memory");
  }
  const uint32_t epoch = ldg_rlx1(&gs->epoch);

  if (w == 9) {
    const int mo = g * 512 + 16 * hI + 2 * jI;
    const uint32_t xo0 = ldg_nc1(gx + mo * 2), xo1 = ldg_nc1(gx + mo * 2 + 16);
    const int par = epoch & 1;
    const uint32_t t0 = gtime32();
    const uint4 z = make_uint4(0, 0, 0, 0);
    uint32_t sel;
    {
      uint32_t* pa = gin + blk(cta, 5, 0) + 960;
      uint32_t* pb = gin + blk(cta, 5, 1) + 960;
      until_ns(t0 + T.PR_T0);
      if (lane < 4) stg4(reinterpret_cast<uint4*>(lane & 2 ? pa : pb) + (lane & 1), z);
      uint32_t ma = 0xffffffffu, mb = 0xffffffffu;
      if (lane == 0) {
#pragma unroll 1
        for (int i = 0; i < 2 * T.PR_N; i++) {
          const uint32_t c0 = clk32();
          uint32_t v;
          asm volatile("atom.relaxed.gpu.global.add.u32 %0, [%1], 1;" : "=r"(v) : "l"(i & 1 ? pb : pa) : "memory");
          if (v == 0xffffffffu) __trap();
          const uint32_t d = clk32() - c0;
          if (i & 1) mb = min(mb, d); else ma = min(ma, d);
        }
      }
      sel = __shfl_sync(~0u, (uint32_t)(mb < ma), 0);
      if (T.LOC == 1) sel ^= 1;
      if (T.LOC == 2) sel ^= (cta ^ (cta >> 3)) & 1;
      const uint32_t sw = 2 * (epoch + 1) + sel;
      if (lane < 2) stg4(reinterpret_cast<uint4*>(gin + blk(cta, 5, 1) + 896) + lane, make_uint4(sw, sw, sw, sw));
    }
    until_ns(t0 + T.CLR_T0);
    {
#pragma unroll 1
      for (int i0 = 0; i0 < 13; i0++) {
        uint4* q = reinterpret_cast<uint4*>(gin + (i0 < 12 ? blk(cta, i0 >> 1, sel) + (i0 & 1) * 512 : blk(cta, 4, sel ^ 1) + 512)) + lane;
#pragma unroll
        for (int i = 0; i < 4; i++) if (i0 != 11 || i < 3) stg4(q + i * 32, z);
        backoff(T.CLR_CLK);
      }
#pragma unroll
      for (int i = 0; i < 2; i++) {
        if (jI == 1) stg4(reinterpret_cast<uint4*>(gin + blk(cta, 6, i)) + lane, z);
        if (lane < 2) stg4(reinterpret_cast<uint4*>(gin + blk(cta, 5, i) + 928) + lane, z);
        stg4(reinterpret_cast<uint4*>(gin + blk(16 * g, 6 + (cta >> 6), i) + (cta & 63) * 16) + t, z);
      }
      CLK(1);
      {
        uint32_t sv = 0;
        uint32_t u[4];
#pragma unroll
        for (int i = 0; i < 4; i++) u[i] = ldg_rlx1(gin + blk(4 * lane + i, 5, 1) + 896);
#pragma unroll
        for (int i = 0; i < 4; i++) {
          int it = 0;
          while ((u[i] | 1) != 2 * (epoch + 1) + 1) { u[i] = ldg_rlx1(gin + blk(4 * lane + i, 5, 1) + 896); if (++it > SPIN_LIMIT) __trap(); }
          sv |= (u[i] & 1) << (8 * i);
        }
        sts1(sb + OFF_SEL + lane * 4, sv);
      }
      asm volatile("fence.acq_rel.gpu;" ::: "memory");
      CLK(2);
      __syncwarp();
      if (lane < NSYNC) asm volatile("red.relaxed.gpu.global.add.u32 [%0], 1;" ::"l"(&gs->sync[lane][0]) : "memory");
#pragma unroll
      for (int i = 0; i < 4; i++) stg4(reinterpret_cast<uint4*>(gs->QP[par ^ 1] + cta * 512) + i * 32 + lane, z);
      backoff(T.CLR_CLK);
#pragma unroll
      for (int i = 0; i < 4; i++) stg4(reinterpret_cast<uint4*>(gs->QX[par ^ 1] + cta * 512) + i * 32 + lane, z);
      stg4(reinterpret_cast<uint4*>(gs->MOD1[par ^ 1] + cta * 128) + lane, z);
      if (lane < 16) stg4(reinterpret_cast<uint4*>(gs->MOD2[par ^ 1] + cta * 64) + lane, z);
      if (lane == 0) {
        const uint32_t target = (epoch + 1) * NCTA;
        uint32_t c; int it = 0;
        do { backoff(T.CLR_CLK); asm volatile("ld.acquire.gpu.global.u32 %0, [%1];" : "=r"(c) : "l"(&gs->sync[cta % NSYNC][0]) : "memory"); if (++it > SPIN_LIMIT) __trap(); } while ((int)(c - target) < 0);
        mbar_arrive(BAR(BAR_ALLCLR));
      }
      __syncwarp();
    }
    CLK(3);
    uint2 gg[2];
    {
      const uint32_t* pg = gs->MOD2[par] + cta * 16 + g * 2;
      load_units<2, 3 * 2048>(gg, pg);
      check_units<2, 3 * 2048>(gg, pg, T.RB);
    }
    uint32_t anchor;
    {
      uint32_t* const po = gin + blk(16 * (lane & 7), 5, lane >> 3) + 928;
      const uint32_t* const pi = nearbox(cta & ~15, 5) + 928;
      mbar_wait(BAR(BAR_LAST + T.TS_P));
      unsigned long long now; asm volatile("mov.u64 %0, %%globaltimer;" : "=l"(now));
      if (lane < 16) {
        asm volatile("red.relaxed.gpu.global.max.u64 [%0], %1;" ::"l"(po + 2), "l"(now) : "memory");
        asm volatile("red.relaxed.gpu.global.add.u32 [%0], 1;" ::"l"(po + 1) : "memory");
      }
      backoff(T.D_TS);
      uint4 v; int it = 0;
      do { v = ldg_2u64(pi); if (++it > SPIN_LIMIT) __trap(); } while (v.y != NCTA);
      const int age = min(max((int)(gtime32() - v.z), 0), 4000);
      anchor = clk32() - age * 7 / 4 + T.TS_O;
      if (lane == 0) { sts1(sb + OFF_TS, anchor); mbar_arrive(BAR(BAR_TS)); }
      CLK(10);
    }
    {
      const uint32_t* pm = pin(nearbox(4 * hI + 1, 6) + lane * 4);
      wait_clk(anchor, T.A_M);
      uint4 ml = ldg_2u64(pm);
      int it = 0;
      while (ml.y == 0 || ml.w == 0) { ml = ldg_2u64(pm); if (++it > SPIN_LIMIT) __trap(); }
      __syncwarp();
      ITS(2, it);
      float M = fmaxf(__uint_as_float(ml.x), __uint_as_float(ml.z));
      M = fmaxf(M, __shfl_xor_sync(~0u, M, 1)); M = fmaxf(M, __shfl_xor_sync(~0u, M, 2));
      const float e0 = ex2(__uint_as_float(ml.x) - M), e1 = ex2(__uint_as_float(ml.z) - M);
      float l = e0 * __uint_as_float(ml.y) + e1 * __uint_as_float(ml.w);
      l += __shfl_xor_sync(~0u, l, 1); l += __shfl_xor_sync(~0u, l, 2);
      const float inv = __fdividef(1.f, l);
      sts2f(sb + OFF_WV + lane * 8, e0 * inv, e1 * inv);
      __syncwarp();
      if (lane == 0) mbar_arrive(BAR(BAR_WV));
      CLK(11);
    }
    uint32_t* x3o[4];
#pragma unroll
    for (int i = 0; i < 4; i++) x3o[i] = pin(gin + blk(32 * i + 16 * (t >> 1), 6 + (cta >> 6), t) + (cta & 63) * 16 + g * 2);
    uint32_t* const fo = pin(reinterpret_cast<uint32_t*>(gout) + mo / 2 + 4 * (t & 1));
    const uint32_t* const p3 = pin(gin + blk(cta, 4, sel) + t * 16 + g * 2);
    const uint32_t* const p4 = pin(gin + blk(cta, 5, sel) + t * 16 + g * 2);
    const uint32_t one = pin((g & 1) ? 0x3f800000u : 0x00003f80u);
    const float xf[4] = {pin(bf_lo(xo0)), pin(bf_hi(xo0)), pin(bf_lo(xo1)), pin(bf_hi(xo1))};
    const float ga[4] = {pin(bf_lo(gg[0].x)), pin(bf_hi(gg[0].x)), pin(bf_lo(gg[0].y)), pin(bf_hi(gg[0].y))};
    mbar_wait(BAR(BAR_P5D));
    backoff(T.D_X3A);
    wait_clk(anchor, T.A_X1 + T.R_X3A);
    CLK(4);
    float r[4];
    uint32_t x20, x21;
    int it = 0;
    bool ok;
    do {
      ok = sum_pieces<32>(p3, one, r);
      x20 = pack_bf16(xf[0] + ga[0] * r[0], xf[1] + ga[1] * r[1]); x21 = pack_bf16(xf[2] + ga[2] * r[2], xf[3] + ga[3] * r[3]);
#pragma unroll
      for (int i = 0; i < 4; i++) ST3B(!ok || (i == 3 && t >= 2), x3o[i], x20, x21);
    } while (!ok && ++it < SPIN_LIMIT);
    CLK(6);
    ITS(0, it);
    const uint32_t xw = (t & 1) ? x21 : x20, gw = (t & 1) ? gg[1].y : gg[1].x;
    const float xa = pin(bf_lo(xw)), xb = pin(bf_hi(xw)), gba = pin(bf_lo(gw)), gbb = pin(bf_hi(gw));
    if (cta < NFF) { mbar_wait(BAR(BAR_P7D)); backoff(T.D_FIN); } else { backoff(1200); wait_clk(anchor, T.A_X1 + T.R_X3A + T.R_X3B + T.R_FIN); }
    CLK(7);
    do {
      ok = sum_pieces<NFG>(p4, one, r);
      const uint32_t o = pack_bf16(xa + gba * ((t & 1) ? r[2] : r[0]), xb + gbb * ((t & 1) ? r[3] : r[1]));
      if (ok && t < 2) asm volatile("st.global.u32 [%0], %1;" ::"l"(fo), "r"(o) : "memory");
    } while (!ok && ++it < SPIN_LIMIT);
    if (!ok) __trap();
    ITS(1, it);
    CLK(8);
    CLK_DUMP();
    if (cta == 0 && lane == 0) stg1(&gs->epoch, epoch + 1);
    return;
  }

  const int wg = w >> 2, wq = w & 3;
  uint32_t tstore;
  {
    const uint8_t* pw = gwmod + (size_t)(128 * jI + 16 * w + 4 * (g >> 1) + (g & 1)) * 6144 + 64 * hI + 16 * t;
    const uint4 w0 = ldg_nc4(pw), w1 = ldg_nc4(pw + 2 * 6144);
    const uint2 cc = ldg_nc2(gc + g * 1024 + 256 * jI + 32 * w + 8 * t);
    CLK(40);
    const uint32_t a[4] = {silu2(cc.x), 0u, silu2(cc.y), 0u};
    float d[4][4] = {{0.f, 0.f, 0.f, 0.f}, {0.f, 0.f, 0.f, 0.f}, {0.f, 0.f, 0.f, 0.f}, {0.f, 0.f, 0.f, 0.f}};
    mma16816(d[0], a, movm(w0.x), movm(w1.x)); mma16816(d[1], a, movm(w0.y), movm(w1.y));
    mma16816(d[2], a, movm(w0.z), movm(w1.z)); mma16816(d[3], a, movm(w0.w), movm(w1.w));
    CLK(1);
    sts4f(sb + OFF_P0S + w * 1088 + lane * 16, d[0][0], d[0][1], d[1][0], d[1][1]);
    sts4f(sb + OFF_P0S + w * 1088 + 544 + lane * 16, d[2][0], d[2][1], d[3][0], d[3][1]);
    bar_sync(0, NTHREADS);
    if (tid < 128) {
      const uint32_t src = sb + OFF_P0S + ((tid >> 2) & 1) * 544 + (((tid >> 3) & 7) * 4 + 2 * (tid >> 6) + (tid & 1)) * 16 + ((tid >> 1) & 1) * 8;
      float2 v[8];
#pragma unroll
      for (int i = 0; i < 8; i++) v[i] = ldsf2(src + i * 1088);
      const float ax = ((v[0].x + v[1].x) + (v[2].x + v[3].x)) + ((v[4].x + v[5].x) + (v[6].x + v[7].x));
      const float ay = ((v[0].y + v[1].y) + (v[2].y + v[3].y)) + ((v[4].y + v[5].y) + (v[6].y + v[7].y));
      stg1(gs->MOD1[epoch & 1] + jI * 4096 + hI * 128 + tid, nz(pack_bf16(ax, ay)));
    }
    tstore = clk32();
  }
  CLK(2);
  const int par = epoch & 1;
  uint32_t cf[4][4];
  mbar_wait(BAR(BAR_XC));
  {
    uint32_t u[2][4];
    lds4(u[0], sb + OFF_XS + w * 1024 + lane * 16); lds4(u[1], sb + OFF_XS + w * 1024 + 512 + lane * 16);
    float v[16];
#pragma unroll
    for (int i = 0; i < 8; i++) { v[2 * i] = bf_lo(u[i >> 2][i & 3]); v[2 * i + 1] = bf_hi(u[i >> 2][i & 3]); }
    float s = 0.f;
#pragma unroll
    for (int i = 0; i < 16; i++) s += v[i];
#pragma unroll
    for (int o = 16; o; o >>= 1) s += __shfl_xor_sync(~0u, s, o);
    const float mu = s * (1.f / 512.f);
    float q = 0.f;
#pragma unroll
    for (int i = 0; i < 16; i++) { v[i] -= mu; q += v[i] * v[i]; }
#pragma unroll
    for (int o = 16; o; o >>= 1) q += __shfl_xor_sync(~0u, q, o);
    const float rs = rsqrtf(q * (1.f / 512.f) + 1e-5f);
    const bool hi = jI & 2;
    uint32_t o[4];
#pragma unroll
    for (int i = 0; i < 4; i++) o[i] = pack_bf16((hi ? v[8 + 2 * i] : v[2 * i]) * rs, (hi ? v[9 + 2 * i] : v[2 * i + 1]) * rs);
    if ((lane >> 4) == (jI & 1)) sts4(sb + OFF_XN + w * 272 + (lane & 15) * 16, make_uint4(o[0], o[1], o[2], o[3]));
  }
  CLK(3);
  uint32_t aw[8][4];
  {
    const uint32_t* pm = pin(gs->MOD1[par] + (8 * jI + w) * 64 + lane * 2);
    uint32_t* const qpo = pin(gs->QP[par] + (cta * 256 + tid) * 2);
    float d[4] = {0.f, 0.f, 0.f, 0.f};
    wait_clk(tstore, T.D_MOD);
    CLK(4);
    uint2 v[8];
    load_units<8, 2048>(v, pm);
    cbar();
    const uint32_t xn0 = lds1(sb + OFF_XN + g * 272 + w * 32 + t * 4), xn1 = lds1(sb + OFF_XN + g * 272 + w * 32 + 16 + t * 4);
    const bool early = __all_sync(~0u, mbar_test(BAR(BAR_WQ + wg)));
    if (early) load_a_t(aw, sb + OFF_WQ, w, lane);
    int it = 0;
    while (true) {
      uint32_t mn = 0xffffffffu;
#pragma unroll
      for (int i = 0; i < 8; i++) mn = min(mn, min(v[i].x, v[i].y));
      if (mn != 0) break;
#pragma unroll
      for (int i = 0; i < 8; i++) if (v[i].x == 0 || v[i].y == 0) v[i] = ldg_u64(pm + i * 2048);
      if (++it > SPIN_LIMIT) __trap();
    }
    CLK(5);
    ITS(0, it);
    float sc[2][4];
#pragma unroll
    for (int i = 0; i < 2; i++) {
      sc[i][0] = (bf_lo(v[i].x) + bf_lo(v[2 + i].x)) + (bf_lo(v[4 + i].x) + bf_lo(v[6 + i].x));
      sc[i][1] = (bf_hi(v[i].x) + bf_hi(v[2 + i].x)) + (bf_hi(v[4 + i].x) + bf_hi(v[6 + i].x));
      sc[i][2] = (bf_lo(v[i].y) + bf_lo(v[2 + i].y)) + (bf_lo(v[4 + i].y) + bf_lo(v[6 + i].y));
      sc[i][3] = (bf_hi(v[i].y) + bf_hi(v[2 + i].y)) + (bf_hi(v[4 + i].y) + bf_hi(v[6 + i].y));
    }
    sts2(sb + OFF_BS1 + (w >> 1) * 512 + lane * 16 + (w & 1) * 8,
         pack_bf16(bf_lo(xn0) * (1.f + sc[1][0]) + sc[0][0], bf_hi(xn0) * (1.f + sc[1][1]) + sc[0][1]),
         pack_bf16(bf_lo(xn1) * (1.f + sc[1][2]) + sc[0][2], bf_hi(xn1) * (1.f + sc[1][3]) + sc[0][3]));
    if (!early) { mbar_wait(BAR(BAR_WQ + wg)); load_a_t(aw, sb + OFF_WQ, w, lane); }
    CLK(6);
    cbar();
    uint32_t b[4][4];
#pragma unroll
    for (int kk = 0; kk < 4; kk++) lds4(b[kk], sb + OFF_BS1 + kk * 512 + lane * 16);
    mma128(d, aw, b);
    stg_u64(qpo, pack_bf16(d[0], d[1]), pack_bf16(d[2], d[3]));
    tstore = clk32();
    CLK(7);
    if (wg) {
      mbar_wait(BAR(BAR_C));
#pragma unroll
      for (int i = 0; i < 4; i++) lds4(cf[i], sb + OFF_CS + g * 1024 + wq * 256 + i * 64 + t * 16);
#pragma unroll
      for (int i = 0; i < 16; i++) cf[i >> 2][i & 3] = silu2(cf[i >> 2][i & 3]);
    }
    __syncwarp();
    if (lane == 0) mbar_arrive(BAR(BAR_P1D));
  }
  {
    const uint32_t* pq = pin(gs->QP[par] + (hI * 4 * 256 + tid) * 2);
    uint32_t* const qxo = pin(gs->QX[par] + (g * 32 + hI) * 256 + 64 * jI + 8 * w + 2 * t);
    uint2 v[4];
    float d[4] = {0.f, 0.f, 0.f, 0.f};
    wait_clk(tstore, T.D_QP);
    CLK(8);
    load_units<4, 512>(v, pq);
    const uint32_t abase = sb + OFF_WUK + (16 * w + (lane & 15)) * 128;
    auto load_half = [&](int hf) {
#pragma unroll
      for (int ks = 0; ks < 4; ks++) ldsm4(aw[4 * hf + ks], abase + hf * 16384 + (((2 * ks + (lane >> 4)) ^ (lane & 7)) << 4));
    };
    mbar_wait(BAR(BAR_WUK));
    load_half(0);
    const bool early = __all_sync(~0u, mbar_test(BAR(BAR_WUK + 1)));
    if (early) load_half(1);
    const int it = check_units<4, 512>(v, pq, T.RB);
    CLK(9);
    ITS(1, it);
    sum4_to_smem(v, sb + OFF_BS2 + (16 * w + g) * 16 + t * 4);
    if (!early) { mbar_wait(BAR(BAR_WUK + 1)); load_half(1); }
    CLK(10);
    cbar();
    uint32_t b[4][4];
#pragma unroll
    for (int kk = 0; kk < 4; kk++) ldsm4t(b[kk], sb + OFF_BS2 + (32 * kk + lane) * 16);
    mma128(d, aw, b);
    const float sc = 0.08838834764831845f * 1.4426950408889634f;
    stg_u64(qxo, movm(pack_bf16(d[0] * sc, d[1] * sc)), movm(pack_bf16(d[2] * sc, d[3] * sc)));
    tstore = clk32();
    CLK(11);
    if (lane == 0) mbar_arrive(BAR(BAR_P2D));
  }
  if (wg) {
    const int mi = lane >> 3, r = lane & 7;
    const uint32_t a0 = sb + OFF_WM2 + (8 * (r >> 1) + (r & 1) + 2 * (mi >> 1)) * 32 + (mi & 1) * 16;
    mbar_wait(BAR(BAR_WM2));
#pragma unroll
    for (int s = 0; s < 8; s++) ldsm4t(aw[s], a0 + (128 * wq + 32 * (s >> 1) + 4 * (s & 1)) * 32);
    float d[4] = {0.f, 0.f, 0.f, 0.f};
    mma128(d, aw, cf);
    sts4f(sb + OFF_P0B + (tid - 128) * 16, d[0], d[1], d[2], d[3]);
    if (lane == 0) mbar_arrive(BAR(BAR_P0BD));
    bar_sync(3, 128);
    if (w == 4) {
      float4 v[4];
#pragma unroll
      for (int i = 0; i < 4; i++) v[i] = ldsf4(sb + OFF_P0B + (i * 32 + lane) * 16);
      stg_u64(gs->MOD2[par] + cta * 64 + t * 16 + g * 2, movm(pack_bf16((v[0].x + v[1].x) + (v[2].x + v[3].x), (v[0].y + v[1].y) + (v[2].y + v[3].y))),
              movm(pack_bf16((v[0].z + v[1].z) + (v[2].z + v[3].z), (v[0].w + v[1].w) + (v[2].w + v[3].w))));
    }
    CLK(15);
  }
  {
    const uint32_t* qx = pin(gs->QX[par] + ((bs >> 3) * 32 + 16 * hh) * 256 + tid * 4);
    const int ch = tid & 63, h0 = tid >> 6;
    const uint32_t dst = sb + OFF_Q + (ch >> 3) * 2048 + h0 * 128;
    wait_clk(tstore, T.D_QX);
    CLK(12);
    uint4 v[4];
#pragma unroll
    for (int i = 0; i < 4; i++) v[i] = ldg_2u64(qx + i * 1024);
    int it = 0;
    while (true) {
      uint32_t mn = 0xffffffffu;
#pragma unroll
      for (int i = 0; i < 4; i++) mn = min(mn, min(v[i].y, v[i].w));
      if (mn != 0) break;
#pragma unroll
      for (int i = 0; i < 4; i++) if (v[i].y == 0 || v[i].w == 0) v[i] = ldg_2u64(qx + i * 1024);
      if (++it > SPIN_LIMIT) __trap();
    }
    CLK(13);
    ITS(2, it);
#pragma unroll
    for (int i = 0; i < 4; i++) sts4(dst + i * 512 + (((ch & 7) ^ ((4 * i + h0) & 7)) << 4), v[i]);
    asm volatile("fence.proxy.async.shared::cta;" ::: "memory");
    CLK(14);
    cbar();
  }

  uint2 cbf[4], sbf[4];
  const uint32_t* const pcb = gs->MOD2[par] + 2048 + (16 * w + t) * 16 + g * 2;
  uint32_t thand, anchor;
  if (wg == 0) {
    float mh[4];
    float L[8];
#pragma unroll
    for (int i = 0; i < 4; i++) { L[2 * i] = L[2 * i + 1] = 0.f; mh[i] = -INFINITY; }
    constexpr uint32_t dq = desc_lo(OFF_Q);
    const uint32_t ptw = sb + OFF_PT + (8 * (lane >> 4) + (lane & 7)) * 128 + (((2 * wq + ((lane >> 3) & 1)) ^ (lane & 7)) << 4);
    float S[8];
    auto softmax = [&](int tl) {
      auto write_p = [&](const float (&x)[8]) {
        float p[8];
#pragma unroll
        for (int i = 0; i < 8; i++) p[i] = ex2(x[i]);
        stsm4t(ptw + (tl & 1) * 2048, pack_bf16(p[0], p[1]), pack_bf16(p[2], p[3]), pack_bf16(p[4], p[5]), pack_bf16(p[6], p[7]));
        asm volatile("fence.proxy.async.shared::cta;" ::: "memory");
      };
      float x[8];
#pragma unroll
      for (int i = 0; i < 8; i++) x[i] = S[i] - mh[2 * (i >> 2) + (i & 1)];
      if (tl) write_p(x);
      const float ex = fmaxf(fmaxf(fmaxf(x[0], x[1]), fmaxf(x[2], x[3])), fmaxf(fmaxf(x[4], x[5]), fmaxf(x[6], x[7])));
      if (tl == 0 || bar_over(ex)) {
        float mx[4];
#pragma unroll
        for (int i = 0; i < 4; i++) mx[i] = fmaxf(S[4 * (i >> 1) + (i & 1)], S[4 * (i >> 1) + 2 + (i & 1)]);
        const float a = reduce_g(mx, lane, [](float u, float v) { return fmaxf(u, v); });
        stsf(sb + OFF_RED + wq * 64 + (8 * (lane >> 4) + 2 * t + ((lane >> 3) & 1)) * 4, a);
        bar_sync(2, 128);
#pragma unroll
        for (int jn = 0; jn < 2; jn++) {
          float m0 = mh[2 * jn], m1 = mh[2 * jn + 1];
#pragma unroll
          for (int i = 0; i < 4; i++) { const float2 v = ldsf2(sb + OFF_RED + i * 64 + (8 * jn + 2 * t) * 4); m0 = fmaxf(m0, v.x); m1 = fmaxf(m1, v.y); }
          const float a0 = ex2(mh[2 * jn] - m0), a1 = ex2(mh[2 * jn + 1] - m1);
          mh[2 * jn] = m0; mh[2 * jn + 1] = m1;
          L[4 * jn] *= a0; L[4 * jn + 1] *= a1; L[4 * jn + 2] *= a0; L[4 * jn + 3] *= a1;
          if (tid < 4) sts2f(sb + OFF_ALPHA + (8 * jn + 2 * t) * 4, a0, a1);
        }
#pragma unroll
        for (int i = 0; i < 8; i++) x[i] = S[i] - mh[2 * (i >> 2) + (i & 1)];
        write_p(x);
        cbar();
      }
      const uint32_t dpt = __shfl_sync(~0u, desc_lo(OFF_PT) + (tl & 1) * 128, 0);
      wg_fence();
#pragma unroll
      for (int ks = 0; ks < 4; ks++) wgmma_n16_ones(L, ONE2, dpt + ks * 2);
      wg_commit();
    };
    uint32_t da = desc_lo(OFF_RING);
#pragma unroll 1
    for (int tl = 0; tl < 7; tl++) {
      uint32_t ok = 0;
#pragma unroll
      for (int u = 0; u < 4; u++) ok += mbar_test(BAR(BAR_FULL + 4 * tl + u));
      ok = __reduce_min_sync(~0u, ok);
      const uint32_t du = __shfl_sync(~0u, da, 0);
#pragma unroll
      for (int u = 0; u < 4; u++) {
        if (ok != 4) mbar_wait(BAR(BAR_FULL + 4 * tl + u));
        wg_fence();
#pragma unroll
        for (int k = 0; k < 8; k++) {
          const int i = 8 * u + k;
          if (i == 0) wgmma_n16<0, 0>(S, du, dq); else wgmma_n16<0, 1>(S, du + (i >> 2) * 512 + (i & 3) * 2, dq + (i >> 2) * 128 + (i & 3) * 2);
        }
        wg_commit();
      }
      wg_wait<0>();
      acc_fence(S); acc_fence(L);
      if (tl == 0) CLK(15);
      if (tl == 1) CLK(17);
      softmax(tl);
      if (tl == 0) CLK(16);
      if (tl == 1) CLK(18);
      if (tl == 3) CLK(19);
      if (tl == 6) CLK(20);
      da = (tl == 2 || tl == 5) ? da - 8192 : da + 4096;
    }
    if (cta < NFF) { load_units<4, 64>(sbf, pcb); load_units<4, 64>(cbf, pcb + 2048); }
    mbar_wait(BAR(BAR_ALLCLR));
    uint32_t* const mlo = pin(gin + blk(4 * (16 * hh + 4 * (g & 2) + 2 * t + (g & 1)) + 1, 6, g >> 2) + bs * 2);
#pragma unroll
    for (int i = 0; i < 32; i++) {
      if (i == 0 || i == 8 || i == 16 || i == 24 || i == 28) {
        if (i) wg_commit();
        mbar_wait(BAR(BAR_LAST + (i == 28 ? 4 : i >> 3)));
        if (i == 28) CLK(21);
        wg_fence();
      }
      if (i == 0) wgmma_n16<0, 0>(S, da, dq); else wgmma_n16<0, 1>(S, da + (i >> 2) * 512 + (i & 3) * 2, dq + (i >> 2) * 128 + (i & 3) * 2);
    }
    wg_commit();
    wg_wait<0>();
    acc_fence(S); acc_fence(L);
    CLK(22);
    softmax(7);
    CLK(23);
    thand = clk32();
    wg_wait<0>();
    acc_fence(L);
    if (tid < 32) MLST(mlo, __float_as_uint(g & 2 ? (g & 1 ? mh[3] : mh[2]) : (g & 1 ? mh[1] : mh[0])), __float_as_uint(g & 2 ? (g & 1 ? L[5] : L[4]) : (g & 1 ? L[1] : L[0])));
    CLK(24);
  } else {
    float O[8][8];
#pragma unroll
    for (int i = 0; i < 8; i++)
#pragma unroll
      for (int k = 0; k < 8; k++) O[i][k] = 0.f;
    constexpr uint32_t dp = desc_lo(OFF_PT);
    auto handover = [&](int tl) {
      if (tl == 0) { cbar(); return; }
      if (bar_over(0.f)) {
        cbar();
#pragma unroll
        for (int jn = 0; jn < 2; jn++) {
          const float2 a = ldsf2(sb + OFF_ALPHA + (8 * jn + 2 * t) * 4);
#pragma unroll
          for (int mb = 0; mb < 8; mb++) { O[mb][4 * jn] *= a.x; O[mb][4 * jn + 1] *= a.y; O[mb][4 * jn + 2] *= a.x; O[mb][4 * jn + 3] *= a.y; }
        }
      }
    };
    uint32_t da = desc_lo(OFF_RING);
#pragma unroll 1
    for (int tl = 0; tl < 7; tl++) {
      handover(tl);
      const uint32_t dpt = dp + (tl & 1) * 128;
      wg_fence();
#pragma unroll
      for (int i = 0; i < 32; i++) wgmma_n16<1, 1>(O[i >> 2], da + (i >> 2) * 512 + (i & 3) * 128, dpt + (i & 3) * 2);
      wg_commit();
      wg_wait<0>();
#pragma unroll
      for (int mb = 0; mb < 8; mb++) acc_fence(O[mb]);
      if (lane == 0) mbar_arrive(BAR(BAR_EMPTY + tl));
      if (tl == 0) CLK(16);
      if (tl == 1) CLK(18);
      if (tl == 3) CLK(19);
      if (tl == 6) CLK(20);
      da = (tl == 2 || tl == 5) ? da - 8192 : da + 4096;
    }
    if (cta < NFF) { load_units<4, 64>(sbf, pcb); load_units<4, 64>(cbf, pcb + 2048); }
    mbar_wait(BAR(BAR_ALLCLR));
    uint32_t* x1o[8];
#pragma unroll
    for (int i = 0; i < 8; i++)
      x1o[i] = pin(inbox((16 * hh + 8 * ((i >> 1) & 1) + 2 * t + (i & 1)) * 4 + 2 * (i >> 2) + (wq >> 1), bs >> 4) + (bs & 15) * 64 + ((wq & 1) * 8 + g) * 4);
    handover(7);
    CLK(23);
    thand = clk32();
    auto pv = [&](int mb0, int n) {
      wg_fence();
#pragma unroll
      for (int i = 0; i < 16; i++)
        if (i < 4 * n) wgmma_n16<1, 1>(O[mb0 + (i >> 2)], desc_lo(65536) + (mb0 + (i >> 2)) * 512 + (i & 3) * 128, dp + 128 + (i & 3) * 2);
      wg_commit();
    };
    auto publish = [&](int J) {
#pragma unroll
      for (int k = 0; k < 4; k++) acc_fence(O[4 * J + k]);
#pragma unroll
      for (int i = 0; i < 4; i++) {
        const int k = 4 * (i >> 1) + (i & 1);
        stg_cvt8(x1o[4 * J + i], O[4 * J][k], O[4 * J][k + 2], O[4 * J + 1][k], O[4 * J + 1][k + 2],
                 O[4 * J + 2][k], O[4 * J + 2][k + 2], O[4 * J + 3][k], O[4 * J + 3][k + 2]);
      }
    };
    pv(0, 4); pv(4, 4);
    wg_wait<1>(); publish(0);
    wg_wait<0>(); publish(1);
    CLK(24);
  }

  {
    const uint32_t* px = pin(inbox(cta, w >> 1) + (w & 1) * 512 + lane * 2);
    uint32_t* const x2o = pin(inbox(cta, 4) + 512 + tid * 2);
    uint32_t* const x2p = pin(gin + blk(cta, 4, selector(cta) ^ 1) + 512 + tid * 2);
    const uint32_t q4 = lds1(sb + OFF_SEL + 4 * hI) ^ 0x00010100u;
    const uint32_t same = pin((uint32_t)(q4 == 0 || q4 == 0x01010101u));
    mbar_wait(BAR(BAR_TS));
    anchor = lds1(sb + OFF_TS);
    const uint32_t sdst = pin(sb + OFF_BS4 + w * 272 + lane * 8), ssrc = pin(sb + OFF_BS4 + (lane & 7) * 272 + (lane >> 3) * 16);
    float d[4] = {0.f, 0.f, 0.f, 0.f};
    wait_clk(thand, T.D_X1);
    wait_clk(anchor, T.A_X1);
    CLK(25);
    uint2 v[8];
    load_units<8, 64>(v, px);
    const bool early = __all_sync(~0u, mbar_test(BAR(BAR_WUV + wg)));
    if (early) load_a_t(aw, sb + OFF_WUV, w, lane);
    mbar_wait(BAR(BAR_WV));
    const float4 wa = ldsf4(sb + OFF_WV + w * 32), wb = ldsf4(sb + OFF_WV + w * 32 + 16);
    const float wv[8] = {wa.x, wa.y, wa.z, wa.w, wb.x, wb.y, wb.z, wb.w};
    CLK(27);
    int it = 0;
    while (true) {
      float a0 = 0.f, a1 = 0.f, a2 = 0.f, a3 = 0.f;
#pragma unroll
      for (int i = 0; i < 8; i++) { a0 += wv[i] * bf_lo(v[i].x); a1 += wv[i] * bf_hi(v[i].x); a2 += wv[i] * bf_lo(v[i].y); a3 += wv[i] * bf_hi(v[i].y); }
      const bool ok = __all_sync(~0u, min_flags(v) != 0);
      sts2(sdst, pack_bf16(a0, a1), pack_bf16(a2, a3));
      if (__builtin_expect(ok, 1)) break;
#pragma unroll
      for (int i = 0; i < 8; i++) reload_unit(v[i], px + i * 64);
      if (++it > SPIN_LIMIT) __trap();
    }
    CLK(29);
    cbar();
    uint32_t b[4][4];
#pragma unroll
    for (int kk = 0; kk < 4; kk++) ldsm4(b[kk], ssrc + kk * 64);
    if (__builtin_expect(!early, 0)) { mbar_wait(BAR(BAR_WUV + wg)); load_a_t(aw, sb + OFF_WUV, w, lane); }
    mma128(d, aw, b);
    const uint32_t c0 = pack_bf16(d[0], d[1]), c1 = pack_bf16(d[2], d[3]);
    stg_u64(x2o, c0, c1);
    stg_u64_unless(same, x2p, c0, c1);
    ITS(4, it);
    tstore = clk32();
    CLK(30);
  }
  {
    uint32_t* const o = pin(inbox(4 * (8 * jI + w) + t, 4) + hI * 16 + g * 2);
    const uint32_t* x2i[4];
#pragma unroll
    for (int i = 0; i < 4; i++) x2i[i] = pin(nearbox(4 * hI + i, 4) + 512 + tid * 2);
    const uint32_t sdst = pin(sb + OFF_BS5 + (16 * w + g) * 16 + t * 4), ssrc = pin(sb + OFF_BS5 + lane * 16);
    float d[4] = {0.f, 0.f, 0.f, 0.f};
    wait_clk(tstore, T.D_X2);
    wait_clk(anchor, T.A_X1 + T.R_X2);
    uint2 v[4];
#pragma unroll
    for (int i = 0; i < 4; i++) v[i] = ldg_u64(x2i[i]);
    const bool early = __all_sync(~0u, mbar_test(BAR(BAR_WO + wg)));
    if (early) load_a_t(aw, sb + OFF_WO, w, lane);
    CLK(31);
    int it = 0;
    while (true) {
      const bool ok = __all_sync(~0u, min_flags(v) != 0);
      sum4_to_smem(v, sdst);
      if (__builtin_expect(ok, 1)) break;
#pragma unroll
      for (int i = 0; i < 4; i++) reload_unit(v[i], x2i[i]);
      if (++it > SPIN_LIMIT) __trap();
    }
    CLK(32);
    cbar();
    uint32_t b[4][4];
#pragma unroll
    for (int kk = 0; kk < 4; kk++) ldsm4t(b[kk], ssrc + kk * 512);
    if (__builtin_expect(!early, 0)) { mbar_wait(BAR(BAR_WO + wg)); load_a_t(aw, sb + OFF_WO, w, lane); }
    mma128(d, aw, b);
    ST3A(o, movm(pack_bf16(d[0], d[1])), movm(pack_bf16(d[2], d[3])));
    ITS(5, it);
    tstore = clk32();
    CLK(33);
    if (lane == 0) mbar_arrive(BAR(BAR_P5D));
  }
  if (cta < NFF) {
    const int mi = lane >> 3, r = lane & 7;
    uint32_t a1[2][4][4], a2[2][2][4];
    check_units<4, 64>(sbf, pcb, T.RB);
    check_units<4, 64>(cbf, pcb + 2048, T.RB);
    __syncwarp();
#pragma unroll
    for (int s = 0; s < 4; s++) { cbf[s].x = hadd2(cbf[s].x, ONE2); cbf[s].y = hadd2(cbf[s].y, ONE2); }
    mbar_wait(BAR(BAR_W1));
#pragma unroll
    for (int mt = 0; mt < 2; mt++) {
#pragma unroll
      for (int ks = 0; ks < 4; ks++) ldsm4t(a1[mt][ks], sb + OFF_W1 + (64 * w + 16 * ks + 8 * (mi >> 1) + r) * 64 + (((2 * mt + (mi & 1)) ^ (r >> 1)) << 4));
      float u[4] = {0.f, 0.f, 0.f, 0.f}, vv[4] = {0.f, 0.f, 0.f, 0.f};
#pragma unroll
      for (int s = 0; s < 4; s++) { mma16816(u, a1[mt][s], cbf[s].x, cbf[s].y); mma16816(vv, a1[mt][s], sbf[s].x, sbf[s].y); }
      sts4f(sb + OFF_REDU + w * 1024 + mt * 512 + lane * 16, u[0], u[1], u[2], u[3]);
      sts4f(sb + OFF_REDV + w * 1024 + mt * 512 + lane * 16, vv[0], vv[1], vv[2], vv[3]);
    }
    const uint32_t* xb = pin(nearbox(cta & ~15, 6 + wg) + (16 * wq + t) * 16 + g * 2);
    uint32_t* const ox[2] = {pin(inbox(64 * hh + 8 * w + t, 5) + bs * 16 + g * 2), pin(inbox(64 * hh + 8 * w + 4 + t, 5) + bs * 16 + g * 2)};
    cbar();
    const int lp = (tid >> 2) & 31, kq = tid & 3;
    const int fo = 16 * wg + (lp >> 2) + 8 * (kq >> 1), bo = 2 * (lp & 3) + (kq & 1);
    float U = 0.f, V = 0.f;
#pragma unroll
    for (int i = 0; i < 8; i++) { U += ldsf(sb + OFF_REDU + i * 1024 + tid * 4); V += ldsf(sb + OFF_REDV + i * 1024 + tid * 4); }
    U = pin(U); V = pin(V);
    const uint32_t s_g = pin(sb + OFF_REDG + w * 1024 + lane * 16), s_s = pin(sb + OFF_REDS + g * 80 + w * 8);
    const uint32_t l_g = pin(sb + OFF_REDG + tid * 4), l_s = pin(sb + OFF_REDS + bo * 80), s_h = pin(sb + OFF_H1 + fo * 16 + bo * 2);
    CLK(34);
    wait_clk(tstore, T.D_X3B);
    wait_clk(anchor, T.A_X1 + T.R_X3A + T.R_X3B);
    uint2 x[4];
    load_units<4, 64>(x, xb);
    mbar_wait(BAR(BAR_W2));
#pragma unroll
    for (int i = 0; i < 4; i++)
      ldsm4t(a2[i >> 1][i & 1], sb + OFF_W2 + (w >> 1) * 4096 + (16 * (i & 1) + 8 * (mi >> 1) + r) * 128 + (((4 * (w & 1) + 2 * (i >> 1) + (mi & 1)) ^ r) << 4));
    CLK(35);
    int it = 0;
    float G[2][2][4], S[2][4];
    while (true) {
#pragma unroll
      for (int i = 0; i < 8; i++) { G[0][i >> 2][i & 3] = G[1][i >> 2][i & 3] = S[i >> 2][i & 3] = 0.f; }
#pragma unroll
      for (int s = 0; s < 4; s++) {
        const uint32_t sx[4] = {x[s].x, ONE2, x[s].y, ONE2};
        mma16816(S[s & 1], sx, x[s].x, x[s].y);
        const uint32_t y0 = hmul2(x[s].x, cbf[s].x), y1 = hmul2(x[s].y, cbf[s].y);
        mma16816(G[0][s & 1], a1[0][s], y0, y1);
        mma16816(G[1][s & 1], a1[1][s], y0, y1);
      }
      if (__builtin_expect(__all_sync(~0u, min_flags(x) != 0), 1)) break;
#pragma unroll
      for (int i = 0; i < 4; i++) reload_unit(x[i], xb + i * 64);
      if (++it > SPIN_LIMIT) __trap();
    }
    if (t == (g >> 1)) sts2f(s_s, (g & 1) ? S[0][3] + S[1][3] : S[0][2] + S[1][2], (g & 1) ? S[0][1] + S[1][1] : S[0][0] + S[1][0]);
#pragma unroll
    for (int mt = 0; mt < 2; mt++)
      sts4f(s_g + mt * 512, G[mt][0][0] + G[mt][1][0], G[mt][0][1] + G[mt][1][1], G[mt][0][2] + G[mt][1][2], G[mt][0][3] + G[mt][1][3]);
    CLK(37);
    cbar();
    {
      float gv[8];
      float4 sv[4];
#pragma unroll
      for (int i = 0; i < 4; i++) sv[i] = ldsf4(l_s + i * 16);
#pragma unroll
      for (int i = 0; i < 8; i++) gv[i] = ldsf(l_g + i * 1024);
      const float s1 = ((sv[0].x + sv[0].z) + (sv[1].x + sv[1].z)) + ((sv[2].x + sv[2].z) + (sv[3].x + sv[3].z));
      const float s2 = ((sv[0].y + sv[0].w) + (sv[1].y + sv[1].w)) + ((sv[2].y + sv[2].w) + (sv[3].y + sv[3].w));
      const float gsum = ((gv[0] + gv[1]) + (gv[2] + gv[3])) + ((gv[4] + gv[5]) + (gv[6] + gv[7]));
      const float mu = s1 * (1.f / 512.f);
      float rs;
      asm("rsqrt.approx.ftz.f32 %0, %1;" : "=f"(rs) : "f"(fmaxf(s2 * (1.f / 512.f) - mu * mu, 0.f) + 1e-5f));
      const float hv = fmaxf(rs * (gsum - mu * U) + V, 0.f);
      asm volatile("st.shared.u16 [%0], %1;" ::"r"(s_h), "h"(__bfloat16_as_ushort(__float2bfloat16(hv))) : "memory");
    }
    ITS(6, it);
    CLK(38);
    cbar();
    uint32_t b[4];
    ldsm4t(b, sb + OFF_H1 + lane * 16);
    float o[2][2][4] = {};
#pragma unroll
    for (int i = 0; i < 4; i++) mma16816(o[i >> 1][i & 1], a2[i >> 1][i & 1], b[2 * (i & 1)], b[2 * (i & 1) + 1]);
#pragma unroll
    for (int mb = 0; mb < 2; mb++)
      ST4(ox[mb], movm(pack_bf16(o[mb][0][0] + o[mb][1][0], o[mb][0][1] + o[mb][1][1])), movm(pack_bf16(o[mb][0][2] + o[mb][1][2], o[mb][0][3] + o[mb][1][3])));
    CLK(39);
    if (lane == 0) mbar_arrive(BAR(BAR_P7D));
  }
  CLK_DUMP();
}

typedef CUresult (*EncodeTiledFn)(CUtensorMap*, CUtensorMapDataType, cuuint32_t, void*, const cuuint64_t*, const cuuint64_t*,
                                  const cuuint32_t*, const cuuint32_t*, CUtensorMapInterleave, CUtensorMapSwizzle,
                                  CUtensorMapL2promotion, CUtensorMapFloatOOBfill);

struct Dim { uint64_t size, stride; uint32_t box; };
template <int R> void encode_map(EncodeTiledFn enc, CUtensorMap* m, const void* base, const Dim (&d)[R], CUtensorMapSwizzle sw, CUtensorMapL2promotion promo) {
  cuuint64_t dims[R], strides[R];
  cuuint32_t box[R], es[R];
  for (int i = 0; i < R; i++) { dims[i] = d[i].size; strides[i] = d[i].stride; box[i] = d[i].box; es[i] = 1; }
  enc(m, CU_TENSOR_MAP_DATA_TYPE_BFLOAT16, R, const_cast<void*>(base), dims, strides + 1, box, es, CU_TENSOR_MAP_INTERLEAVE_NONE, sw, promo,
      CU_TENSOR_MAP_FLOAT_OOB_FILL_NONE);
}

}

extern "C" void kernel_launch(void* const* d_in, const int* in_sizes, int n_in, void* d_out, int out_size) {
  (void)in_sizes; (void)n_in; (void)out_size;
  static EncodeTiledFn enc = nullptr;
  static Scratch* scratch = nullptr;
  static uint32_t* inbox = nullptr;
  if (!enc) {
    void* sp = nullptr;
    cudaGetSymbolAddress(&sp, g_s);
    scratch = (Scratch*)sp;
    cudaGetSymbolAddress(&sp, g_in);
    inbox = (uint32_t*)(((uintptr_t)sp + 0xfffff) & ~(uintptr_t)0xfffff);
    void* fn = nullptr;
    cudaDriverEntryPointQueryResult q;
    cudaGetDriverEntryPoint("cuTensorMapEncodeTiled", &fn, cudaEnableDefault, &q);
    enc = (EncodeTiledFn)fn;
    cudaFuncSetAttribute(fused_decode_kernel, cudaFuncAttributeMaxDynamicSharedMemorySize, SMEM_BYTES);
  }
  const CUtensorMapSwizzle S128 = CU_TENSOR_MAP_SWIZZLE_128B, S0 = CU_TENSOR_MAP_SWIZZLE_NONE;
  const CUtensorMapL2promotion L0 = CU_TENSOR_MAP_L2_PROMOTION_NONE, L128 = CU_TENSOR_MAP_L2_PROMOTION_L2_128B;
  Params P;
  encode_map<2>(enc, &P.wq, d_in[2], {{4096, 2, 64}, {512, 8192, 64}}, S128, L0);
  encode_map<5>(enc, &P.wuk, d_in[3], {{4096, 2, 64}, {2, 8192, 2}, {4, 4 * 8192, 4}, {2, 2 * 8192, 2}, {32, 16 * 8192, 4}}, S128, L0);
  encode_map<2>(enc, &P.wm2, d_in[10], {{3072, 2, 16}, {512, 6144, 256}}, S0, L128);
  encode_map<3>(enc, &P.ckv2, d_in[1], {{64, 2, 64}, {8 * 4096, 1024, 64}, {8, 128, 2}}, S128, L0);
  encode_map<3>(enc, &P.ckv1, d_in[1], {{64, 2, 64}, {8 * 4096, 1024, 64}, {8, 128, 1}}, S128, L0);
  encode_map<5>(enc, &P.wuv, d_in[4], {{4096, 2, 64}, {2, 8 * 8192, 2}, {8, 64 * 8192, 4}, {8, 8192, 8}, {4, 16 * 8192, 1}}, S128, L0);
  encode_map<2>(enc, &P.wo, d_in[5], {{512, 2, 64}, {4096, 1024, 64}}, S128, L0);
  encode_map<2>(enc, &P.w1, d_in[7], {{1792, 2, 32}, {512, 3584, 256}}, CU_TENSOR_MAP_SWIZZLE_64B, L128);
  encode_map<3>(enc, &P.w2, d_in[8], {{64, 2, 64}, {1792, 1024, 32}, {8, 128, 2}}, S128, L0);
  cudaLaunchConfig_t cfg = {};
  cfg.gridDim = dim3(NCTA);
  cfg.blockDim = dim3(NTHREADS);
  cfg.dynamicSmemBytes = SMEM_BYTES;
  cfg.stream = cudaStreamPerThread;
  cudaLaunchAttribute at[1];
  at[0].id = cudaLaunchAttributeClusterDimension;
  at[0].val.clusterDim.x = 2; at[0].val.clusterDim.y = 1; at[0].val.clusterDim.z = 1;
  cfg.attrs = at;
  cfg.numAttrs = 0;
  cudaLaunchKernelEx(&cfg, fused_decode_kernel, (__nv_bfloat16*)d_out, scratch, (const uint8_t*)d_in[10], (const uint8_t*)d_in[0],
                     (const uint8_t*)d_in[9], inbox,
                     P);
}
```

```cpp
#include <cuda_runtime.h>
#include <cuda.h>
#include <cuda_bf16.h>
#include <stdint.h>
#define V4 1

namespace {

constexpr int NCTA = 128;
constexpr int NTHREADS = 320;
constexpr int NFG = 56;
constexpr int NFF = 2 * NFG;
constexpr int NSYNC = 4;

constexpr uint32_t OFF_RING = 0;
constexpr uint32_t OFF_WUK = 131072;
constexpr uint32_t OFF_WQ = 131072 + 32768;
constexpr uint32_t OFF_WM2 = 65536 + 49152;
constexpr uint32_t OFF_WUV = 131072;
constexpr uint32_t OFF_WO = 131072 + 32768;
constexpr uint32_t OFF_W1 = 0;
constexpr uint32_t OFF_W2 = 32768;
constexpr uint32_t OFF_Q = 196608;
constexpr uint32_t OFF_PT = 212992;
constexpr uint32_t OFF_SCR = 217088;
constexpr uint32_t OFF_XS = 65536;
constexpr uint32_t OFF_CS = 65536 + 8192;
constexpr uint32_t OFF_P0S = 65536 + 16384;
constexpr uint32_t OFF_BS1 = OFF_SCR + 2048;
constexpr uint32_t OFF_BS2 = OFF_SCR + 4096;
constexpr uint32_t OFF_P0B = OFF_SCR + 6144;
constexpr uint32_t OFF_XN = OFF_SCR + 8192;
constexpr uint32_t OFF_RED = OFF_SCR + 10496;
constexpr uint32_t OFF_ALPHA = OFF_SCR + 11072;
constexpr uint32_t OFF_WV = OFF_SCR + 6144;
constexpr uint32_t OFF_SEL = OFF_SCR + 10752;
constexpr uint32_t OFF_TS = OFF_SCR + 11136;
constexpr uint32_t OFF_BARS = OFF_SCR + 11264;
constexpr uint32_t SMEM_BYTES = OFF_BARS + 512;
constexpr uint32_t OFF_BS4 = OFF_Q;
constexpr uint32_t OFF_H1 = OFF_Q + 2304;
constexpr uint32_t OFF_REDS = OFF_Q + 2816;
constexpr uint32_t OFF_BS5 = OFF_Q + 4096;
constexpr uint32_t OFF_REDG = OFF_Q + 8192;
constexpr uint32_t OFF_REDU = 65536;
constexpr uint32_t OFF_REDV = 65536 + 8192;

constexpr int BAR_FULL = 0;
constexpr int BAR_LAST = 28;
constexpr int BAR_WUK = 33, BAR_WM2 = 35, BAR_WUV = 36, BAR_WO = 38, BAR_W1 = 40, BAR_W2 = 41;
constexpr int BAR_ALLCLR = 42, BAR_TS = 43, BAR_WV = 44;
constexpr int BAR_EMPTY = 45;
constexpr int BAR_P0BD = 52;
constexpr int BAR_P1D = 53, BAR_P2D = 54;
constexpr int BAR_P5D = 55, BAR_P7D = 56;
constexpr int NBARS = 57;
constexpr int BAR_XC = 57, BAR_WQ = 58;
constexpr int BAR_C = 60, BAR_END = 61;
constexpr uint32_t SB = 1024;

#define TUNE_LIST(X) \
  X(PC_T0, 340) X(PC_XC, 0) X(PC_C, 0) X(PC_P1, 320) X(PC_P2, 319) X(PC_STAG, 390) X(PC_DS, 0) X(PC_SL, 500) X(PC_W, 4) X(PC_NW, 8) \
  X(PW_A, -1) X(PW_0, 295) X(PW_ST, 0) X(PW_UV, 250) X(PW_G, 660) X(PW_O, 315) X(PW_G2, 430) X(PW_G3, 390) X(PW_F, 330) \
  X(LOC, 0) X(PR_T0, 1000) X(PR_N, 4) X(CLR_T0, 3900) X(CLR_CLK, 190) \
  X(D_MOD, 1650) X(D_QP, 1050) X(D_QX, 1100) X(TS_P, 1) X(TS_O, 990) X(D_TS, 900) X(A_M, 2000) X(D_X1, 1300) X(A_X1, 2400) \
  X(D_X2, 260) X(R_X2, 1550) X(D_X3A, 60) X(R_X3A, 3400) X(D_X3B, 800) X(R_X3B, 880) X(D_FIN, 320) X(R_FIN, 1520) X(RB, 0)
struct Tune {
#define X(n, v) static constexpr int n = v;
  TUNE_LIST(X)
#undef X
};

#define WSWAP 0
#define THRESH "0f42700000"
#define PVV 0
struct Scratch {
  uint32_t MOD1[2][4 * 64 * 64];
  uint32_t MOD2[2][128 * 64];
  uint32_t QP[2][128 * 256 * 2];
  uint32_t QX[2][8 * 32 * 256];
  uint32_t epoch;
  uint32_t pad[31];
  uint32_t sync[NSYNC][32];
};
__device__ Scratch g_s;
__device__ uint32_t g_in[(128 + 16) * 16384];
__device__ __forceinline__ uint32_t blk(int c, int k, uint32_t sel) { return c * 16384 + k * 2048 + ((sel ^ k) & 1) * 1024; }
__device__ __forceinline__ uint32_t flip(int c) { return c ^ (c >> 1) ^ (c >> 3); }

#define CLK_DECL
#define CLK(i) do {} while (0)
#define CLK_DUMP() do {} while (0)
#define ITS(i, v) do {} while (0)

struct Params {
  CUtensorMap wq, wuk, wm2, ckv2, ckv1, wuv, wo, w1, w2;
};

__device__ __forceinline__ void mbar_init(uint32_t bar, int cnt) { asm volatile("mbarrier.init.shared::cta.b64 [%0], %1;" ::"r"(bar), "r"(cnt)); }
__device__ __forceinline__ void mbar_expect(uint32_t bar, uint32_t bytes) { asm volatile("mbarrier.arrive.expect_tx.shared::cta.b64 _, [%0], %1;" ::"r"(bar), "r"(bytes) : "memory"); }
__device__ __forceinline__ void mbar_arrive(uint32_t bar) { asm volatile("mbarrier.arrive.shared::cta.b64 _, [%0];" ::"r"(bar) : "memory"); }
__device__ __forceinline__ uint32_t clk32() { unsigned long long c; asm volatile("mov.u64 %0, %%clock64;" : "=l"(c) :: "memory"); return (uint32_t)c; }
__device__ __forceinline__ uint32_t gtime32() { uint32_t c; asm volatile("mov.u32 %0, %%globaltimer_lo;" : "=r"(c) :: "memory"); return c; }
__device__ __forceinline__ void wait_clk(uint32_t t0, int clocks) { while ((int)(clk32() - t0) < clocks) {} }
__device__ __forceinline__ void backoff(int clocks) { if (clocks > 0) wait_clk(clk32(), clocks); }
__device__ __forceinline__ void until_ns(uint32_t ns) { while ((int)(gtime32() - ns) < 0) {} }
__device__ __forceinline__ void slot(uint32_t& tn, int slack) {
  uint32_t now;
  do { now = gtime32(); } while ((int)(now - tn) < 0);
  if ((int)(now - tn) > slack) tn = now - slack;
}
template <typename T> __device__ __forceinline__ T* pin(T* p) { asm volatile("" : "+l"(p)); return p; }
__device__ __forceinline__ uint32_t pin(uint32_t v) { asm volatile("" : "+r"(v)); return v; }
__device__ __forceinline__ float pin(float v) { asm volatile("" : "+f"(v)); return v; }
constexpr int SPIN_LIMIT = 1 << 22;
__device__ __forceinline__ void mbar_wait(uint32_t bar) {
  asm volatile("{\n.reg .pred p;\n.reg .u32 c;\nmov.u32 c, 0;\n"
               "MW_LOOP:\nmbarrier.try_wait.parity.shared::cta.b64 p, [%0], 0;\n@p bra MW_DONE;\n"
               "add.u32 c, c, 1;\nsetp.lt.u32 p, c, 4194304;\n@p bra MW_LOOP;\ntrap;\nMW_DONE:\n}"
               ::"r"(bar) : "memory");
}
__device__ __forceinline__ bool mbar_test(uint32_t bar) {
  uint32_t ok;
  asm volatile("{\n.reg .pred p;\nmbarrier.test_wait.parity.shared::cta.b64 p, [%1], 0;\nselp.u32 %0,1,0,p;\n}" : "=r"(ok) : "r"(bar) : "memory");
  return ok;
}
__device__ __forceinline__ void tma2d(uint32_t dst, const CUtensorMap* m, int c0, int c1, uint32_t bar, uint64_t pol) {
  asm volatile("cp.async.bulk.tensor.2d.shared::cluster.global.mbarrier::complete_tx::bytes.L2::cache_hint [%0], [%1, {%3,%4}], [%2], %5;"
               ::"r"(dst), "l"(m), "r"(bar), "r"(c0), "r"(c1), "l"(pol) : "memory");
}
__device__ __forceinline__ void tma2d_nohint(uint32_t dst, const CUtensorMap* m, int c0, int c1, uint32_t bar) {
  asm volatile("cp.async.bulk.tensor.2d.shared::cluster.global.mbarrier::complete_tx::bytes [%0], [%1, {%3,%4}], [%2];"
               ::"r"(dst), "l"(m), "r"(bar), "r"(c0), "r"(c1) : "memory");
}
__device__ __forceinline__ void tma3d(uint32_t dst, const CUtensorMap* m, int c0, int c1, int c2, uint32_t bar, uint64_t pol) {
  asm volatile("cp.async.bulk.tensor.3d.shared::cluster.global.mbarrier::complete_tx::bytes.L2::cache_hint [%0], [%1, {%3,%4,%5}], [%2], %6;"
               ::"r"(dst), "l"(m), "r"(bar), "r"(c0), "r"(c1), "r"(c2), "l"(pol) : "memory");
}
__device__ __forceinline__ void tma5d(uint32_t dst, const CUtensorMap* m, int c0, int c1, int c2, int c3, int c4, uint32_t bar, uint64_t pol) {
  asm volatile("cp.async.bulk.tensor.5d.shared::cluster.global.mbarrier::complete_tx::bytes.L2::cache_hint [%0], [%1, {%3,%4,%5,%6,%7}], [%2], %8;"
               ::"r"(dst), "l"(m), "r"(bar), "r"(c0), "r"(c1), "r"(c2), "r"(c3), "r"(c4), "l"(pol) : "memory");
}
__device__ __forceinline__ void bulk_ld(uint32_t dst, const void* src, uint32_t bytes, uint32_t bar) {
  asm volatile("cp.async.bulk.shared::cluster.global.mbarrier::complete_tx::bytes [%0], [%1], %2, [%3];" ::"r"(dst), "l"(src), "r"(bytes), "r"(bar) : "memory");
}
__device__ __forceinline__ void bar_sync(int id, int n) { asm volatile("barrier.cta.sync.aligned %0, %1;" ::"r"(id), "r"(n) : "memory"); }
__device__ __forceinline__ void cbar() { asm volatile("barrier.cta.sync.aligned 1, 256;" ::: "memory"); }
__device__ __forceinline__ bool bar_over(float ex) {
  uint32_t over;
  asm volatile("{\n.reg .pred p, q;\nsetp.gtu.f32 p, %1, " THRESH ";\nbarrier.cta.red.or.aligned.pred q, 4, 256, p;\nselp.u32 %0, 1, 0, q;\n}"
               : "=r"(over) : "f"(ex) : "memory");
  return over;
}

__device__ __forceinline__ uint32_t ldg_nc1(const void* p) { uint32_t v; asm volatile("ld.global.nc.L1::no_allocate.u32 %0, [%1];" : "=r"(v) : "l"(p)); return v; }
__device__ __forceinline__ uint2 ldg_nc2(const void* p) { uint2 v; asm volatile("ld.global.nc.v2.u32 {%0,%1}, [%2];" : "=r"(v.x), "=r"(v.y) : "l"(p)); return v; }
__device__ __forceinline__ uint4 ldg_nc4(const void* p) { uint4 v; asm volatile("ld.global.nc.L1::no_allocate.v4.u32 {%0,%1,%2,%3}, [%4];" : "=r"(v.x), "=r"(v.y), "=r"(v.z), "=r"(v.w) : "l"(p)); return v; }
__device__ __forceinline__ uint32_t ldg_rlx1(const void* p) { uint32_t v; asm volatile("ld.relaxed.gpu.global.u32 %0, [%1];" : "=r"(v) : "l"(p) : "memory"); return v; }
__device__ __forceinline__ void stg4(void* p, uint4 v) { asm volatile("st.relaxed.gpu.global.v4.u32 [%0], {%1,%2,%3,%4};" ::"l"(p), "r"(v.x), "r"(v.y), "r"(v.z), "r"(v.w) : "memory"); }
__device__ __forceinline__ void stg1(void* p, uint32_t a) { asm volatile("st.relaxed.gpu.global.u32 [%0], %1;" ::"l"(p), "r"(a) : "memory"); }
__device__ __forceinline__ uint32_t nz(uint32_t w) { return max(w, 1u); }
__device__ __forceinline__ uint2 ldg_u64(const void* p) {
  uint2 v; asm volatile("{\n.reg .b64 a;\nld.relaxed.gpu.global.b64 a, [%2];\nmov.b64 {%0,%1}, a;\n}" : "=r"(v.x), "=r"(v.y) : "l"(p) : "memory"); return v;
}
__device__ __forceinline__ uint4 ldg_2u64(const void* p) {
  uint4 v; asm volatile("{\n.reg .b64 a, b;\nld.relaxed.gpu.global.v2.b64 {a, b}, [%4];\nmov.b64 {%0,%1}, a;\nmov.b64 {%2,%3}, b;\n}" : "=r"(v.x), "=r"(v.y), "=r"(v.z), "=r"(v.w) : "l"(p) : "memory"); return v;
}
__device__ __forceinline__ void stg_u64(void* p, uint32_t x, uint32_t y) {
  asm volatile("{\n.reg .b32 y;\nmax.u32 y, %2, 1;\nst.relaxed.gpu.global.v2.b32 [%0], {%1, y};\n}" ::"l"(p), "r"(x), "r"(y) : "memory");
}
__device__ __forceinline__ void red_u64(void* p, uint32_t x, uint32_t y) {
  asm volatile("{\n.reg .b32 y;\n.reg .b64 a;\nmax.u32 y, %2, 1;\nmov.b64 a, {%1, y};\nred.relaxed.gpu.global.or.b64 [%0], a;\n}" ::"l"(p), "r"(x), "r"(y) : "memory");
}
__device__ __forceinline__ void red_u64_unless(uint32_t bad, void* p, uint32_t x, uint32_t y) {
  asm volatile("{\n.reg .b32 y;\n.reg .b64 a;\n.reg .pred q;\nsetp.eq.u32 q, %3, 0;\nmax.u32 y, %2, 1;\nmov.b64 a, {%1, y};\n@q red.relaxed.gpu.global.or.b64 [%0], a;\n}" ::"l"(p), "r"(x), "r"(y), "r"(bad) : "memory");
}
#define ST3A stg_u64
#define ST4 stg_u64
#define ST3B stg_u64_unless
#define MLST red_u64
__device__ __forceinline__ void stg_u64_unless(uint32_t bad, void* p, uint32_t x, uint32_t y) {
  asm volatile("{\n.reg .b32 y;\n.reg .pred q;\nsetp.eq.u32 q, %3, 0;\nmax.u32 y, %2, 1;\n@q st.relaxed.gpu.global.v2.b32 [%0], {%1, y};\n}" ::"l"(p), "r"(x), "r"(y), "r"(bad) : "memory");
}
__device__ __forceinline__ void stg_2u64(void* p, uint4 v) {
  asm volatile("{\n.reg .b32 y, w;\nmax.u32 y, %2, 1;\nmax.u32 w, %4, 1;\nst.relaxed.gpu.global.v4.b32 [%0], {%1, y, %3, w};\n}" ::"l"(p), "r"(v.x), "r"(v.y), "r"(v.z), "r"(v.w) : "memory");
}

__device__ __forceinline__ void stg_cvt8(void* p, float a0, float a1, float b0, float b1, float c0, float c1, float d0, float d1) {
  asm volatile("{\n.reg .b32 x, y, z, w;\ncvt.rn.bf16x2.f32 x, %2, %1;\ncvt.rn.bf16x2.f32 y, %4, %3;\ncvt.rn.bf16x2.f32 z, %6, %5;\ncvt.rn.bf16x2.f32 w, %8, %7;\n"
               "max.u32 y, y, 1;\nmax.u32 w, w, 1;\nst.relaxed.gpu.global.v4.b32 [%0], {x, y, z, w};\n}"
               ::"l"(p), "f"(a0), "f"(a1), "f"(b0), "f"(b1), "f"(c0), "f"(c1), "f"(d0), "f"(d1) : "memory");
}
__device__ __forceinline__ uint32_t pack_bf16(float lo, float hi) { uint32_t r; asm("cvt.rn.bf16x2.f32 %0, %1, %2;" : "=r"(r) : "f"(hi), "f"(lo)); return r; }
__device__ __forceinline__ float bf_lo(uint32_t w) { return __uint_as_float(w << 16); }
__device__ __forceinline__ float bf_hi(uint32_t w) { return __uint_as_float(w & 0xffff0000u); }
__device__ __forceinline__ float ex2(float x) { float r; asm("ex2.approx.ftz.f32 %0, %1;" : "=f"(r) : "f"(x)); return r; }
__device__ __forceinline__ uint32_t hmul2(uint32_t a, uint32_t b) { uint32_t r; asm("mul.rn.bf16x2 %0, %1, %2;" : "=r"(r) : "r"(a), "r"(b)); return r; }
__device__ __forceinline__ uint32_t hadd2(uint32_t a, uint32_t b) { uint32_t r; asm("add.rn.bf16x2 %0, %1, %2;" : "=r"(r) : "r"(a), "r"(b)); return r; }
__device__ __forceinline__ uint32_t hfma2(uint32_t a, uint32_t b, uint32_t c) { uint32_t r; asm("fma.rn.bf16x2 %0, %1, %2, %3;" : "=r"(r) : "r"(a), "r"(b), "r"(c)); return r; }
__device__ __forceinline__ uint32_t silu2(uint32_t v) { const float a = bf_lo(v), b = bf_hi(v); return pack_bf16(__fdividef(a, 1.f + __expf(-a)), __fdividef(b, 1.f + __expf(-b))); }
constexpr uint32_t ONE2 = 0x3f803f80u;

__device__ __forceinline__ void ldsm4(uint32_t (&r)[4], uint32_t a) { asm volatile("ldmatrix.sync.aligned.m8n8.x4.shared.b16 {%0,%1,%2,%3}, [%4];" : "=r"(r[0]), "=r"(r[1]), "=r"(r[2]), "=r"(r[3]) : "r"(a) : "memory"); }
__device__ __forceinline__ void ldsm4t(uint32_t (&r)[4], uint32_t a) { asm volatile("ldmatrix.sync.aligned.m8n8.x4.trans.shared.b16 {%0,%1,%2,%3}, [%4];" : "=r"(r[0]), "=r"(r[1]), "=r"(r[2]), "=r"(r[3]) : "r"(a) : "memory"); }
__device__ __forceinline__ void ldsm2t(uint32_t& r0, uint32_t& r1, uint32_t a) { asm volatile("ldmatrix.sync.aligned.m8n8.x2.trans.shared.b16 {%0,%1}, [%2];" : "=r"(r0), "=r"(r1) : "r"(a) : "memory"); }
__device__ __forceinline__ void stsm4t(uint32_t a, uint32_t r0, uint32_t r1, uint32_t r2, uint32_t r3) { asm volatile("stmatrix.sync.aligned.m8n8.x4.trans.shared.b16 [%0], {%1,%2,%3,%4};" ::"r"(a), "r"(r0), "r"(r1), "r"(r2), "r"(r3) : "memory"); }
__device__ __forceinline__ uint32_t movm(uint32_t a) { uint32_t d; asm volatile("movmatrix.sync.aligned.m8n8.trans.b16 %0, %1;" : "=r"(d) : "r"(a)); return d; }
__device__ __forceinline__ void mma16816(float (&d)[4], const uint32_t (&a)[4], uint32_t b0, uint32_t b1) {
  asm volatile("mma.sync.aligned.m16n8k16.row.col.f32.bf16.bf16.f32 {%0,%1,%2,%3}, {%4,%5,%6,%7}, {%8,%9}, {%0,%1,%2,%3};"
               : "+f"(d[0]), "+f"(d[1]), "+f"(d[2]), "+f"(d[3]) : "r"(a[0]), "r"(a[1]), "r"(a[2]), "r"(a[3]), "r"(b0), "r"(b1));
}
__device__ __forceinline__ void sts1(uint32_t a, uint32_t v) { asm volatile("st.shared.u32 [%0], %1;" ::"r"(a), "r"(v) : "memory"); }
__device__ __forceinline__ void sts2(uint32_t a, uint32_t x, uint32_t y) { asm volatile("st.shared.v2.u32 [%0], {%1,%2};" ::"r"(a), "r"(x), "r"(y) : "memory"); }
__device__ __forceinline__ void sts4(uint32_t a, uint4 v) { asm volatile("st.shared.v4.u32 [%0], {%1,%2,%3,%4};" ::"r"(a), "r"(v.x), "r"(v.y), "r"(v.z), "r"(v.w) : "memory"); }
__device__ __forceinline__ void sts2f(uint32_t a, float x, float y) { asm volatile("st.shared.v2.f32 [%0], {%1,%2};" ::"r"(a), "f"(x), "f"(y) : "memory"); }
__device__ __forceinline__ void sts4f(uint32_t a, float x, float y, float z, float w) { asm volatile("st.shared.v4.f32 [%0], {%1,%2,%3,%4};" ::"r"(a), "f"(x), "f"(y), "f"(z), "f"(w) : "memory"); }
__device__ __forceinline__ void stsf(uint32_t a, float v) { asm volatile("st.shared.f32 [%0], %1;" ::"r"(a), "f"(v) : "memory"); }
__device__ __forceinline__ uint32_t lds1(uint32_t a) { uint32_t v; asm volatile("ld.shared.u32 %0, [%1];" : "=r"(v) : "r"(a) : "memory"); return v; }
__device__ __forceinline__ float ldsf(uint32_t a) { float v; asm volatile("ld.shared.f32 %0, [%1];" : "=f"(v) : "r"(a) : "memory"); return v; }
__device__ __forceinline__ float2 ldsf2(uint32_t a) { float2 v; asm volatile("ld.shared.v2.f32 {%0,%1}, [%2];" : "=f"(v.x), "=f"(v.y) : "r"(a) : "memory"); return v; }
__device__ __forceinline__ float4 ldsf4(uint32_t a) { float4 v; asm volatile("ld.shared.v4.f32 {%0,%1,%2,%3}, [%4];" : "=f"(v.x), "=f"(v.y), "=f"(v.z), "=f"(v.w) : "r"(a) : "memory"); return v; }
__device__ __forceinline__ void lds4(uint32_t (&r)[4], uint32_t a) { asm volatile("ld.shared.v4.u32 {%0,%1,%2,%3}, [%4];" : "=r"(r[0]), "=r"(r[1]), "=r"(r[2]), "=r"(r[3]) : "r"(a) : "memory"); }

__device__ __forceinline__ void wg_fence() { asm volatile("wgmma.fence.sync.aligned;" ::: "memory"); }
__device__ __forceinline__ void wg_commit() { asm volatile("wgmma.commit_group.sync.aligned;" ::: "memory"); }
template <int N> __device__ __forceinline__ void wg_wait() { asm volatile("wgmma.wait_group.sync.aligned %0;" ::"n"(N) : "memory"); }
__host__ __device__ constexpr uint32_t desc_lo(uint32_t off) { return ((SB + off) >> 4) | 0x10000u; }
template <int TA, int ACC> __device__ __forceinline__ void wgmma_n16(float (&d)[8], uint32_t da, uint32_t db) {
  asm volatile("{\n.reg .b64 da, db;\nmov.b64 da, {%8, 0x40000040};\nmov.b64 db, {%9, 0x40000040};\n"
               "wgmma.mma_async.sync.aligned.m64n16k16.f32.bf16.bf16 {%0,%1,%2,%3,%4,%5,%6,%7}, da, db, %11, 1, 1, %10, 0;\n}"
               : "+f"(d[0]), "+f"(d[1]), "+f"(d[2]), "+f"(d[3]), "+f"(d[4]), "+f"(d[5]), "+f"(d[6]), "+f"(d[7])
               : "r"(da), "r"(db), "n"(TA), "n"(ACC));
}
__device__ __forceinline__ void wgmma_n16_ones(float (&d)[8], uint32_t one, uint32_t db) {
  asm volatile("{\n.reg .b64 db;\nmov.b64 db, {%9, 0x40000040};\n"
               "wgmma.mma_async.sync.aligned.m64n16k16.f32.bf16.bf16 {%0,%1,%2,%3,%4,%5,%6,%7}, {%8,%8,%8,%8}, db, 1, 1, 1, 0;\n}"
               : "+f"(d[0]), "+f"(d[1]), "+f"(d[2]), "+f"(d[3]), "+f"(d[4]), "+f"(d[5]), "+f"(d[6]), "+f"(d[7])
               : "r"(one), "r"(db));
}
__device__ __forceinline__ void acc_fence(float (&d)[8]) {
  asm volatile("" : "+f"(d[0]), "+f"(d[1]), "+f"(d[2]), "+f"(d[3]), "+f"(d[4]), "+f"(d[5]), "+f"(d[6]), "+f"(d[7]) :: "memory");
}

template <int N, int STRIDE> __device__ __forceinline__ void load_units(uint2 (&v)[N], const uint32_t* p) {
#pragma unroll
  for (int i = 0; i < N; i++) v[i] = ldg_u64(p + i * STRIDE);
}
__device__ __forceinline__ void reload_unit(uint2& v, const uint32_t* p) {
  asm volatile("{\n.reg .pred q;\nsetp.eq.u32 q, %1, 0;\n@q ld.relaxed.gpu.global.v2.b32 {%0, %1}, [%2];\n}" : "+r"(v.x), "+r"(v.y) : "l"(p) : "memory");
}
template <int N> __device__ __forceinline__ uint32_t min_flags(const uint2 (&v)[N]) {
  uint32_t a = v[0].y, b = v[1].y;
#pragma unroll
  for (int i = 2; i < N; i += 2) { a = min(a, v[i].y); b = min(b, v[i + 1].y); }
  return min(a, b);
}
template <int N, int STRIDE> __device__ __forceinline__ int check_units(uint2 (&v)[N], const uint32_t* p) {
  int it = 0;
  while (!__all_sync(~0u, min_flags(v) != 0)) {
#pragma unroll
    for (int i = 0; i < N; i++) reload_unit(v[i], p + i * STRIDE);
    if (++it > SPIN_LIMIT) __trap();
  }
  return it;
}
__device__ __forceinline__ void sum4_to_smem(const uint2 (&v)[4], uint32_t dst) {
  const float c0 = (bf_lo(v[0].x) + bf_lo(v[1].x)) + (bf_lo(v[2].x) + bf_lo(v[3].x));
  const float c1 = (bf_hi(v[0].x) + bf_hi(v[1].x)) + (bf_hi(v[2].x) + bf_hi(v[3].x));
  const float c2 = (bf_lo(v[0].y) + bf_lo(v[1].y)) + (bf_lo(v[2].y) + bf_lo(v[3].y));
  const float c3 = (bf_hi(v[0].y) + bf_hi(v[1].y)) + (bf_hi(v[2].y) + bf_hi(v[3].y));
  sts1(dst, pack_bf16(c0, c1));
  sts1(dst + 128, pack_bf16(c2, c3));
}
__device__ __forceinline__ uint32_t a_t_offset(int w, int lane) {
  const int mi = lane >> 3, r = lane & 7;
  return (w >> 2) * 16384 + (8 * (mi >> 1) + r) * 128 + (((2 * (w & 3) + (mi & 1)) ^ r) << 4);
}
__device__ __forceinline__ void load_a_t(uint32_t (&a)[8][4], uint32_t base) {
#pragma unroll
  for (int ks = 0; ks < 8; ks++) ldsm4t(a[ks], base + ks * 2048);
}
__device__ __forceinline__ void mma128(float (&d)[4], const uint32_t (&a)[8][4], const uint32_t (&b)[4][4]) {
  float e[4][4] = {{d[0], d[1], d[2], d[3]}, {0.f, 0.f, 0.f, 0.f}, {0.f, 0.f, 0.f, 0.f}, {0.f, 0.f, 0.f, 0.f}};
#pragma unroll
  for (int kk = 0; kk < 4; kk++) { mma16816(e[(2 * kk) & 3], a[2 * kk], b[kk][0], b[kk][1]); mma16816(e[(2 * kk + 1) & 3], a[2 * kk + 1], b[kk][2], b[kk][3]); }
#pragma unroll
  for (int i = 0; i < 4; i++) d[i] = (e[0][i] + e[1][i]) + (e[2][i] + e[3][i]);
}
template <int NP> __device__ __forceinline__ bool sum_pieces(const uint32_t* p0, uint32_t one, float (&r)[4]) {
  uint2 v[NP / 4];
  load_units<NP / 4, 64>(v, p0);
  float d[4][4] = {};
#pragma unroll
  for (int i = 0; i < NP / 8; i++) { const uint32_t a[4] = {v[2 * i].x, v[2 * i].y, v[2 * i + 1].x, v[2 * i + 1].y}; mma16816(d[i & 3], a, one, one); }
  const bool ok = __all_sync(~0u, min_flags(v) != 0);
#pragma unroll
  for (int k = 0; k < 4; k++) r[k] = (d[0][k] + d[1][k]) + (d[2][k] + d[3][k]);
  return ok;
}
template <typename F> __device__ __forceinline__ float reduce_g(const float (&x)[4], int lane, F f) {
  const bool u4 = lane & 16, u3 = lane & 8;
  const float a0 = f(u4 ? x[2] : x[0], __shfl_xor_sync(~0u, u4 ? x[0] : x[2], 16));
  const float a1 = f(u4 ? x[3] : x[1], __shfl_xor_sync(~0u, u4 ? x[1] : x[3], 16));
  const float b = f(u3 ? a1 : a0, __shfl_xor_sync(~0u, u3 ? a0 : a1, 8));
  return f(b, __shfl_xor_sync(~0u, b, 4));
}

__global__ void __launch_bounds__(NTHREADS, 1)
fused_decode_kernel(__nv_bfloat16* __restrict__ gout, Scratch* __restrict__ gs, const uint8_t* __restrict__ gwmod,
                    const uint8_t* __restrict__ gx, const uint8_t* __restrict__ gc, uint32_t* __restrict__ gin,
                    const __grid_constant__ Params P) {
  constexpr Tune T{};
  extern __shared__ __align__(1024) uint8_t smem_raw[];
  constexpr uint32_t sb = SB;
  const int tid = __shfl_xor_sync(0xffffffffu, threadIdx.x ^ 1, 1), lane = tid & 31;
  const int w = __shfl_sync(0xffffffffu, threadIdx.x >> 5, 0);
  const int cta = blockIdx.x;
  auto BAR = [](int i) { return SB + OFF_BARS + 8 * i; };
  auto selector = [&](int c) { uint32_t v; asm volatile("ld.shared.u8 %0, [%1];" : "=r"(v) : "r"(sb + OFF_SEL + c) : "memory"); return v; };
  auto inbox = [&](int c, int k) { return gin + blk(c, k, selector(c)); };
  auto nearbox = [&](int c, int k) { return gin + blk(c, k, selector(cta) ^ flip((c ^ cta) & 15)); };
  const int g = lane >> 2, t = lane & 3;
  const int hI = cta >> 2, jI = cta & 3;
  const int bs = cta >> 1, hh = cta & 1;

  CLK_DECL;
  CLK(0);
  if (w == 8) {
    CLK(7);
    const uint32_t t_entry = gtime32();
    CLK(8);
    if (lane == 0) {
      if ((uint32_t)__cvta_generic_to_shared(smem_raw) != SB) __trap();
      mbar_init(BAR(BAR_WQ), 1); mbar_init(BAR(BAR_WQ + 1), 1); mbar_init(BAR(BAR_XC), 1); mbar_init(BAR(BAR_C), 1);
      asm volatile("fence.mbarrier_init.release.cluster;" ::: "memory");
      asm volatile("prefetch.tensormap [%0];" ::"l"(&P.wq) : "memory");
      mbar_expect(BAR(BAR_XC), 8192); mbar_expect(BAR(BAR_C), 8192); mbar_expect(BAR(BAR_WQ), 16384); mbar_expect(BAR(BAR_WQ + 1), 16384);
      CLK(9);
    }
    __syncwarp();
    asm volatile("barrier.cta.arrive.aligned 0, %0;" ::"n"(NTHREADS) : "memory");
    CLK(10);
    uint32_t tn = t_entry + T.PC_T0 + ((bs * 37) & 63) * T.PC_STAG / 64;
    const int h = hI, j = jI;
    if (lane == 0) {
      uint64_t pol; asm volatile("createpolicy.fractional.L2::evict_first.b64 %0, 1.0;" : "=l"(pol));
#pragma unroll
      for (int u = 0; u < 4; u++) {
        until_ns(tn + u * T.PC_P1);
        if (u == 0) CLK(11);
        tma2d(sb + OFF_WQ + u * 8192, &P.wq, 128 * h + 64 * (u >> 1), 128 * j + 64 * (u & 1), BAR(BAR_WQ + (u >> 1)), pol);
        if (u == T.PC_XC) {
#pragma unroll
          for (int i = 0; i < 4; i++) { const int o = ((i + cta) & 3) * 2048; bulk_ld(sb + OFF_XS + o, gx + o, 2048, BAR(BAR_XC)); }
        }
        if (u == T.PC_C) {
#pragma unroll
          for (int i = 0; i < 4; i++) { const int o = ((i + cta) & 3) * 2048; bulk_ld(sb + OFF_CS + o, gc + o, 2048, BAR(BAR_C)); }
        }
        if (u == 0) {
          CLK(1);
          asm volatile("prefetch.tensormap [%0];" ::"l"(&P.wuk) : "memory");
          asm volatile("prefetch.tensormap [%0];" ::"l"(&P.wm2) : "memory");
          asm volatile("prefetch.tensormap [%0];" ::"l"(&P.ckv2) : "memory");
        }
      }
    }
    __syncwarp();
    tn += 4 * T.PC_P1;
    bar_sync(5, 64);
    if (lane == 0) {
      uint64_t pol; asm volatile("createpolicy.fractional.L2::evict_first.b64 %0, 1.0;" : "=l"(pol));
#pragma unroll
      for (int u = 0; u < 4; u++) {
        if ((u & 1) == (T.PC_W > 3) && T.PC_NW) mbar_wait(BAR(BAR_WQ + (u >> 1)));
        slot(tn, T.PC_SL);
        tma5d(sb + OFF_WUK + u * 8192, &P.wuk, 128 * h + 64 * (u >> 1), 0, 0, 0, 8 * j + 4 * (u & 1), BAR(BAR_WUK + (u >> 1)), pol);
        tn += T.PC_P1;
      }
#pragma unroll
      for (int u = 0; u < 2; u++) {
        if (u == (T.PC_W > 3) && T.PC_NW) mbar_wait(BAR(BAR_WUK));
        slot(tn, T.PC_SL);
        tma2d_nohint(sb + OFF_WM2 + u * 8192, &P.wm2, 1024 + 16 * cta, 256 * u, BAR(BAR_WM2));
        tn += T.PC_P1;
      }
      const int row0 = (bs >> 3) * 4096 + (bs & 7) * 64;
      uint32_t dst = sb + OFF_RING;
      const int p2 = T.PC_P2 + (32 - ((bs * 37) & 63)) * T.PC_DS / 1024;
#pragma unroll 1
      for (int n = 0; n < 31; n++) {
        if (n >= 4 && (n < 12 || (n & 3) == 0)) mbar_wait(BAR(n >= 12 ? BAR_EMPTY + (n >> 2) - 3 : n == 7 ? BAR_P0BD : (n == 8 || n == 9) ? BAR_P2D : BAR_P1D));
        if (n < T.PC_NW) {
          if (n >= T.PC_W) mbar_wait(BAR(BAR_FULL + n - T.PC_W));
          else if ((n & 1) == (T.PC_W > 3)) mbar_wait(BAR(n < 2 ? BAR_WUK + 1 : BAR_WM2));
        }
        slot(tn, T.PC_SL);
        tma3d(dst, &P.ckv2, 0, row0 + (n >> 2) * 512, 2 * (n & 3), BAR(BAR_FULL + n), pol);
        dst = (n == 11 || n == 23) ? sb + OFF_RING : dst + 16384;
        tn += n >= 15 ? p2 : T.PC_P2;
        if (n == 4) CLK(2);
        if (n == 12) CLK(3);
        if (n == 20) CLK(4);
        if (n == 28) CLK(5);
        if (n == 24) {
          asm volatile("prefetch.tensormap [%0];" ::"l"(&P.ckv1) : "memory");
          asm volatile("prefetch.tensormap [%0];" ::"l"(&P.wuv) : "memory");
          asm volatile("prefetch.tensormap [%0];" ::"l"(&P.wo) : "memory");
          asm volatile("prefetch.tensormap [%0];" ::"l"(&P.w1) : "memory");
          asm volatile("prefetch.tensormap [%0];" ::"l"(&P.w2) : "memory");
        }
      }
      slot(tn, T.PC_SL);
      tma3d(dst, &P.ckv1, 0, row0 + 7 * 512, 6, BAR(BAR_LAST + 3), pol);
      tma3d(dst + 8192, &P.ckv1, 0, row0 + 7 * 512, 7, BAR(BAR_LAST + 4), pol);
      tn += T.PC_P2;
      CLK(6);
      auto unit = [&](int u) {
        if (u < 4) tma5d(sb + OFF_WUV + u * 8192, &P.wuv, 128 * h + 64 * (u >> 1), 0, 4 * (j >> 1), 0, 2 * (j & 1) + (u & 1), BAR(BAR_WUV + (u >> 1)), pol);
        else if (u < 8) tma2d(sb + OFF_WO + (u - 4) * 8192, &P.wo, 128 * j + 64 * ((u - 4) >> 1), 128 * h + 64 * (u & 1), BAR(BAR_WO + ((u - 4) >> 1)), pol);
        else if (u < 10) { if (cta < NFF) tma2d_nohint(sb + OFF_W1 + (u - 8) * 16384, &P.w1, 32 * bs, 256 * (u - 8), BAR(BAR_W1)); }
        else if (cta < NFF) tma3d(sb + OFF_W2 + (u - 10) * 8192, &P.w2, 0, 32 * bs, 4 * hh + 2 * (u - 10), BAR(BAR_W2), pol);
      };
      mbar_wait(BAR(BAR_EMPTY + 5));
      if (T.PW_A >= 0) { mbar_wait(BAR(BAR_LAST + T.PW_A)); tn = gtime32(); }
      tn += T.PW_0 + ((cta * 37) & 127) * T.PW_ST / 128;
#pragma unroll
      for (int u = 0; u < 12; u++) {
        if (u == 8) mbar_wait(BAR(BAR_EMPTY + 6));
        until_ns(tn);
        unit(WSWAP && u >= 8 ? (u ^ 2) : u);
        tn += u < 3 ? T.PW_UV : u == 3 ? T.PW_G : u < 7 ? T.PW_O : u == 7 ? T.PW_G2 : u == 9 ? T.PW_G3 : T.PW_F;
      }
      CLK_DUMP();
    }
    return;
  }

  if (w == 9) {
    if (lane == 0) {
#pragma unroll
      for (int i = 0; i < NBARS; i++) mbar_init(BAR(i), i >= BAR_P1D ? 8 : i >= BAR_EMPTY ? 4 : 1);
      asm volatile("fence.mbarrier_init.release.cluster;" ::: "memory");
    }
    __syncwarp();
    mbar_expect(BAR(lane), lane == BAR_LAST + 3 ? 8192 : 16384);
    if (lane < BAR_ALLCLR - 32) mbar_expect(BAR(32 + lane), lane == 0 ? 8192 : lane == BAR_W1 - 32 ? 32768 : 16384);
    CLK(9);
    asm volatile("barrier.cta.arrive.aligned 5, 64;" ::: "memory");
    asm volatile("barrier.cta.arrive.aligned 0, %0;" ::"n"(NTHREADS) : "memory");
  }
  const uint32_t epoch = ldg_rlx1(&gs->epoch);

  if (w == 9) {
    const int mo = g * 512 + 16 * hI + 2 * jI;
    const uint32_t xo0 = ldg_nc1(gx + mo * 2), xo1 = ldg_nc1(gx + mo * 2 + 16);
    const int par = epoch & 1;
    const uint32_t t0 = gtime32();
    const uint4 z = make_uint4(0, 0, 0, 0);
    uint32_t sel;
    {
      uint32_t* pa = gin + blk(cta, 5, 0) + 960;
      uint32_t* pb = gin + blk(cta, 5, 1) + 960;
      until_ns(t0 + T.PR_T0);
      if (lane < 4) stg4(reinterpret_cast<uint4*>(lane & 2 ? pa : pb) + (lane & 1), z);
      uint32_t ma = 0xffffffffu, mb = 0xffffffffu;
#pragma unroll 1
      for (int i = 0; i < 2 * T.PR_N; i++) {
        const uint32_t c0 = clk32();
        asm volatile("{\n.reg .pred q;\n.reg .b32 v;\nsetp.eq.u32 q, %1, 0;\nmov.u32 v, 0;\n@q atom.relaxed.gpu.global.add.u32 v, [%0], 1;\n"
                     "setp.eq.u32 q, v, 0xffffffff;\n@q trap;\n}" ::"l"(i & 1 ? pb : pa), "r"(lane) : "memory");
        const uint32_t d = clk32() - c0;
        if (i & 1) mb = min(mb, d); else ma = min(ma, d);
      }
      sel = __shfl_sync(~0u, (uint32_t)(mb < ma), 0);
      if (T.LOC == 1) sel ^= 1;
      if (T.LOC == 2) sel ^= (cta ^ (cta >> 3)) & 1;
      const uint32_t sw = 2 * (epoch + 1) + sel;
      if (lane < 2) stg4(reinterpret_cast<uint4*>(gin + blk(cta, 5, 1) + 896) + lane, make_uint4(sw, sw, sw, sw));
    }
    until_ns(t0 + T.CLR_T0);
    {
#pragma unroll 1
      for (int i0 = 0; i0 < 13; i0++) {
        uint4* q = reinterpret_cast<uint4*>(gin + (i0 < 12 ? blk(cta, i0 >> 1, sel) + (i0 & 1) * 512 : blk(cta, 4, sel ^ 1) + 512)) + lane;
#pragma unroll
        for (int i = 0; i < 4; i++) if (i0 != 11 || i < 3) stg4(q + i * 32, z);
        backoff(T.CLR_CLK);
      }
#pragma unroll
      for (int i = 0; i < 2; i++) {
        if (jI == 1) stg4(reinterpret_cast<uint4*>(gin + blk(cta, 6, i)) + lane, z);
        if (lane < 2) stg4(reinterpret_cast<uint4*>(gin + blk(cta, 5, i) + 928) + lane, z);
        stg4(reinterpret_cast<uint4*>(gin + blk(16 * g, 6 + (cta >> 6), i) + (cta & 63) * 16) + t, z);
      }
      CLK(1);
      {
        uint32_t sv = 0;
        uint32_t u[4];
        int it = 0;
        do {
#pragma unroll
          for (int i = 0; i < 4; i++) u[i] = ldg_rlx1(gin + blk(4 * lane + i, 5, 1) + 896) ^ (2 * (epoch + 1));
          if (++it > SPIN_LIMIT) __trap();
        } while (!__all_sync(~0u, (u[0] | u[1] | u[2] | u[3]) < 2));
#pragma unroll
        for (int i = 0; i < 4; i++) sv |= u[i] << (8 * i);
        sts1(sb + OFF_SEL + lane * 4, sv);
      }
      asm volatile("fence.acq_rel.gpu;" ::: "memory");
      CLK(2);
      __syncwarp();
      if (lane < NSYNC) asm volatile("red.relaxed.gpu.global.add.u32 [%0], 1;" ::"l"(&gs->sync[lane][0]) : "memory");
#pragma unroll
      for (int i = 0; i < 4; i++) stg4(reinterpret_cast<uint4*>(gs->QP[par ^ 1] + cta * 512) + i * 32 + lane, z);
      backoff(T.CLR_CLK);
#pragma unroll
      for (int i = 0; i < 4; i++) stg4(reinterpret_cast<uint4*>(gs->QX[par ^ 1] + cta * 512) + i * 32 + lane, z);
      stg4(reinterpret_cast<uint4*>(gs->MOD1[par ^ 1] + cta * 128) + lane, z);
      if (lane < 16) stg4(reinterpret_cast<uint4*>(gs->MOD2[par ^ 1] + cta * 64) + lane, z);
      const uint32_t target = (epoch + 1) * NCTA;
      uint32_t c; int it = 0;
      do {
        backoff(T.CLR_CLK);
        asm volatile("ld.acquire.gpu.global.u32 %0, [%1];" : "=r"(c) : "l"(&gs->sync[cta % NSYNC][0]) : "memory");
        if (++it > SPIN_LIMIT) __trap();
      } while (!__all_sync(~0u, (int)(c - target) >= 0));
      if (lane == 0) mbar_arrive(BAR(BAR_ALLCLR));
    }
    CLK(3);
    uint2 gg[2];
    {
      const uint32_t* pg = gs->MOD2[par] + cta * 16 + g * 2;
      load_units<2, 3 * 2048>(gg, pg);
      check_units<2, 3 * 2048>(gg, pg);
    }
    uint32_t anchor;
    {
      uint32_t* const po = gin + blk(16 * (lane & 7), 5, lane >> 3) + 928;
      const uint32_t* const pi = nearbox(cta & ~15, 5) + 928;
      mbar_wait(BAR(BAR_LAST + T.TS_P));
      unsigned long long now; asm volatile("mov.u64 %0, %%globaltimer;" : "=l"(now));
      if (lane < 16) {
        asm volatile("red.relaxed.gpu.global.max.u64 [%0], %1;" ::"l"(po + 2), "l"(now) : "memory");
        asm volatile("red.relaxed.gpu.global.add.u32 [%0], 1;" ::"l"(po + 1) : "memory");
      }
      backoff(T.D_TS);
      uint4 v; int it = 0;
      do { v = ldg_2u64(pi); if (++it > SPIN_LIMIT) __trap(); } while (!__all_sync(~0u, v.y == NCTA));
      const int age = min(max((int)(gtime32() - v.z), 0), 4000);
      anchor = clk32() - age * 7 / 4 + T.TS_O;
      if (lane == 0) { sts1(sb + OFF_TS, anchor); mbar_arrive(BAR(BAR_TS)); }
      CLK(10);
    }
    {
      const uint32_t* pm = pin(nearbox(4 * hI + 1, 6) + lane * 4);
      wait_clk(anchor, T.A_M);
      uint4 ml = ldg_2u64(pm);
      int it = 0;
      while (!__all_sync(~0u, ml.y != 0 && ml.w != 0)) { ml = ldg_2u64(pm); if (++it > SPIN_LIMIT) __trap(); }
      ITS(2, it);
      float M = fmaxf(__uint_as_float(ml.x), __uint_as_float(ml.z));
      M = fmaxf(M, __shfl_xor_sync(~0u, M, 1)); M = fmaxf(M, __shfl_xor_sync(~0u, M, 2));
      const float e0 = ex2(__uint_as_float(ml.x) - M), e1 = ex2(__uint_as_float(ml.z) - M);
      float l = e0 * __uint_as_float(ml.y) + e1 * __uint_as_float(ml.w);
      l += __shfl_xor_sync(~0u, l, 1); l += __shfl_xor_sync(~0u, l, 2);
      const float inv = __fdividef(1.f, l);
      sts2f(sb + OFF_WV + lane * 8, e0 * inv, e1 * inv);
      __syncwarp();
      if (lane == 0) mbar_arrive(BAR(BAR_WV));
      CLK(11);
    }
    uint32_t* x3o[4];
#pragma unroll
    for (int i = 0; i < 4; i++) x3o[i] = pin(gin + blk(32 * i + 16 * (t >> 1), 6 + (cta >> 6), t) + (cta & 63) * 16 + g * 2);
    uint32_t* const fo = pin(reinterpret_cast<uint32_t*>(gout) + mo / 2 + 4 * (t & 1));
    const uint32_t* const p3 = pin(gin + blk(cta, 4, sel) + t * 16 + g * 2);
    const uint32_t* const p4 = pin(gin + blk(cta, 5, sel) + t * 16 + g * 2);
    const uint32_t one = pin((g & 1) ? 0x3f800000u : 0x00003f80u);
    const float xf[4] = {pin(bf_lo(xo0)), pin(bf_hi(xo0)), pin(bf_lo(xo1)), pin(bf_hi(xo1))};
    const float ga[4] = {pin(bf_lo(gg[0].x)), pin(bf_hi(gg[0].x)), pin(bf_lo(gg[0].y)), pin(bf_hi(gg[0].y))};
    mbar_wait(BAR(BAR_P5D));
    backoff(T.D_X3A);
    wait_clk(anchor, T.A_X1 + T.R_X3A);
    CLK(4);
    float r[4];
    uint32_t x20, x21;
    int it = 0;
    bool ok;
    do {
      ok = sum_pieces<32>(p3, one, r);
      x20 = pack_bf16(xf[0] + ga[0] * r[0], xf[1] + ga[1] * r[1]); x21 = pack_bf16(xf[2] + ga[2] * r[2], xf[3] + ga[3] * r[3]);
#pragma unroll
      for (int i = 0; i < 4; i++) ST3B(!ok || (i == 3 && t >= 2), x3o[i], x20, x21);
    } while (!ok && ++it < SPIN_LIMIT);
    CLK(6);
    ITS(0, it);
    const uint32_t xw = (t & 1) ? x21 : x20, gw = (t & 1) ? gg[1].y : gg[1].x;
    const float xa = pin(bf_lo(xw)), xb = pin(bf_hi(xw)), gba = pin(bf_lo(gw)), gbb = pin(bf_hi(gw));
    if (cta < NFF) { mbar_wait(BAR(BAR_P7D)); backoff(T.D_FIN); } else { backoff(1200); wait_clk(anchor, T.A_X1 + T.R_X3A + T.R_X3B + T.R_FIN); }
    CLK(7);
    do {
      ok = sum_pieces<NFG>(p4, one, r);
      const uint32_t o = pack_bf16(xa + gba * ((t & 1) ? r[2] : r[0]), xb + gbb * ((t & 1) ? r[3] : r[1]));
      if (ok && t < 2) asm volatile("st.global.u32 [%0], %1;" ::"l"(fo), "r"(o) : "memory");
    } while (!ok && ++it < SPIN_LIMIT);
    if (!ok) __trap();
    ITS(1, it);
    CLK(8);
    CLK_DUMP();
    if (cta == 0 && lane == 0) stg1(&gs->epoch, epoch + 1);
    return;
  }

  const int wg = w >> 2, wq = w & 3;
  uint32_t tstore;
  {
    const uint8_t* pw = gwmod + (size_t)(128 * jI + 16 * w + 4 * (g >> 1) + (g & 1)) * 6144 + 64 * hI + 16 * t;
    const uint4 w0 = ldg_nc4(pw), w1 = ldg_nc4(pw + 2 * 6144);
    const uint2 cc = ldg_nc2(gc + g * 1024 + 256 * jI + 32 * w + 8 * t);
    CLK(40);
    const uint32_t a[4] = {silu2(cc.x), 0u, silu2(cc.y), 0u};
    float d[4][4] = {{0.f, 0.f, 0.f, 0.f}, {0.f, 0.f, 0.f, 0.f}, {0.f, 0.f, 0.f, 0.f}, {0.f, 0.f, 0.f, 0.f}};
    mma16816(d[0], a, movm(w0.x), movm(w1.x)); mma16816(d[1], a, movm(w0.y), movm(w1.y));
    mma16816(d[2], a, movm(w0.z), movm(w1.z)); mma16816(d[3], a, movm(w0.w), movm(w1.w));
    CLK(1);
    sts4f(sb + OFF_P0S + w * 1088 + lane * 16, d[0][0], d[0][1], d[1][0], d[1][1]);
    sts4f(sb + OFF_P0S + w * 1088 + 544 + lane * 16, d[2][0], d[2][1], d[3][0], d[3][1]);
    bar_sync(0, NTHREADS);
    if (tid < 128) {
      const uint32_t src = sb + OFF_P0S + ((tid >> 2) & 1) * 544 + (((tid >> 3) & 7) * 4 + 2 * (tid >> 6) + (tid & 1)) * 16 + ((tid >> 1) & 1) * 8;
      float2 v[8];
#pragma unroll
      for (int i = 0; i < 8; i++) v[i] = ldsf2(src + i * 1088);
      const float ax = ((v[0].x + v[1].x) + (v[2].x + v[3].x)) + ((v[4].x + v[5].x) + (v[6].x + v[7].x));
      const float ay = ((v[0].y + v[1].y) + (v[2].y + v[3].y)) + ((v[4].y + v[5].y) + (v[6].y + v[7].y));
      stg1(gs->MOD1[epoch & 1] + jI * 4096 + hI * 128 + tid, nz(pack_bf16(ax, ay)));
    }
    tstore = clk32();
  }
  CLK(2);
  const int par = epoch & 1;
  uint32_t cf[4][4];
  mbar_wait(BAR(BAR_XC));
  {
    uint32_t u[2][4];
    lds4(u[0], sb + OFF_XS + w * 1024 + lane * 16); lds4(u[1], sb + OFF_XS + w * 1024 + 512 + lane * 16);
    float v[16];
#pragma unroll
    for (int i = 0; i < 8; i++) { v[2 * i] = bf_lo(u[i >> 2][i & 3]); v[2 * i + 1] = bf_hi(u[i >> 2][i & 3]); }
    float s = 0.f;
#pragma unroll
    for (int i = 0; i < 16; i++) s += v[i];
#pragma unroll
    for (int o = 16; o; o >>= 1) s += __shfl_xor_sync(~0u, s, o);
    const float mu = s * (1.f / 512.f);
    float q = 0.f;
#pragma unroll
    for (int i = 0; i < 16; i++) { v[i] -= mu; q += v[i] * v[i]; }
#pragma unroll
    for (int o = 16; o; o >>= 1) q += __shfl_xor_sync(~0u, q, o);
    const float rs = rsqrtf(q * (1.f / 512.f) + 1e-5f);
    const bool hi = jI & 2;
    uint32_t o[4];
#pragma unroll
    for (int i = 0; i < 4; i++) o[i] = pack_bf16((hi ? v[8 + 2 * i] : v[2 * i]) * rs, (hi ? v[9 + 2 * i] : v[2 * i + 1]) * rs);
    if ((lane >> 4) == (jI & 1)) sts4(sb + OFF_XN + w * 272 + (lane & 15) * 16, make_uint4(o[0], o[1], o[2], o[3]));
  }
  CLK(3);
  uint32_t aw[8][4];
  const uint32_t abase = __shfl_sync(~0u, sb + a_t_offset(w, lane), lane);
  {
    const uint32_t* pm = pin(gs->MOD1[par] + (8 * jI + w) * 64 + lane * 2);
    uint32_t* const qpo = pin(gs->QP[par] + (cta * 256 + tid) * 2);
    float d[4] = {0.f, 0.f, 0.f, 0.f};
    wait_clk(tstore, T.D_MOD);
    CLK(4);
    uint2 v[8];
    load_units<8, 2048>(v, pm);
    cbar();
    const uint32_t xn0 = lds1(sb + OFF_XN + g * 272 + w * 32 + t * 4), xn1 = lds1(sb + OFF_XN + g * 272 + w * 32 + 16 + t * 4);
    const bool early = __all_sync(~0u, mbar_test(BAR(BAR_WQ + wg)));
    if (early) load_a_t(aw, abase + OFF_WQ);
    int it = 0;
    while (true) {
      uint32_t mn = 0xffffffffu;
#pragma unroll
      for (int i = 0; i < 8; i++) mn = min(mn, min(v[i].x, v[i].y));
      if (__all_sync(~0u, mn != 0)) break;
#pragma unroll
      for (int i = 0; i < 8; i++) { if (v[i].x == 0) v[i].y = 0; reload_unit(v[i], pm + i * 2048); }
      if (++it > SPIN_LIMIT) __trap();
    }
    CLK(5);
    ITS(0, it);
    float sc[2][4];
#pragma unroll
    for (int i = 0; i < 2; i++) {
      sc[i][0] = (bf_lo(v[i].x) + bf_lo(v[2 + i].x)) + (bf_lo(v[4 + i].x) + bf_lo(v[6 + i].x));
      sc[i][1] = (bf_hi(v[i].x) + bf_hi(v[2 + i].x)) + (bf_hi(v[4 + i].x) + bf_hi(v[6 + i].x));
      sc[i][2] = (bf_lo(v[i].y) + bf_lo(v[2 + i].y)) + (bf_lo(v[4 + i].y) + bf_lo(v[6 + i].y));
      sc[i][3] = (bf_hi(v[i].y) + bf_hi(v[2 + i].y)) + (bf_hi(v[4 + i].y) + bf_hi(v[6 + i].y));
    }
    sts2(sb + OFF_BS1 + (w >> 1) * 512 + lane * 16 + (w & 1) * 8,
         pack_bf16(bf_lo(xn0) * (1.f + sc[1][0]) + sc[0][0], bf_hi(xn0) * (1.f + sc[1][1]) + sc[0][1]),
         pack_bf16(bf_lo(xn1) * (1.f + sc[1][2]) + sc[0][2], bf_hi(xn1) * (1.f + sc[1][3]) + sc[0][3]));
    if (!early) { mbar_wait(BAR(BAR_WQ + wg)); load_a_t(aw, abase + OFF_WQ); }
    CLK(6);
    cbar();
    uint32_t b[4][4];
#pragma unroll
    for (int kk = 0; kk < 4; kk++) lds4(b[kk], sb + OFF_BS1 + kk * 512 + lane * 16);
    mma128(d, aw, b);
    stg_u64(qpo, pack_bf16(d[0], d[1]), pack_bf16(d[2], d[3]));
    tstore = clk32();
    CLK(7);
    if (wg) {
      mbar_wait(BAR(BAR_C));
#pragma unroll
      for (int i = 0; i < 4; i++) lds4(cf[i], sb + OFF_CS + g * 1024 + wq * 256 + i * 64 + t * 16);
#pragma unroll
      for (int i = 0; i < 16; i++) cf[i >> 2][i & 3] = silu2(cf[i >> 2][i & 3]);
    }
    __syncwarp();
    if (lane == 0) mbar_arrive(BAR(BAR_P1D));
  }
  {
    const uint32_t* pq = pin(gs->QP[par] + (hI * 4 * 256 + tid) * 2);
    uint32_t* const qxo = pin(gs->QX[par] + (g * 32 + hI) * 256 + 64 * jI + 8 * w + 2 * t);
    uint2 v[4];
    float d[4] = {0.f, 0.f, 0.f, 0.f};
    wait_clk(tstore, T.D_QP);
    CLK(8);
    load_units<4, 512>(v, pq);
    const uint32_t kbase = sb + OFF_WUK + (16 * w + (lane & 15)) * 128;
    auto load_half = [&](int hf) {
#pragma unroll
      for (int ks = 0; ks < 4; ks++) ldsm4(aw[4 * hf + ks], kbase + hf * 16384 + (((2 * ks + (lane >> 4)) ^ (lane & 7)) << 4));
    };
    mbar_wait(BAR(BAR_WUK));
    load_half(0);
    const bool early = __all_sync(~0u, mbar_test(BAR(BAR_WUK + 1)));
    if (early) load_half(1);
    const int it = check_units<4, 512>(v, pq);
    CLK(9);
    ITS(1, it);
    sum4_to_smem(v, sb + OFF_BS2 + (16 * w + g) * 16 + t * 4);
    if (!early) { mbar_wait(BAR(BAR_WUK + 1)); load_half(1); }
    CLK(10);
    cbar();
    uint32_t b[4][4];
#pragma unroll
    for (int kk = 0; kk < 4; kk++) ldsm4t(b[kk], sb + OFF_BS2 + (32 * kk + lane) * 16);
    mma128(d, aw, b);
    const float sc = 0.08838834764831845f * 1.4426950408889634f;
    stg_u64(qxo, movm(pack_bf16(d[0] * sc, d[1] * sc)), movm(pack_bf16(d[2] * sc, d[3] * sc)));
    tstore = clk32();
    CLK(11);
    if (lane == 0) mbar_arrive(BAR(BAR_P2D));
  }
  if (wg) {
    const int mi = lane >> 3, r = lane & 7;
    const uint32_t a0 = sb + OFF_WM2 + (8 * (r >> 1) + (r & 1) + 2 * (mi >> 1)) * 32 + (mi & 1) * 16;
    mbar_wait(BAR(BAR_WM2));
#pragma unroll
    for (int s = 0; s < 8; s++) ldsm4t(aw[s], a0 + (128 * wq + 32 * (s >> 1) + 4 * (s & 1)) * 32);
    float d[4] = {0.f, 0.f, 0.f, 0.f};
    mma128(d, aw, cf);
    sts4f(sb + OFF_P0B + (tid - 128) * 16, d[0], d[1], d[2], d[3]);
    if (lane == 0) mbar_arrive(BAR(BAR_P0BD));
    bar_sync(3, 128);
    if (w == 4) {
      float4 v[4];
#pragma unroll
      for (int i = 0; i < 4; i++) v[i] = ldsf4(sb + OFF_P0B + (i * 32 + lane) * 16);
      stg_u64(gs->MOD2[par] + cta * 64 + t * 16 + g * 2, movm(pack_bf16((v[0].x + v[1].x) + (v[2].x + v[3].x), (v[0].y + v[1].y) + (v[2].y + v[3].y))),
              movm(pack_bf16((v[0].z + v[1].z) + (v[2].z + v[3].z), (v[0].w + v[1].w) + (v[2].w + v[3].w))));
    }
    CLK(15);
  }
  {
    const uint32_t* qx = pin(gs->QX[par] + ((bs >> 3) * 32 + 16 * hh) * 256 + tid * 4);
    const int ch = tid & 63, h0 = tid >> 6;
    const uint32_t dst = sb + OFF_Q + (ch >> 3) * 2048 + h0 * 128;
    wait_clk(tstore, T.D_QX);
    CLK(12);
    uint4 v[4];
#pragma unroll
    for (int i = 0; i < 4; i++) v[i] = ldg_2u64(qx + i * 1024);
    int it = 0;
    while (true) {
      uint32_t mn = 0xffffffffu;
#pragma unroll
      for (int i = 0; i < 4; i++) mn = min(mn, min(v[i].y, v[i].w));
      if (__all_sync(~0u, mn != 0)) break;
#pragma unroll
      for (int i = 0; i < 4; i++)
        asm volatile("{\n.reg .pred q;\nsetp.eq.u32 q, %5, 0;\n@q ld.relaxed.gpu.global.v4.b32 {%0, %1, %2, %3}, [%4];\n}"
                     : "+r"(v[i].x), "+r"(v[i].y), "+r"(v[i].z), "+r"(v[i].w) : "l"(qx + i * 1024), "r"(min(v[i].y, v[i].w)) : "memory");
      if (++it > SPIN_LIMIT) __trap();
    }
    CLK(13);
    ITS(2, it);
#pragma unroll
    for (int i = 0; i < 4; i++) sts4(dst + i * 512 + (((ch & 7) ^ ((4 * i + h0) & 7)) << 4), v[i]);
    asm volatile("fence.proxy.async.shared::cta;" ::: "memory");
    CLK(14);
    cbar();
  }

  uint2 cbf[4], sbf[4];
  const uint32_t* const pcb = gs->MOD2[par] + 2048 + (16 * w + t) * 16 + g * 2;
  uint32_t thand, anchor;
  const uint32_t opaque0 = w >> 4;
  if (wg == 0) {
    float mh[4];
    float L[8];
#pragma unroll
    for (int i = 0; i < 4; i++) { L[2 * i] = L[2 * i + 1] = 0.f; mh[i] = -INFINITY; }
    constexpr uint32_t dq = desc_lo(OFF_Q);
    const uint32_t ptw = sb + OFF_PT + (8 * (lane >> 4) + (lane & 7)) * 128 + (((2 * wq + ((lane >> 3) & 1)) ^ (lane & 7)) << 4);
    float S[8];
    auto softmax = [&](int tl) {
      auto write_p = [&](const float (&x)[8]) {
        float p[8];
#pragma unroll
        for (int i = 0; i < 8; i++) p[i] = ex2(x[i]);
        stsm4t(ptw + (tl & 1) * 2048, pack_bf16(p[0], p[1]), pack_bf16(p[2], p[3]), pack_bf16(p[4], p[5]), pack_bf16(p[6], p[7]));
        asm volatile("fence.proxy.async.shared::cta;" ::: "memory");
      };
      float x[8];
#pragma unroll
      for (int i = 0; i < 8; i++) x[i] = S[i] - mh[2 * (i >> 2) + (i & 1)];
      if (tl) write_p(x);
      const float ex = fmaxf(fmaxf(fmaxf(x[0], x[1]), fmaxf(x[2], x[3])), fmaxf(fmaxf(x[4], x[5]), fmaxf(x[6], x[7])));
      if (tl == 0 || bar_over(ex)) {
        float mx[4];
#pragma unroll
        for (int i = 0; i < 4; i++) mx[i] = fmaxf(S[4 * (i >> 1) + (i & 1)], S[4 * (i >> 1) + 2 + (i & 1)]);
        const float a = reduce_g(mx, lane, [](float u, float v) { return fmaxf(u, v); });
        stsf(sb + OFF_RED + wq * 64 + (8 * (lane >> 4) + 2 * t + ((lane >> 3) & 1)) * 4, a);
        bar_sync(2, 128);
#pragma unroll
        for (int jn = 0; jn < 2; jn++) {
          float m0 = mh[2 * jn], m1 = mh[2 * jn + 1];
#pragma unroll
          for (int i = 0; i < 4; i++) { const float2 v = ldsf2(sb + OFF_RED + i * 64 + (8 * jn + 2 * t) * 4); m0 = fmaxf(m0, v.x); m1 = fmaxf(m1, v.y); }
          const float a0 = ex2(mh[2 * jn] - m0), a1 = ex2(mh[2 * jn + 1] - m1);
          mh[2 * jn] = m0; mh[2 * jn + 1] = m1;
          L[4 * jn] *= a0; L[4 * jn + 1] *= a1; L[4 * jn + 2] *= a0; L[4 * jn + 3] *= a1;
          if (tid < 4) sts2f(sb + OFF_ALPHA + (8 * jn + 2 * t) * 4, a0, a1);
        }
        asm volatile("barrier.cta.arrive.aligned 1, 256;" ::: "memory");
#pragma unroll
        for (int i = 0; i < 8; i++) x[i] = S[i] - mh[2 * (i >> 2) + (i & 1)];
        write_p(x);
        bar_over(0.f);
      }
      const uint32_t dpt = __shfl_sync(~0u, desc_lo(OFF_PT) + (tl & 1) * 128, 0);
      wg_fence();
#pragma unroll
      for (int ks = 0; ks < 4; ks++) wgmma_n16_ones(L, ONE2, dpt + ks * 2);
      wg_commit();
    };
    uint32_t da = desc_lo(OFF_RING);
#pragma unroll 1
    for (int tl = 0; tl < 7; tl++) {
      uint32_t ok = 0;
#pragma unroll
      for (int u = 0; u < 4; u++) ok += mbar_test(BAR(BAR_FULL + 4 * tl + u));
      ok = __reduce_min_sync(~0u, ok);
      const uint32_t du = __shfl_sync(~0u, da, 0);
#pragma unroll
      for (int u = 0; u < 4; u++) {
        if (ok != 4) mbar_wait(BAR(BAR_FULL + 4 * tl + u));
        wg_fence();
#pragma unroll
        for (int k = 0; k < 8; k++) {
          const int i = 8 * u + k;
          if (i == 0) wgmma_n16<0, 0>(S, du, dq); else wgmma_n16<0, 1>(S, du + (i >> 2) * 512 + (i & 3) * 2, dq + (i >> 2) * 128 + (i & 3) * 2);
        }
        wg_commit();
      }
      wg_wait<0>();
      acc_fence(S); acc_fence(L);
      if (tl == 0) CLK(15);
      if (tl == 1) CLK(17);
      softmax(tl);
      if (tl == 0) CLK(16);
      if (tl == 1) CLK(18);
      if (tl == 3) CLK(19);
      if (tl == 6) CLK(20);
      da = (tl == 2 || tl == 5) ? da - 8192 : da + 4096;
    }
    if (cta < NFF) { load_units<4, 64>(sbf, pcb); load_units<4, 64>(cbf, pcb + 2048); }
    mbar_wait(BAR(BAR_ALLCLR));
    uint32_t* const mlo = pin(gin + blk(4 * (16 * hh + 4 * (g & 2) + 2 * t + (g & 1)) + 1, 6, g >> 2) + bs * 2);
#pragma unroll
    for (int i = 0; i < 32; i++) {
      if (i == 0 || i == 8 || i == 16 || i == 24 || i == 28) {
        if (i) wg_commit();
        mbar_wait(BAR(BAR_LAST + (i == 28 ? 4 : i >> 3)));
        if (i == 28) CLK(21);
        wg_fence();
      }
      if (i == 0) wgmma_n16<0, 0>(S, desc_lo(65536), dq); else wgmma_n16<0, 1>(S, desc_lo(65536) + (i >> 2) * 512 + (i & 3) * 2, dq + (i >> 2) * 128 + (i & 3) * 2);
    }
    wg_commit();
    wg_wait<0>();
    acc_fence(S); acc_fence(L);
    CLK(22);
    softmax(7);
    CLK(23);
    thand = clk32();
    wg_wait<0>();
    acc_fence(L);
    if (tid < 32) MLST(mlo, __float_as_uint(g & 2 ? (g & 1 ? mh[3] : mh[2]) : (g & 1 ? mh[1] : mh[0])), __float_as_uint(g & 2 ? (g & 1 ? L[5] : L[4]) : (g & 1 ? L[1] : L[0])));
    CLK(24);
  } else {
    float O[8][8];
#pragma unroll
    for (int i = 0; i < 8; i++)
#pragma unroll
      for (int k = 0; k < 8; k++) O[i][k] = 0.f;
    constexpr uint32_t dp = desc_lo(OFF_PT);
    auto handover = [&](int tl) {
      uint32_t over = opaque0 + (tl == 0);
#pragma unroll 1
      do {
        if (over) {
          cbar();
#pragma unroll
          for (int jn = 0; jn < 2; jn++) {
            const float2 a = ldsf2(sb + OFF_ALPHA + (8 * jn + 2 * t) * 4);
#pragma unroll
            for (int mb = 0; mb < 8; mb++) { O[mb][4 * jn] *= a.x; O[mb][4 * jn + 1] *= a.y; O[mb][4 * jn + 2] *= a.x; O[mb][4 * jn + 3] *= a.y; }
          }
        }
        over++;
      } while (bar_over(0.f));
    };
    uint32_t da = desc_lo(OFF_RING);
#pragma unroll 1
    for (int tl = 0; tl < 7; tl++) {
      handover(tl);
      const uint32_t dpt = dp + (tl & 1) * 128;
      wg_fence();
#pragma unroll
      for (int i = 0; i < 32; i++) wgmma_n16<1, 1>(O[i >> 2], da + (i >> 2) * 512 + (i & 3) * 128, dpt + (i & 3) * 2);
      wg_commit();
      wg_wait<0>();
#pragma unroll
      for (int mb = 0; mb < 8; mb++) acc_fence(O[mb]);
      if (lane == 0) mbar_arrive(BAR(BAR_EMPTY + tl));
      if (tl == 0) CLK(16);
      if (tl == 1) CLK(18);
      if (tl == 3) CLK(19);
      if (tl == 6) CLK(20);
      da = (tl == 2 || tl == 5) ? da - 8192 : da + 4096;
    }
    if (cta < NFF) { load_units<4, 64>(sbf, pcb); load_units<4, 64>(cbf, pcb + 2048); }
    mbar_wait(BAR(BAR_ALLCLR));
    uint32_t* x1o[8];
#pragma unroll
    for (int i = 0; i < 8; i++)
      x1o[i] = pin(inbox((16 * hh + 8 * ((i >> 1) & 1) + 2 * t + (i & 1)) * 4 + 2 * (i >> 2) + (wq >> 1), bs >> 4) + (bs & 15) * 64 + ((wq & 1) * 8 + g) * 4);
    handover(7);
    CLK(23);
    thand = clk32();
    auto pv = [&](int mb0, int n) {
      wg_fence();
#pragma unroll
      for (int i = 0; i < 16; i++)
        if (i < 4 * n) wgmma_n16<1, 1>(O[mb0 + (i >> 2)], desc_lo(65536) + (mb0 + (i >> 2)) * 512 + (i & 3) * 128, dp + 128 + (i & 3) * 2);
      wg_commit();
    };
    auto publish = [&](int J) {
#pragma unroll
      for (int k = 0; k < 4; k++) acc_fence(O[4 * J + k]);
#pragma unroll
      for (int i = 0; i < 4; i++) {
        const int k = 4 * (i >> 1) + (i & 1);
        stg_cvt8(x1o[4 * J + i], O[4 * J][k], O[4 * J][k + 2], O[4 * J + 1][k], O[4 * J + 1][k + 2],
                 O[4 * J + 2][k], O[4 * J + 2][k + 2], O[4 * J + 3][k], O[4 * J + 3][k + 2]);
      }
    };
    pv(0, 4); pv(4, 4);
    wg_wait<1>(); publish(0);
    wg_wait<0>(); publish(1);
    CLK(24);
  }

  {
    const uint32_t* px = pin(inbox(cta, w >> 1) + (w & 1) * 512 + lane * 2);
    uint32_t* const x2o = pin(inbox(cta, 4) + 512 + tid * 2);
    uint32_t* const x2p = pin(gin + blk(cta, 4, selector(cta) ^ 1) + 512 + tid * 2);
    const uint32_t q4 = lds1(sb + OFF_SEL + 4 * hI) ^ 0x00010100u;
    const uint32_t same = pin((uint32_t)(q4 == 0 || q4 == 0x01010101u));
    mbar_wait(BAR(BAR_TS));
    anchor = lds1(sb + OFF_TS);
    const uint32_t sdst = pin(sb + OFF_BS4 + w * 272 + lane * 8), ssrc = pin(sb + OFF_BS4 + (lane & 7) * 272 + (lane >> 3) * 16);
    float d[4] = {0.f, 0.f, 0.f, 0.f};
    wait_clk(thand, T.D_X1);
    wait_clk(anchor, T.A_X1);
    CLK(25);
    uint2 v[8];
    load_units<8, 64>(v, px);
    const bool early = __all_sync(~0u, mbar_test(BAR(BAR_WUV + wg)));
    if (early) load_a_t(aw, abase + OFF_WUV);
    mbar_wait(BAR(BAR_WV));
    const float4 wa = ldsf4(sb + OFF_WV + w * 32), wb = ldsf4(sb + OFF_WV + w * 32 + 16);
    const float wv[8] = {wa.x, wa.y, wa.z, wa.w, wb.x, wb.y, wb.z, wb.w};
    CLK(27);
    uint32_t it = opaque0;
    bool ok;
#pragma unroll 1
    do {
      if (it) {
#pragma unroll
        for (int i = 0; i < 8; i++) reload_unit(v[i], px + i * 64);
        if (it > SPIN_LIMIT) __trap();
      }
      it++;
      float a0 = 0.f, a1 = 0.f, a2 = 0.f, a3 = 0.f;
#pragma unroll
      for (int i = 0; i < 8; i++) { a0 += wv[i] * bf_lo(v[i].x); a1 += wv[i] * bf_hi(v[i].x); a2 += wv[i] * bf_lo(v[i].y); a3 += wv[i] * bf_hi(v[i].y); }
      ok = __all_sync(~0u, min_flags(v) != 0);
      sts2(sdst, pack_bf16(a0, a1), pack_bf16(a2, a3));
    } while (!ok);
    CLK(29);
    cbar();
    uint32_t b[4][4];
#pragma unroll
    for (int kk = 0; kk < 4; kk++) ldsm4(b[kk], ssrc + kk * 64);
    if (__builtin_expect(!early, 0)) { mbar_wait(BAR(BAR_WUV + wg)); load_a_t(aw, abase + OFF_WUV); }
    mma128(d, aw, b);
    const uint32_t c0 = pack_bf16(d[0], d[1]), c1 = pack_bf16(d[2], d[3]);
    stg_u64(x2o, c0, c1);
    stg_u64_unless(same, x2p, c0, c1);
    ITS(4, it - 1);
    tstore = clk32();
    CLK(30);
  }
  {
    uint32_t* const o = pin(inbox(4 * (8 * jI + w) + t, 4) + hI * 16 + g * 2);
    const uint32_t* x2i[4];
#pragma unroll
    for (int i = 0; i < 4; i++) x2i[i] = pin(nearbox(4 * hI + i, 4) + 512 + tid * 2);
    const uint32_t sdst = pin(sb + OFF_BS5 + (16 * w + g) * 16 + t * 4), ssrc = pin(sb + OFF_BS5 + lane * 16);
    float d[4] = {0.f, 0.f, 0.f, 0.f};
    wait_clk(tstore, T.D_X2);
    wait_clk(anchor, T.A_X1 + T.R_X2);
    uint2 v[4];
#pragma unroll
    for (int i = 0; i < 4; i++) v[i] = ldg_u64(x2i[i]);
    const bool early = __all_sync(~0u, mbar_test(BAR(BAR_WO + wg)));
    if (early) load_a_t(aw, abase + OFF_WO);
    CLK(31);
    uint32_t it = opaque0;
    bool ok;
#pragma unroll 1
    do {
      if (it) {
#pragma unroll
        for (int i = 0; i < 4; i++) reload_unit(v[i], x2i[i]);
        if (it > SPIN_LIMIT) __trap();
      }
      it++;
      ok = __all_sync(~0u, min_flags(v) != 0);
      sum4_to_smem(v, sdst);
    } while (!ok);
    CLK(32);
    cbar();
    uint32_t b[4][4];
#pragma unroll
    for (int kk = 0; kk < 4; kk++) ldsm4t(b[kk], ssrc + kk * 512);
    if (__builtin_expect(!early, 0)) { mbar_wait(BAR(BAR_WO + wg)); load_a_t(aw, abase + OFF_WO); }
    mma128(d, aw, b);
    ST3A(o, movm(pack_bf16(d[0], d[1])), movm(pack_bf16(d[2], d[3])));
    ITS(5, it - 1);
    tstore = clk32();
    CLK(33);
    if (lane == 0) mbar_arrive(BAR(BAR_P5D));
  }
  if (cta < NFF) {
    const int mi = lane >> 3, r = lane & 7;
    uint32_t a1[2][4][4], a2[2][2][4];
    check_units<4, 64>(sbf, pcb);
    check_units<4, 64>(cbf, pcb + 2048);
    __syncwarp();
#pragma unroll
    for (int s = 0; s < 4; s++) { cbf[s].x = hadd2(cbf[s].x, ONE2); cbf[s].y = hadd2(cbf[s].y, ONE2); }
    mbar_wait(BAR(BAR_W1));
#pragma unroll
    for (int mt = 0; mt < 2; mt++) {
#pragma unroll
      for (int ks = 0; ks < 4; ks++) ldsm4t(a1[mt][ks], sb + OFF_W1 + (64 * w + 16 * ks + 8 * (mi >> 1) + r) * 64 + (((2 * mt + (mi & 1)) ^ (r >> 1)) << 4));
      float u[4] = {0.f, 0.f, 0.f, 0.f}, vv[4] = {0.f, 0.f, 0.f, 0.f};
#pragma unroll
      for (int s = 0; s < 4; s++) { mma16816(u, a1[mt][s], cbf[s].x, cbf[s].y); mma16816(vv, a1[mt][s], sbf[s].x, sbf[s].y); }
      sts4f(sb + OFF_REDU + w * 1024 + mt * 512 + lane * 16, u[0], u[1], u[2], u[3]);
      sts4f(sb + OFF_REDV + w * 1024 + mt * 512 + lane * 16, vv[0], vv[1], vv[2], vv[3]);
    }
    const uint32_t* xb = pin(nearbox(cta & ~15, 6 + wg) + (16 * wq + t) * 16 + g * 2);
    uint32_t* const ox[2] = {pin(inbox(64 * hh + 8 * w + t, 5) + bs * 16 + g * 2), pin(inbox(64 * hh + 8 * w + 4 + t, 5) + bs * 16 + g * 2)};
    cbar();
    const int lp = (tid >> 2) & 31, kq = tid & 3;
    const int fo = 16 * wg + (lp >> 2) + 8 * (kq >> 1), bo = 2 * (lp & 3) + (kq & 1);
    float U = 0.f, V = 0.f;
#pragma unroll
    for (int i = 0; i < 8; i++) { U += ldsf(sb + OFF_REDU + i * 1024 + tid * 4); V += ldsf(sb + OFF_REDV + i * 1024 + tid * 4); }
    U = pin(U); V = pin(V);
    const uint32_t s_g = pin(sb + OFF_REDG + w * 1024 + lane * 16), s_s = pin(sb + OFF_REDS + g * 80 + w * 8);
    const uint32_t l_g = pin(sb + OFF_REDG + tid * 4), l_s = pin(sb + OFF_REDS + bo * 80), s_h = pin(sb + OFF_H1 + fo * 16 + bo * 2);
    CLK(34);
    wait_clk(tstore, T.D_X3B);
    wait_clk(anchor, T.A_X1 + T.R_X3A + T.R_X3B);
    uint2 x[4];
    load_units<4, 64>(x, xb);
    mbar_wait(BAR(BAR_W2));
#pragma unroll
    for (int i = 0; i < 4; i++)
      ldsm4t(a2[i >> 1][i & 1], sb + OFF_W2 + (w >> 1) * 4096 + (16 * (i & 1) + 8 * (mi >> 1) + r) * 128 + (((4 * (w & 1) + 2 * (i >> 1) + (mi & 1)) ^ r) << 4));
    CLK(35);
    uint32_t it = opaque0;
    float G[2][2][4], S[2][4];
#pragma unroll 1
    do {
      if (it) {
#pragma unroll
        for (int i = 0; i < 4; i++) reload_unit(x[i], xb + i * 64);
        if (it > SPIN_LIMIT) __trap();
      }
      it++;
#pragma unroll
      for (int i = 0; i < 8; i++) { G[0][i >> 2][i & 3] = G[1][i >> 2][i & 3] = S[i >> 2][i & 3] = 0.f; }
#pragma unroll
      for (int s = 0; s < 4; s++) {
        const uint32_t sx[4] = {x[s].x, ONE2, x[s].y, ONE2};
        mma16816(S[s & 1], sx, x[s].x, x[s].y);
        const uint32_t y0 = hmul2(x[s].x, cbf[s].x), y1 = hmul2(x[s].y, cbf[s].y);
        mma16816(G[0][s & 1], a1[0][s], y0, y1);
        mma16816(G[1][s & 1], a1[1][s], y0, y1);
      }
    } while (!__all_sync(~0u, min_flags(x) != 0));
    if (t == (g >> 1)) sts2f(s_s, (g & 1) ? S[0][3] + S[1][3] : S[0][2] + S[1][2], (g & 1) ? S[0][1] + S[1][1] : S[0][0] + S[1][0]);
#pragma unroll
    for (int mt = 0; mt < 2; mt++)
      sts4f(s_g + mt * 512, G[mt][0][0] + G[mt][1][0], G[mt][0][1] + G[mt][1][1], G[mt][0][2] + G[mt][1][2], G[mt][0][3] + G[mt][1][3]);
    CLK(37);
    cbar();
    {
      float gv[8];
      float4 sv[4];
#pragma unroll
      for (int i = 0; i < 4; i++) sv[i] = ldsf4(l_s + i * 16);
#pragma unroll
      for (int i = 0; i < 8; i++) gv[i] = ldsf(l_g + i * 1024);
      const float s1 = ((sv[0].x + sv[0].z) + (sv[1].x + sv[1].z)) + ((sv[2].x + sv[2].z) + (sv[3].x + sv[3].z));
      const float s2 = ((sv[0].y + sv[0].w) + (sv[1].y + sv[1].w)) + ((sv[2].y + sv[2].w) + (sv[3].y + sv[3].w));
      const float gsum = ((gv[0] + gv[1]) + (gv[2] + gv[3])) + ((gv[4] + gv[5]) + (gv[6] + gv[7]));
      const float mu = s1 * (1.f / 512.f);
      float rs;
      asm("rsqrt.approx.ftz.f32 %0, %1;" : "=f"(rs) : "f"(fmaxf(s2 * (1.f / 512.f) - mu * mu, 0.f) + 1e-5f));
      const float hv = fmaxf(rs * (gsum - mu * U) + V, 0.f);
      asm volatile("st.shared.u16 [%0], %1;" ::"r"(s_h), "h"(__bfloat16_as_ushort(__float2bfloat16(hv))) : "memory");
    }
    ITS(6, it - 1);
    CLK(38);
    cbar();
    uint32_t b[4];
    ldsm4t(b, sb + OFF_H1 + lane * 16);
    float o[2][2][4] = {};
#pragma unroll
    for (int i = 0; i < 4; i++) mma16816(o[i >> 1][i & 1], a2[i >> 1][i & 1], b[2 * (i & 1)], b[2 * (i & 1) + 1]);
#pragma unroll
    for (int mb = 0; mb < 2; mb++)
      ST4(ox[mb], movm(pack_bf16(o[mb][0][0] + o[mb][1][0], o[mb][0][1] + o[mb][1][1])), movm(pack_bf16(o[mb][0][2] + o[mb][1][2], o[mb][0][3] + o[mb][1][3])));
    CLK(39);
    if (lane == 0) mbar_arrive(BAR(BAR_P7D));
  }
  CLK_DUMP();
}

typedef CUresult (*EncodeTiledFn)(CUtensorMap*, CUtensorMapDataType, cuuint32_t, void*, const cuuint64_t*, const cuuint64_t*,
                                  const cuuint32_t*, const cuuint32_t*, CUtensorMapInterleave, CUtensorMapSwizzle,
                                  CUtensorMapL2promotion, CUtensorMapFloatOOBfill);

struct Dim { uint64_t size, stride; uint32_t box; };
template <int R> void encode_map(EncodeTiledFn enc, CUtensorMap* m, const void* base, const Dim (&d)[R], CUtensorMapSwizzle sw, CUtensorMapL2promotion promo) {
  cuuint64_t dims[R], strides[R];
  cuuint32_t box[R], es[R];
  for (int i = 0; i < R; i++) { dims[i] = d[i].size; strides[i] = d[i].stride; box[i] = d[i].box; es[i] = 1; }
  enc(m, CU_TENSOR_MAP_DATA_TYPE_BFLOAT16, R, const_cast<void*>(base), dims, strides + 1, box, es, CU_TENSOR_MAP_INTERLEAVE_NONE, sw, promo,
      CU_TENSOR_MAP_FLOAT_OOB_FILL_NONE);
}

}

extern "C" void kernel_launch(void* const* d_in, const int* in_sizes, int n_in, void* d_out, int out_size) {
  (void)in_sizes; (void)n_in; (void)out_size;
  static EncodeTiledFn enc = nullptr;
  static Scratch* scratch = nullptr;
  static uint32_t* inbox = nullptr;
  if (!enc) {
    void* sp = nullptr;
    cudaGetSymbolAddress(&sp, g_s);
    scratch = (Scratch*)sp;
    cudaGetSymbolAddress(&sp, g_in);
    inbox = (uint32_t*)(((uintptr_t)sp + 0xfffff) & ~(uintptr_t)0xfffff);
    void* fn = nullptr;
    cudaDriverEntryPointQueryResult q;
    cudaGetDriverEntryPoint("cuTensorMapEncodeTiled", &fn, cudaEnableDefault, &q);
    enc = (EncodeTiledFn)fn;
    cudaFuncSetAttribute(fused_decode_kernel, cudaFuncAttributeMaxDynamicSharedMemorySize, SMEM_BYTES);
  }
  const CUtensorMapSwizzle S128 = CU_TENSOR_MAP_SWIZZLE_128B, S0 = CU_TENSOR_MAP_SWIZZLE_NONE;
  const CUtensorMapL2promotion L0 = CU_TENSOR_MAP_L2_PROMOTION_NONE, L128 = CU_TENSOR_MAP_L2_PROMOTION_L2_128B;
  Params P;
  encode_map<2>(enc, &P.wq, d_in[2], {{4096, 2, 64}, {512, 8192, 64}}, S128, L0);
  encode_map<5>(enc, &P.wuk, d_in[3], {{4096, 2, 64}, {2, 8192, 2}, {4, 4 * 8192, 4}, {2, 2 * 8192, 2}, {32, 16 * 8192, 4}}, S128, L0);
  encode_map<2>(enc, &P.wm2, d_in[10], {{3072, 2, 16}, {512, 6144, 256}}, S0, L128);
  encode_map<3>(enc, &P.ckv2, d_in[1], {{64, 2, 64}, {8 * 4096, 1024, 64}, {8, 128, 2}}, S128, L0);
  encode_map<3>(enc, &P.ckv1, d_in[1], {{64, 2, 64}, {8 * 4096, 1024, 64}, {8, 128, 1}}, S128, L0);
  encode_map<5>(enc, &P.wuv, d_in[4], {{4096, 2, 64}, {2, 8 * 8192, 2}, {8, 64 * 8192, 4}, {8, 8192, 8}, {4, 16 * 8192, 1}}, S128, L0);
  encode_map<2>(enc, &P.wo, d_in[5], {{512, 2, 64}, {4096, 1024, 64}}, S128, L0);
  encode_map<2>(enc, &P.w1, d_in[7], {{1792, 2, 32}, {512, 3584, 256}}, CU_TENSOR_MAP_SWIZZLE_64B, L128);
  encode_map<3>(enc, &P.w2, d_in[8], {{64, 2, 64}, {1792, 1024, 32}, {8, 128, 2}}, S128, L0);
  fused_decode_kernel<<<NCTA, NTHREADS, SMEM_BYTES>>>((__nv_bfloat16*)d_out, scratch, (const uint8_t*)d_in[10], (const uint8_t*)d_in[0],
                     (const uint8_t*)d_in[9], inbox,
                     P);
}
```

```cpp
#include <cuda_runtime.h>
#include <cuda.h>
#include <cuda_bf16.h>
#include <stdint.h>
#define V4 1

namespace {

constexpr int NCTA = 128;
constexpr int NTHREADS = 320;
constexpr int NFG = 56;
constexpr int NFF = 2 * NFG;
constexpr int NSYNC = 4;

constexpr uint32_t OFF_RING = 0;
constexpr uint32_t OFF_WUK = 131072;
constexpr uint32_t OFF_WQ = 131072 + 32768;
constexpr uint32_t OFF_WM2 = 65536 + 49152;
constexpr uint32_t OFF_WUV = 131072;
constexpr uint32_t OFF_WO = 131072 + 32768;
constexpr uint32_t OFF_W1 = 0;
constexpr uint32_t OFF_W2 = 32768;
constexpr uint32_t OFF_Q = 196608;
constexpr uint32_t OFF_PT = 212992;
constexpr uint32_t OFF_SCR = 217088;
constexpr uint32_t OFF_XS = 65536;
constexpr uint32_t OFF_CS = 65536 + 8192;
constexpr uint32_t OFF_P0S = 65536 + 16384;
constexpr uint32_t OFF_BS1 = OFF_SCR + 2048;
constexpr uint32_t OFF_BS2 = OFF_SCR + 4096;
constexpr uint32_t OFF_P0B = OFF_SCR + 6144;
constexpr uint32_t OFF_XN = OFF_SCR + 8192;
constexpr uint32_t OFF_RED = OFF_SCR + 10496;
constexpr uint32_t OFF_ALPHA = OFF_SCR + 11072;
constexpr uint32_t OFF_WV = OFF_SCR + 6144;
constexpr uint32_t OFF_SEL = OFF_SCR + 10752;
constexpr uint32_t OFF_TS = OFF_SCR + 11136;
constexpr uint32_t OFF_BARS = OFF_SCR + 11264;
constexpr uint32_t SMEM_BYTES = OFF_BARS + 512;
constexpr uint32_t OFF_BS4 = OFF_Q;
constexpr uint32_t OFF_H1 = OFF_Q + 2304;
constexpr uint32_t OFF_REDS = OFF_Q + 2816;
constexpr uint32_t OFF_BS5 = OFF_Q + 4096;
constexpr uint32_t OFF_REDG = OFF_Q + 8192;
constexpr uint32_t OFF_REDU = 65536;
constexpr uint32_t OFF_REDV = 65536 + 8192;

constexpr int BAR_FULL = 0;
constexpr int BAR_LAST = 28;
constexpr int BAR_WUK = 33, BAR_WM2 = 35, BAR_WUV = 36, BAR_WO = 38, BAR_W1 = 40, BAR_W2 = 41;
constexpr int BAR_ALLCLR = 42, BAR_TS = 43, BAR_WV = 44;
constexpr int BAR_EMPTY = 45;
constexpr int BAR_P0BD = 52;
constexpr int BAR_P1D = 53, BAR_P2D = 54;
constexpr int BAR_P5D = 55, BAR_P7D = 56;
constexpr int NBARS = 57;
constexpr int BAR_XC = 57, BAR_WQ = 58;
constexpr int BAR_C = 60, BAR_END = 61;
constexpr uint32_t SB = 1024;

#define TUNE_LIST(X) \
  X(PC_T0, 340) X(PC_XC, 0) X(PC_C, 0) X(PC_P1, 320) X(PC_PM, 225) X(PC_P2, 319) X(PC_STAG, 390) X(PC_DS, 0) X(PC_SL, 500) X(PC_W, 4) X(PC_NW, 8) \
  X(PW_A, -1) X(PW_0, 280) X(PW_ST, 0) X(PW_UV, 250) X(PW_G, 610) X(PW_O, 345) X(PW_G2, 430) X(PW_G3, 390) X(PW_F, 330) X(PW_GB, -100) \
  X(LOC, 0) X(PR_T0, 1000) X(PR_N, 4) X(CLR_T0, 3900) X(CLR_CLK, 190) \
  X(D_MOD, 1550) X(D_QP, 1100) X(D_QX, 950) X(TS_P, 1) X(TS_O, 1150) X(D_TS, 900) X(A_M, 1750) X(D_X1, 1400) X(A_X1, 2460) X(R_X0, 1100) \
  X(D_X2, 260) X(R_X2, 1000) X(D_X3A, 60) X(R_X3A, 3080) X(D_X3B, 800) X(R_X3B, 980) X(D_FIN, 320) X(R_FIN, 1520) X(RB, 0)
struct Tune {
#define X(n, v) static constexpr int n = v;
  TUNE_LIST(X)
#undef X
};

#define THRESH "0f42700000"
#define PVV 0
struct Scratch {
  uint32_t MOD1[2][4 * 64 * 64];
  uint32_t MOD2[2][128 * 64];
  uint32_t QP[2][128 * 256 * 2];
  uint32_t QX[2][8 * 32 * 256];
  uint32_t epoch;
  uint32_t pad[31];
  uint32_t sync[NSYNC][32];
};
__device__ Scratch g_s;
__device__ uint32_t g_in[(128 + 16) * 16384];
__device__ __forceinline__ uint32_t blk(int c, int k, uint32_t sel) { return c * 16384 + k * 2048 + ((sel ^ k) & 1) * 1024; }
__device__ __forceinline__ uint32_t flip(int c) { return c ^ (c >> 1) ^ (c >> 3); }

#define CLK_DECL
#define CLK(i) do {} while (0)
#define CLK_DUMP() do {} while (0)
#define ITS(i, v) do {} while (0)

struct Params {
  CUtensorMap wq, wuk, wm2, wm3, ckv2, ckv1, wuv, wo, w1, w2;
};

__device__ __forceinline__ void mbar_init(uint32_t bar, int cnt) { asm volatile("mbarrier.init.shared::cta.b64 [%0], %1;" ::"r"(bar), "r"(cnt)); }
__device__ __forceinline__ void mbar_expect(uint32_t bar, uint32_t bytes) { asm volatile("mbarrier.arrive.expect_tx.shared::cta.b64 _, [%0], %1;" ::"r"(bar), "r"(bytes) : "memory"); }
__device__ __forceinline__ void mbar_arrive(uint32_t bar) { asm volatile("mbarrier.arrive.shared::cta.b64 _, [%0];" ::"r"(bar) : "memory"); }
__device__ __forceinline__ uint32_t clk32() { unsigned long long c; asm volatile("mov.u64 %0, %%clock64;" : "=l"(c) :: "memory"); return (uint32_t)c; }
__device__ __forceinline__ uint32_t gtime32() { uint32_t c; asm volatile("mov.u32 %0, %%globaltimer_lo;" : "=r"(c) :: "memory"); return c; }
__device__ __forceinline__ void wait_clk(uint32_t t0, int clocks) { while ((int)(clk32() - t0) < clocks) {} }
__device__ __forceinline__ void backoff(int clocks) { if (clocks > 0) wait_clk(clk32(), clocks); }
__device__ __forceinline__ void until_ns(uint32_t ns) { while ((int)(gtime32() - ns) < 0) {} }
__device__ __forceinline__ void slot(uint32_t& tn, int slack) {
  uint32_t now;
  do { now = gtime32(); } while ((int)(now - tn) < 0);
  if ((int)(now - tn) > slack) tn = now - slack;
}
template <typename T> __device__ __forceinline__ T* pin(T* p) { asm volatile("" : "+l"(p)); return p; }
__device__ __forceinline__ uint32_t pin(uint32_t v) { asm volatile("" : "+r"(v)); return v; }
__device__ __forceinline__ float pin(float v) { asm volatile("" : "+f"(v)); return v; }
constexpr int SPIN_LIMIT = 1 << 22;
__device__ __forceinline__ void mbar_wait(uint32_t bar) {
  asm volatile("{\n.reg .pred p;\n.reg .u32 c;\nmov.u32 c, 0;\n"
               "MW_LOOP:\nmbarrier.try_wait.parity.shared::cta.b64 p, [%0], 0;\n@p bra MW_DONE;\n"
               "add.u32 c, c, 1;\nsetp.lt.u32 p, c, 4194304;\n@p bra MW_LOOP;\ntrap;\nMW_DONE:\n}"
               ::"r"(bar) : "memory");
}
__device__ __forceinline__ bool mbar_test(uint32_t bar) {
  uint32_t ok;
  asm volatile("{\n.reg .pred p;\nmbarrier.test_wait.parity.shared::cta.b64 p, [%1], 0;\nselp.u32 %0,1,0,p;\n}" : "=r"(ok) : "r"(bar) : "memory");
  return ok;
}
__device__ __forceinline__ void tma2d(uint32_t dst, const CUtensorMap* m, int c0, int c1, uint32_t bar, uint64_t pol) {
  asm volatile("cp.async.bulk.tensor.2d.shared::cluster.global.mbarrier::complete_tx::bytes.L2::cache_hint [%0], [%1, {%3,%4}], [%2], %5;"
               ::"r"(dst), "l"(m), "r"(bar), "r"(c0), "r"(c1), "l"(pol) : "memory");
}
__device__ __forceinline__ void tma2d_nohint(uint32_t dst, const CUtensorMap* m, int c0, int c1, uint32_t bar) {
  asm volatile("cp.async.bulk.tensor.2d.shared::cluster.global.mbarrier::complete_tx::bytes [%0], [%1, {%3,%4}], [%2];"
               ::"r"(dst), "l"(m), "r"(bar), "r"(c0), "r"(c1) : "memory");
}
__device__ __forceinline__ void tma3d(uint32_t dst, const CUtensorMap* m, int c0, int c1, int c2, uint32_t bar, uint64_t pol) {
  asm volatile("cp.async.bulk.tensor.3d.shared::cluster.global.mbarrier::complete_tx::bytes.L2::cache_hint [%0], [%1, {%3,%4,%5}], [%2], %6;"
               ::"r"(dst), "l"(m), "r"(bar), "r"(c0), "r"(c1), "r"(c2), "l"(pol) : "memory");
}
__device__ __forceinline__ void tma5d(uint32_t dst, const CUtensorMap* m, int c0, int c1, int c2, int c3, int c4, uint32_t bar, uint64_t pol) {
  asm volatile("cp.async.bulk.tensor.5d.shared::cluster.global.mbarrier::complete_tx::bytes.L2::cache_hint [%0], [%1, {%3,%4,%5,%6,%7}], [%2], %8;"
               ::"r"(dst), "l"(m), "r"(bar), "r"(c0), "r"(c1), "r"(c2), "r"(c3), "r"(c4), "l"(pol) : "memory");
}
__device__ __forceinline__ void bulk_ld(uint32_t dst, const void* src, uint32_t bytes, uint32_t bar) {
  asm volatile("cp.async.bulk.shared::cluster.global.mbarrier::complete_tx::bytes [%0], [%1], %2, [%3];" ::"r"(dst), "l"(src), "r"(bytes), "r"(bar) : "memory");
}
__device__ __forceinline__ void bar_sync(int id, int n) { asm volatile("barrier.cta.sync.aligned %0, %1;" ::"r"(id), "r"(n) : "memory"); }
__device__ __forceinline__ void cbar() { asm volatile("barrier.cta.sync.aligned 1, 256;" ::: "memory"); }
__device__ __forceinline__ bool bar_over(float ex) {
  uint32_t over;
  asm volatile("{\n.reg .pred p, q;\nsetp.gtu.f32 p, %1, " THRESH ";\nbarrier.cta.red.or.aligned.pred q, 4, 256, p;\nselp.u32 %0, 1, 0, q;\n}"
               : "=r"(over) : "f"(ex) : "memory");
  return over;
}

__device__ __forceinline__ uint32_t ldg_nc1(const void* p) { uint32_t v; asm volatile("ld.global.nc.L1::no_allocate.u32 %0, [%1];" : "=r"(v) : "l"(p)); return v; }
__device__ __forceinline__ uint2 ldg_nc2(const void* p) { uint2 v; asm volatile("ld.global.nc.v2.u32 {%0,%1}, [%2];" : "=r"(v.x), "=r"(v.y) : "l"(p)); return v; }
__device__ __forceinline__ uint4 ldg_nc4(const void* p) { uint4 v; asm volatile("ld.global.nc.L1::no_allocate.v4.u32 {%0,%1,%2,%3}, [%4];" : "=r"(v.x), "=r"(v.y), "=r"(v.z), "=r"(v.w) : "l"(p)); return v; }
__device__ __forceinline__ uint32_t ldg_rlx1(const void* p) { uint32_t v; asm volatile("ld.relaxed.gpu.global.u32 %0, [%1];" : "=r"(v) : "l"(p) : "memory"); return v; }
__device__ __forceinline__ void stg4(void* p, uint4 v) { asm volatile("st.relaxed.gpu.global.v4.u32 [%0], {%1,%2,%3,%4};" ::"l"(p), "r"(v.x), "r"(v.y), "r"(v.z), "r"(v.w) : "memory"); }
__device__ __forceinline__ void stg1(void* p, uint32_t a) { asm volatile("st.relaxed.gpu.global.u32 [%0], %1;" ::"l"(p), "r"(a) : "memory"); }
__device__ __forceinline__ uint32_t nz(uint32_t w) { return max(w, 1u); }
__device__ __forceinline__ uint2 ldg_u64(const void* p) {
  uint2 v; asm volatile("{\n.reg .b64 a;\nld.relaxed.gpu.global.b64 a, [%2];\nmov.b64 {%0,%1}, a;\n}" : "=r"(v.x), "=r"(v.y) : "l"(p) : "memory"); return v;
}
__device__ __forceinline__ uint4 ldg_2u64(const void* p) {
  uint4 v; asm volatile("{\n.reg .b64 a, b;\nld.relaxed.gpu.global.v2.b64 {a, b}, [%4];\nmov.b64 {%0,%1}, a;\nmov.b64 {%2,%3}, b;\n}" : "=r"(v.x), "=r"(v.y), "=r"(v.z), "=r"(v.w) : "l"(p) : "memory"); return v;
}
__device__ __forceinline__ void stg_u64(void* p, uint32_t x, uint32_t y) {
  asm volatile("{\n.reg .b32 y;\nmax.u32 y, %2, 1;\nst.relaxed.gpu.global.v2.b32 [%0], {%1, y};\n}" ::"l"(p), "r"(x), "r"(y) : "memory");
}
__device__ __forceinline__ void red_u64(void* p, uint32_t x, uint32_t y) {
  asm volatile("{\n.reg .b32 y;\n.reg .b64 a;\nmax.u32 y, %2, 1;\nmov.b64 a, {%1, y};\nred.relaxed.gpu.global.or.b64 [%0], a;\n}" ::"l"(p), "r"(x), "r"(y) : "memory");
}
__device__ __forceinline__ void red_u64_unless(uint32_t bad, void* p, uint32_t x, uint32_t y) {
  asm volatile("{\n.reg .b32 y;\n.reg .b64 a;\n.reg .pred q;\nsetp.eq.u32 q, %3, 0;\nmax.u32 y, %2, 1;\nmov.b64 a, {%1, y};\n@q red.relaxed.gpu.global.or.b64 [%0], a;\n}" ::"l"(p), "r"(x), "r"(y), "r"(bad) : "memory");
}
#define ST3A stg_u64
#define ST4 stg_u64
#define ST3B stg_u64_unless
#define MLST red_u64
__device__ __forceinline__ void stg_u64_unless(uint32_t bad, void* p, uint32_t x, uint32_t y) {
  asm volatile("{\n.reg .b32 y;\n.reg .pred q;\nsetp.eq.u32 q, %3, 0;\nmax.u32 y, %2, 1;\n@q st.relaxed.gpu.global.v2.b32 [%0], {%1, y};\n}" ::"l"(p), "r"(x), "r"(y), "r"(bad) : "memory");
}
__device__ __forceinline__ void stg_2u64(void* p, uint4 v) {
  asm volatile("{\n.reg .b32 y, w;\nmax.u32 y, %2, 1;\nmax.u32 w, %4, 1;\nst.relaxed.gpu.global.v4.b32 [%0], {%1, y, %3, w};\n}" ::"l"(p), "r"(v.x), "r"(v.y), "r"(v.z), "r"(v.w) : "memory");
}

__device__ __forceinline__ void stg_cvt8(void* p, float a0, float a1, float b0, float b1, float c0, float c1, float d0, float d1) {
  asm volatile("{\n.reg .b32 x, y, z, w;\ncvt.rn.bf16x2.f32 x, %2, %1;\ncvt.rn.bf16x2.f32 y, %4, %3;\ncvt.rn.bf16x2.f32 z, %6, %5;\ncvt.rn.bf16x2.f32 w, %8, %7;\n"
               "max.u32 y, y, 1;\nmax.u32 w, w, 1;\nst.relaxed.gpu.global.v4.b32 [%0], {x, y, z, w};\n}"
               ::"l"(p), "f"(a0), "f"(a1), "f"(b0), "f"(b1), "f"(c0), "f"(c1), "f"(d0), "f"(d1) : "memory");
}
__device__ __forceinline__ uint32_t pack_bf16(float lo, float hi) { uint32_t r; asm("cvt.rn.bf16x2.f32 %0, %1, %2;" : "=r"(r) : "f"(hi), "f"(lo)); return r; }
__device__ __forceinline__ float bf_lo(uint32_t w) { return __uint_as_float(w << 16); }
__device__ __forceinline__ float bf_hi(uint32_t w) { return __uint_as_float(w & 0xffff0000u); }
__device__ __forceinline__ float ex2(float x) { float r; asm("ex2.approx.ftz.f32 %0, %1;" : "=f"(r) : "f"(x)); return r; }
__device__ __forceinline__ uint32_t hmul2(uint32_t a, uint32_t b) { uint32_t r; asm("mul.rn.bf16x2 %0, %1, %2;" : "=r"(r) : "r"(a), "r"(b)); return r; }
__device__ __forceinline__ uint32_t hadd2(uint32_t a, uint32_t b) { uint32_t r; asm("add.rn.bf16x2 %0, %1, %2;" : "=r"(r) : "r"(a), "r"(b)); return r; }
__device__ __forceinline__ uint32_t hfma2(uint32_t a, uint32_t b, uint32_t c) { uint32_t r; asm("fma.rn.bf16x2 %0, %1, %2, %3;" : "=r"(r) : "r"(a), "r"(b), "r"(c)); return r; }
__device__ __forceinline__ uint32_t silu2(uint32_t v) { const float a = bf_lo(v), b = bf_hi(v); return pack_bf16(__fdividef(a, 1.f + __expf(-a)), __fdividef(b, 1.f + __expf(-b))); }
constexpr uint32_t ONE2 = 0x3f803f80u;

__device__ __forceinline__ void ldsm4(uint32_t (&r)[4], uint32_t a) { asm volatile("ldmatrix.sync.aligned.m8n8.x4.shared.b16 {%0,%1,%2,%3}, [%4];" : "=r"(r[0]), "=r"(r[1]), "=r"(r[2]), "=r"(r[3]) : "r"(a) : "memory"); }
__device__ __forceinline__ void ldsm4t(uint32_t (&r)[4], uint32_t a) { asm volatile("ldmatrix.sync.aligned.m8n8.x4.trans.shared.b16 {%0,%1,%2,%3}, [%4];" : "=r"(r[0]), "=r"(r[1]), "=r"(r[2]), "=r"(r[3]) : "r"(a) : "memory"); }
__device__ __forceinline__ void ldsm2t(uint32_t& r0, uint32_t& r1, uint32_t a) { asm volatile("ldmatrix.sync.aligned.m8n8.x2.trans.shared.b16 {%0,%1}, [%2];" : "=r"(r0), "=r"(r1) : "r"(a) : "memory"); }
__device__ __forceinline__ void stsm4t(uint32_t a, uint32_t r0, uint32_t r1, uint32_t r2, uint32_t r3) { asm volatile("stmatrix.sync.aligned.m8n8.x4.trans.shared.b16 [%0], {%1,%2,%3,%4};" ::"r"(a), "r"(r0), "r"(r1), "r"(r2), "r"(r3) : "memory"); }
__device__ __forceinline__ uint32_t movm(uint32_t a) { uint32_t d; asm volatile("movmatrix.sync.aligned.m8n8.trans.b16 %0, %1;" : "=r"(d) : "r"(a)); return d; }
__device__ __forceinline__ void mma16816(float (&d)[4], const uint32_t (&a)[4], uint32_t b0, uint32_t b1) {
  asm volatile("mma.sync.aligned.m16n8k16.row.col.f32.bf16.bf16.f32 {%0,%1,%2,%3}, {%4,%5,%6,%7}, {%8,%9}, {%0,%1,%2,%3};"
               : "+f"(d[0]), "+f"(d[1]), "+f"(d[2]), "+f"(d[3]) : "r"(a[0]), "r"(a[1]), "r"(a[2]), "r"(a[3]), "r"(b0), "r"(b1));
}
__device__ __forceinline__ void sts1(uint32_t a, uint32_t v) { asm volatile("st.shared.u32 [%0], %1;" ::"r"(a), "r"(v) : "memory"); }
__device__ __forceinline__ void sts2(uint32_t a, uint32_t x, uint32_t y) { asm volatile("st.shared.v2.u32 [%0], {%1,%2};" ::"r"(a), "r"(x), "r"(y) : "memory"); }
__device__ __forceinline__ void sts4(uint32_t a, uint4 v) { asm volatile("st.shared.v4.u32 [%0], {%1,%2,%3,%4};" ::"r"(a), "r"(v.x), "r"(v.y), "r"(v.z), "r"(v.w) : "memory"); }
__device__ __forceinline__ void sts2f(uint32_t a, float x, float y) { asm volatile("st.shared.v2.f32 [%0], {%1,%2};" ::"r"(a), "f"(x), "f"(y) : "memory"); }
__device__ __forceinline__ void sts4f(uint32_t a, float x, float y, float z, float w) { asm volatile("st.shared.v4.f32 [%0], {%1,%2,%3,%4};" ::"r"(a), "f"(x), "f"(y), "f"(z), "f"(w) : "memory"); }
__device__ __forceinline__ void stsf(uint32_t a, float v) { asm volatile("st.shared.f32 [%0], %1;" ::"r"(a), "f"(v) : "memory"); }
__device__ __forceinline__ uint32_t lds1(uint32_t a) { uint32_t v; asm volatile("ld.shared.u32 %0, [%1];" : "=r"(v) : "r"(a) : "memory"); return v; }
__device__ __forceinline__ float ldsf(uint32_t a) { float v; asm volatile("ld.shared.f32 %0, [%1];" : "=f"(v) : "r"(a) : "memory"); return v; }
__device__ __forceinline__ float2 ldsf2(uint32_t a) { float2 v; asm volatile("ld.shared.v2.f32 {%0,%1}, [%2];" : "=f"(v.x), "=f"(v.y) : "r"(a) : "memory"); return v; }
__device__ __forceinline__ float4 ldsf4(uint32_t a) { float4 v; asm volatile("ld.shared.v4.f32 {%0,%1,%2,%3}, [%4];" : "=f"(v.x), "=f"(v.y), "=f"(v.z), "=f"(v.w) : "r"(a) : "memory"); return v; }
__device__ __forceinline__ void lds4(uint32_t (&r)[4], uint32_t a) { asm volatile("ld.shared.v4.u32 {%0,%1,%2,%3}, [%4];" : "=r"(r[0]), "=r"(r[1]), "=r"(r[2]), "=r"(r[3]) : "r"(a) : "memory"); }

__device__ __forceinline__ void wg_fence() { asm volatile("wgmma.fence.sync.aligned;" ::: "memory"); }
__device__ __forceinline__ void wg_commit() { asm volatile("wgmma.commit_group.sync.aligned;" ::: "memory"); }
template <int N> __device__ __forceinline__ void wg_wait() { asm volatile("wgmma.wait_group.sync.aligned %0;" ::"n"(N) : "memory"); }
__host__ __device__ constexpr uint32_t desc_lo(uint32_t off) { return ((SB + off) >> 4) | 0x10000u; }
template <int TA, int ACC> __device__ __forceinline__ void wgmma_n16(float (&d)[8], uint32_t da, uint32_t db) {
  asm volatile("{\n.reg .b64 da, db;\nmov.b64 da, {%8, 0x40000040};\nmov.b64 db, {%9, 0x40000040};\n"
               "wgmma.mma_async.sync.aligned.m64n16k16.f32.bf16.bf16 {%0,%1,%2,%3,%4,%5,%6,%7}, da, db, %11, 1, 1, %10, 0;\n}"
               : "+f"(d[0]), "+f"(d[1]), "+f"(d[2]), "+f"(d[3]), "+f"(d[4]), "+f"(d[5]), "+f"(d[6]), "+f"(d[7])
               : "r"(da), "r"(db), "n"(TA), "n"(ACC));
}
__device__ __forceinline__ void wgmma_n16_ones(float (&d)[8], uint32_t one, uint32_t db) {
  asm volatile("{\n.reg .b64 db;\nmov.b64 db, {%9, 0x40000040};\n"
               "wgmma.mma_async.sync.aligned.m64n16k16.f32.bf16.bf16 {%0,%1,%2,%3,%4,%5,%6,%7}, {%8,%8,%8,%8}, db, 1, 1, 1, 0;\n}"
               : "+f"(d[0]), "+f"(d[1]), "+f"(d[2]), "+f"(d[3]), "+f"(d[4]), "+f"(d[5]), "+f"(d[6]), "+f"(d[7])
               : "r"(one), "r"(db));
}
__device__ __forceinline__ void acc_fence(float (&d)[8]) {
  asm volatile("" : "+f"(d[0]), "+f"(d[1]), "+f"(d[2]), "+f"(d[3]), "+f"(d[4]), "+f"(d[5]), "+f"(d[6]), "+f"(d[7]) :: "memory");
}

template <int N, int STRIDE> __device__ __forceinline__ void load_units(uint2 (&v)[N], const uint32_t* p) {
#pragma unroll
  for (int i = 0; i < N; i++) v[i] = ldg_u64(p + i * STRIDE);
}
__device__ __forceinline__ void reload_unit(uint2& v, const uint32_t* p) {
  asm volatile("{\n.reg .pred q;\nsetp.eq.u32 q, %1, 0;\n@q ld.relaxed.gpu.global.v2.b32 {%0, %1}, [%2];\n}" : "+r"(v.x), "+r"(v.y) : "l"(p) : "memory");
}
template <int N> __device__ __forceinline__ uint32_t min_flags(const uint2 (&v)[N]) {
  uint32_t a = v[0].y, b = v[1].y;
#pragma unroll
  for (int i = 2; i < N; i += 2) { a = min(a, v[i].y); b = min(b, v[i + 1].y); }
  return min(a, b);
}
template <int N, int STRIDE> __device__ __forceinline__ int check_units(uint2 (&v)[N], const uint32_t* p) {
  int it = 0;
  while (!__all_sync(~0u, min_flags(v) != 0)) {
#pragma unroll
    for (int i = 0; i < N; i++) reload_unit(v[i], p + i * STRIDE);
    if (++it > SPIN_LIMIT) __trap();
  }
  return it;
}
__device__ __forceinline__ void sum4_to_smem(const uint2 (&v)[4], uint32_t dst) {
  const float c0 = (bf_lo(v[0].x) + bf_lo(v[1].x)) + (bf_lo(v[2].x) + bf_lo(v[3].x));
  const float c1 = (bf_hi(v[0].x) + bf_hi(v[1].x)) + (bf_hi(v[2].x) + bf_hi(v[3].x));
  const float c2 = (bf_lo(v[0].y) + bf_lo(v[1].y)) + (bf_lo(v[2].y) + bf_lo(v[3].y));
  const float c3 = (bf_hi(v[0].y) + bf_hi(v[1].y)) + (bf_hi(v[2].y) + bf_hi(v[3].y));
  sts1(dst, pack_bf16(c0, c1));
  sts1(dst + 128, pack_bf16(c2, c3));
}
__device__ __forceinline__ uint32_t a_t_offset(int w, int lane) {
  const int mi = lane >> 3, r = lane & 7;
  return (w >> 2) * 16384 + (8 * (mi >> 1) + r) * 128 + (((2 * (w & 3) + (mi & 1)) ^ r) << 4);
}
__device__ __forceinline__ void load_a_t(uint32_t (&a)[8][4], uint32_t base) {
#pragma unroll
  for (int ks = 0; ks < 8; ks++) ldsm4t(a[ks], base + ks * 2048);
}
__device__ __forceinline__ void mma128(float (&d)[4], const uint32_t (&a)[8][4], const uint32_t (&b)[4][4]) {
  float e[4][4] = {{d[0], d[1], d[2], d[3]}, {0.f, 0.f, 0.f, 0.f}, {0.f, 0.f, 0.f, 0.f}, {0.f, 0.f, 0.f, 0.f}};
#pragma unroll
  for (int kk = 0; kk < 4; kk++) { mma16816(e[(2 * kk) & 3], a[2 * kk], b[kk][0], b[kk][1]); mma16816(e[(2 * kk + 1) & 3], a[2 * kk + 1], b[kk][2], b[kk][3]); }
#pragma unroll
  for (int i = 0; i < 4; i++) d[i] = (e[0][i] + e[1][i]) + (e[2][i] + e[3][i]);
}
template <int NP> __device__ __forceinline__ bool sum_pieces(const uint32_t* p0, uint32_t one, float (&r)[4]) {
  uint2 v[NP / 4];
  load_units<NP / 4, 64>(v, p0);
  float d[4][4] = {};
#pragma unroll
  for (int i = 0; i < NP / 8; i++) { const uint32_t a[4] = {v[2 * i].x, v[2 * i].y, v[2 * i + 1].x, v[2 * i + 1].y}; mma16816(d[i & 3], a, one, one); }
  const bool ok = __all_sync(~0u, min_flags(v) != 0);
#pragma unroll
  for (int k = 0; k < 4; k++) r[k] = (d[0][k] + d[1][k]) + (d[2][k] + d[3][k]);
  return ok;
}
template <typename F> __device__ __forceinline__ float reduce_g(const float (&x)[4], int lane, F f) {
  const bool u4 = lane & 16, u3 = lane & 8;
  const float a0 = f(u4 ? x[2] : x[0], __shfl_xor_sync(~0u, u4 ? x[0] : x[2], 16));
  const float a1 = f(u4 ? x[3] : x[1], __shfl_xor_sync(~0u, u4 ? x[1] : x[3], 16));
  const float b = f(u3 ? a1 : a0, __shfl_xor_sync(~0u, u3 ? a0 : a1, 8));
  return f(b, __shfl_xor_sync(~0u, b, 4));
}

__global__ void __launch_bounds__(NTHREADS, 1)
fused_decode_kernel(__nv_bfloat16* __restrict__ gout, Scratch* __restrict__ gs, const uint8_t* __restrict__ gwmod,
                    const uint8_t* __restrict__ gx, const uint8_t* __restrict__ gc, uint32_t* __restrict__ gin,
                    const __grid_constant__ Params P) {
  constexpr Tune T{};
  extern __shared__ __align__(1024) uint8_t smem_raw[];
  constexpr uint32_t sb = SB;
  const int tid = __shfl_xor_sync(0xffffffffu, threadIdx.x ^ 1, 1), lane = tid & 31;
  const int w = __shfl_sync(0xffffffffu, threadIdx.x >> 5, 0);
  const int cta = blockIdx.x;
  auto BAR = [](int i) { return SB + OFF_BARS + 8 * i; };
  auto selector = [&](int c) { uint32_t v; asm volatile("ld.shared.u8 %0, [%1];" : "=r"(v) : "r"(sb + OFF_SEL + c) : "memory"); return v; };
  auto inbox = [&](int c, int k) { return gin + blk(c, k, selector(c)); };
  auto nearbox = [&](int c, int k) { return gin + blk(c, k, selector(cta) ^ flip((c ^ cta) & 15)); };
  const int g = lane >> 2, t = lane & 3;
  const int hI = cta >> 2, jI = cta & 3;
  const int bs = cta >> 1, hh = cta & 1;

  CLK_DECL;
  CLK(0);
  if (w == 8) {
    CLK(7);
    const uint32_t t_entry = gtime32();
    CLK(8);
    if (lane == 0) {
      if ((uint32_t)__cvta_generic_to_shared(smem_raw) != SB) __trap();
      mbar_init(BAR(BAR_WQ), 1); mbar_init(BAR(BAR_WQ + 1), 1); mbar_init(BAR(BAR_XC), 1); mbar_init(BAR(BAR_C), 1);
      asm volatile("fence.mbarrier_init.release.cluster;" ::: "memory");
      asm volatile("prefetch.tensormap [%0];" ::"l"(&P.wq) : "memory");
      mbar_expect(BAR(BAR_XC), 8192); mbar_expect(BAR(BAR_C), 8192); mbar_expect(BAR(BAR_WQ), 16384); mbar_expect(BAR(BAR_WQ + 1), 16384);
      CLK(9);
    }
    __syncwarp();
    asm volatile("barrier.cta.arrive.aligned 0, %0;" ::"n"(NTHREADS) : "memory");
    CLK(10);
    uint32_t tn = t_entry + T.PC_T0 + ((bs * 37) & 63) * T.PC_STAG / 64;
    const int h = hI, j = jI;
    if (lane == 0) {
      uint64_t pol; asm volatile("createpolicy.fractional.L2::evict_first.b64 %0, 1.0;" : "=l"(pol));
#pragma unroll
      for (int u = 0; u < 4; u++) {
        until_ns(tn + u * T.PC_P1);
        if (u == 0) CLK(11);
        tma2d(sb + OFF_WQ + u * 8192, &P.wq, 128 * h + 64 * (u >> 1), 128 * j + 64 * (u & 1), BAR(BAR_WQ + (u >> 1)), pol);
        if (u == T.PC_XC) {
#pragma unroll
          for (int i = 0; i < 4; i++) { const int o = ((i + cta) & 3) * 2048; bulk_ld(sb + OFF_XS + o, gx + o, 2048, BAR(BAR_XC)); }
        }
        if (u == T.PC_C) {
#pragma unroll
          for (int i = 0; i < 4; i++) { const int o = ((i + cta) & 3) * 2048; bulk_ld(sb + OFF_CS + o, gc + o, 2048, BAR(BAR_C)); }
        }
        if (u == 0) {
          CLK(1);
          asm volatile("prefetch.tensormap [%0];" ::"l"(&P.wuk) : "memory");
          asm volatile("prefetch.tensormap [%0];" ::"l"(&P.wm2) : "memory");
          asm volatile("prefetch.tensormap [%0];" ::"l"(&P.ckv2) : "memory");
        }
      }
    }
    __syncwarp();
    tn += 4 * T.PC_P1;
    bar_sync(5, 64);
    if (lane == 0) {
      uint64_t pol; asm volatile("createpolicy.fractional.L2::evict_first.b64 %0, 1.0;" : "=l"(pol));
#pragma unroll
      for (int u = 0; u < 4; u++) {
        if ((u & 1) == (T.PC_W > 3) && T.PC_NW) mbar_wait(BAR(BAR_WQ + (u >> 1)));
        slot(tn, T.PC_SL);
        tma5d(sb + OFF_WUK + u * 8192, &P.wuk, 128 * h + 64 * (u >> 1), 0, 0, 0, 8 * j + 4 * (u & 1), BAR(BAR_WUK + (u >> 1)), pol);
        tn += T.PC_P1;
      }
#pragma unroll
      for (int u = 0; u < 2; u++) {
        if (u == (T.PC_W > 3) && T.PC_NW) mbar_wait(BAR(BAR_WUK));
        slot(tn, T.PC_SL);
        if (j != 3) tma2d_nohint(sb + OFF_WM2 + u * 8192, &P.wm2, 1024 + 16 * (3 * h + j), 256 * u, BAR(BAR_WM2));
        tn += T.PC_PM;
      }
      const int row0 = (bs >> 3) * 4096 + (bs & 7) * 64;
      uint32_t dst = sb + OFF_RING;
      const int p2 = T.PC_P2 + (32 - ((bs * 37) & 63)) * T.PC_DS / 1024;
#pragma unroll 1
      for (int n = 0; n < 31; n++) {
        if (n >= 4 && (n < 12 || (n & 3) == 0)) mbar_wait(BAR(n >= 12 ? BAR_EMPTY + (n >> 2) - 3 : (n == 7 && j != 3) ? BAR_P0BD : (n == 8 || n == 9) ? BAR_P2D : BAR_P1D));
        if (n < T.PC_NW) {
          if (n >= T.PC_W) mbar_wait(BAR(BAR_FULL + n - T.PC_W));
          else if ((n & 1) == (T.PC_W > 3)) mbar_wait(BAR((n < 2 || j == 3) ? BAR_WUK + 1 : BAR_WM2));
        }
        slot(tn, T.PC_SL);
        tma3d(dst, &P.ckv2, 0, row0 + (n >> 2) * 512, 2 * (n & 3), BAR(BAR_FULL + n), pol);
        dst = (n == 11 || n == 23) ? sb + OFF_RING : dst + 16384;
        tn += n >= 15 ? p2 : T.PC_P2;
        if (n == 4) CLK(2);
        if (n == 12) CLK(3);
        if (n == 20) CLK(4);
        if (n == 28) CLK(5);
        if (n == 24) {
          asm volatile("prefetch.tensormap [%0];" ::"l"(&P.ckv1) : "memory");
          asm volatile("prefetch.tensormap [%0];" ::"l"(&P.wuv) : "memory");
          asm volatile("prefetch.tensormap [%0];" ::"l"(&P.wo) : "memory");
          asm volatile("prefetch.tensormap [%0];" ::"l"(cta < NFF ? &P.w1 : &P.wm3) : "memory");
          asm volatile("prefetch.tensormap [%0];" ::"l"(&P.w2) : "memory");
        }
      }
      slot(tn, T.PC_SL);
      tma3d(dst, &P.ckv1, 0, row0 + 7 * 512, 6, BAR(BAR_LAST + 3), pol);
      tma3d(dst + 8192, &P.ckv1, 0, row0 + 7 * 512, 7, BAR(BAR_LAST + 4), pol);
      tn += T.PC_P2;
      CLK(6);
      auto unit = [&](int u) {
        if (u < 4) tma5d(sb + OFF_WUV + u * 8192, &P.wuv, 128 * h + 64 * (u >> 1), 0, 4 * (j >> 1), 0, 2 * (j & 1) + (u & 1), BAR(BAR_WUV + (u >> 1)), pol);
        else if (u < 8) tma2d(sb + OFF_WO + (u - 4) * 8192, &P.wo, 128 * j + 64 * ((u - 4) >> 1), 128 * h + 64 * (u & 1), BAR(BAR_WO + ((u - 4) >> 1)), pol);
        else if (u < 10) { if (cta < NFF) tma2d_nohint(sb + OFF_W1 + (u - 8) * 16384, &P.w1, 32 * bs, 256 * (u - 8), BAR(BAR_W1)); }
        else if (cta < NFF) tma3d(sb + OFF_W2 + (u - 10) * 8192, &P.w2, 0, 32 * bs, 4 * hh + 2 * (u - 10), BAR(BAR_W2), pol);
        else tma2d_nohint(sb + OFF_W1 + (u - 10) * 16384, &P.wm3, 2560 + 32 * (cta - NFF), 256 * (u - 10), BAR(BAR_W1));
      };
      mbar_wait(BAR(BAR_EMPTY + 5));
      if (T.PW_A >= 0) { mbar_wait(BAR(BAR_LAST + T.PW_A)); tn = gtime32(); }
      tn += T.PW_0 + ((cta * 37) & 127) * T.PW_ST / 128;
#pragma unroll
      for (int u = 0; u < 12; u++) {
        if (u == 8) mbar_wait(BAR(BAR_EMPTY + 6));
        if (u == 10 && cta >= NFF) tn += T.PW_GB;
        until_ns(tn);
        unit(u);
        tn += u < 3 ? T.PW_UV : u == 3 ? T.PW_G : u < 7 ? T.PW_O : u == 7 ? T.PW_G2 : u == 9 ? T.PW_G3 : T.PW_F;
      }
      CLK_DUMP();
    }
    return;
  }

  if (w == 9) {
    if (lane == 0) {
#pragma unroll
      for (int i = 0; i < NBARS; i++) mbar_init(BAR(i), i >= BAR_P1D ? 8 : i >= BAR_EMPTY ? 4 : 1);
      asm volatile("fence.mbarrier_init.release.cluster;" ::: "memory");
    }
    __syncwarp();
    mbar_expect(BAR(lane), lane == BAR_LAST + 3 ? 8192 : 16384);
    if (lane < BAR_ALLCLR - 32) mbar_expect(BAR(32 + lane), lane == 0 ? 8192 : lane == BAR_W1 - 32 ? 32768 : 16384);
    CLK(9);
    asm volatile("barrier.cta.arrive.aligned 5, 64;" ::: "memory");
    asm volatile("barrier.cta.arrive.aligned 0, %0;" ::"n"(NTHREADS) : "memory");
  }
  const uint32_t epoch = ldg_rlx1(&gs->epoch);

  if (w == 9) {
    const int mo = g * 512 + 16 * hI + 2 * jI;
    const uint32_t xo0 = ldg_nc1(gx + mo * 2), xo1 = ldg_nc1(gx + mo * 2 + 16);
    const int par = epoch & 1;
    const uint32_t t0 = gtime32();
    const uint4 z = make_uint4(0, 0, 0, 0);
    uint32_t sel;
    {
      uint32_t* pa = gin + blk(cta, 5, 0) + 960;
      uint32_t* pb = gin + blk(cta, 5, 1) + 960;
      until_ns(t0 + T.PR_T0);
      if (lane < 4) stg4(reinterpret_cast<uint4*>(lane & 2 ? pa : pb) + (lane & 1), z);
      uint32_t ma = 0xffffffffu, mb = 0xffffffffu;
#pragma unroll 1
      for (int i = 0; i < 2 * T.PR_N; i++) {
        const uint32_t c0 = clk32();
        asm volatile("{\n.reg .pred q;\n.reg .b32 v;\nsetp.eq.u32 q, %1, 0;\nmov.u32 v, 0;\n@q atom.relaxed.gpu.global.add.u32 v, [%0], 1;\n"
                     "setp.eq.u32 q, v, 0xffffffff;\n@q trap;\n}" ::"l"(i & 1 ? pb : pa), "r"(lane) : "memory");
        const uint32_t d = clk32() - c0;
        if (i & 1) mb = min(mb, d); else ma = min(ma, d);
      }
      sel = __shfl_sync(~0u, (uint32_t)(mb < ma), 0);
      if (T.LOC == 1) sel ^= 1;
      if (T.LOC == 2) sel ^= (cta ^ (cta >> 3)) & 1;
      const uint32_t sw = 2 * (epoch + 1) + sel;
      if (lane < 2) stg4(reinterpret_cast<uint4*>(gin + blk(cta, 5, 1) + 896) + lane, make_uint4(sw, sw, sw, sw));
    }
    until_ns(t0 + T.CLR_T0);
    {
#pragma unroll 1
      for (int i0 = 0; i0 < 13; i0++) {
        uint4* q = reinterpret_cast<uint4*>(gin + (i0 < 12 ? blk(cta, i0 >> 1, sel) + (i0 & 1) * 512 : blk(cta, 4, sel ^ 1) + 512)) + lane;
#pragma unroll
        for (int i = 0; i < 4; i++) if (i0 != 11 || i < 3) stg4(q + i * 32, z);
        backoff(T.CLR_CLK);
      }
#pragma unroll
      for (int i = 0; i < 2; i++) {
        if (jI == 1) stg4(reinterpret_cast<uint4*>(gin + blk(cta, 6, i)) + lane, z);
        if (lane < 2) stg4(reinterpret_cast<uint4*>(gin + blk(cta, 5, i) + 928) + lane, z);
        stg4(reinterpret_cast<uint4*>(gin + blk(16 * g, 6 + (cta >> 6), i) + (cta & 63) * 16) + t, z);
      }
      CLK(1);
      {
        uint32_t sv = 0;
        uint32_t u[4];
        int it = 0;
        do {
#pragma unroll
          for (int i = 0; i < 4; i++) u[i] = ldg_rlx1(gin + blk(4 * lane + i, 5, 1) + 896) ^ (2 * (epoch + 1));
          if (++it > SPIN_LIMIT) __trap();
        } while (!__all_sync(~0u, (u[0] | u[1] | u[2] | u[3]) < 2));
#pragma unroll
        for (int i = 0; i < 4; i++) sv |= u[i] << (8 * i);
        sts1(sb + OFF_SEL + lane * 4, sv);
      }
      asm volatile("fence.acq_rel.gpu;" ::: "memory");
      CLK(2);
      __syncwarp();
      if (lane < NSYNC) asm volatile("red.relaxed.gpu.global.add.u32 [%0], 1;" ::"l"(&gs->sync[lane][0]) : "memory");
#pragma unroll
      for (int i = 0; i < 4; i++) stg4(reinterpret_cast<uint4*>(gs->QP[par ^ 1] + cta * 512) + i * 32 + lane, z);
      backoff(T.CLR_CLK);
#pragma unroll
      for (int i = 0; i < 4; i++) stg4(reinterpret_cast<uint4*>(gs->QX[par ^ 1] + cta * 512) + i * 32 + lane, z);
      stg4(reinterpret_cast<uint4*>(gs->MOD1[par ^ 1] + cta * 128) + lane, z);
      if (lane < 16) stg4(reinterpret_cast<uint4*>(gs->MOD2[par ^ 1] + cta * 64) + lane, z);
      const uint32_t target = (epoch + 1) * NCTA;
      uint32_t c; int it = 0;
      do {
        backoff(T.CLR_CLK);
        asm volatile("ld.acquire.gpu.global.u32 %0, [%1];" : "=r"(c) : "l"(&gs->sync[cta % NSYNC][0]) : "memory");
        if (++it > SPIN_LIMIT) __trap();
      } while (!__all_sync(~0u, (int)(c - target) >= 0));
      if (lane == 0) mbar_arrive(BAR(BAR_ALLCLR));
    }
    CLK(3);
    const uint32_t* const pg = gs->MOD2[par] + cta * 16 + g * 2;
    auto gate = [&](const uint32_t* q) { uint2 u; int it = 0; do { u = ldg_u64(q); if (++it > SPIN_LIMIT) __trap(); } while (!__all_sync(~0u, u.y != 0)); return u; };
    const uint2 gau = gate(pg);
    uint32_t anchor;
    {
      uint32_t* const po = gin + blk(16 * (lane & 7), 5, lane >> 3) + 928;
      const uint32_t* const pi = nearbox(cta & ~15, 5) + 928;
      mbar_wait(BAR(BAR_LAST + T.TS_P));
      unsigned long long now; asm volatile("mov.u64 %0, %%globaltimer;" : "=l"(now));
      if (lane < 16) {
        asm volatile("red.relaxed.gpu.global.max.u64 [%0], %1;" ::"l"(po + 2), "l"(now) : "memory");
        asm volatile("red.relaxed.gpu.global.add.u32 [%0], 1;" ::"l"(po + 1) : "memory");
      }
      backoff(T.D_TS);
      uint4 v; int it = 0;
      do { v = ldg_2u64(pi); if (++it > SPIN_LIMIT) __trap(); } while (!__all_sync(~0u, v.y == NCTA));
      const int age = min(max((int)(gtime32() - v.z), 0), 4000);
      anchor = clk32() - age * 7 / 4 + T.TS_O;
      if (lane == 0) { sts1(sb + OFF_TS, anchor); mbar_arrive(BAR(BAR_TS)); }
      CLK(10);
    }
    {
      const uint32_t* pm = pin(nearbox(4 * hI + 1, 6) + lane * 4);
      wait_clk(anchor, T.A_M);
      uint4 ml = ldg_2u64(pm);
      int it = 0;
      while (!__all_sync(~0u, ml.y != 0 && ml.w != 0)) { ml = ldg_2u64(pm); if (++it > SPIN_LIMIT) __trap(); }
      ITS(2, it);
      float M = fmaxf(__uint_as_float(ml.x), __uint_as_float(ml.z));
      M = fmaxf(M, __shfl_xor_sync(~0u, M, 1)); M = fmaxf(M, __shfl_xor_sync(~0u, M, 2));
      const float e0 = ex2(__uint_as_float(ml.x) - M), e1 = ex2(__uint_as_float(ml.z) - M);
      float l = e0 * __uint_as_float(ml.y) + e1 * __uint_as_float(ml.w);
      l += __shfl_xor_sync(~0u, l, 1); l += __shfl_xor_sync(~0u, l, 2);
      const float inv = __fdividef(1.f, l);
      sts2f(sb + OFF_WV + lane * 8, e0 * inv, e1 * inv);
      __syncwarp();
      if (lane == 0) mbar_arrive(BAR(BAR_WV));
      CLK(11);
    }
    uint32_t* x3o[4];
#pragma unroll
    for (int i = 0; i < 4; i++) x3o[i] = pin(gin + blk(32 * i + 16 * (t >> 1), 6 + (cta >> 6), t) + (cta & 63) * 16 + g * 2);
    uint32_t* const fo = pin(reinterpret_cast<uint32_t*>(gout) + mo / 2 + 4 * (t & 1));
    const uint32_t* const p3 = pin(gin + blk(cta, 4, sel) + t * 16 + g * 2);
    const uint32_t* const p4 = pin(gin + blk(cta, 5, sel) + t * 16 + g * 2);
    const uint32_t one = pin((g & 1) ? 0x3f800000u : 0x00003f80u);
    const float xf[4] = {pin(bf_lo(xo0)), pin(bf_hi(xo0)), pin(bf_lo(xo1)), pin(bf_hi(xo1))};
    const float ga[4] = {pin(bf_lo(gau.x)), pin(bf_hi(gau.x)), pin(bf_lo(gau.y)), pin(bf_hi(gau.y))};
    mbar_wait(BAR(BAR_P5D));
    backoff(T.D_X3A);
    wait_clk(anchor, T.A_X1 + T.R_X3A);
    CLK(4);
    float r[4];
    uint32_t x20, x21;
    int it = 0;
    bool ok;
    do {
      ok = sum_pieces<32>(p3, one, r);
      x20 = pack_bf16(xf[0] + ga[0] * r[0], xf[1] + ga[1] * r[1]); x21 = pack_bf16(xf[2] + ga[2] * r[2], xf[3] + ga[3] * r[3]);
#pragma unroll
      for (int i = 0; i < 4; i++) ST3B(!ok || (i == 3 && t >= 2), x3o[i], x20, x21);
    } while (!ok && ++it < SPIN_LIMIT);
    CLK(6);
    ITS(0, it);
    const uint32_t xw = (t & 1) ? x21 : x20;
    const float xa = pin(bf_lo(xw)), xb = pin(bf_hi(xw));
    if (cta < NFF) mbar_wait(BAR(BAR_P7D)); else wait_clk(anchor, T.A_X1 + T.R_X3A + T.R_X3B + T.R_FIN - T.D_FIN);
    uint2 gbu = ldg_u64(pg + 3 * 2048);
    backoff(T.D_FIN);
    CLK(7);
    do {
      ok = sum_pieces<NFG>(p4, one, r);
      ok = ok && __all_sync(~0u, gbu.y != 0);
      const uint32_t gw = (t & 1) ? gbu.y : gbu.x;
      const uint32_t o = pack_bf16(xa + bf_lo(gw) * ((t & 1) ? r[2] : r[0]), xb + bf_hi(gw) * ((t & 1) ? r[3] : r[1]));
      if (ok && t < 2) asm volatile("st.global.u32 [%0], %1;" ::"l"(fo), "r"(o) : "memory");
      reload_unit(gbu, pg + 3 * 2048);
    } while (!ok && ++it < SPIN_LIMIT);
    if (!ok) __trap();
    ITS(1, it);
    CLK(8);
    CLK_DUMP();
    if (cta == 0 && lane == 0) stg1(&gs->epoch, epoch + 1);
    return;
  }

  const int wg = w >> 2, wq = w & 3;
  uint32_t tstore;
  {
    const uint8_t* pw = gwmod + (size_t)(128 * jI + 16 * w + 4 * (g >> 1) + (g & 1)) * 6144 + 64 * hI + 16 * t;
    const uint4 w0 = ldg_nc4(pw), w1 = ldg_nc4(pw + 2 * 6144);
    const uint2 cc = ldg_nc2(gc + g * 1024 + 256 * jI + 32 * w + 8 * t);
    CLK(40);
    const uint32_t a[4] = {silu2(cc.x), 0u, silu2(cc.y), 0u};
    float d[4][4] = {{0.f, 0.f, 0.f, 0.f}, {0.f, 0.f, 0.f, 0.f}, {0.f, 0.f, 0.f, 0.f}, {0.f, 0.f, 0.f, 0.f}};
    mma16816(d[0], a, movm(w0.x), movm(w1.x)); mma16816(d[1], a, movm(w0.y), movm(w1.y));
    mma16816(d[2], a, movm(w0.z), movm(w1.z)); mma16816(d[3], a, movm(w0.w), movm(w1.w));
    CLK(1);
    sts4f(sb + OFF_P0S + w * 1088 + lane * 16, d[0][0], d[0][1], d[1][0], d[1][1]);
    sts4f(sb + OFF_P0S + w * 1088 + 544 + lane * 16, d[2][0], d[2][1], d[3][0], d[3][1]);
    bar_sync(0, NTHREADS);
    if (tid < 128) {
      const uint32_t src = sb + OFF_P0S + ((tid >> 2) & 1) * 544 + (((tid >> 3) & 7) * 4 + 2 * (tid >> 6) + (tid & 1)) * 16 + ((tid >> 1) & 1) * 8;
      float2 v[8];
#pragma unroll
      for (int i = 0; i < 8; i++) v[i] = ldsf2(src + i * 1088);
      const float ax = ((v[0].x + v[1].x) + (v[2].x + v[3].x)) + ((v[4].x + v[5].x) + (v[6].x + v[7].x));
      const float ay = ((v[0].y + v[1].y) + (v[2].y + v[3].y)) + ((v[4].y + v[5].y) + (v[6].y + v[7].y));
      stg1(gs->MOD1[epoch & 1] + jI * 4096 + hI * 128 + tid, nz(pack_bf16(ax, ay)));
    }
    tstore = clk32();
  }
  CLK(2);
  const int par = epoch & 1;
  uint32_t cf[4][4];
  mbar_wait(BAR(BAR_XC));
  {
    uint32_t u[2][4];
    lds4(u[0], sb + OFF_XS + w * 1024 + lane * 16); lds4(u[1], sb + OFF_XS + w * 1024 + 512 + lane * 16);
    float v[16];
#pragma unroll
    for (int i = 0; i < 8; i++) { v[2 * i] = bf_lo(u[i >> 2][i & 3]); v[2 * i + 1] = bf_hi(u[i >> 2][i & 3]); }
    float s = 0.f;
#pragma unroll
    for (int i = 0; i < 16; i++) s += v[i];
#pragma unroll
    for (int o = 16; o; o >>= 1) s += __shfl_xor_sync(~0u, s, o);
    const float mu = s * (1.f / 512.f);
    float q = 0.f;
#pragma unroll
    for (int i = 0; i < 16; i++) { v[i] -= mu; q += v[i] * v[i]; }
#pragma unroll
    for (int o = 16; o; o >>= 1) q += __shfl_xor_sync(~0u, q, o);
    const float rs = rsqrtf(q * (1.f / 512.f) + 1e-5f);
    const bool hi = jI & 2;
    uint32_t o[4];
#pragma unroll
    for (int i = 0; i < 4; i++) o[i] = pack_bf16((hi ? v[8 + 2 * i] : v[2 * i]) * rs, (hi ? v[9 + 2 * i] : v[2 * i + 1]) * rs);
    if ((lane >> 4) == (jI & 1)) sts4(sb + OFF_XN + w * 272 + (lane & 15) * 16, make_uint4(o[0], o[1], o[2], o[3]));
  }
  CLK(3);
  uint32_t aw[8][4];
  const uint32_t abase = __shfl_sync(~0u, sb + a_t_offset(w, lane), lane);
  {
    const uint32_t* pm = pin(gs->MOD1[par] + (8 * jI + w) * 64 + lane * 2);
    uint32_t* const qpo = pin(gs->QP[par] + (cta * 256 + tid) * 2);
    float d[4] = {0.f, 0.f, 0.f, 0.f};
    wait_clk(tstore, T.D_MOD);
    CLK(4);
    uint2 v[8];
    load_units<8, 2048>(v, pm);
    cbar();
    const uint32_t xn0 = lds1(sb + OFF_XN + g * 272 + w * 32 + t * 4), xn1 = lds1(sb + OFF_XN + g * 272 + w * 32 + 16 + t * 4);
    const bool early = __all_sync(~0u, mbar_test(BAR(BAR_WQ + wg)));
    if (early) load_a_t(aw, abase + OFF_WQ);
    int it = 0;
    while (true) {
      uint32_t mn = 0xffffffffu;
#pragma unroll
      for (int i = 0; i < 8; i++) mn = min(mn, min(v[i].x, v[i].y));
      if (__all_sync(~0u, mn != 0)) break;
#pragma unroll
      for (int i = 0; i < 8; i++) { if (v[i].x == 0) v[i].y = 0; reload_unit(v[i], pm + i * 2048); }
      if (++it > SPIN_LIMIT) __trap();
    }
    CLK(5);
    ITS(0, it);
    float sc[2][4];
#pragma unroll
    for (int i = 0; i < 2; i++) {
      sc[i][0] = (bf_lo(v[i].x) + bf_lo(v[2 + i].x)) + (bf_lo(v[4 + i].x) + bf_lo(v[6 + i].x));
      sc[i][1] = (bf_hi(v[i].x) + bf_hi(v[2 + i].x)) + (bf_hi(v[4 + i].x) + bf_hi(v[6 + i].x));
      sc[i][2] = (bf_lo(v[i].y) + bf_lo(v[2 + i].y)) + (bf_lo(v[4 + i].y) + bf_lo(v[6 + i].y));
      sc[i][3] = (bf_hi(v[i].y) + bf_hi(v[2 + i].y)) + (bf_hi(v[4 + i].y) + bf_hi(v[6 + i].y));
    }
    sts2(sb + OFF_BS1 + (w >> 1) * 512 + lane * 16 + (w & 1) * 8,
         pack_bf16(bf_lo(xn0) * (1.f + sc[1][0]) + sc[0][0], bf_hi(xn0) * (1.f + sc[1][1]) + sc[0][1]),
         pack_bf16(bf_lo(xn1) * (1.f + sc[1][2]) + sc[0][2], bf_hi(xn1) * (1.f + sc[1][3]) + sc[0][3]));
    if (!early) { mbar_wait(BAR(BAR_WQ + wg)); load_a_t(aw, abase + OFF_WQ); }
    CLK(6);
    cbar();
    uint32_t b[4][4];
#pragma unroll
    for (int kk = 0; kk < 4; kk++) lds4(b[kk], sb + OFF_BS1 + kk * 512 + lane * 16);
    mma128(d, aw, b);
    stg_u64(qpo, pack_bf16(d[0], d[1]), pack_bf16(d[2], d[3]));
    tstore = clk32();
    CLK(7);
    if (wg) {
      mbar_wait(BAR(BAR_C));
#pragma unroll
      for (int i = 0; i < 4; i++) lds4(cf[i], sb + OFF_CS + g * 1024 + wq * 256 + i * 64 + t * 16);
#pragma unroll
      for (int i = 0; i < 16; i++) cf[i >> 2][i & 3] = silu2(cf[i >> 2][i & 3]);
    }
    __syncwarp();
    if (lane == 0) mbar_arrive(BAR(BAR_P1D));
  }
  {
    const uint32_t* pq = pin(gs->QP[par] + (hI * 4 * 256 + tid) * 2);
    uint32_t* const qxo = pin(gs->QX[par] + (g * 32 + hI) * 256 + 64 * jI + 8 * w + 2 * t);
    uint2 v[4];
    float d[4] = {0.f, 0.f, 0.f, 0.f};
    wait_clk(tstore, T.D_QP);
    CLK(8);
    load_units<4, 512>(v, pq);
    const uint32_t kbase = sb + OFF_WUK + (16 * w + (lane & 15)) * 128;
    auto load_half = [&](int hf) {
#pragma unroll
      for (int ks = 0; ks < 4; ks++) ldsm4(aw[4 * hf + ks], kbase + hf * 16384 + (((2 * ks + (lane >> 4)) ^ (lane & 7)) << 4));
    };
    mbar_wait(BAR(BAR_WUK));
    load_half(0);
    const bool early = __all_sync(~0u, mbar_test(BAR(BAR_WUK + 1)));
    if (early) load_half(1);
    const int it = check_units<4, 512>(v, pq);
    CLK(9);
    ITS(1, it);
    sum4_to_smem(v, sb + OFF_BS2 + (16 * w + g) * 16 + t * 4);
    if (!early) { mbar_wait(BAR(BAR_WUK + 1)); load_half(1); }
    CLK(10);
    cbar();
    uint32_t b[4][4];
#pragma unroll
    for (int kk = 0; kk < 4; kk++) ldsm4t(b[kk], sb + OFF_BS2 + (32 * kk + lane) * 16);
    mma128(d, aw, b);
    const float sc = 0.08838834764831845f * 1.4426950408889634f;
    stg_u64(qxo, movm(pack_bf16(d[0] * sc, d[1] * sc)), movm(pack_bf16(d[2] * sc, d[3] * sc)));
    tstore = clk32();
    CLK(11);
    if (lane == 0) mbar_arrive(BAR(BAR_P2D));
  }
  if (wg && jI != 3) {
    const int mi = lane >> 3, r = lane & 7;
    const uint32_t a0 = sb + OFF_WM2 + (8 * (r >> 1) + (r & 1) + 2 * (mi >> 1)) * 32 + (mi & 1) * 16;
    mbar_wait(BAR(BAR_WM2));
#pragma unroll
    for (int s = 0; s < 8; s++) ldsm4t(aw[s], a0 + (128 * wq + 32 * (s >> 1) + 4 * (s & 1)) * 32);
    float d[4] = {0.f, 0.f, 0.f, 0.f};
    mma128(d, aw, cf);
    sts4f(sb + OFF_P0B + (tid - 128) * 16, d[0], d[1], d[2], d[3]);
    if (lane == 0) mbar_arrive(BAR(BAR_P0BD));
    bar_sync(3, 128);
    if (w == 4) {
      float4 v[4];
#pragma unroll
      for (int i = 0; i < 4; i++) v[i] = ldsf4(sb + OFF_P0B + (i * 32 + lane) * 16);
      stg_u64(gs->MOD2[par] + (3 * hI + jI) * 64 + t * 16 + g * 2, movm(pack_bf16((v[0].x + v[1].x) + (v[2].x + v[3].x), (v[0].y + v[1].y) + (v[2].y + v[3].y))),
              movm(pack_bf16((v[0].z + v[1].z) + (v[2].z + v[3].z), (v[0].w + v[1].w) + (v[2].w + v[3].w))));
    }
    CLK(15);
  }
  {
    const uint32_t* qx = pin(gs->QX[par] + ((bs >> 3) * 32 + 16 * hh) * 256 + tid * 4);
    const int ch = tid & 63, h0 = tid >> 6;
    const uint32_t dst = sb + OFF_Q + (ch >> 3) * 2048 + h0 * 128;
    wait_clk(tstore, T.D_QX);
    CLK(12);
    uint4 v[4];
#pragma unroll
    for (int i = 0; i < 4; i++) v[i] = ldg_2u64(qx + i * 1024);
    int it = 0;
    while (true) {
      uint32_t mn = 0xffffffffu;
#pragma unroll
      for (int i = 0; i < 4; i++) mn = min(mn, min(v[i].y, v[i].w));
      if (__all_sync(~0u, mn != 0)) break;
#pragma unroll
      for (int i = 0; i < 4; i++)
        asm volatile("{\n.reg .pred q;\nsetp.eq.u32 q, %5, 0;\n@q ld.relaxed.gpu.global.v4.b32 {%0, %1, %2, %3}, [%4];\n}"
                     : "+r"(v[i].x), "+r"(v[i].y), "+r"(v[i].z), "+r"(v[i].w) : "l"(qx + i * 1024), "r"(min(v[i].y, v[i].w)) : "memory");
      if (++it > SPIN_LIMIT) __trap();
    }
    CLK(13);
    ITS(2, it);
#pragma unroll
    for (int i = 0; i < 4; i++) sts4(dst + i * 512 + (((ch & 7) ^ ((4 * i + h0) & 7)) << 4), v[i]);
    asm volatile("fence.proxy.async.shared::cta;" ::: "memory");
    CLK(14);
    cbar();
  }

  uint2 cbf[4], sbf[4];
  const uint32_t* const pcb = gs->MOD2[par] + 2048 + (16 * w + t) * 16 + g * 2;
  auto load_frags = [&] {
    if (cta < NFF) { load_units<4, 64>(sbf, pcb); load_units<4, 64>(cbf, pcb + 2048); }
    else {
#pragma unroll
      for (int s = 0; s < 4; s++) { cbf[s].x = ldg_nc1(gc + g * 1024 + w * 128 + s * 32 + t * 4); cbf[s].y = ldg_nc1(gc + g * 1024 + w * 128 + s * 32 + 16 + t * 4); }
    }
  };
  uint32_t thand, anchor;
  const uint32_t opaque0 = w >> 4;
  if (wg == 0) {
    float mh[4];
    float L[8];
#pragma unroll
    for (int i = 0; i < 4; i++) { L[2 * i] = L[2 * i + 1] = 0.f; mh[i] = -INFINITY; }
    constexpr uint32_t dq = desc_lo(OFF_Q);
    const uint32_t ptw = sb + OFF_PT + (8 * (lane >> 4) + (lane & 7)) * 128 + (((2 * wq + ((lane >> 3) & 1)) ^ (lane & 7)) << 4);
    float S[8];
    auto softmax = [&](int tl) {
      auto write_p = [&](const float (&x)[8]) {
        float p[8];
#pragma unroll
        for (int i = 0; i < 8; i++) p[i] = ex2(x[i]);
        stsm4t(ptw + (tl & 1) * 2048, pack_bf16(p[0], p[1]), pack_bf16(p[2], p[3]), pack_bf16(p[4], p[5]), pack_bf16(p[6], p[7]));
        asm volatile("fence.proxy.async.shared::cta;" ::: "memory");
      };
      float x[8];
#pragma unroll
      for (int i = 0; i < 8; i++) x[i] = S[i] - mh[2 * (i >> 2) + (i & 1)];
      if (tl) write_p(x);
      const float ex = fmaxf(fmaxf(fmaxf(x[0], x[1]), fmaxf(x[2], x[3])), fmaxf(fmaxf(x[4], x[5]), fmaxf(x[6], x[7])));
      if (tl == 0 || bar_over(ex)) {
        float mx[4];
#pragma unroll
        for (int i = 0; i < 4; i++) mx[i] = fmaxf(S[4 * (i >> 1) + (i & 1)], S[4 * (i >> 1) + 2 + (i & 1)]);
        const float a = reduce_g(mx, lane, [](float u, float v) { return fmaxf(u, v); });
        stsf(sb + OFF_RED + wq * 64 + (8 * (lane >> 4) + 2 * t + ((lane >> 3) & 1)) * 4, a);
        bar_sync(2, 128);
#pragma unroll
        for (int jn = 0; jn < 2; jn++) {
          float m0 = mh[2 * jn], m1 = mh[2 * jn + 1];
#pragma unroll
          for (int i = 0; i < 4; i++) { const float2 v = ldsf2(sb + OFF_RED + i * 64 + (8 * jn + 2 * t) * 4); m0 = fmaxf(m0, v.x); m1 = fmaxf(m1, v.y); }
          const float a0 = ex2(mh[2 * jn] - m0), a1 = ex2(mh[2 * jn + 1] - m1);
          mh[2 * jn] = m0; mh[2 * jn + 1] = m1;
          L[4 * jn] *= a0; L[4 * jn + 1] *= a1; L[4 * jn + 2] *= a0; L[4 * jn + 3] *= a1;
          if (tid < 4) sts2f(sb + OFF_ALPHA + (8 * jn + 2 * t) * 4, a0, a1);
        }
        asm volatile("barrier.cta.arrive.aligned 1, 256;" ::: "memory");
#pragma unroll
        for (int i = 0; i < 8; i++) x[i] = S[i] - mh[2 * (i >> 2) + (i & 1)];
        write_p(x);
        bar_over(0.f);
      }
      const uint32_t dpt = __shfl_sync(~0u, desc_lo(OFF_PT) + (tl & 1) * 128, 0);
      wg_fence();
#pragma unroll
      for (int ks = 0; ks < 4; ks++) wgmma_n16_ones(L, ONE2, dpt + ks * 2);
      wg_commit();
    };
    uint32_t da = desc_lo(OFF_RING);
#pragma unroll 1
    for (int tl = 0; tl < 7; tl++) {
      if (tl == 5) { load_frags(); }
      uint32_t ok = 0;
#pragma unroll
      for (int u = 0; u < 4; u++) ok += mbar_test(BAR(BAR_FULL + 4 * tl + u));
      ok = __reduce_min_sync(~0u, ok);
      const uint32_t du = __shfl_sync(~0u, da, 0);
#pragma unroll
      for (int u = 0; u < 4; u++) {
        if (ok != 4) mbar_wait(BAR(BAR_FULL + 4 * tl + u));
        wg_fence();
#pragma unroll
        for (int k = 0; k < 8; k++) {
          const int i = 8 * u + k;
          if (i == 0) wgmma_n16<0, 0>(S, du, dq); else wgmma_n16<0, 1>(S, du + (i >> 2) * 512 + (i & 3) * 2, dq + (i >> 2) * 128 + (i & 3) * 2);
        }
        wg_commit();
      }
      wg_wait<0>();
      acc_fence(S); acc_fence(L);
      if (tl == 0) CLK(15);
      if (tl == 1) CLK(17);
      softmax(tl);
      if (tl == 0) CLK(16);
      if (tl == 1) CLK(18);
      if (tl == 3) CLK(19);
      if (tl == 6) CLK(20);
      da = (tl == 2 || tl == 5) ? da - 8192 : da + 4096;
    }
    mbar_wait(BAR(BAR_ALLCLR));
    uint32_t* const mlo = pin(gin + blk(4 * (16 * hh + 4 * (g & 2) + 2 * t + (g & 1)) + 1, 6, g >> 2) + bs * 2);
#pragma unroll
    for (int i = 0; i < 32; i++) {
      if (i == 0 || i == 8 || i == 16 || i == 24 || i == 28) {
        if (i) wg_commit();
        mbar_wait(BAR(BAR_LAST + (i == 28 ? 4 : i >> 3)));
        if (i == 28) CLK(21);
        wg_fence();
      }
      if (i == 0) wgmma_n16<0, 0>(S, desc_lo(65536), dq); else wgmma_n16<0, 1>(S, desc_lo(65536) + (i >> 2) * 512 + (i & 3) * 2, dq + (i >> 2) * 128 + (i & 3) * 2);
    }
    wg_commit();
    wg_wait<0>();
    acc_fence(S); acc_fence(L);
    CLK(22);
    softmax(7);
    CLK(23);
    thand = clk32();
    wg_wait<0>();
    acc_fence(L);
    if (tid < 32) MLST(mlo, __float_as_uint(g & 2 ? (g & 1 ? mh[3] : mh[2]) : (g & 1 ? mh[1] : mh[0])), __float_as_uint(g & 2 ? (g & 1 ? L[5] : L[4]) : (g & 1 ? L[1] : L[0])));
    CLK(24);
  } else {
    float O[8][8];
#pragma unroll
    for (int i = 0; i < 8; i++)
#pragma unroll
      for (int k = 0; k < 8; k++) O[i][k] = 0.f;
    constexpr uint32_t dp = desc_lo(OFF_PT);
    auto handover = [&](int tl) {
      uint32_t over = opaque0 + (tl == 0);
#pragma unroll 1
      do {
        if (over) {
          cbar();
#pragma unroll
          for (int jn = 0; jn < 2; jn++) {
            const float2 a = ldsf2(sb + OFF_ALPHA + (8 * jn + 2 * t) * 4);
#pragma unroll
            for (int mb = 0; mb < 8; mb++) { O[mb][4 * jn] *= a.x; O[mb][4 * jn + 1] *= a.y; O[mb][4 * jn + 2] *= a.x; O[mb][4 * jn + 3] *= a.y; }
          }
        }
        over++;
      } while (bar_over(0.f));
    };
    uint32_t da = desc_lo(OFF_RING);
#pragma unroll 1
    for (int tl = 0; tl < 7; tl++) {
      if (tl == 5) load_frags();
      handover(tl);
      const uint32_t dpt = dp + (tl & 1) * 128;
      wg_fence();
#pragma unroll
      for (int i = 0; i < 32; i++) wgmma_n16<1, 1>(O[i >> 2], da + (i >> 2) * 512 + (i & 3) * 128, dpt + (i & 3) * 2);
      wg_commit();
      wg_wait<0>();
#pragma unroll
      for (int mb = 0; mb < 8; mb++) acc_fence(O[mb]);
      if (lane == 0) mbar_arrive(BAR(BAR_EMPTY + tl));
      if (tl == 0) CLK(16);
      if (tl == 1) CLK(18);
      if (tl == 3) CLK(19);
      if (tl == 6) CLK(20);
      da = (tl == 2 || tl == 5) ? da - 8192 : da + 4096;
    }
    mbar_wait(BAR(BAR_ALLCLR));
    uint32_t* x1o[8];
#pragma unroll
    for (int i = 0; i < 8; i++)
      x1o[i] = pin(inbox((16 * hh + 8 * ((i >> 1) & 1) + 2 * t + (i & 1)) * 4 + 2 * (i >> 2) + (wq >> 1), bs >> 4) + (bs & 15) * 64 + ((wq & 1) * 8 + g) * 4);
    handover(7);
    CLK(23);
    thand = clk32();
    auto pv = [&](int mb0, int n) {
      wg_fence();
#pragma unroll
      for (int i = 0; i < 16; i++)
        if (i < 4 * n) wgmma_n16<1, 1>(O[mb0 + (i >> 2)], desc_lo(65536) + (mb0 + (i >> 2)) * 512 + (i & 3) * 128, dp + 128 + (i & 3) * 2);
      wg_commit();
    };
    auto publish = [&](int J) {
#pragma unroll
      for (int k = 0; k < 4; k++) acc_fence(O[4 * J + k]);
#pragma unroll
      for (int i = 0; i < 4; i++) {
        const int k = 4 * (i >> 1) + (i & 1);
        stg_cvt8(x1o[4 * J + i], O[4 * J][k], O[4 * J][k + 2], O[4 * J + 1][k], O[4 * J + 1][k + 2],
                 O[4 * J + 2][k], O[4 * J + 2][k + 2], O[4 * J + 3][k], O[4 * J + 3][k + 2]);
      }
    };
    pv(0, 4); pv(4, 4);
    wg_wait<1>(); publish(0);
    wg_wait<0>(); publish(1);
    CLK(24);
  }

  {
    const uint32_t* px = pin(inbox(cta, w >> 1) + (w & 1) * 512 + lane * 2);
    uint32_t* const x2o = pin(inbox(cta, 4) + 512 + tid * 2);
    uint32_t* const x2p = pin(gin + blk(cta, 4, selector(cta) ^ 1) + 512 + tid * 2);
    const uint32_t q4 = lds1(sb + OFF_SEL + 4 * hI) ^ 0x00010100u;
    const uint32_t same = pin((uint32_t)(q4 == 0 || q4 == 0x01010101u));
    mbar_wait(BAR(BAR_TS));
    anchor = lds1(sb + OFF_TS);
    const uint32_t sdst = pin(sb + OFF_BS4 + w * 272 + lane * 8), ssrc = pin(sb + OFF_BS4 + (lane & 7) * 272 + (lane >> 3) * 16);
    float d[4] = {0.f, 0.f, 0.f, 0.f};
    if (cta >= NFF) {
#pragma unroll
      for (int s = 0; s < 4; s++) { cbf[s].x = silu2(cbf[s].x); cbf[s].y = silu2(cbf[s].y); }
    }
    wait_clk(thand, T.D_X1);
    wait_clk(anchor, T.A_X1 - T.R_X0);
    uint2 v[8];
    load_units<8, 64>(v, px);
    if (T.R_X0) {
      wait_clk(anchor, T.A_X1);
#pragma unroll
      for (int i = 0; i < 8; i++) reload_unit(v[i], px + i * 64);
    }
    CLK(25);
    const bool early = __all_sync(~0u, mbar_test(BAR(BAR_WUV + wg)));
    if (early) load_a_t(aw, abase + OFF_WUV);
    mbar_wait(BAR(BAR_WV));
    const float4 wa = ldsf4(sb + OFF_WV + w * 32), wb = ldsf4(sb + OFF_WV + w * 32 + 16);
    const float wv[8] = {wa.x, wa.y, wa.z, wa.w, wb.x, wb.y, wb.z, wb.w};
    CLK(27);
    uint32_t it = opaque0;
    bool ok;
#pragma unroll 1
    do {
      if (it) {
#pragma unroll
        for (int i = 0; i < 8; i++) reload_unit(v[i], px + i * 64);
        if (it > SPIN_LIMIT) __trap();
      }
      it++;
      float a0 = 0.f, a1 = 0.f, a2 = 0.f, a3 = 0.f;
#pragma unroll
      for (int i = 0; i < 8; i++) { a0 += wv[i] * bf_lo(v[i].x); a1 += wv[i] * bf_hi(v[i].x); a2 += wv[i] * bf_lo(v[i].y); a3 += wv[i] * bf_hi(v[i].y); }
      ok = __all_sync(~0u, min_flags(v) != 0);
      sts2(sdst, pack_bf16(a0, a1), pack_bf16(a2, a3));
    } while (!ok);
    CLK(29);
    cbar();
    uint32_t b[4][4];
#pragma unroll
    for (int kk = 0; kk < 4; kk++) ldsm4(b[kk], ssrc + kk * 64);
    if (__builtin_expect(!early, 0)) { mbar_wait(BAR(BAR_WUV + wg)); load_a_t(aw, abase + OFF_WUV); }
    mma128(d, aw, b);
    const uint32_t c0 = pack_bf16(d[0], d[1]), c1 = pack_bf16(d[2], d[3]);
    stg_u64(x2o, c0, c1);
    stg_u64_unless(same, x2p, c0, c1);
    ITS(4, it - 1);
    tstore = clk32();
    CLK(30);
  }
  {
    uint32_t* const o = pin(inbox(4 * (8 * jI + w) + t, 4) + hI * 16 + g * 2);
    const uint32_t* x2i[4];
#pragma unroll
    for (int i = 0; i < 4; i++) x2i[i] = pin(nearbox(4 * hI + i, 4) + 512 + tid * 2);
    const uint32_t sdst = pin(sb + OFF_BS5 + (16 * w + g) * 16 + t * 4), ssrc = pin(sb + OFF_BS5 + lane * 16);
    float d[4] = {0.f, 0.f, 0.f, 0.f};
    wait_clk(tstore, T.D_X2);
    wait_clk(anchor, T.A_X1 + T.R_X2);
    uint2 v[4];
#pragma unroll
    for (int i = 0; i < 4; i++) v[i] = ldg_u64(x2i[i]);
    const bool early = __all_sync(~0u, mbar_test(BAR(BAR_WO + wg)));
    if (early) load_a_t(aw, abase + OFF_WO);
    CLK(31);
    uint32_t it = opaque0;
    bool ok;
#pragma unroll 1
    do {
      if (it) {
#pragma unroll
        for (int i = 0; i < 4; i++) reload_unit(v[i], x2i[i]);
        if (it > SPIN_LIMIT) __trap();
      }
      it++;
      ok = __all_sync(~0u, min_flags(v) != 0);
      sum4_to_smem(v, sdst);
    } while (!ok);
    CLK(32);
    cbar();
    uint32_t b[4][4];
#pragma unroll
    for (int kk = 0; kk < 4; kk++) ldsm4t(b[kk], ssrc + kk * 512);
    if (__builtin_expect(!early, 0)) { mbar_wait(BAR(BAR_WO + wg)); load_a_t(aw, abase + OFF_WO); }
    mma128(d, aw, b);
    ST3A(o, movm(pack_bf16(d[0], d[1])), movm(pack_bf16(d[2], d[3])));
    ITS(5, it - 1);
    tstore = clk32();
    CLK(33);
    if (lane == 0) mbar_arrive(BAR(BAR_P5D));
  }
  if (cta < NFF) {
    const int mi = lane >> 3, r = lane & 7;
    uint32_t a1[2][4][4], a2[2][2][4];
    check_units<4, 64>(sbf, pcb);
    check_units<4, 64>(cbf, pcb + 2048);
    __syncwarp();
#pragma unroll
    for (int s = 0; s < 4; s++) { cbf[s].x = hadd2(cbf[s].x, ONE2); cbf[s].y = hadd2(cbf[s].y, ONE2); }
    mbar_wait(BAR(BAR_W1));
#pragma unroll
    for (int mt = 0; mt < 2; mt++) {
#pragma unroll
      for (int ks = 0; ks < 4; ks++) ldsm4t(a1[mt][ks], sb + OFF_W1 + (64 * w + 16 * ks + 8 * (mi >> 1) + r) * 64 + (((2 * mt + (mi & 1)) ^ (r >> 1)) << 4));
      float u[4] = {0.f, 0.f, 0.f, 0.f}, vv[4] = {0.f, 0.f, 0.f, 0.f};
#pragma unroll
      for (int s = 0; s < 4; s++) { mma16816(u, a1[mt][s], cbf[s].x, cbf[s].y); mma16816(vv, a1[mt][s], sbf[s].x, sbf[s].y); }
      sts4f(sb + OFF_REDU + w * 1024 + mt * 512 + lane * 16, u[0], u[1], u[2], u[3]);
      sts4f(sb + OFF_REDV + w * 1024 + mt * 512 + lane * 16, vv[0], vv[1], vv[2], vv[3]);
    }
    const uint32_t* xb = pin(nearbox(cta & ~15, 6 + wg) + (16 * wq + t) * 16 + g * 2);
    uint32_t* const ox[2] = {pin(inbox(64 * hh + 8 * w + t, 5) + bs * 16 + g * 2), pin(inbox(64 * hh + 8 * w + 4 + t, 5) + bs * 16 + g * 2)};
    cbar();
    const int lp = (tid >> 2) & 31, kq = tid & 3;
    const int fo = 16 * wg + (lp >> 2) + 8 * (kq >> 1), bo = 2 * (lp & 3) + (kq & 1);
    float U = 0.f, V = 0.f;
#pragma unroll
    for (int i = 0; i < 8; i++) { U += ldsf(sb + OFF_REDU + i * 1024 + tid * 4); V += ldsf(sb + OFF_REDV + i * 1024 + tid * 4); }
    U = pin(U); V = pin(V);
    const uint32_t s_g = pin(sb + OFF_REDG + w * 1024 + lane * 16), s_s = pin(sb + OFF_REDS + g * 80 + w * 8);
    const uint32_t l_g = pin(sb + OFF_REDG + tid * 4), l_s = pin(sb + OFF_REDS + bo * 80), s_h = pin(sb + OFF_H1 + fo * 16 + bo * 2);
    CLK(34);
    wait_clk(tstore, T.D_X3B);
    wait_clk(anchor, T.A_X1 + T.R_X3A + T.R_X3B);
    uint2 x[4];
    load_units<4, 64>(x, xb);
    mbar_wait(BAR(BAR_W2));
#pragma unroll
    for (int i = 0; i < 4; i++)
      ldsm4t(a2[i >> 1][i & 1], sb + OFF_W2 + (w >> 1) * 4096 + (16 * (i & 1) + 8 * (mi >> 1) + r) * 128 + (((4 * (w & 1) + 2 * (i >> 1) + (mi & 1)) ^ r) << 4));
    CLK(35);
    uint32_t it = opaque0;
    float G[2][2][4], S[2][4];
#pragma unroll 1
    do {
      if (it) {
#pragma unroll
        for (int i = 0; i < 4; i++) reload_unit(x[i], xb + i * 64);
        if (it > SPIN_LIMIT) __trap();
      }
      it++;
#pragma unroll
      for (int i = 0; i < 8; i++) { G[0][i >> 2][i & 3] = G[1][i >> 2][i & 3] = S[i >> 2][i & 3] = 0.f; }
#pragma unroll
      for (int s = 0; s < 4; s++) {
        const uint32_t sx[4] = {x[s].x, ONE2, x[s].y, ONE2};
        mma16816(S[s & 1], sx, x[s].x, x[s].y);
        const uint32_t y0 = hmul2(x[s].x, cbf[s].x), y1 = hmul2(x[s].y, cbf[s].y);
        mma16816(G[0][s & 1], a1[0][s], y0, y1);
        mma16816(G[1][s & 1], a1[1][s], y0, y1);
      }
    } while (!__all_sync(~0u, min_flags(x) != 0));
    if (t == (g >> 1)) sts2f(s_s, (g & 1) ? S[0][3] + S[1][3] : S[0][2] + S[1][2], (g & 1) ? S[0][1] + S[1][1] : S[0][0] + S[1][0]);
#pragma unroll
    for (int mt = 0; mt < 2; mt++)
      sts4f(s_g + mt * 512, G[mt][0][0] + G[mt][1][0], G[mt][0][1] + G[mt][1][1], G[mt][0][2] + G[mt][1][2], G[mt][0][3] + G[mt][1][3]);
    CLK(37);
    cbar();
    {
      float gv[8];
      float4 sv[4];
#pragma unroll
      for (int i = 0; i < 4; i++) sv[i] = ldsf4(l_s + i * 16);
#pragma unroll
      for (int i = 0; i < 8; i++) gv[i] = ldsf(l_g + i * 1024);
      const float s1 = ((sv[0].x + sv[0].z) + (sv[1].x + sv[1].z)) + ((sv[2].x + sv[2].z) + (sv[3].x + sv[3].z));
      const float s2 = ((sv[0].y + sv[0].w) + (sv[1].y + sv[1].w)) + ((sv[2].y + sv[2].w) + (sv[3].y + sv[3].w));
      const float gsum = ((gv[0] + gv[1]) + (gv[2] + gv[3])) + ((gv[4] + gv[5]) + (gv[6] + gv[7]));
      const float mu = s1 * (1.f / 512.f);
      float rs;
      asm("rsqrt.approx.ftz.f32 %0, %1;" : "=f"(rs) : "f"(fmaxf(s2 * (1.f / 512.f) - mu * mu, 0.f) + 1e-5f));
      const float hv = fmaxf(rs * (gsum - mu * U) + V, 0.f);
      asm volatile("st.shared.u16 [%0], %1;" ::"r"(s_h), "h"(__bfloat16_as_ushort(__float2bfloat16(hv))) : "memory");
    }
    ITS(6, it - 1);
    CLK(38);
    cbar();
    uint32_t b[4];
    ldsm4t(b, sb + OFF_H1 + lane * 16);
    float o[2][2][4] = {};
#pragma unroll
    for (int i = 0; i < 4; i++) mma16816(o[i >> 1][i & 1], a2[i >> 1][i & 1], b[2 * (i & 1)], b[2 * (i & 1) + 1]);
#pragma unroll
    for (int mb = 0; mb < 2; mb++)
      ST4(ox[mb], movm(pack_bf16(o[mb][0][0] + o[mb][1][0], o[mb][0][1] + o[mb][1][1])), movm(pack_bf16(o[mb][0][2] + o[mb][1][2], o[mb][0][3] + o[mb][1][3])));
    CLK(39);
    if (lane == 0) mbar_arrive(BAR(BAR_P7D));
  } else {
    const int mi = lane >> 3, r = lane & 7;
    mbar_wait(BAR(BAR_W1));
#pragma unroll
    for (int mt = 0; mt < 2; mt++) {
      float u[4] = {0.f, 0.f, 0.f, 0.f};
#pragma unroll
      for (int ks = 0; ks < 4; ks++) ldsm4t(aw[4 * mt + ks], sb + OFF_W1 + (64 * w + 16 * ks + 8 * (mi >> 1) + r) * 64 + (((2 * mt + (mi & 1)) ^ (r >> 1)) << 4));
#pragma unroll
      for (int ks = 0; ks < 4; ks++) mma16816(u, aw[4 * mt + ks], cbf[ks].x, cbf[ks].y);
      sts4f(sb + OFF_REDU + w * 1024 + mt * 512 + lane * 16, u[0], u[1], u[2], u[3]);
    }
    cbar();
    if (w < 2) {
      float4 v[8];
#pragma unroll
      for (int i = 0; i < 8; i++) v[i] = ldsf4(sb + OFF_REDU + i * 1024 + tid * 16);
      stg_u64(gs->MOD2[par] + (96 + 2 * (cta - NFF) + w) * 64 + t * 16 + g * 2,
              movm(pack_bf16(((v[0].x + v[1].x) + (v[2].x + v[3].x)) + ((v[4].x + v[5].x) + (v[6].x + v[7].x)), ((v[0].y + v[1].y) + (v[2].y + v[3].y)) + ((v[4].y + v[5].y) + (v[6].y + v[7].y)))),
              movm(pack_bf16(((v[0].z + v[1].z) + (v[2].z + v[3].z)) + ((v[4].z + v[5].z) + (v[6].z + v[7].z)), ((v[0].w + v[1].w) + (v[2].w + v[3].w)) + ((v[4].w + v[5].w) + (v[6].w + v[7].w)))));
    }
    CLK(26);
  }
  CLK_DUMP();
}

typedef CUresult (*EncodeTiledFn)(CUtensorMap*, CUtensorMapDataType, cuuint32_t, void*, const cuuint64_t*, const cuuint64_t*,
                                  const cuuint32_t*, const cuuint32_t*, CUtensorMapInterleave, CUtensorMapSwizzle,
                                  CUtensorMapL2promotion, CUtensorMapFloatOOBfill);

struct Dim { uint64_t size, stride; uint32_t box; };
template <int R> void encode_map(EncodeTiledFn enc, CUtensorMap* m, const void* base, const Dim (&d)[R], CUtensorMapSwizzle sw, CUtensorMapL2promotion promo) {
  cuuint64_t dims[R], strides[R];
  cuuint32_t box[R], es[R];
  for (int i = 0; i < R; i++) { dims[i] = d[i].size; strides[i] = d[i].stride; box[i] = d[i].box; es[i] = 1; }
  enc(m, CU_TENSOR_MAP_DATA_TYPE_BFLOAT16, R, const_cast<void*>(base), dims, strides + 1, box, es, CU_TENSOR_MAP_INTERLEAVE_NONE, sw, promo,
      CU_TENSOR_MAP_FLOAT_OOB_FILL_NONE);
}

}

extern "C" void kernel_launch(void* const* d_in, const int* in_sizes, int n_in, void* d_out, int out_size) {
  (void)in_sizes; (void)n_in; (void)out_size;
  static EncodeTiledFn enc = nullptr;
  static Scratch* scratch = nullptr;
  static uint32_t* inbox = nullptr;
  if (!enc) {
    void* sp = nullptr;
    cudaGetSymbolAddress(&sp, g_s);
    scratch = (Scratch*)sp;
    cudaGetSymbolAddress(&sp, g_in);
    inbox = (uint32_t*)(((uintptr_t)sp + 0xfffff) & ~(uintptr_t)0xfffff);
    void* fn = nullptr;
    cudaDriverEntryPointQueryResult q;
    cudaGetDriverEntryPoint("cuTensorMapEncodeTiled", &fn, cudaEnableDefault, &q);
    enc = (EncodeTiledFn)fn;
    cudaFuncSetAttribute(fused_decode_kernel, cudaFuncAttributeMaxDynamicSharedMemorySize, SMEM_BYTES);
  }
  const CUtensorMapSwizzle S128 = CU_TENSOR_MAP_SWIZZLE_128B, S0 = CU_TENSOR_MAP_SWIZZLE_NONE;
  const CUtensorMapL2promotion L0 = CU_TENSOR_MAP_L2_PROMOTION_NONE, L128 = CU_TENSOR_MAP_L2_PROMOTION_L2_128B;
  Params P;
  encode_map<2>(enc, &P.wq, d_in[2], {{4096, 2, 64}, {512, 8192, 64}}, S128, L0);
  encode_map<5>(enc, &P.wuk, d_in[3], {{4096, 2, 64}, {2, 8192, 2}, {4, 4 * 8192, 4}, {2, 2 * 8192, 2}, {32, 16 * 8192, 4}}, S128, L0);
  encode_map<2>(enc, &P.wm2, d_in[10], {{3072, 2, 16}, {512, 6144, 256}}, S0, L128);
  encode_map<2>(enc, &P.wm3, d_in[10], {{3072, 2, 32}, {512, 6144, 256}}, CU_TENSOR_MAP_SWIZZLE_64B, L128);
  encode_map<3>(enc, &P.ckv2, d_in[1], {{64, 2, 64}, {8 * 4096, 1024, 64}, {8, 128, 2}}, S128, L0);
  encode_map<3>(enc, &P.ckv1, d_in[1], {{64, 2, 64}, {8 * 4096, 1024, 64}, {8, 128, 1}}, S128, L0);
  encode_map<5>(enc, &P.wuv, d_in[4], {{4096, 2, 64}, {2, 8 * 8192, 2}, {8, 64 * 8192, 4}, {8, 8192, 8}, {4, 16 * 8192, 1}}, S128, L0);
  encode_map<2>(enc, &P.wo, d_in[5], {{512, 2, 64}, {4096, 1024, 64}}, S128, L0);
  encode_map<2>(enc, &P.w1, d_in[7], {{1792, 2, 32}, {512, 3584, 256}}, CU_TENSOR_MAP_SWIZZLE_64B, L128);
  encode_map<3>(enc, &P.w2, d_in[8], {{64, 2, 64}, {1792, 1024, 32}, {8, 128, 2}}, S128, L0);
  fused_decode_kernel<<<NCTA, NTHREADS, SMEM_BYTES>>>((__nv_bfloat16*)d_out, scratch, (const uint8_t*)d_in[10], (const uint8_t*)d_in[0],
                     (const uint8_t*)d_in[9], inbox,
                     P);
}
```

```cpp
#include <cuda_runtime.h>
#include <cuda.h>
#include <cuda_bf16.h>
#include <stdint.h>
#define V4 1

namespace {

constexpr int NCTA = 128;
constexpr int NTHREADS = 320;
constexpr int NFG = 56;
constexpr int NFF = 2 * NFG;
constexpr int NSYNC = 4;

constexpr uint32_t OFF_RING = 0;
constexpr uint32_t OFF_WUK = 131072;
constexpr uint32_t OFF_WQ = 131072 + 32768;
constexpr uint32_t OFF_WM2 = 65536 + 49152;
constexpr uint32_t OFF_WUV = 131072;
constexpr uint32_t OFF_WO = 131072 + 32768;
constexpr uint32_t OFF_W1 = 0;
constexpr uint32_t OFF_W2 = 32768;
constexpr uint32_t OFF_Q = 196608;
constexpr uint32_t OFF_PT = 212992;
constexpr uint32_t OFF_SCR = 217088;
constexpr uint32_t OFF_XS = 65536;
constexpr uint32_t OFF_CS = 65536 + 8192;
constexpr uint32_t OFF_P0S = 65536 + 16384;
constexpr uint32_t OFF_BS1 = OFF_SCR + 2048;
constexpr uint32_t OFF_BS2 = OFF_SCR + 4096;
constexpr uint32_t OFF_P0B = OFF_SCR + 6144;
constexpr uint32_t OFF_XN = OFF_SCR + 8192;
constexpr uint32_t OFF_RED = OFF_SCR + 10496;
constexpr uint32_t OFF_ALPHA = OFF_SCR + 11072;
constexpr uint32_t OFF_WV = OFF_SCR + 6144;
constexpr uint32_t OFF_SEL = OFF_SCR + 10752;
constexpr uint32_t OFF_TS = OFF_SCR + 11136;
constexpr uint32_t OFF_BARS = OFF_SCR + 11264;
constexpr uint32_t SMEM_BYTES = OFF_BARS + 512;
constexpr uint32_t OFF_BS4 = OFF_Q;
constexpr uint32_t OFF_H1 = OFF_Q + 2304;
constexpr uint32_t OFF_REDS = OFF_Q + 2816;
constexpr uint32_t OFF_BS5 = OFF_Q + 4096;
constexpr uint32_t OFF_REDG = OFF_Q + 8192;
constexpr uint32_t OFF_REDU = 65536;
constexpr uint32_t OFF_REDV = 65536 + 8192;

constexpr int BAR_FULL = 0;
constexpr int BAR_LAST = 28;
constexpr int BAR_WUK = 33, BAR_WM2 = 35, BAR_WUV = 36, BAR_WO = 38, BAR_W1 = 40, BAR_W2 = 41;
constexpr int BAR_ALLCLR = 42, BAR_TS = 43, BAR_WV = 44;
constexpr int BAR_EMPTY = 45;
constexpr int BAR_P0BD = 53;
constexpr int BAR_P1D = 54, BAR_P2D = 55;
constexpr int BAR_P5D = 56, BAR_P7D = 57;
constexpr int NBARS = 58;
constexpr int BAR_XC = 58, BAR_WQ = 59;
constexpr int BAR_C = 61, BAR_END = 62;
constexpr uint32_t SB = 1024;

#define TUNE_LIST(X) \
  X(PC_T0, 340) X(PC_XC, 0) X(PC_C, 0) X(PC_P1, 320) X(PC_PM, 225) X(PC_P2, 319) X(PC_STAG, 390) X(PC_DS, 0) X(PC_SL, 500) X(PC_W, 4) X(PC_NW, 8) \
  X(PW_A, -1) X(PW_0, 280) X(PW_ST, 0) X(PW_UV, 250) X(PW_G, 610) X(PW_O, 345) X(PW_G2, 430) X(PW_G3, 390) X(PW_F, 330) X(PW_GB, -100) \
  X(LOC, 0) X(PR_T0, 1000) X(PR_N, 4) X(CLR_T0, 3900) X(CLR_CLK, 190) \
  X(D_MOD, 1550) X(D_QP, 1100) X(D_QX, 950) X(TS_P, 1) X(TS_O, 1150) X(D_TS, 900) X(A_M, 1750) X(D_X1, 1400) X(A_X1, 2460) X(R_X0, 1100) \
  X(D_X2, 260) X(R_X2, 1000) X(D_X3A, 60) X(R_X3A, 3080) X(D_X3B, 800) X(R_X3B, 980) X(D_FIN, 320) X(R_FIN, 1520) X(RB, 0)
struct Tune {
#define X(n, v) static constexpr int n = v;
  TUNE_LIST(X)
#undef X
};

#define THRESH "0f42700000"
struct Scratch {
  uint32_t MOD1[2][4 * 64 * 64];
  uint32_t MOD2[2][128 * 64];
  uint32_t QP[2][128 * 256 * 2];
  uint32_t QX[2][8 * 32 * 256];
  uint32_t epoch;
  uint32_t pad[31];
  uint32_t sync[NSYNC][32];
};
__device__ Scratch g_s;
__device__ uint32_t g_in[(128 + 16) * 16384];
__device__ __forceinline__ uint32_t blk(int c, int k, uint32_t sel) { return c * 16384 + k * 2048 + ((sel ^ k) & 1) * 1024; }
__device__ __forceinline__ uint32_t flip(int c) { return c ^ (c >> 1) ^ (c >> 3); }

#define CLK_DECL
#define CLK(i) do {} while (0)
#define CLK_DUMP() do {} while (0)
#define ITS(i, v) do {} while (0)

struct Params {
  CUtensorMap wq, wuk, wm2, wm3, ckv2, ckv1, wuv, wo, w1, w2;
};

__device__ __forceinline__ void mbar_init(uint32_t bar, int cnt) { asm volatile("mbarrier.init.shared::cta.b64 [%0], %1;" ::"r"(bar), "r"(cnt)); }
__device__ __forceinline__ void mbar_expect(uint32_t bar, uint32_t bytes) { asm volatile("mbarrier.arrive.expect_tx.shared::cta.b64 _, [%0], %1;" ::"r"(bar), "r"(bytes) : "memory"); }
__device__ __forceinline__ void mbar_arrive(uint32_t bar) { asm volatile("mbarrier.arrive.shared::cta.b64 _, [%0];" ::"r"(bar) : "memory"); }
__device__ __forceinline__ uint32_t clk32() { unsigned long long c; asm volatile("mov.u64 %0, %%clock64;" : "=l"(c) :: "memory"); return (uint32_t)c; }
__device__ __forceinline__ uint32_t gtime32() { uint32_t c; asm volatile("mov.u32 %0, %%globaltimer_lo;" : "=r"(c) :: "memory"); return c; }
__device__ __forceinline__ void wait_clk(uint32_t t0, int clocks) { while ((int)(clk32() - t0) < clocks) {} }
__device__ __forceinline__ void backoff(int clocks) { if (clocks > 0) wait_clk(clk32(), clocks); }
__device__ __forceinline__ void until_ns(uint32_t ns) { while ((int)(gtime32() - ns) < 0) {} }
__device__ __forceinline__ void slot(uint32_t& tn, int slack) {
  uint32_t now;
  do { now = gtime32(); } while ((int)(now - tn) < 0);
  if ((int)(now - tn) > slack) tn = now - slack;
}
template <typename T> __device__ __forceinline__ T* pin(T* p) { asm volatile("" : "+l"(p)); return p; }
__device__ __forceinline__ uint32_t pin(uint32_t v) { asm volatile("" : "+r"(v)); return v; }
__device__ __forceinline__ float pin(float v) { asm volatile("" : "+f"(v)); return v; }
constexpr int SPIN_LIMIT = 1 << 22;
__device__ __forceinline__ void mbar_wait(uint32_t bar) {
  asm volatile("{\n.reg .pred p;\n.reg .u32 c;\nmov.u32 c, 0;\n"
               "MW_LOOP:\nmbarrier.try_wait.parity.shared::cta.b64 p, [%0], 0;\n@p bra MW_DONE;\n"
               "add.u32 c, c, 1;\nsetp.lt.u32 p, c, 4194304;\n@p bra MW_LOOP;\ntrap;\nMW_DONE:\n}"
               ::"r"(bar) : "memory");
}
__device__ __forceinline__ bool mbar_test(uint32_t bar) {
  uint32_t ok;
  asm volatile("{\n.reg .pred p;\nmbarrier.test_wait.parity.shared::cta.b64 p, [%1], 0;\nselp.u32 %0,1,0,p;\n}" : "=r"(ok) : "r"(bar) : "memory");
  return ok;
}
__device__ __forceinline__ void tma2d(uint32_t dst, const CUtensorMap* m, int c0, int c1, uint32_t bar, uint64_t pol) {
  asm volatile("cp.async.bulk.tensor.2d.shared::cluster.global.mbarrier::complete_tx::bytes.L2::cache_hint [%0], [%1, {%3,%4}], [%2], %5;"
               ::"r"(dst), "l"(m), "r"(bar), "r"(c0), "r"(c1), "l"(pol) : "memory");
}
__device__ __forceinline__ void tma2d_nohint(uint32_t dst, const CUtensorMap* m, int c0, int c1, uint32_t bar) {
  asm volatile("cp.async.bulk.tensor.2d.shared::cluster.global.mbarrier::complete_tx::bytes [%0], [%1, {%3,%4}], [%2];"
               ::"r"(dst), "l"(m), "r"(bar), "r"(c0), "r"(c1) : "memory");
}
__device__ __forceinline__ void tma3d(uint32_t dst, const CUtensorMap* m, int c0, int c1, int c2, uint32_t bar, uint64_t pol) {
  asm volatile("cp.async.bulk.tensor.3d.shared::cluster.global.mbarrier::complete_tx::bytes.L2::cache_hint [%0], [%1, {%3,%4,%5}], [%2], %6;"
               ::"r"(dst), "l"(m), "r"(bar), "r"(c0), "r"(c1), "r"(c2), "l"(pol) : "memory");
}
__device__ __forceinline__ void tma5d(uint32_t dst, const CUtensorMap* m, int c0, int c1, int c2, int c3, int c4, uint32_t bar, uint64_t pol) {
  asm volatile("cp.async.bulk.tensor.5d.shared::cluster.global.mbarrier::complete_tx::bytes.L2::cache_hint [%0], [%1, {%3,%4,%5,%6,%7}], [%2], %8;"
               ::"r"(dst), "l"(m), "r"(bar), "r"(c0), "r"(c1), "r"(c2), "r"(c3), "r"(c4), "l"(pol) : "memory");
}
__device__ __forceinline__ void bulk_ld(uint32_t dst, const void* src, uint32_t bytes, uint32_t bar) {
  asm volatile("cp.async.bulk.shared::cluster.global.mbarrier::complete_tx::bytes [%0], [%1], %2, [%3];" ::"r"(dst), "l"(src), "r"(bytes), "r"(bar) : "memory");
}
__device__ __forceinline__ void bar_sync(int id, int n) { asm volatile("barrier.cta.sync.aligned %0, %1;" ::"r"(id), "r"(n) : "memory"); }
__device__ __forceinline__ void cbar() { asm volatile("barrier.cta.sync.aligned 1, 256;" ::: "memory"); }
__device__ __forceinline__ bool bar_over(float ex) {
  uint32_t over;
  asm volatile("{\n.reg .pred p, q;\nsetp.gtu.f32 p, %1, " THRESH ";\nbarrier.cta.red.or.aligned.pred q, 4, 256, p;\nselp.u32 %0, 1, 0, q;\n}"
               : "=r"(over) : "f"(ex) : "memory");
  return over;
}

__device__ __forceinline__ uint32_t ldg_nc1(const void* p) { uint32_t v; asm volatile("ld.global.nc.L1::no_allocate.u32 %0, [%1];" : "=r"(v) : "l"(p)); return v; }
__device__ __forceinline__ uint2 ldg_nc2(const void* p) { uint2 v; asm volatile("ld.global.nc.v2.u32 {%0,%1}, [%2];" : "=r"(v.x), "=r"(v.y) : "l"(p)); return v; }
__device__ __forceinline__ uint4 ldg_nc4(const void* p) { uint4 v; asm volatile("ld.global.nc.L1::no_allocate.v4.u32 {%0,%1,%2,%3}, [%4];" : "=r"(v.x), "=r"(v.y), "=r"(v.z), "=r"(v.w) : "l"(p)); return v; }
__device__ __forceinline__ uint32_t ldg_rlx1(const void* p) { uint32_t v; asm volatile("ld.relaxed.gpu.global.u32 %0, [%1];" : "=r"(v) : "l"(p) : "memory"); return v; }
__device__ __forceinline__ void stg4(void* p, uint4 v) { asm volatile("st.relaxed.gpu.global.v4.u32 [%0], {%1,%2,%3,%4};" ::"l"(p), "r"(v.x), "r"(v.y), "r"(v.z), "r"(v.w) : "memory"); }
__device__ __forceinline__ void stg1(void* p, uint32_t a) { asm volatile("st.relaxed.gpu.global.u32 [%0], %1;" ::"l"(p), "r"(a) : "memory"); }
__device__ __forceinline__ uint32_t nz(uint32_t w) { return max(w, 1u); }
__device__ __forceinline__ uint2 ldg_u64(const void* p) {
  uint2 v; asm volatile("{\n.reg .b64 a;\nld.relaxed.gpu.global.b64 a, [%2];\nmov.b64 {%0,%1}, a;\n}" : "=r"(v.x), "=r"(v.y) : "l"(p) : "memory"); return v;
}
__device__ __forceinline__ uint4 ldg_2u64(const void* p) {
  uint4 v; asm volatile("{\n.reg .b64 a, b;\nld.relaxed.gpu.global.v2.b64 {a, b}, [%4];\nmov.b64 {%0,%1}, a;\nmov.b64 {%2,%3}, b;\n}" : "=r"(v.x), "=r"(v.y), "=r"(v.z), "=r"(v.w) : "l"(p) : "memory"); return v;
}
__device__ __forceinline__ void stg_u64(void* p, uint32_t x, uint32_t y) {
  asm volatile("{\n.reg .b32 y;\nmax.u32 y, %2, 1;\nst.relaxed.gpu.global.v2.b32 [%0], {%1, y};\n}" ::"l"(p), "r"(x), "r"(y) : "memory");
}
__device__ __forceinline__ void red_u64(void* p, uint32_t x, uint32_t y) {
  asm volatile("{\n.reg .b32 y;\n.reg .b64 a;\nmax.u32 y, %2, 1;\nmov.b64 a, {%1, y};\nred.relaxed.gpu.global.or.b64 [%0], a;\n}" ::"l"(p), "r"(x), "r"(y) : "memory");
}
__device__ __forceinline__ void red_u64_unless(uint32_t bad, void* p, uint32_t x, uint32_t y) {
  asm volatile("{\n.reg .b32 y;\n.reg .b64 a;\n.reg .pred q;\nsetp.eq.u32 q, %3, 0;\nmax.u32 y, %2, 1;\nmov.b64 a, {%1, y};\n@q red.relaxed.gpu.global.or.b64 [%0], a;\n}" ::"l"(p), "r"(x), "r"(y), "r"(bad) : "memory");
}
#define ST3A stg_u64
#define ST4 stg_u64
#define ST3B stg_u64_unless
#define MLST red_u64
__device__ __forceinline__ void stg_u64_unless(uint32_t bad, void* p, uint32_t x, uint32_t y) {
  asm volatile("{\n.reg .b32 y;\n.reg .pred q;\nsetp.eq.u32 q, %3, 0;\nmax.u32 y, %2, 1;\n@q st.relaxed.gpu.global.v2.b32 [%0], {%1, y};\n}" ::"l"(p), "r"(x), "r"(y), "r"(bad) : "memory");
}
__device__ __forceinline__ void stg_2u64(void* p, uint4 v) {
  asm volatile("{\n.reg .b32 y, w;\nmax.u32 y, %2, 1;\nmax.u32 w, %4, 1;\nst.relaxed.gpu.global.v4.b32 [%0], {%1, y, %3, w};\n}" ::"l"(p), "r"(v.x), "r"(v.y), "r"(v.z), "r"(v.w) : "memory");
}

__device__ __forceinline__ void stg_cvt8(void* p, float a0, float a1, float b0, float b1, float c0, float c1, float d0, float d1) {
  asm volatile("{\n.reg .b32 x, y, z, w;\ncvt.rn.bf16x2.f32 x, %2, %1;\ncvt.rn.bf16x2.f32 y, %4, %3;\ncvt.rn.bf16x2.f32 z, %6, %5;\ncvt.rn.bf16x2.f32 w, %8, %7;\n"
               "max.u32 y, y, 1;\nmax.u32 w, w, 1;\nst.relaxed.gpu.global.v4.b32 [%0], {x, y, z, w};\n}"
               ::"l"(p), "f"(a0), "f"(a1), "f"(b0), "f"(b1), "f"(c0), "f"(c1), "f"(d0), "f"(d1) : "memory");
}
__device__ __forceinline__ uint32_t pack_bf16(float lo, float hi) { uint32_t r; asm("cvt.rn.bf16x2.f32 %0, %1, %2;" : "=r"(r) : "f"(hi), "f"(lo)); return r; }
__device__ __forceinline__ float bf_lo(uint32_t w) { return __uint_as_float(w << 16); }
__device__ __forceinline__ float bf_hi(uint32_t w) { return __uint_as_float(w & 0xffff0000u); }
__device__ __forceinline__ float ex2(float x) { float r; asm("ex2.approx.ftz.f32 %0, %1;" : "=f"(r) : "f"(x)); return r; }
__device__ __forceinline__ uint32_t hmul2(uint32_t a, uint32_t b) { uint32_t r; asm("mul.rn.bf16x2 %0, %1, %2;" : "=r"(r) : "r"(a), "r"(b)); return r; }
__device__ __forceinline__ uint32_t hadd2(uint32_t a, uint32_t b) { uint32_t r; asm("add.rn.bf16x2 %0, %1, %2;" : "=r"(r) : "r"(a), "r"(b)); return r; }
__device__ __forceinline__ uint32_t hfma2(uint32_t a, uint32_t b, uint32_t c) { uint32_t r; asm("fma.rn.bf16x2 %0, %1, %2, %3;" : "=r"(r) : "r"(a), "r"(b), "r"(c)); return r; }
__device__ __forceinline__ uint32_t silu2(uint32_t v) { const float a = bf_lo(v), b = bf_hi(v); return pack_bf16(__fdividef(a, 1.f + __expf(-a)), __fdividef(b, 1.f + __expf(-b))); }
constexpr uint32_t ONE2 = 0x3f803f80u;

__device__ __forceinline__ void ldsm4(uint32_t (&r)[4], uint32_t a) { asm volatile("ldmatrix.sync.aligned.m8n8.x4.shared.b16 {%0,%1,%2,%3}, [%4];" : "=r"(r[0]), "=r"(r[1]), "=r"(r[2]), "=r"(r[3]) : "r"(a) : "memory"); }
__device__ __forceinline__ void ldsm4t(uint32_t (&r)[4], uint32_t a) { asm volatile("ldmatrix.sync.aligned.m8n8.x4.trans.shared.b16 {%0,%1,%2,%3}, [%4];" : "=r"(r[0]), "=r"(r[1]), "=r"(r[2]), "=r"(r[3]) : "r"(a) : "memory"); }
__device__ __forceinline__ void ldsm2t(uint32_t& r0, uint32_t& r1, uint32_t a) { asm volatile("ldmatrix.sync.aligned.m8n8.x2.trans.shared.b16 {%0,%1}, [%2];" : "=r"(r0), "=r"(r1) : "r"(a) : "memory"); }
__device__ __forceinline__ void stsm4t(uint32_t a, uint32_t r0, uint32_t r1, uint32_t r2, uint32_t r3) { asm volatile("stmatrix.sync.aligned.m8n8.x4.trans.shared.b16 [%0], {%1,%2,%3,%4};" ::"r"(a), "r"(r0), "r"(r1), "r"(r2), "r"(r3) : "memory"); }
__device__ __forceinline__ uint32_t movm(uint32_t a) { uint32_t d; asm volatile("movmatrix.sync.aligned.m8n8.trans.b16 %0, %1;" : "=r"(d) : "r"(a)); return d; }
__device__ __forceinline__ void mma16816(float (&d)[4], const uint32_t (&a)[4], uint32_t b0, uint32_t b1) {
  asm volatile("mma.sync.aligned.m16n8k16.row.col.f32.bf16.bf16.f32 {%0,%1,%2,%3}, {%4,%5,%6,%7}, {%8,%9}, {%0,%1,%2,%3};"
               : "+f"(d[0]), "+f"(d[1]), "+f"(d[2]), "+f"(d[3]) : "r"(a[0]), "r"(a[1]), "r"(a[2]), "r"(a[3]), "r"(b0), "r"(b1));
}
__device__ __forceinline__ void sts1(uint32_t a, uint32_t v) { asm volatile("st.shared.u32 [%0], %1;" ::"r"(a), "r"(v) : "memory"); }
__device__ __forceinline__ void sts2(uint32_t a, uint32_t x, uint32_t y) { asm volatile("st.shared.v2.u32 [%0], {%1,%2};" ::"r"(a), "r"(x), "r"(y) : "memory"); }
__device__ __forceinline__ void sts4(uint32_t a, uint4 v) { asm volatile("st.shared.v4.u32 [%0], {%1,%2,%3,%4};" ::"r"(a), "r"(v.x), "r"(v.y), "r"(v.z), "r"(v.w) : "memory"); }
__device__ __forceinline__ void sts2f(uint32_t a, float x, float y) { asm volatile("st.shared.v2.f32 [%0], {%1,%2};" ::"r"(a), "f"(x), "f"(y) : "memory"); }
__device__ __forceinline__ void sts4f(uint32_t a, float x, float y, float z, float w) { asm volatile("st.shared.v4.f32 [%0], {%1,%2,%3,%4};" ::"r"(a), "f"(x), "f"(y), "f"(z), "f"(w) : "memory"); }
__device__ __forceinline__ void stsf(uint32_t a, float v) { asm volatile("st.shared.f32 [%0], %1;" ::"r"(a), "f"(v) : "memory"); }
__device__ __forceinline__ uint32_t lds1(uint32_t a) { uint32_t v; asm volatile("ld.shared.u32 %0, [%1];" : "=r"(v) : "r"(a) : "memory"); return v; }
__device__ __forceinline__ float ldsf(uint32_t a) { float v; asm volatile("ld.shared.f32 %0, [%1];" : "=f"(v) : "r"(a) : "memory"); return v; }
__device__ __forceinline__ float2 ldsf2(uint32_t a) { float2 v; asm volatile("ld.shared.v2.f32 {%0,%1}, [%2];" : "=f"(v.x), "=f"(v.y) : "r"(a) : "memory"); return v; }
__device__ __forceinline__ float4 ldsf4(uint32_t a) { float4 v; asm volatile("ld.shared.v4.f32 {%0,%1,%2,%3}, [%4];" : "=f"(v.x), "=f"(v.y), "=f"(v.z), "=f"(v.w) : "r"(a) : "memory"); return v; }
__device__ __forceinline__ void lds4(uint32_t (&r)[4], uint32_t a) { asm volatile("ld.shared.v4.u32 {%0,%1,%2,%3}, [%4];" : "=r"(r[0]), "=r"(r[1]), "=r"(r[2]), "=r"(r[3]) : "r"(a) : "memory"); }

__device__ __forceinline__ void wg_fence() { asm volatile("wgmma.fence.sync.aligned;" ::: "memory"); }
__device__ __forceinline__ void wg_commit() { asm volatile("wgmma.commit_group.sync.aligned;" ::: "memory"); }
template <int N> __device__ __forceinline__ void wg_wait() { asm volatile("wgmma.wait_group.sync.aligned %0;" ::"n"(N) : "memory"); }
__host__ __device__ constexpr uint32_t desc_lo(uint32_t off) { return ((SB + off) >> 4) | 0x10000u; }
template <int TA, int ACC> __device__ __forceinline__ void wgmma_n16(float (&d)[8], uint32_t da, uint32_t db) {
  asm volatile("{\n.reg .b64 da, db;\nmov.b64 da, {%8, 0x40000040};\nmov.b64 db, {%9, 0x40000040};\n"
               "wgmma.mma_async.sync.aligned.m64n16k16.f32.bf16.bf16 {%0,%1,%2,%3,%4,%5,%6,%7}, da, db, %11, 1, 1, %10, 0;\n}"
               : "+f"(d[0]), "+f"(d[1]), "+f"(d[2]), "+f"(d[3]), "+f"(d[4]), "+f"(d[5]), "+f"(d[6]), "+f"(d[7])
               : "r"(da), "r"(db), "n"(TA), "n"(ACC));
}
__device__ __forceinline__ void wgmma_n16_ones(float (&d)[8], uint32_t one, uint32_t db) {
  asm volatile("{\n.reg .b64 db;\nmov.b64 db, {%9, 0x40000040};\n"
               "wgmma.mma_async.sync.aligned.m64n16k16.f32.bf16.bf16 {%0,%1,%2,%3,%4,%5,%6,%7}, {%8,%8,%8,%8}, db, 1, 1, 1, 0;\n}"
               : "+f"(d[0]), "+f"(d[1]), "+f"(d[2]), "+f"(d[3]), "+f"(d[4]), "+f"(d[5]), "+f"(d[6]), "+f"(d[7])
               : "r"(one), "r"(db));
}
__device__ __forceinline__ void acc_fence(float (&d)[8]) {
  asm volatile("" : "+f"(d[0]), "+f"(d[1]), "+f"(d[2]), "+f"(d[3]), "+f"(d[4]), "+f"(d[5]), "+f"(d[6]), "+f"(d[7]) :: "memory");
}

template <int N, int STRIDE> __device__ __forceinline__ void load_units(uint2 (&v)[N], const uint32_t* p) {
#pragma unroll
  for (int i = 0; i < N; i++) v[i] = ldg_u64(p + i * STRIDE);
}
__device__ __forceinline__ void reload_unit(uint2& v, const uint32_t* p) {
  asm volatile("{\n.reg .pred q;\nsetp.eq.u32 q, %1, 0;\n@q ld.relaxed.gpu.global.v2.b32 {%0, %1}, [%2];\n}" : "+r"(v.x), "+r"(v.y) : "l"(p) : "memory");
}
template <int N> __device__ __forceinline__ uint32_t min_flags(const uint2 (&v)[N]) {
  uint32_t a = v[0].y, b = v[1].y;
#pragma unroll
  for (int i = 2; i < N; i += 2) { a = min(a, v[i].y); b = min(b, v[i + 1].y); }
  return min(a, b);
}
template <int N, int STRIDE> __device__ __forceinline__ int check_units(uint2 (&v)[N], const uint32_t* p) {
  int it = 0;
  while (!__all_sync(~0u, min_flags(v) != 0)) {
#pragma unroll
    for (int i = 0; i < N; i++) reload_unit(v[i], p + i * STRIDE);
    if (++it > SPIN_LIMIT) __trap();
  }
  return it;
}
__device__ __forceinline__ void sum4_to_smem(const uint2 (&v)[4], uint32_t dst) {
  const float c0 = (bf_lo(v[0].x) + bf_lo(v[1].x)) + (bf_lo(v[2].x) + bf_lo(v[3].x));
  const float c1 = (bf_hi(v[0].x) + bf_hi(v[1].x)) + (bf_hi(v[2].x) + bf_hi(v[3].x));
  const float c2 = (bf_lo(v[0].y) + bf_lo(v[1].y)) + (bf_lo(v[2].y) + bf_lo(v[3].y));
  const float c3 = (bf_hi(v[0].y) + bf_hi(v[1].y)) + (bf_hi(v[2].y) + bf_hi(v[3].y));
  sts1(dst, pack_bf16(c0, c1));
  sts1(dst + 128, pack_bf16(c2, c3));
}
__device__ __forceinline__ uint32_t a_t_offset(int w, int lane) {
  const int mi = lane >> 3, r = lane & 7;
  return (w >> 2) * 16384 + (8 * (mi >> 1) + r) * 128 + (((2 * (w & 3) + (mi & 1)) ^ r) << 4);
}
__device__ __forceinline__ void load_a_t(uint32_t (&a)[8][4], uint32_t base) {
#pragma unroll
  for (int ks = 0; ks < 8; ks++) ldsm4t(a[ks], base + ks * 2048);
}
__device__ __forceinline__ void mma128(float (&d)[4], const uint32_t (&a)[8][4], const uint32_t (&b)[4][4]) {
  float e[4][4] = {{d[0], d[1], d[2], d[3]}, {0.f, 0.f, 0.f, 0.f}, {0.f, 0.f, 0.f, 0.f}, {0.f, 0.f, 0.f, 0.f}};
#pragma unroll
  for (int kk = 0; kk < 4; kk++) { mma16816(e[(2 * kk) & 3], a[2 * kk], b[kk][0], b[kk][1]); mma16816(e[(2 * kk + 1) & 3], a[2 * kk + 1], b[kk][2], b[kk][3]); }
#pragma unroll
  for (int i = 0; i < 4; i++) d[i] = (e[0][i] + e[1][i]) + (e[2][i] + e[3][i]);
}
template <int NP> __device__ __forceinline__ bool sum_pieces(const uint32_t* p0, uint32_t one, float (&r)[4]) {
  uint2 v[NP / 4];
  load_units<NP / 4, 64>(v, p0);
  float d[4][4] = {};
#pragma unroll
  for (int i = 0; i < NP / 8; i++) { const uint32_t a[4] = {v[2 * i].x, v[2 * i].y, v[2 * i + 1].x, v[2 * i + 1].y}; mma16816(d[i & 3], a, one, one); }
  const bool ok = __all_sync(~0u, min_flags(v) != 0);
#pragma unroll
  for (int k = 0; k < 4; k++) r[k] = (d[0][k] + d[1][k]) + (d[2][k] + d[3][k]);
  return ok;
}
template <typename F> __device__ __forceinline__ float reduce_g(const float (&x)[4], int lane, F f) {
  const bool u4 = lane & 16, u3 = lane & 8;
  const float a0 = f(u4 ? x[2] : x[0], __shfl_xor_sync(~0u, u4 ? x[0] : x[2], 16));
  const float a1 = f(u4 ? x[3] : x[1], __shfl_xor_sync(~0u, u4 ? x[1] : x[3], 16));
  const float b = f(u3 ? a1 : a0, __shfl_xor_sync(~0u, u3 ? a0 : a1, 8));
  return f(b, __shfl_xor_sync(~0u, b, 4));
}

__global__ void __launch_bounds__(NTHREADS, 1)
fused_decode_kernel(__nv_bfloat16* __restrict__ gout, Scratch* __restrict__ gs, const uint8_t* __restrict__ gwmod,
                    const uint8_t* __restrict__ gx, const uint8_t* __restrict__ gc, uint32_t* __restrict__ gin,
                    const __grid_constant__ Params P) {
  constexpr Tune T{};
  extern __shared__ __align__(1024) uint8_t smem_raw[];
  constexpr uint32_t sb = SB;
  const int tid = __shfl_xor_sync(0xffffffffu, threadIdx.x ^ 1, 1), lane = tid & 31;
  const int w = __shfl_sync(0xffffffffu, threadIdx.x >> 5, 0);
  const int cta = blockIdx.x;
  auto BAR = [](int i) { return SB + OFF_BARS + 8 * i; };
  auto selector = [&](int c) { uint32_t v; asm volatile("ld.shared.u8 %0, [%1];" : "=r"(v) : "r"(sb + OFF_SEL + c) : "memory"); return v; };
  auto inbox = [&](int c, int k) { return gin + blk(c, k, selector(c)); };
  auto nearbox = [&](int c, int k) { return gin + blk(c, k, selector(cta) ^ flip((c ^ cta) & 15)); };
  const int g = lane >> 2, t = lane & 3;
  const int hI = cta >> 2, jI = cta & 3;
  const int bs = cta >> 1, hh = cta & 1;

  CLK_DECL;
  CLK(0);
  if (w == 8) {
    CLK(7);
    const uint32_t t_entry = gtime32();
    CLK(8);
    if (lane == 0) {
      if ((uint32_t)__cvta_generic_to_shared(smem_raw) != SB) __trap();
      mbar_init(BAR(BAR_WQ), 1); mbar_init(BAR(BAR_WQ + 1), 1); mbar_init(BAR(BAR_XC), 1); mbar_init(BAR(BAR_C), 1);
      asm volatile("fence.mbarrier_init.release.cluster;" ::: "memory");
      asm volatile("prefetch.tensormap [%0];" ::"l"(&P.wq) : "memory");
      mbar_expect(BAR(BAR_XC), 8192); mbar_expect(BAR(BAR_C), 8192); mbar_expect(BAR(BAR_WQ), 16384); mbar_expect(BAR(BAR_WQ + 1), 16384);
      CLK(9);
    }
    __syncwarp();
    asm volatile("barrier.cta.arrive.aligned 0, %0;" ::"n"(NTHREADS) : "memory");
    CLK(10);
    uint32_t tn = t_entry + T.PC_T0 + ((bs * 37) & 63) * T.PC_STAG / 64;
    const int h = hI, j = jI;
    if (lane == 0) {
      uint64_t pol; asm volatile("createpolicy.fractional.L2::evict_first.b64 %0, 1.0;" : "=l"(pol));
#pragma unroll
      for (int u = 0; u < 4; u++) {
        until_ns(tn + u * T.PC_P1);
        if (u == 0) CLK(11);
        tma2d(sb + OFF_WQ + u * 8192, &P.wq, 128 * h + 64 * (u >> 1), 128 * j + 64 * (u & 1), BAR(BAR_WQ + (u >> 1)), pol);
        if (u == T.PC_XC) {
#pragma unroll
          for (int i = 0; i < 4; i++) { const int o = ((i + cta) & 3) * 2048; bulk_ld(sb + OFF_XS + o, gx + o, 2048, BAR(BAR_XC)); }
        }
        if (u == T.PC_C) {
#pragma unroll
          for (int i = 0; i < 4; i++) { const int o = ((i + cta) & 3) * 2048; bulk_ld(sb + OFF_CS + o, gc + o, 2048, BAR(BAR_C)); }
        }
        if (u == 0) {
          CLK(1);
          asm volatile("prefetch.tensormap [%0];" ::"l"(&P.wuk) : "memory");
          asm volatile("prefetch.tensormap [%0];" ::"l"(&P.wm2) : "memory");
          asm volatile("prefetch.tensormap [%0];" ::"l"(&P.ckv2) : "memory");
        }
      }
    }
    __syncwarp();
    tn += 4 * T.PC_P1;
    bar_sync(5, 64);
    if (lane == 0) {
      uint64_t pol; asm volatile("createpolicy.fractional.L2::evict_first.b64 %0, 1.0;" : "=l"(pol));
#pragma unroll
      for (int u = 0; u < 4; u++) {
        if ((u & 1) == (T.PC_W > 3) && T.PC_NW) mbar_wait(BAR(BAR_WQ + (u >> 1)));
        slot(tn, T.PC_SL);
        tma5d(sb + OFF_WUK + u * 8192, &P.wuk, 128 * h + 64 * (u >> 1), 0, 0, 0, 8 * j + 4 * (u & 1), BAR(BAR_WUK + (u >> 1)), pol);
        tn += T.PC_P1;
      }
#pragma unroll
      for (int u = 0; u < 2; u++) {
        if (u == (T.PC_W > 3) && T.PC_NW) mbar_wait(BAR(BAR_WUK));
        slot(tn, T.PC_SL);
        if (j != 3) tma2d_nohint(sb + OFF_WM2 + u * 8192, &P.wm2, 1024 + 16 * (3 * h + j), 256 * u, BAR(BAR_WM2));
        tn += T.PC_PM;
      }
      const int row0 = (bs >> 3) * 4096 + (bs & 7) * 64;
      uint32_t dst = sb + OFF_RING;
      const int p2 = T.PC_P2 + (32 - ((bs * 37) & 63)) * T.PC_DS / 1024;
#pragma unroll 1
      for (int n = 0; n < 31; n++) {
        if (n >= 4 && (n < 12 || (n & 3) == 0)) mbar_wait(BAR(n >= 12 ? BAR_EMPTY + (n >> 2) - 3 : (n == 7 && j != 3) ? BAR_P0BD : (n == 8 || n == 9) ? BAR_P2D : BAR_P1D));
        if (n < T.PC_NW) {
          if (n >= T.PC_W) mbar_wait(BAR(BAR_FULL + n - T.PC_W));
          else if ((n & 1) == (T.PC_W > 3)) mbar_wait(BAR((n < 2 || j == 3) ? BAR_WUK + 1 : BAR_WM2));
        }
        slot(tn, T.PC_SL);
        tma3d(dst, &P.ckv2, 0, row0 + (n >> 2) * 512, 2 * (n & 3), BAR(BAR_FULL + n), pol);
        dst = (n == 11 || n == 23) ? sb + OFF_RING : dst + 16384;
        tn += n >= 15 ? p2 : T.PC_P2;
        if (n == 4) CLK(2);
        if (n == 12) CLK(3);
        if (n == 20) CLK(4);
        if (n == 28) CLK(5);
        if (n == 24) {
          asm volatile("prefetch.tensormap [%0];" ::"l"(&P.ckv1) : "memory");
          asm volatile("prefetch.tensormap [%0];" ::"l"(&P.wuv) : "memory");
          asm volatile("prefetch.tensormap [%0];" ::"l"(&P.wo) : "memory");
          asm volatile("prefetch.tensormap [%0];" ::"l"(cta < NFF ? &P.w1 : &P.wm3) : "memory");
          asm volatile("prefetch.tensormap [%0];" ::"l"(&P.w2) : "memory");
        }
      }
      slot(tn, T.PC_SL);
      tma3d(dst, &P.ckv1, 0, row0 + 7 * 512, 6, BAR(BAR_LAST + 3), pol);
      tma3d(dst + 8192, &P.ckv1, 0, row0 + 7 * 512, 7, BAR(BAR_LAST + 4), pol);
      tn += T.PC_P2;
      CLK(6);
      auto unit = [&](int u) {
        if (u < 4) tma5d(sb + OFF_WUV + u * 8192, &P.wuv, 128 * h + 64 * (u >> 1), 0, 4 * (j >> 1), 0, 2 * (j & 1) + (u & 1), BAR(BAR_WUV + (u >> 1)), pol);
        else if (u < 8) tma2d(sb + OFF_WO + (u - 4) * 8192, &P.wo, 128 * j + 64 * ((u - 4) >> 1), 128 * h + 64 * (u & 1), BAR(BAR_WO + ((u - 4) >> 1)), pol);
        else if (u < 10) { if (cta < NFF) tma2d_nohint(sb + OFF_W1 + (u - 8) * 16384, &P.w1, 32 * bs, 256 * (u - 8), BAR(BAR_W1)); }
        else if (cta < NFF) tma3d(sb + OFF_W2 + (u - 10) * 8192, &P.w2, 0, 32 * bs, 4 * hh + 2 * (u - 10), BAR(BAR_W2), pol);
        else tma2d_nohint(sb + OFF_W1 + (u - 10) * 16384, &P.wm3, 2560 + 32 * (cta - NFF), 256 * (u - 10), BAR(BAR_W1));
      };
      mbar_wait(BAR(BAR_EMPTY + 5));
      if (T.PW_A >= 0) { mbar_wait(BAR(BAR_LAST + T.PW_A)); tn = gtime32(); }
      tn += T.PW_0 + ((cta * 37) & 127) * T.PW_ST / 128;
#pragma unroll
      for (int u = 0; u < 12; u++) {
        if (u == 8) mbar_wait(BAR(BAR_EMPTY + 6));
        if (u == 10 && cta >= NFF) tn += T.PW_GB;
        until_ns(tn);
        unit(u);
        tn += u < 3 ? T.PW_UV : u == 3 ? T.PW_G : u < 7 ? T.PW_O : u == 7 ? T.PW_G2 : u == 9 ? T.PW_G3 : T.PW_F;
      }
      CLK_DUMP();
    }
    return;
  }

  if (w == 9) {
    if (lane == 0) {
#pragma unroll
      for (int i = 0; i < NBARS; i++) mbar_init(BAR(i), i >= BAR_P1D ? 8 : i >= BAR_EMPTY ? 4 : 1);
      asm volatile("fence.mbarrier_init.release.cluster;" ::: "memory");
    }
    __syncwarp();
    mbar_expect(BAR(lane), lane == BAR_LAST + 3 ? 8192 : 16384);
    if (lane < BAR_ALLCLR - 32) mbar_expect(BAR(32 + lane), lane == 0 ? 8192 : lane == BAR_W1 - 32 ? 32768 : 16384);
    CLK(9);
    asm volatile("barrier.cta.arrive.aligned 5, 64;" ::: "memory");
    asm volatile("barrier.cta.arrive.aligned 0, %0;" ::"n"(NTHREADS) : "memory");
  }
  const uint32_t epoch = ldg_rlx1(&gs->epoch);

  if (w == 9) {
    const int mo = g * 512 + 16 * hI + 2 * jI;
    const uint32_t xo0 = ldg_nc1(gx + mo * 2), xo1 = ldg_nc1(gx + mo * 2 + 16);
    const int par = epoch & 1;
    const uint32_t t0 = gtime32();
    const uint4 z = make_uint4(0, 0, 0, 0);
    uint32_t sel;
    {
      uint32_t* pa = gin + blk(cta, 5, 0) + 960;
      uint32_t* pb = gin + blk(cta, 5, 1) + 960;
      until_ns(t0 + T.PR_T0);
      if (lane < 4) stg4(reinterpret_cast<uint4*>(lane & 2 ? pa : pb) + (lane & 1), z);
      uint32_t ma = 0xffffffffu, mb = 0xffffffffu;
#pragma unroll 1
      for (int i = 0; i < 2 * T.PR_N; i++) {
        const uint32_t c0 = clk32();
        asm volatile("{\n.reg .pred q;\n.reg .b32 v;\nsetp.eq.u32 q, %1, 0;\nmov.u32 v, 0;\n@q atom.relaxed.gpu.global.add.u32 v, [%0], 1;\n"
                     "setp.eq.u32 q, v, 0xffffffff;\n@q trap;\n}" ::"l"(i & 1 ? pb : pa), "r"(lane) : "memory");
        const uint32_t d = clk32() - c0;
        if (i & 1) mb = min(mb, d); else ma = min(ma, d);
      }
      sel = __shfl_sync(~0u, (uint32_t)(mb < ma), 0);
      if (T.LOC == 1) sel ^= 1;
      if (T.LOC == 2) sel ^= (cta ^ (cta >> 3)) & 1;
      const uint32_t sw = 2 * (epoch + 1) + sel;
      if (lane < 2) stg4(reinterpret_cast<uint4*>(gin + blk(cta, 5, 1) + 896) + lane, make_uint4(sw, sw, sw, sw));
    }
    until_ns(t0 + T.CLR_T0);
    {
#pragma unroll 1
      for (int i0 = 0; i0 < 13; i0++) {
        uint4* q = reinterpret_cast<uint4*>(gin + (i0 < 12 ? blk(cta, i0 >> 1, sel) + (i0 & 1) * 512 : blk(cta, 4, sel ^ 1) + 512)) + lane;
#pragma unroll
        for (int i = 0; i < 4; i++) if (i0 != 11 || i < 3) stg4(q + i * 32, z);
        backoff(T.CLR_CLK);
      }
#pragma unroll
      for (int i = 0; i < 2; i++) {
        if (jI == 1) stg4(reinterpret_cast<uint4*>(gin + blk(cta, 6, i)) + lane, z);
        if (lane < 2) stg4(reinterpret_cast<uint4*>(gin + blk(cta, 5, i) + 928) + lane, z);
        stg4(reinterpret_cast<uint4*>(gin + blk(16 * g, 6 + (cta >> 6), i) + (cta & 63) * 16) + t, z);
      }
      CLK(1);
      {
        uint32_t sv = 0;
        uint32_t u[4];
        int it = 0;
        do {
#pragma unroll
          for (int i = 0; i < 4; i++) u[i] = ldg_rlx1(gin + blk(4 * lane + i, 5, 1) + 896) ^ (2 * (epoch + 1));
          if (++it > SPIN_LIMIT) __trap();
        } while (!__all_sync(~0u, (u[0] | u[1] | u[2] | u[3]) < 2));
#pragma unroll
        for (int i = 0; i < 4; i++) sv |= u[i] << (8 * i);
        sts1(sb + OFF_SEL + lane * 4, sv);
      }
      asm volatile("fence.acq_rel.gpu;" ::: "memory");
      CLK(2);
      __syncwarp();
      if (lane < NSYNC) asm volatile("red.relaxed.gpu.global.add.u32 [%0], 1;" ::"l"(&gs->sync[lane][0]) : "memory");
#pragma unroll
      for (int i = 0; i < 4; i++) stg4(reinterpret_cast<uint4*>(gs->QP[par ^ 1] + cta * 512) + i * 32 + lane, z);
      backoff(T.CLR_CLK);
#pragma unroll
      for (int i = 0; i < 4; i++) stg4(reinterpret_cast<uint4*>(gs->QX[par ^ 1] + cta * 512) + i * 32 + lane, z);
      stg4(reinterpret_cast<uint4*>(gs->MOD1[par ^ 1] + cta * 128) + lane, z);
      if (lane < 16) stg4(reinterpret_cast<uint4*>(gs->MOD2[par ^ 1] + cta * 64) + lane, z);
      const uint32_t target = (epoch + 1) * NCTA;
      uint32_t c; int it = 0;
      do {
        backoff(T.CLR_CLK);
        asm volatile("ld.acquire.gpu.global.u32 %0, [%1];" : "=r"(c) : "l"(&gs->sync[cta % NSYNC][0]) : "memory");
        if (++it > SPIN_LIMIT) __trap();
      } while (!__all_sync(~0u, (int)(c - target) >= 0));
      if (lane == 0) mbar_arrive(BAR(BAR_ALLCLR));
    }
    CLK(3);
    const uint32_t* const pg = gs->MOD2[par] + cta * 16 + g * 2;
    auto gate = [&](const uint32_t* q) { uint2 u; int it = 0; do { u = ldg_u64(q); if (++it > SPIN_LIMIT) __trap(); } while (!__all_sync(~0u, u.y != 0)); return u; };
    const uint2 gau = gate(pg);
    uint32_t anchor;
    {
      uint32_t* const po = gin + blk(16 * (lane & 7), 5, lane >> 3) + 928;
      const uint32_t* const pi = nearbox(cta & ~15, 5) + 928;
      mbar_wait(BAR(BAR_LAST + T.TS_P));
      unsigned long long now; asm volatile("mov.u64 %0, %%globaltimer;" : "=l"(now));
      if (lane < 16) {
        asm volatile("red.relaxed.gpu.global.max.u64 [%0], %1;" ::"l"(po + 2), "l"(now) : "memory");
        asm volatile("red.relaxed.gpu.global.add.u32 [%0], 1;" ::"l"(po + 1) : "memory");
      }
      backoff(T.D_TS);
      uint4 v; int it = 0;
      do { v = ldg_2u64(pi); if (++it > SPIN_LIMIT) __trap(); } while (!__all_sync(~0u, v.y == NCTA));
      const int age = min(max((int)(gtime32() - v.z), 0), 4000);
      anchor = clk32() - age * 7 / 4 + T.TS_O;
      if (lane == 0) { sts1(sb + OFF_TS, anchor); mbar_arrive(BAR(BAR_TS)); }
      CLK(10);
    }
    {
      const uint32_t* pm = pin(nearbox(4 * hI + 1, 6) + lane * 4);
      wait_clk(anchor, T.A_M);
      uint4 ml = ldg_2u64(pm);
      int it = 0;
      while (!__all_sync(~0u, ml.y != 0 && ml.w != 0)) { ml = ldg_2u64(pm); if (++it > SPIN_LIMIT) __trap(); }
      ITS(2, it);
      float M = fmaxf(__uint_as_float(ml.x), __uint_as_float(ml.z));
      M = fmaxf(M, __shfl_xor_sync(~0u, M, 1)); M = fmaxf(M, __shfl_xor_sync(~0u, M, 2));
      const float e0 = ex2(__uint_as_float(ml.x) - M), e1 = ex2(__uint_as_float(ml.z) - M);
      float l = e0 * __uint_as_float(ml.y) + e1 * __uint_as_float(ml.w);
      l += __shfl_xor_sync(~0u, l, 1); l += __shfl_xor_sync(~0u, l, 2);
      const float inv = __fdividef(1.f, l);
      sts2f(sb + OFF_WV + lane * 8, e0 * inv, e1 * inv);
      __syncwarp();
      if (lane == 0) mbar_arrive(BAR(BAR_WV));
      CLK(11);
    }
    uint32_t* x3o[4];
#pragma unroll
    for (int i = 0; i < 4; i++) x3o[i] = pin(gin + blk(32 * i + 16 * (t >> 1), 6 + (cta >> 6), t) + (cta & 63) * 16 + g * 2);
    uint32_t* const fo = pin(reinterpret_cast<uint32_t*>(gout) + mo / 2 + 4 * (t & 1));
    const uint32_t* const p3 = pin(gin + blk(cta, 4, sel) + t * 16 + g * 2);
    const uint32_t* const p4 = pin(gin + blk(cta, 5, sel) + t * 16 + g * 2);
    const uint32_t one = pin((g & 1) ? 0x3f800000u : 0x00003f80u);
    const float xf[4] = {pin(bf_lo(xo0)), pin(bf_hi(xo0)), pin(bf_lo(xo1)), pin(bf_hi(xo1))};
    const float ga[4] = {pin(bf_lo(gau.x)), pin(bf_hi(gau.x)), pin(bf_lo(gau.y)), pin(bf_hi(gau.y))};
    mbar_wait(BAR(BAR_P5D));
    backoff(T.D_X3A);
    wait_clk(anchor, T.A_X1 + T.R_X3A);
    CLK(4);
    float r[4];
    uint32_t x20, x21;
    int it = 0;
    bool ok;
    do {
      ok = sum_pieces<32>(p3, one, r);
      x20 = pack_bf16(xf[0] + ga[0] * r[0], xf[1] + ga[1] * r[1]); x21 = pack_bf16(xf[2] + ga[2] * r[2], xf[3] + ga[3] * r[3]);
#pragma unroll
      for (int i = 0; i < 4; i++) ST3B(!ok || (i == 3 && t >= 2), x3o[i], x20, x21);
    } while (!ok && ++it < SPIN_LIMIT);
    CLK(6);
    ITS(0, it);
    const uint32_t xw = (t & 1) ? x21 : x20;
    const float xa = pin(bf_lo(xw)), xb = pin(bf_hi(xw));
    if (cta < NFF) mbar_wait(BAR(BAR_P7D)); else wait_clk(anchor, T.A_X1 + T.R_X3A + T.R_X3B + T.R_FIN - T.D_FIN);
    uint2 gbu = ldg_u64(pg + 3 * 2048);
    backoff(T.D_FIN);
    CLK(7);
    do {
      ok = sum_pieces<NFG>(p4, one, r);
      ok = ok && __all_sync(~0u, gbu.y != 0);
      const uint32_t gw = (t & 1) ? gbu.y : gbu.x;
      const uint32_t o = pack_bf16(xa + bf_lo(gw) * ((t & 1) ? r[2] : r[0]), xb + bf_hi(gw) * ((t & 1) ? r[3] : r[1]));
      if (ok && t < 2) asm volatile("st.global.u32 [%0], %1;" ::"l"(fo), "r"(o) : "memory");
      reload_unit(gbu, pg + 3 * 2048);
    } while (!ok && ++it < SPIN_LIMIT);
    if (!ok) __trap();
    ITS(1, it);
    CLK(8);
    CLK_DUMP();
    if (cta == 0 && lane == 0) stg1(&gs->epoch, epoch + 1);
    return;
  }

  const int wg = w >> 2, wq = w & 3;
  uint32_t tstore;
  {
    const uint8_t* pw = gwmod + (size_t)(128 * jI + 16 * w + 4 * (g >> 1) + (g & 1)) * 6144 + 64 * hI + 16 * t;
    const uint4 w0 = ldg_nc4(pw), w1 = ldg_nc4(pw + 2 * 6144);
    const uint2 cc = ldg_nc2(gc + g * 1024 + 256 * jI + 32 * w + 8 * t);
    CLK(40);
    const uint32_t a[4] = {silu2(cc.x), 0u, silu2(cc.y), 0u};
    float d[4][4] = {{0.f, 0.f, 0.f, 0.f}, {0.f, 0.f, 0.f, 0.f}, {0.f, 0.f, 0.f, 0.f}, {0.f, 0.f, 0.f, 0.f}};
    mma16816(d[0], a, movm(w0.x), movm(w1.x)); mma16816(d[1], a, movm(w0.y), movm(w1.y));
    mma16816(d[2], a, movm(w0.z), movm(w1.z)); mma16816(d[3], a, movm(w0.w), movm(w1.w));
    CLK(1);
    sts4f(sb + OFF_P0S + w * 1088 + lane * 16, d[0][0], d[0][1], d[1][0], d[1][1]);
    sts4f(sb + OFF_P0S + w * 1088 + 544 + lane * 16, d[2][0], d[2][1], d[3][0], d[3][1]);
    bar_sync(0, NTHREADS);
    if (tid < 128) {
      const uint32_t src = sb + OFF_P0S + ((tid >> 2) & 1) * 544 + (((tid >> 3) & 7) * 4 + 2 * (tid >> 6) + (tid & 1)) * 16 + ((tid >> 1) & 1) * 8;
      float2 v[8];
#pragma unroll
      for (int i = 0; i < 8; i++) v[i] = ldsf2(src + i * 1088);
      const float ax = ((v[0].x + v[1].x) + (v[2].x + v[3].x)) + ((v[4].x + v[5].x) + (v[6].x + v[7].x));
      const float ay = ((v[0].y + v[1].y) + (v[2].y + v[3].y)) + ((v[4].y + v[5].y) + (v[6].y + v[7].y));
      stg1(gs->MOD1[epoch & 1] + jI * 4096 + hI * 128 + tid, nz(pack_bf16(ax, ay)));
    }
    tstore = clk32();
  }
  CLK(2);
  const int par = epoch & 1;
  uint32_t cf[4][4];
  mbar_wait(BAR(BAR_XC));
  {
    uint32_t u[2][4];
    lds4(u[0], sb + OFF_XS + w * 1024 + lane * 16); lds4(u[1], sb + OFF_XS + w * 1024 + 512 + lane * 16);
    float v[16];
#pragma unroll
    for (int i = 0; i < 8; i++) { v[2 * i] = bf_lo(u[i >> 2][i & 3]); v[2 * i + 1] = bf_hi(u[i >> 2][i & 3]); }
    float s = 0.f;
#pragma unroll
    for (int i = 0; i < 16; i++) s += v[i];
#pragma unroll
    for (int o = 16; o; o >>= 1) s += __shfl_xor_sync(~0u, s, o);
    const float mu = s * (1.f / 512.f);
    float q = 0.f;
#pragma unroll
    for (int i = 0; i < 16; i++) { v[i] -= mu; q += v[i] * v[i]; }
#pragma unroll
    for (int o = 16; o; o >>= 1) q += __shfl_xor_sync(~0u, q, o);
    const float rs = rsqrtf(q * (1.f / 512.f) + 1e-5f);
    const bool hi = jI & 2;
    uint32_t o[4];
#pragma unroll
    for (int i = 0; i < 4; i++) o[i] = pack_bf16((hi ? v[8 + 2 * i] : v[2 * i]) * rs, (hi ? v[9 + 2 * i] : v[2 * i + 1]) * rs);
    if ((lane >> 4) == (jI & 1)) sts4(sb + OFF_XN + w * 272 + (lane & 15) * 16, make_uint4(o[0], o[1], o[2], o[3]));
  }
  CLK(3);
  uint32_t aw[8][4];
  const uint32_t abase = __shfl_sync(~0u, sb + a_t_offset(w, lane), lane);
  {
    const uint32_t* pm = pin(gs->MOD1[par] + (8 * jI + w) * 64 + lane * 2);
    uint32_t* const qpo = pin(gs->QP[par] + (cta * 256 + tid) * 2);
    float d[4] = {0.f, 0.f, 0.f, 0.f};
    wait_clk(tstore, T.D_MOD);
    CLK(4);
    uint2 v[8];
    load_units<8, 2048>(v, pm);
    cbar();
    const uint32_t xn0 = lds1(sb + OFF_XN + g * 272 + w * 32 + t * 4), xn1 = lds1(sb + OFF_XN + g * 272 + w * 32 + 16 + t * 4);
    const bool early = __all_sync(~0u, mbar_test(BAR(BAR_WQ + wg)));
    if (early) load_a_t(aw, abase + OFF_WQ);
    int it = 0;
    while (true) {
      uint32_t mn = 0xffffffffu;
#pragma unroll
      for (int i = 0; i < 8; i++) mn = min(mn, min(v[i].x, v[i].y));
      if (__all_sync(~0u, mn != 0)) break;
#pragma unroll
      for (int i = 0; i < 8; i++) { if (v[i].x == 0) v[i].y = 0; reload_unit(v[i], pm + i * 2048); }
      if (++it > SPIN_LIMIT) __trap();
    }
    CLK(5);
    ITS(0, it);
    float sc[2][4];
#pragma unroll
    for (int i = 0; i < 2; i++) {
      sc[i][0] = (bf_lo(v[i].x) + bf_lo(v[2 + i].x)) + (bf_lo(v[4 + i].x) + bf_lo(v[6 + i].x));
      sc[i][1] = (bf_hi(v[i].x) + bf_hi(v[2 + i].x)) + (bf_hi(v[4 + i].x) + bf_hi(v[6 + i].x));
      sc[i][2] = (bf_lo(v[i].y) + bf_lo(v[2 + i].y)) + (bf_lo(v[4 + i].y) + bf_lo(v[6 + i].y));
      sc[i][3] = (bf_hi(v[i].y) + bf_hi(v[2 + i].y)) + (bf_hi(v[4 + i].y) + bf_hi(v[6 + i].y));
    }
    sts2(sb + OFF_BS1 + (w >> 1) * 512 + lane * 16 + (w & 1) * 8,
         pack_bf16(bf_lo(xn0) * (1.f + sc[1][0]) + sc[0][0], bf_hi(xn0) * (1.f + sc[1][1]) + sc[0][1]),
         pack_bf16(bf_lo(xn1) * (1.f + sc[1][2]) + sc[0][2], bf_hi(xn1) * (1.f + sc[1][3]) + sc[0][3]));
    if (!early) { mbar_wait(BAR(BAR_WQ + wg)); load_a_t(aw, abase + OFF_WQ); }
    CLK(6);
    cbar();
    uint32_t b[4][4];
#pragma unroll
    for (int kk = 0; kk < 4; kk++) lds4(b[kk], sb + OFF_BS1 + kk * 512 + lane * 16);
    mma128(d, aw, b);
    stg_u64(qpo, pack_bf16(d[0], d[1]), pack_bf16(d[2], d[3]));
    tstore = clk32();
    CLK(7);
    if (wg) {
      mbar_wait(BAR(BAR_C));
#pragma unroll
      for (int i = 0; i < 4; i++) lds4(cf[i], sb + OFF_CS + g * 1024 + wq * 256 + i * 64 + t * 16);
#pragma unroll
      for (int i = 0; i < 16; i++) cf[i >> 2][i & 3] = silu2(cf[i >> 2][i & 3]);
    }
    __syncwarp();
    if (lane == 0) mbar_arrive(BAR(BAR_P1D));
  }
  {
    const uint32_t* pq = pin(gs->QP[par] + (hI * 4 * 256 + tid) * 2);
    uint32_t* const qxo = pin(gs->QX[par] + (g * 32 + hI) * 256 + 64 * jI + 8 * w + 2 * t);
    uint2 v[4];
    float d[4] = {0.f, 0.f, 0.f, 0.f};
    wait_clk(tstore, T.D_QP);
    CLK(8);
    load_units<4, 512>(v, pq);
    const uint32_t kbase = sb + OFF_WUK + (16 * w + (lane & 15)) * 128;
    auto load_half = [&](int hf) {
#pragma unroll
      for (int ks = 0; ks < 4; ks++) ldsm4(aw[4 * hf + ks], kbase + hf * 16384 + (((2 * ks + (lane >> 4)) ^ (lane & 7)) << 4));
    };
    mbar_wait(BAR(BAR_WUK));
    load_half(0);
    const bool early = __all_sync(~0u, mbar_test(BAR(BAR_WUK + 1)));
    if (early) load_half(1);
    const int it = check_units<4, 512>(v, pq);
    CLK(9);
    ITS(1, it);
    sum4_to_smem(v, sb + OFF_BS2 + (16 * w + g) * 16 + t * 4);
    if (!early) { mbar_wait(BAR(BAR_WUK + 1)); load_half(1); }
    CLK(10);
    cbar();
    uint32_t b[4][4];
#pragma unroll
    for (int kk = 0; kk < 4; kk++) ldsm4t(b[kk], sb + OFF_BS2 + (32 * kk + lane) * 16);
    mma128(d, aw, b);
    const float sc = 0.08838834764831845f * 1.4426950408889634f;
    stg_u64(qxo, movm(pack_bf16(d[0] * sc, d[1] * sc)), movm(pack_bf16(d[2] * sc, d[3] * sc)));
    tstore = clk32();
    CLK(11);
    if (lane == 0) mbar_arrive(BAR(BAR_P2D));
  }
  if (wg && jI != 3) {
    const int mi = lane >> 3, r = lane & 7;
    const uint32_t a0 = sb + OFF_WM2 + (8 * (r >> 1) + (r & 1) + 2 * (mi >> 1)) * 32 + (mi & 1) * 16;
    mbar_wait(BAR(BAR_WM2));
#pragma unroll
    for (int s = 0; s < 8; s++) ldsm4t(aw[s], a0 + (128 * wq + 32 * (s >> 1) + 4 * (s & 1)) * 32);
    float d[4] = {0.f, 0.f, 0.f, 0.f};
    mma128(d, aw, cf);
    sts4f(sb + OFF_P0B + (tid - 128) * 16, d[0], d[1], d[2], d[3]);
    if (lane == 0) mbar_arrive(BAR(BAR_P0BD));
    bar_sync(3, 128);
    if (w == 4) {
      float4 v[4];
#pragma unroll
      for (int i = 0; i < 4; i++) v[i] = ldsf4(sb + OFF_P0B + (i * 32 + lane) * 16);
      stg_u64(gs->MOD2[par] + (3 * hI + jI) * 64 + t * 16 + g * 2, movm(pack_bf16((v[0].x + v[1].x) + (v[2].x + v[3].x), (v[0].y + v[1].y) + (v[2].y + v[3].y))),
              movm(pack_bf16((v[0].z + v[1].z) + (v[2].z + v[3].z), (v[0].w + v[1].w) + (v[2].w + v[3].w))));
    }
    CLK(15);
  }
  {
    const uint32_t* qx = pin(gs->QX[par] + ((bs >> 3) * 32 + 16 * hh) * 256 + tid * 4);
    const int ch = tid & 63, h0 = tid >> 6;
    const uint32_t dst = sb + OFF_Q + (ch >> 3) * 2048 + h0 * 128;
    wait_clk(tstore, T.D_QX);
    CLK(12);
    uint4 v[4];
#pragma unroll
    for (int i = 0; i < 4; i++) v[i] = ldg_2u64(qx + i * 1024);
    int it = 0;
    while (true) {
      uint32_t mn = 0xffffffffu;
#pragma unroll
      for (int i = 0; i < 4; i++) mn = min(mn, min(v[i].y, v[i].w));
      if (__all_sync(~0u, mn != 0)) break;
#pragma unroll
      for (int i = 0; i < 4; i++)
        asm volatile("{\n.reg .pred q;\nsetp.eq.u32 q, %5, 0;\n@q ld.relaxed.gpu.global.v4.b32 {%0, %1, %2, %3}, [%4];\n}"
                     : "+r"(v[i].x), "+r"(v[i].y), "+r"(v[i].z), "+r"(v[i].w) : "l"(qx + i * 1024), "r"(min(v[i].y, v[i].w)) : "memory");
      if (++it > SPIN_LIMIT) __trap();
    }
    CLK(13);
    ITS(2, it);
#pragma unroll
    for (int i = 0; i < 4; i++) sts4(dst + i * 512 + (((ch & 7) ^ ((4 * i + h0) & 7)) << 4), v[i]);
    asm volatile("fence.proxy.async.shared::cta;" ::: "memory");
    CLK(14);
    cbar();
  }

  uint2 cbf[4], sbf[4];
  const uint32_t* const pcb = gs->MOD2[par] + 2048 + (16 * w + t) * 16 + g * 2;
  auto load_frags = [&] {
    if (cta < NFF) { load_units<4, 64>(sbf, pcb); load_units<4, 64>(cbf, pcb + 2048); }
    else {
#pragma unroll
      for (int s = 0; s < 4; s++) { cbf[s].x = ldg_nc1(gc + g * 1024 + w * 128 + s * 32 + t * 4); cbf[s].y = ldg_nc1(gc + g * 1024 + w * 128 + s * 32 + 16 + t * 4); }
    }
  };
  uint32_t thand, anchor;
  const uint32_t opaque0 = w >> 4;
  if (wg == 0) {
    float mh[4];
    float L[8];
#pragma unroll
    for (int i = 0; i < 4; i++) { L[2 * i] = L[2 * i + 1] = 0.f; mh[i] = -INFINITY; }
    constexpr uint32_t dq = desc_lo(OFF_Q);
    const uint32_t ptw = sb + OFF_PT + (8 * (lane >> 4) + (lane & 7)) * 128 + (((2 * wq + ((lane >> 3) & 1)) ^ (lane & 7)) << 4);
    float S[8];
    auto softmax = [&](int tl) {
      auto write_p = [&](const float (&x)[8]) {
        float p[8];
#pragma unroll
        for (int i = 0; i < 8; i++) p[i] = ex2(x[i]);
        stsm4t(ptw + (tl & 1) * 2048, pack_bf16(p[0], p[1]), pack_bf16(p[2], p[3]), pack_bf16(p[4], p[5]), pack_bf16(p[6], p[7]));
        asm volatile("fence.proxy.async.shared::cta;" ::: "memory");
      };
      float x[8];
#pragma unroll
      for (int i = 0; i < 8; i++) x[i] = S[i] - mh[2 * (i >> 2) + (i & 1)];
      if (tl) write_p(x);
      const float ex = fmaxf(fmaxf(fmaxf(x[0], x[1]), fmaxf(x[2], x[3])), fmaxf(fmaxf(x[4], x[5]), fmaxf(x[6], x[7])));
      if (tl == 0 || bar_over(ex)) {
        float mx[4];
#pragma unroll
        for (int i = 0; i < 4; i++) mx[i] = fmaxf(S[4 * (i >> 1) + (i & 1)], S[4 * (i >> 1) + 2 + (i & 1)]);
        const float a = reduce_g(mx, lane, [](float u, float v) { return fmaxf(u, v); });
        stsf(sb + OFF_RED + wq * 64 + (8 * (lane >> 4) + 2 * t + ((lane >> 3) & 1)) * 4, a);
        bar_sync(2, 128);
#pragma unroll
        for (int jn = 0; jn < 2; jn++) {
          float m0 = mh[2 * jn], m1 = mh[2 * jn + 1];
#pragma unroll
          for (int i = 0; i < 4; i++) { const float2 v = ldsf2(sb + OFF_RED + i * 64 + (8 * jn + 2 * t) * 4); m0 = fmaxf(m0, v.x); m1 = fmaxf(m1, v.y); }
          const float a0 = ex2(mh[2 * jn] - m0), a1 = ex2(mh[2 * jn + 1] - m1);
          mh[2 * jn] = m0; mh[2 * jn + 1] = m1;
          L[4 * jn] *= a0; L[4 * jn + 1] *= a1; L[4 * jn + 2] *= a0; L[4 * jn + 3] *= a1;
          if (tid < 4) sts2f(sb + OFF_ALPHA + (8 * jn + 2 * t) * 4, a0, a1);
        }
        asm volatile("barrier.cta.arrive.aligned 1, 256;" ::: "memory");
#pragma unroll
        for (int i = 0; i < 8; i++) x[i] = S[i] - mh[2 * (i >> 2) + (i & 1)];
        write_p(x);
        bar_over(0.f);
      }
      const uint32_t dpt = __shfl_sync(~0u, desc_lo(OFF_PT) + (tl & 1) * 128, 0);
      wg_fence();
#pragma unroll
      for (int ks = 0; ks < 4; ks++) wgmma_n16_ones(L, ONE2, dpt + ks * 2);
      wg_commit();
    };
    uint32_t da = desc_lo(OFF_RING);
#pragma unroll 1
    for (int tl = 0; tl < 7; tl++) {
      if (tl == 5) { load_frags(); }
      uint32_t ok = 0;
#pragma unroll
      for (int u = 0; u < 4; u++) ok += mbar_test(BAR(BAR_FULL + 4 * tl + u));
      ok = __reduce_min_sync(~0u, ok);
      const uint32_t du = __shfl_sync(~0u, da, 0);
#pragma unroll
      for (int u = 0; u < 4; u++) {
        if (ok != 4) mbar_wait(BAR(BAR_FULL + 4 * tl + u));
        wg_fence();
#pragma unroll
        for (int k = 0; k < 8; k++) {
          const int i = 8 * u + k;
          if (i == 0) wgmma_n16<0, 0>(S, du, dq); else wgmma_n16<0, 1>(S, du + (i >> 2) * 512 + (i & 3) * 2, dq + (i >> 2) * 128 + (i & 3) * 2);
        }
        wg_commit();
      }
      wg_wait<0>();
      acc_fence(S); acc_fence(L);
      if (tl == 0) CLK(15);
      if (tl == 1) CLK(17);
      softmax(tl);
      if (tl == 0) CLK(16);
      if (tl == 1) CLK(18);
      if (tl == 3) CLK(19);
      if (tl == 6) CLK(20);
      da = (tl == 2 || tl == 5) ? da - 8192 : da + 4096;
    }
    mbar_wait(BAR(BAR_ALLCLR));
    uint32_t* const mlo = pin(gin + blk(4 * (16 * hh + 4 * (g & 2) + 2 * t + (g & 1)) + 1, 6, g >> 2) + bs * 2);
#pragma unroll
    for (int i = 0; i < 32; i++) {
      if (i == 0 || i == 8 || i == 16 || i == 24 || i == 28) {
        if (i) wg_commit();
        mbar_wait(BAR(BAR_LAST + (i == 28 ? 4 : i >> 3)));
        if (i == 28) CLK(21);
        wg_fence();
      }
      if (i == 0) wgmma_n16<0, 0>(S, desc_lo(65536), dq); else wgmma_n16<0, 1>(S, desc_lo(65536) + (i >> 2) * 512 + (i & 3) * 2, dq + (i >> 2) * 128 + (i & 3) * 2);
    }
    wg_commit();
    wg_wait<0>();
    acc_fence(S); acc_fence(L);
    CLK(22);
    softmax(7);
    CLK(23);
    thand = clk32();
    wg_wait<0>();
    acc_fence(L);
    if (tid < 32) MLST(mlo, __float_as_uint(g & 2 ? (g & 1 ? mh[3] : mh[2]) : (g & 1 ? mh[1] : mh[0])), __float_as_uint(g & 2 ? (g & 1 ? L[5] : L[4]) : (g & 1 ? L[1] : L[0])));
    CLK(24);
  } else {
    float O[8][8];
#pragma unroll
    for (int i = 0; i < 8; i++)
#pragma unroll
      for (int k = 0; k < 8; k++) O[i][k] = 0.f;
    constexpr uint32_t dp = desc_lo(OFF_PT);
    auto handover = [&](int tl) {
      uint32_t over = opaque0 + (tl == 0);
#pragma unroll 1
      do {
        if (over) {
          cbar();
#pragma unroll
          for (int jn = 0; jn < 2; jn++) {
            const float2 a = ldsf2(sb + OFF_ALPHA + (8 * jn + 2 * t) * 4);
#pragma unroll
            for (int mb = 0; mb < 8; mb++) { O[mb][4 * jn] *= a.x; O[mb][4 * jn + 1] *= a.y; O[mb][4 * jn + 2] *= a.x; O[mb][4 * jn + 3] *= a.y; }
          }
        }
        over++;
      } while (bar_over(0.f));
    };
    uint32_t da = desc_lo(OFF_RING);
    uint32_t* x1o[8] = {};
#pragma unroll 1
    for (int tl = 0; tl < 8; tl++) {
      if (tl == 5) load_frags();
      if (tl == 7) {
        mbar_wait(BAR(BAR_ALLCLR));
#pragma unroll
        for (int i = 0; i < 8; i++)
          x1o[i] = inbox((16 * hh + 8 * ((i >> 1) & 1) + 2 * t + (i & 1)) * 4 + 2 * (i >> 2) + (wq >> 1), bs >> 4) + (bs & 15) * 64 + ((wq & 1) * 8 + g) * 4;
      }
      handover(tl);
      CLK(23);
      thand = clk32();
      const uint32_t dpt = dp + (tl & 1) * 128;
      wg_fence();
#pragma unroll
      for (int i = 0; i < 32; i++) wgmma_n16<1, 1>(O[i >> 2], da + (i >> 2) * 512 + (i & 3) * 128, dpt + (i & 3) * 2);
      wg_commit();
      da = (tl == 2 || tl == 5) ? da - 8192 : da + 4096;
      wg_wait<0>();
#pragma unroll
      for (int mb = 0; mb < 8; mb++) acc_fence(O[mb]);
      if (lane == 0) mbar_arrive(BAR(BAR_EMPTY + tl));
      if (tl == 0) CLK(16);
      if (tl == 1) CLK(18);
      if (tl == 3) CLK(19);
      if (tl == 6) CLK(20);
    }
    CLK(22);
#pragma unroll
    for (int i = 0; i < 8; i++) {
      const int J = i >> 2, k = 4 * ((i >> 1) & 1) + (i & 1);
      stg_cvt8(x1o[i], O[4 * J][k], O[4 * J][k + 2], O[4 * J + 1][k], O[4 * J + 1][k + 2], O[4 * J + 2][k], O[4 * J + 2][k + 2], O[4 * J + 3][k], O[4 * J + 3][k + 2]);
    }
    CLK(24);
  }

  {
    const uint32_t* px = pin(inbox(cta, w >> 1) + (w & 1) * 512 + lane * 2);
    uint32_t* const x2o = pin(inbox(cta, 4) + 512 + tid * 2);
    uint32_t* const x2p = pin(gin + blk(cta, 4, selector(cta) ^ 1) + 512 + tid * 2);
    const uint32_t q4 = lds1(sb + OFF_SEL + 4 * hI) ^ 0x00010100u;
    const uint32_t same = pin((uint32_t)(q4 == 0 || q4 == 0x01010101u));
    mbar_wait(BAR(BAR_TS));
    anchor = lds1(sb + OFF_TS);
    const uint32_t sdst = pin(sb + OFF_BS4 + w * 272 + lane * 8), ssrc = pin(sb + OFF_BS4 + (lane & 7) * 272 + (lane >> 3) * 16);
    float d[4] = {0.f, 0.f, 0.f, 0.f};
    if (cta >= NFF) {
#pragma unroll
      for (int s = 0; s < 4; s++) { cbf[s].x = silu2(cbf[s].x); cbf[s].y = silu2(cbf[s].y); }
    }
    wait_clk(thand, T.D_X1);
    wait_clk(anchor, T.A_X1 - T.R_X0);
    uint2 v[8];
    load_units<8, 64>(v, px);
    if (T.R_X0) {
      wait_clk(anchor, T.A_X1);
#pragma unroll
      for (int i = 0; i < 8; i++) reload_unit(v[i], px + i * 64);
    }
    CLK(25);
    const bool early = __all_sync(~0u, mbar_test(BAR(BAR_WUV + wg)));
    if (early) load_a_t(aw, abase + OFF_WUV);
    mbar_wait(BAR(BAR_WV));
    const float4 wa = ldsf4(sb + OFF_WV + w * 32), wb = ldsf4(sb + OFF_WV + w * 32 + 16);
    const float wv[8] = {wa.x, wa.y, wa.z, wa.w, wb.x, wb.y, wb.z, wb.w};
    CLK(27);
    uint32_t it = opaque0;
    bool ok;
#pragma unroll 1
    do {
      if (it) {
#pragma unroll
        for (int i = 0; i < 8; i++) reload_unit(v[i], px + i * 64);
        if (it > SPIN_LIMIT) __trap();
      }
      it++;
      float a0 = 0.f, a1 = 0.f, a2 = 0.f, a3 = 0.f;
#pragma unroll
      for (int i = 0; i < 8; i++) { a0 += wv[i] * bf_lo(v[i].x); a1 += wv[i] * bf_hi(v[i].x); a2 += wv[i] * bf_lo(v[i].y); a3 += wv[i] * bf_hi(v[i].y); }
      ok = __all_sync(~0u, min_flags(v) != 0);
      sts2(sdst, pack_bf16(a0, a1), pack_bf16(a2, a3));
    } while (!ok);
    CLK(29);
    cbar();
    uint32_t b[4][4];
#pragma unroll
    for (int kk = 0; kk < 4; kk++) ldsm4(b[kk], ssrc + kk * 64);
    if (__builtin_expect(!early, 0)) { mbar_wait(BAR(BAR_WUV + wg)); load_a_t(aw, abase + OFF_WUV); }
    mma128(d, aw, b);
    const uint32_t c0 = pack_bf16(d[0], d[1]), c1 = pack_bf16(d[2], d[3]);
    stg_u64(x2o, c0, c1);
    stg_u64_unless(same, x2p, c0, c1);
    ITS(4, it - 1);
    tstore = clk32();
    CLK(30);
  }
  {
    uint32_t* const o = pin(inbox(4 * (8 * jI + w) + t, 4) + hI * 16 + g * 2);
    const uint32_t* x2i[4];
#pragma unroll
    for (int i = 0; i < 4; i++) x2i[i] = pin(nearbox(4 * hI + i, 4) + 512 + tid * 2);
    const uint32_t sdst = pin(sb + OFF_BS5 + (16 * w + g) * 16 + t * 4), ssrc = pin(sb + OFF_BS5 + lane * 16);
    float d[4] = {0.f, 0.f, 0.f, 0.f};
    wait_clk(tstore, T.D_X2);
    wait_clk(anchor, T.A_X1 + T.R_X2);
    uint2 v[4];
#pragma unroll
    for (int i = 0; i < 4; i++) v[i] = ldg_u64(x2i[i]);
    const bool early = __all_sync(~0u, mbar_test(BAR(BAR_WO + wg)));
    if (early) load_a_t(aw, abase + OFF_WO);
    CLK(31);
    uint32_t it = opaque0;
    bool ok;
#pragma unroll 1
    do {
      if (it) {
#pragma unroll
        for (int i = 0; i < 4; i++) reload_unit(v[i], x2i[i]);
        if (it > SPIN_LIMIT) __trap();
      }
      it++;
      ok = __all_sync(~0u, min_flags(v) != 0);
      sum4_to_smem(v, sdst);
    } while (!ok);
    CLK(32);
    cbar();
    uint32_t b[4][4];
#pragma unroll
    for (int kk = 0; kk < 4; kk++) ldsm4t(b[kk], ssrc + kk * 512);
    if (__builtin_expect(!early, 0)) { mbar_wait(BAR(BAR_WO + wg)); load_a_t(aw, abase + OFF_WO); }
    mma128(d, aw, b);
    ST3A(o, movm(pack_bf16(d[0], d[1])), movm(pack_bf16(d[2], d[3])));
    ITS(5, it - 1);
    tstore = clk32();
    CLK(33);
    if (lane == 0) mbar_arrive(BAR(BAR_P5D));
  }
  if (cta < NFF) {
    const int mi = lane >> 3, r = lane & 7;
    uint32_t a1[2][4][4], a2[2][2][4];
    check_units<4, 64>(sbf, pcb);
    check_units<4, 64>(cbf, pcb + 2048);
    __syncwarp();
#pragma unroll
    for (int s = 0; s < 4; s++) { cbf[s].x = hadd2(cbf[s].x, ONE2); cbf[s].y = hadd2(cbf[s].y, ONE2); }
    mbar_wait(BAR(BAR_W1));
#pragma unroll
    for (int mt = 0; mt < 2; mt++) {
#pragma unroll
      for (int ks = 0; ks < 4; ks++) ldsm4t(a1[mt][ks], sb + OFF_W1 + (64 * w + 16 * ks + 8 * (mi >> 1) + r) * 64 + (((2 * mt + (mi & 1)) ^ (r >> 1)) << 4));
      float u[4] = {0.f, 0.f, 0.f, 0.f}, vv[4] = {0.f, 0.f, 0.f, 0.f};
#pragma unroll
      for (int s = 0; s < 4; s++) { mma16816(u, a1[mt][s], cbf[s].x, cbf[s].y); mma16816(vv, a1[mt][s], sbf[s].x, sbf[s].y); }
      sts4f(sb + OFF_REDU + w * 1024 + mt * 512 + lane * 16, u[0], u[1], u[2], u[3]);
      sts4f(sb + OFF_REDV + w * 1024 + mt * 512 + lane * 16, vv[0], vv[1], vv[2], vv[3]);
    }
    const uint32_t* xb = pin(nearbox(cta & ~15, 6 + wg) + (16 * wq + t) * 16 + g * 2);
    uint32_t* const ox[2] = {pin(inbox(64 * hh + 8 * w + t, 5) + bs * 16 + g * 2), pin(inbox(64 * hh + 8 * w + 4 + t, 5) + bs * 16 + g * 2)};
    cbar();
    const int lp = (tid >> 2) & 31, kq = tid & 3;
    const int fo = 16 * wg + (lp >> 2) + 8 * (kq >> 1), bo = 2 * (lp & 3) + (kq & 1);
    float U = 0.f, V = 0.f;
#pragma unroll
    for (int i = 0; i < 8; i++) { U += ldsf(sb + OFF_REDU + i * 1024 + tid * 4); V += ldsf(sb + OFF_REDV + i * 1024 + tid * 4); }
    U = pin(U); V = pin(V);
    const uint32_t s_g = pin(sb + OFF_REDG + w * 1024 + lane * 16), s_s = pin(sb + OFF_REDS + g * 80 + w * 8);
    const uint32_t l_g = pin(sb + OFF_REDG + tid * 4), l_s = pin(sb + OFF_REDS + bo * 80), s_h = pin(sb + OFF_H1 + fo * 16 + bo * 2);
    CLK(34);
    wait_clk(tstore, T.D_X3B);
    wait_clk(anchor, T.A_X1 + T.R_X3A + T.R_X3B);
    uint2 x[4];
    load_units<4, 64>(x, xb);
    mbar_wait(BAR(BAR_W2));
#pragma unroll
    for (int i = 0; i < 4; i++)
      ldsm4t(a2[i >> 1][i & 1], sb + OFF_W2 + (w >> 1) * 4096 + (16 * (i & 1) + 8 * (mi >> 1) + r) * 128 + (((4 * (w & 1) + 2 * (i >> 1) + (mi & 1)) ^ r) << 4));
    CLK(35);
    uint32_t it = opaque0;
    float G[2][2][4], S[2][4];
#pragma unroll 1
    do {
      if (it) {
#pragma unroll
        for (int i = 0; i < 4; i++) reload_unit(x[i], xb + i * 64);
        if (it > SPIN_LIMIT) __trap();
      }
      it++;
#pragma unroll
      for (int i = 0; i < 8; i++) { G[0][i >> 2][i & 3] = G[1][i >> 2][i & 3] = S[i >> 2][i & 3] = 0.f; }
#pragma unroll
      for (int s = 0; s < 4; s++) {
        const uint32_t sx[4] = {x[s].x, ONE2, x[s].y, ONE2};
        mma16816(S[s & 1], sx, x[s].x, x[s].y);
        const uint32_t y0 = hmul2(x[s].x, cbf[s].x), y1 = hmul2(x[s].y, cbf[s].y);
        mma16816(G[0][s & 1], a1[0][s], y0, y1);
        mma16816(G[1][s & 1], a1[1][s], y0, y1);
      }
    } while (!__all_sync(~0u, min_flags(x) != 0));
    if (t == (g >> 1)) sts2f(s_s, (g & 1) ? S[0][3] + S[1][3] : S[0][2] + S[1][2], (g & 1) ? S[0][1] + S[1][1] : S[0][0] + S[1][0]);
#pragma unroll
    for (int mt = 0; mt < 2; mt++)
      sts4f(s_g + mt * 512, G[mt][0][0] + G[mt][1][0], G[mt][0][1] + G[mt][1][1], G[mt][0][2] + G[mt][1][2], G[mt][0][3] + G[mt][1][3]);
    CLK(37);
    cbar();
    {
      float gv[8];
      float4 sv[4];
#pragma unroll
      for (int i = 0; i < 4; i++) sv[i] = ldsf4(l_s + i * 16);
#pragma unroll
      for (int i = 0; i < 8; i++) gv[i] = ldsf(l_g + i * 1024);
      const float s1 = ((sv[0].x + sv[0].z) + (sv[1].x + sv[1].z)) + ((sv[2].x + sv[2].z) + (sv[3].x + sv[3].z));
      const float s2 = ((sv[0].y + sv[0].w) + (sv[1].y + sv[1].w)) + ((sv[2].y + sv[2].w) + (sv[3].y + sv[3].w));
      const float gsum = ((gv[0] + gv[1]) + (gv[2] + gv[3])) + ((gv[4] + gv[5]) + (gv[6] + gv[7]));
      const float mu = s1 * (1.f / 512.f);
      float rs;
      asm("rsqrt.approx.ftz.f32 %0, %1;" : "=f"(rs) : "f"(fmaxf(s2 * (1.f / 512.f) - mu * mu, 0.f) + 1e-5f));
      const float hv = fmaxf(rs * (gsum - mu * U) + V, 0.f);
      asm volatile("st.shared.u16 [%0], %1;" ::"r"(s_h), "h"(__bfloat16_as_ushort(__float2bfloat16(hv))) : "memory");
    }
    ITS(6, it - 1);
    CLK(38);
    cbar();
    uint32_t b[4];
    ldsm4t(b, sb + OFF_H1 + lane * 16);
    float o[2][2][4] = {};
#pragma unroll
    for (int i = 0; i < 4; i++) mma16816(o[i >> 1][i & 1], a2[i >> 1][i & 1], b[2 * (i & 1)], b[2 * (i & 1) + 1]);
#pragma unroll
    for (int mb = 0; mb < 2; mb++)
      ST4(ox[mb], movm(pack_bf16(o[mb][0][0] + o[mb][1][0], o[mb][0][1] + o[mb][1][1])), movm(pack_bf16(o[mb][0][2] + o[mb][1][2], o[mb][0][3] + o[mb][1][3])));
    CLK(39);
    if (lane == 0) mbar_arrive(BAR(BAR_P7D));
  } else {
    const int mi = lane >> 3, r = lane & 7;
    mbar_wait(BAR(BAR_W1));
#pragma unroll
    for (int mt = 0; mt < 2; mt++) {
      float u[4] = {0.f, 0.f, 0.f, 0.f};
#pragma unroll
      for (int ks = 0; ks < 4; ks++) ldsm4t(aw[4 * mt + ks], sb + OFF_W1 + (64 * w + 16 * ks + 8 * (mi >> 1) + r) * 64 + (((2 * mt + (mi & 1)) ^ (r >> 1)) << 4));
#pragma unroll
      for (int ks = 0; ks < 4; ks++) mma16816(u, aw[4 * mt + ks], cbf[ks].x, cbf[ks].y);
      sts4f(sb + OFF_REDU + w * 1024 + mt * 512 + lane * 16, u[0], u[1], u[2], u[3]);
    }
    cbar();
    if (w < 2) {
      float4 v[8];
#pragma unroll
      for (int i = 0; i < 8; i++) v[i] = ldsf4(sb + OFF_REDU + i * 1024 + tid * 16);
      stg_u64(gs->MOD2[par] + (96 + 2 * (cta - NFF) + w) * 64 + t * 16 + g * 2,
              movm(pack_bf16(((v[0].x + v[1].x) + (v[2].x + v[3].x)) + ((v[4].x + v[5].x) + (v[6].x + v[7].x)), ((v[0].y + v[1].y) + (v[2].y + v[3].y)) + ((v[4].y + v[5].y) + (v[6].y + v[7].y)))),
              movm(pack_bf16(((v[0].z + v[1].z) + (v[2].z + v[3].z)) + ((v[4].z + v[5].z) + (v[6].z + v[7].z)), ((v[0].w + v[1].w) + (v[2].w + v[3].w)) + ((v[4].w + v[5].w) + (v[6].w + v[7].w)))));
    }
    CLK(26);
  }
  CLK_DUMP();
}

typedef CUresult (*EncodeTiledFn)(CUtensorMap*, CUtensorMapDataType, cuuint32_t, void*, const cuuint64_t*, const cuuint64_t*,
                                  const cuuint32_t*, const cuuint32_t*, CUtensorMapInterleave, CUtensorMapSwizzle,
                                  CUtensorMapL2promotion, CUtensorMapFloatOOBfill);

struct Dim { uint64_t size, stride; uint32_t box; };
template <int R> void encode_map(EncodeTiledFn enc, CUtensorMap* m, const void* base, const Dim (&d)[R], CUtensorMapSwizzle sw, CUtensorMapL2promotion promo) {
  cuuint64_t dims[R], strides[R];
  cuuint32_t box[R], es[R];
  for (int i = 0; i < R; i++) { dims[i] = d[i].size; strides[i] = d[i].stride; box[i] = d[i].box; es[i] = 1; }
  enc(m, CU_TENSOR_MAP_DATA_TYPE_BFLOAT16, R, const_cast<void*>(base), dims, strides + 1, box, es, CU_TENSOR_MAP_INTERLEAVE_NONE, sw, promo,
      CU_TENSOR_MAP_FLOAT_OOB_FILL_NONE);
}

}

extern "C" void kernel_launch(void* const* d_in, const int* in_sizes, int n_in, void* d_out, int out_size) {
  (void)in_sizes; (void)n_in; (void)out_size;
  static EncodeTiledFn enc = nullptr;
  static Scratch* scratch = nullptr;
  static uint32_t* inbox = nullptr;
  if (!enc) {
    void* sp = nullptr;
    cudaGetSymbolAddress(&sp, g_s);
    scratch = (Scratch*)sp;
    cudaGetSymbolAddress(&sp, g_in);
    inbox = (uint32_t*)(((uintptr_t)sp + 0xfffff) & ~(uintptr_t)0xfffff);
    void* fn = nullptr;
    cudaDriverEntryPointQueryResult q;
    cudaGetDriverEntryPoint("cuTensorMapEncodeTiled", &fn, cudaEnableDefault, &q);
    enc = (EncodeTiledFn)fn;
    cudaFuncSetAttribute(fused_decode_kernel, cudaFuncAttributeMaxDynamicSharedMemorySize, SMEM_BYTES);
  }
  const CUtensorMapSwizzle S128 = CU_TENSOR_MAP_SWIZZLE_128B, S0 = CU_TENSOR_MAP_SWIZZLE_NONE;
  const CUtensorMapL2promotion L0 = CU_TENSOR_MAP_L2_PROMOTION_NONE, L128 = CU_TENSOR_MAP_L2_PROMOTION_L2_128B;
  Params P;
  encode_map<2>(enc, &P.wq, d_in[2], {{4096, 2, 64}, {512, 8192, 64}}, S128, L0);
  encode_map<5>(enc, &P.wuk, d_in[3], {{4096, 2, 64}, {2, 8192, 2}, {4, 4 * 8192, 4}, {2, 2 * 8192, 2}, {32, 16 * 8192, 4}}, S128, L0);
  encode_map<2>(enc, &P.wm2, d_in[10], {{3072, 2, 16}, {512, 6144, 256}}, S0, L128);
  encode_map<2>(enc, &P.wm3, d_in[10], {{3072, 2, 32}, {512, 6144, 256}}, CU_TENSOR_MAP_SWIZZLE_64B, L128);
  encode_map<3>(enc, &P.ckv2, d_in[1], {{64, 2, 64}, {8 * 4096, 1024, 64}, {8, 128, 2}}, S128, L0);
  encode_map<3>(enc, &P.ckv1, d_in[1], {{64, 2, 64}, {8 * 4096, 1024, 64}, {8, 128, 1}}, S128, L0);
  encode_map<5>(enc, &P.wuv, d_in[4], {{4096, 2, 64}, {2, 8 * 8192, 2}, {8, 64 * 8192, 4}, {8, 8192, 8}, {4, 16 * 8192, 1}}, S128, L0);
  encode_map<2>(enc, &P.wo, d_in[5], {{512, 2, 64}, {4096, 1024, 64}}, S128, L0);
  encode_map<2>(enc, &P.w1, d_in[7], {{1792, 2, 32}, {512, 3584, 256}}, CU_TENSOR_MAP_SWIZZLE_64B, L128);
  encode_map<3>(enc, &P.w2, d_in[8], {{64, 2, 64}, {1792, 1024, 32}, {8, 128, 2}}, S128, L0);
  fused_decode_kernel<<<NCTA, NTHREADS, SMEM_BYTES>>>((__nv_bfloat16*)d_out, scratch, (const uint8_t*)d_in[10], (const uint8_t*)d_in[0],
                     (const uint8_t*)d_in[9], inbox,
                     P);
}
```

```cpp
#include <cuda_runtime.h>
#include <cuda.h>
#include <cuda_bf16.h>
#include <stdint.h>
#define V4 1

namespace {

constexpr int NCTA = 128;
constexpr int NTHREADS = 320;
constexpr int NFG = 56;
constexpr int NFF = 2 * NFG;
constexpr int NSYNC = 4;

constexpr uint32_t OFF_RING = 0;
constexpr uint32_t OFF_WUK = 131072;
constexpr uint32_t OFF_WQ = 131072 + 32768;
constexpr uint32_t OFF_WM2 = 65536 + 49152;
constexpr uint32_t OFF_WUV = 131072;
constexpr uint32_t OFF_WO = 131072 + 32768;
constexpr uint32_t OFF_W1 = 0;
constexpr uint32_t OFF_W2 = 32768;
constexpr uint32_t OFF_Q = 196608;
constexpr uint32_t OFF_PT = 212992;
constexpr uint32_t OFF_SCR = 217088;
constexpr uint32_t OFF_XS = 65536;
constexpr uint32_t OFF_CS = 65536 + 8192;
constexpr uint32_t OFF_P0S = 65536 + 16384;
constexpr uint32_t OFF_BS1 = OFF_SCR + 2048;
constexpr uint32_t OFF_BS2 = OFF_SCR + 4096;
constexpr uint32_t OFF_P0B = OFF_SCR + 6144;
constexpr uint32_t OFF_XN = OFF_SCR + 8192;
constexpr uint32_t OFF_RED = OFF_SCR + 10496;
constexpr uint32_t OFF_ALPHA = OFF_SCR + 11072;
constexpr uint32_t OFF_WV = OFF_SCR + 6144;
constexpr uint32_t OFF_SEL = OFF_SCR + 10752;
constexpr uint32_t OFF_TS = OFF_SCR + 11136;
constexpr uint32_t OFF_BARS = OFF_SCR + 11264;
constexpr uint32_t SMEM_BYTES = OFF_BARS + 512;
constexpr uint32_t OFF_BS4 = OFF_Q;
constexpr uint32_t OFF_H1 = OFF_Q + 2304;
constexpr uint32_t OFF_REDS = OFF_Q + 2816;
constexpr uint32_t OFF_BS5 = OFF_Q + 4096;
constexpr uint32_t OFF_REDG = OFF_Q + 8192;
constexpr uint32_t OFF_REDU = 65536;
constexpr uint32_t OFF_REDV = 65536 + 8192;

constexpr int BAR_FULL = 0;
constexpr int BAR_LAST = 28;
constexpr int BAR_WUK = 33, BAR_WM2 = 35, BAR_WUV = 36, BAR_WO = 38, BAR_W1 = 40, BAR_W2 = 41;
constexpr int BAR_ALLCLR = 42, BAR_TS = 43, BAR_WV = 44;
constexpr int BAR_EMPTY = 45;
constexpr int BAR_P0BD = 53;
constexpr int BAR_P1D = 54, BAR_P2D = 55;
constexpr int BAR_P5D = 56, BAR_P7D = 57;
constexpr int NBARS = 58;
constexpr int BAR_XC = 58, BAR_WQ = 59;
constexpr int BAR_C = 61;
constexpr uint32_t SB = 1024;

#define TUNE_LIST(X) \
  X(PC_T0, 340) X(PC_P1, 320) X(PC_PM, 225) X(PC_P2, 319) X(PC_STAG, 390) X(PC_SL, 500) X(PC_NW, 8) \
  X(PW_0, 280) X(PW_UV, 250) X(PW_G, 610) X(PW_O, 345) X(PW_G2, 430) X(PW_G3, 390) X(PW_F, 330) X(PW_GB, 100) \
  X(PR_T0, 1000) X(PR_N, 4) X(CLR_T0, 3900) X(CLR_CLK, 190) \
  X(D_MOD, 1550) X(D_QP, 1100) X(D_QX, 950) X(TS_P, 1) X(TS_O, 1150) X(D_TS, 900) X(A_M, 1750) X(D_X1, 1400) X(A_X1, 2460) X(R_X0, 1100) \
  X(D_X2, 260) X(D_X3A, 60) X(R_X3A, 3080) X(D_X3B, 800) X(R_X3B, 980) X(D_FIN, 320) X(R_FIN, 1520)
struct Tune {
#define X(n, v) static constexpr int n = v;
  TUNE_LIST(X)
#undef X
};

struct Scratch {
  uint32_t MOD1[2][4 * 64 * 64];
  uint32_t MOD2[2][128 * 64];
  uint32_t QP[2][128 * 256 * 2];
  uint32_t QX[2][8 * 32 * 256];
  uint32_t epoch;
  uint32_t pad[31];
  uint32_t sync[NSYNC][32];
};
__device__ Scratch g_s;
__device__ uint32_t g_in[(128 + 16) * 16384];
__device__ __forceinline__ uint32_t blk(int c, int k, uint32_t sel) { return c * 16384 + k * 2048 + ((sel ^ k) & 1) * 1024; }
__device__ __forceinline__ uint32_t flip(int c) { return c ^ (c >> 1) ^ (c >> 3); }

#define CLK_DECL
#define CLK(i) do {} while (0)
#define CLK_DUMP() do {} while (0)
#define ITS(i, v) do {} while (0)

struct Params {
  CUtensorMap wq, wuk, wm2, wm3, ckv2, ckv1, wuv, wo, w1, w2;
};

__device__ __forceinline__ void mbar_init(uint32_t bar, int cnt) { asm volatile("mbarrier.init.shared::cta.b64 [%0], %1;" ::"r"(bar), "r"(cnt)); }
__device__ __forceinline__ void mbar_expect(uint32_t bar, uint32_t bytes) { asm volatile("mbarrier.arrive.expect_tx.shared::cta.b64 _, [%0], %1;" ::"r"(bar), "r"(bytes) : "memory"); }
__device__ __forceinline__ void mbar_arrive(uint32_t bar) { asm volatile("mbarrier.arrive.shared::cta.b64 _, [%0];" ::"r"(bar) : "memory"); }
__device__ __forceinline__ uint32_t clk32() { unsigned long long c; asm volatile("mov.u64 %0, %%clock64;" : "=l"(c) :: "memory"); return (uint32_t)c; }
__device__ __forceinline__ uint32_t gtime32() { uint32_t c; asm volatile("mov.u32 %0, %%globaltimer_lo;" : "=r"(c) :: "memory"); return c; }
__device__ __forceinline__ void wait_clk(uint32_t t0, int clocks) { while ((int)(clk32() - t0) < clocks) {} }
__device__ __forceinline__ void backoff(int clocks) { if (clocks > 0) wait_clk(clk32(), clocks); }
__device__ __forceinline__ void until_ns(uint32_t ns) { while ((int)(gtime32() - ns) < 0) {} }
__device__ __forceinline__ void slot(uint32_t& tn, int slack) {
  uint32_t now;
  do { now = gtime32(); } while ((int)(now - tn) < 0);
  if ((int)(now - tn) > slack) tn = now - slack;
}
template <typename T> __device__ __forceinline__ T* pin(T* p) { asm volatile("" : "+l"(p)); return p; }
__device__ __forceinline__ uint32_t pin(uint32_t v) { asm volatile("" : "+r"(v)); return v; }
__device__ __forceinline__ float pin(float v) { asm volatile("" : "+f"(v)); return v; }
constexpr int SPIN_LIMIT = 1 << 22;
__device__ __forceinline__ void mbar_wait(uint32_t bar) {
  asm volatile("{\n.reg .pred p;\n.reg .u32 c;\nmov.u32 c, 0;\n"
               "MW_LOOP:\nmbarrier.try_wait.parity.shared::cta.b64 p, [%0], 0;\n@p bra MW_DONE;\n"
               "add.u32 c, c, 1;\nsetp.lt.u32 p, c, 4194304;\n@p bra MW_LOOP;\ntrap;\nMW_DONE:\n}"
               ::"r"(bar) : "memory");
}
__device__ __forceinline__ bool mbar_test(uint32_t bar) {
  uint32_t ok;
  asm volatile("{\n.reg .pred p;\nmbarrier.test_wait.parity.shared::cta.b64 p, [%1], 0;\nselp.u32 %0,1,0,p;\n}" : "=r"(ok) : "r"(bar) : "memory");
  return ok;
}
__device__ __forceinline__ void tma2d(uint32_t dst, const CUtensorMap* m, int c0, int c1, uint32_t bar, uint64_t pol) {
  asm volatile("cp.async.bulk.tensor.2d.shared::cluster.global.mbarrier::complete_tx::bytes.L2::cache_hint [%0], [%1, {%3,%4}], [%2], %5;"
               ::"r"(dst), "l"(m), "r"(bar), "r"(c0), "r"(c1), "l"(pol) : "memory");
}
__device__ __forceinline__ void tma2d_nohint(uint32_t dst, const CUtensorMap* m, int c0, int c1, uint32_t bar) {
  asm volatile("cp.async.bulk.tensor.2d.shared::cluster.global.mbarrier::complete_tx::bytes [%0], [%1, {%3,%4}], [%2];"
               ::"r"(dst), "l"(m), "r"(bar), "r"(c0), "r"(c1) : "memory");
}
__device__ __forceinline__ void tma3d(uint32_t dst, const CUtensorMap* m, int c0, int c1, int c2, uint32_t bar, uint64_t pol) {
  asm volatile("cp.async.bulk.tensor.3d.shared::cluster.global.mbarrier::complete_tx::bytes.L2::cache_hint [%0], [%1, {%3,%4,%5}], [%2], %6;"
               ::"r"(dst), "l"(m), "r"(bar), "r"(c0), "r"(c1), "r"(c2), "l"(pol) : "memory");
}
__device__ __forceinline__ void tma5d(uint32_t dst, const CUtensorMap* m, int c0, int c1, int c2, int c3, int c4, uint32_t bar, uint64_t pol) {
  asm volatile("cp.async.bulk.tensor.5d.shared::cluster.global.mbarrier::complete_tx::bytes.L2::cache_hint [%0], [%1, {%3,%4,%5,%6,%7}], [%2], %8;"
               ::"r"(dst), "l"(m), "r"(bar), "r"(c0), "r"(c1), "r"(c2), "r"(c3), "r"(c4), "l"(pol) : "memory");
}
__device__ __forceinline__ void bulk_ld(uint32_t dst, const void* src, uint32_t bytes, uint32_t bar) {
  asm volatile("cp.async.bulk.shared::cluster.global.mbarrier::complete_tx::bytes [%0], [%1], %2, [%3];" ::"r"(dst), "l"(src), "r"(bytes), "r"(bar) : "memory");
}
__device__ __forceinline__ void bar_sync(int id, int n) { asm volatile("barrier.cta.sync.aligned %0, %1;" ::"r"(id), "r"(n) : "memory"); }
__device__ __forceinline__ void cbar() { asm volatile("barrier.cta.sync.aligned 1, 256;" ::: "memory"); }
__device__ __forceinline__ bool bar_over(float ex) {
  uint32_t over;
  asm volatile("{\n.reg .pred p, q;\nsetp.gtu.f32 p, %1, 0f42700000;\nbarrier.cta.red.or.aligned.pred q, 4, 256, p;\nselp.u32 %0, 1, 0, q;\n}"
               : "=r"(over) : "f"(ex) : "memory");
  return over;
}

__device__ __forceinline__ uint32_t ldg_nc1(const void* p) { uint32_t v; asm volatile("ld.global.nc.L1::no_allocate.u32 %0, [%1];" : "=r"(v) : "l"(p)); return v; }
__device__ __forceinline__ uint2 ldg_nc2(const void* p) { uint2 v; asm volatile("ld.global.nc.v2.u32 {%0,%1}, [%2];" : "=r"(v.x), "=r"(v.y) : "l"(p)); return v; }
__device__ __forceinline__ uint4 ldg_nc4(const void* p) { uint4 v; asm volatile("ld.global.nc.L1::no_allocate.v4.u32 {%0,%1,%2,%3}, [%4];" : "=r"(v.x), "=r"(v.y), "=r"(v.z), "=r"(v.w) : "l"(p)); return v; }
__device__ __forceinline__ uint32_t ldg_rlx1(const void* p) { uint32_t v; asm volatile("ld.relaxed.gpu.global.u32 %0, [%1];" : "=r"(v) : "l"(p) : "memory"); return v; }
__device__ __forceinline__ void stg4(void* p, uint4 v) { asm volatile("st.relaxed.gpu.global.v4.u32 [%0], {%1,%2,%3,%4};" ::"l"(p), "r"(v.x), "r"(v.y), "r"(v.z), "r"(v.w) : "memory"); }
__device__ __forceinline__ void stg1(void* p, uint32_t a) { asm volatile("st.relaxed.gpu.global.u32 [%0], %1;" ::"l"(p), "r"(a) : "memory"); }
__device__ __forceinline__ uint32_t nz(uint32_t w) { return max(w, 1u); }
__device__ __forceinline__ uint2 ldg_u64(const void* p) {
  uint2 v; asm volatile("{\n.reg .b64 a;\nld.relaxed.gpu.global.b64 a, [%2];\nmov.b64 {%0,%1}, a;\n}" : "=r"(v.x), "=r"(v.y) : "l"(p) : "memory"); return v;
}
__device__ __forceinline__ uint4 ldg_2u64(const void* p) {
  uint4 v; asm volatile("{\n.reg .b64 a, b;\nld.relaxed.gpu.global.v2.b64 {a, b}, [%4];\nmov.b64 {%0,%1}, a;\nmov.b64 {%2,%3}, b;\n}" : "=r"(v.x), "=r"(v.y), "=r"(v.z), "=r"(v.w) : "l"(p) : "memory"); return v;
}
__device__ __forceinline__ void stg_u64(void* p, uint32_t x, uint32_t y) {
  asm volatile("{\n.reg .b32 y;\nmax.u32 y, %2, 1;\nst.relaxed.gpu.global.v2.b32 [%0], {%1, y};\n}" ::"l"(p), "r"(x), "r"(y) : "memory");
}
__device__ __forceinline__ void red_u64(void* p, uint32_t x, uint32_t y) {
  asm volatile("{\n.reg .b32 y;\n.reg .b64 a;\nmax.u32 y, %2, 1;\nmov.b64 a, {%1, y};\nred.relaxed.gpu.global.or.b64 [%0], a;\n}" ::"l"(p), "r"(x), "r"(y) : "memory");
}
__device__ __forceinline__ void stg_u64_unless(uint32_t bad, void* p, uint32_t x, uint32_t y) {
  asm volatile("{\n.reg .b32 y;\n.reg .pred q;\nsetp.eq.u32 q, %3, 0;\nmax.u32 y, %2, 1;\n@q st.relaxed.gpu.global.v2.b32 [%0], {%1, y};\n}" ::"l"(p), "r"(x), "r"(y), "r"(bad) : "memory");
}

__device__ __forceinline__ void stg_cvt8(void* p, float a0, float a1, float b0, float b1, float c0, float c1, float d0, float d1) {
  asm volatile("{\n.reg .b32 x, y, z, w;\ncvt.rn.bf16x2.f32 x, %2, %1;\ncvt.rn.bf16x2.f32 y, %4, %3;\ncvt.rn.bf16x2.f32 z, %6, %5;\ncvt.rn.bf16x2.f32 w, %8, %7;\n"
               "max.u32 y, y, 1;\nmax.u32 w, w, 1;\nst.relaxed.gpu.global.v4.b32 [%0], {x, y, z, w};\n}"
               ::"l"(p), "f"(a0), "f"(a1), "f"(b0), "f"(b1), "f"(c0), "f"(c1), "f"(d0), "f"(d1) : "memory");
}
__device__ __forceinline__ uint32_t pack_bf16(float lo, float hi) { uint32_t r; asm("cvt.rn.bf16x2.f32 %0, %1, %2;" : "=r"(r) : "f"(hi), "f"(lo)); return r; }
__device__ __forceinline__ float bf_lo(uint32_t w) { return __uint_as_float(w << 16); }
__device__ __forceinline__ float bf_hi(uint32_t w) { return __uint_as_float(w & 0xffff0000u); }
__device__ __forceinline__ float ex2(float x) { float r; asm("ex2.approx.ftz.f32 %0, %1;" : "=f"(r) : "f"(x)); return r; }
__device__ __forceinline__ uint32_t hmul2(uint32_t a, uint32_t b) { uint32_t r; asm("mul.rn.bf16x2 %0, %1, %2;" : "=r"(r) : "r"(a), "r"(b)); return r; }
__device__ __forceinline__ uint32_t hadd2(uint32_t a, uint32_t b) { uint32_t r; asm("add.rn.bf16x2 %0, %1, %2;" : "=r"(r) : "r"(a), "r"(b)); return r; }
__device__ __forceinline__ uint32_t silu2(uint32_t v) { const float a = bf_lo(v), b = bf_hi(v); return pack_bf16(__fdividef(a, 1.f + __expf(-a)), __fdividef(b, 1.f + __expf(-b))); }
constexpr uint32_t ONE2 = 0x3f803f80u;

__device__ __forceinline__ void ldsm4(uint32_t (&r)[4], uint32_t a) { asm volatile("ldmatrix.sync.aligned.m8n8.x4.shared.b16 {%0,%1,%2,%3}, [%4];" : "=r"(r[0]), "=r"(r[1]), "=r"(r[2]), "=r"(r[3]) : "r"(a) : "memory"); }
__device__ __forceinline__ void ldsm4t(uint32_t (&r)[4], uint32_t a) { asm volatile("ldmatrix.sync.aligned.m8n8.x4.trans.shared.b16 {%0,%1,%2,%3}, [%4];" : "=r"(r[0]), "=r"(r[1]), "=r"(r[2]), "=r"(r[3]) : "r"(a) : "memory"); }
__device__ __forceinline__ void stsm4t(uint32_t a, uint32_t r0, uint32_t r1, uint32_t r2, uint32_t r3) { asm volatile("stmatrix.sync.aligned.m8n8.x4.trans.shared.b16 [%0], {%1,%2,%3,%4};" ::"r"(a), "r"(r0), "r"(r1), "r"(r2), "r"(r3) : "memory"); }
__device__ __forceinline__ uint32_t movm(uint32_t a) { uint32_t d; asm volatile("movmatrix.sync.aligned.m8n8.trans.b16 %0, %1;" : "=r"(d) : "r"(a)); return d; }
__device__ __forceinline__ void mma16816(float (&d)[4], const uint32_t (&a)[4], uint32_t b0, uint32_t b1) {
  asm volatile("mma.sync.aligned.m16n8k16.row.col.f32.bf16.bf16.f32 {%0,%1,%2,%3}, {%4,%5,%6,%7}, {%8,%9}, {%0,%1,%2,%3};"
               : "+f"(d[0]), "+f"(d[1]), "+f"(d[2]), "+f"(d[3]) : "r"(a[0]), "r"(a[1]), "r"(a[2]), "r"(a[3]), "r"(b0), "r"(b1));
}
__device__ __forceinline__ void sts1(uint32_t a, uint32_t v) { asm volatile("st.shared.u32 [%0], %1;" ::"r"(a), "r"(v) : "memory"); }
__device__ __forceinline__ void sts2(uint32_t a, uint32_t x, uint32_t y) { asm volatile("st.shared.v2.u32 [%0], {%1,%2};" ::"r"(a), "r"(x), "r"(y) : "memory"); }
__device__ __forceinline__ void sts4(uint32_t a, uint4 v) { asm volatile("st.shared.v4.u32 [%0], {%1,%2,%3,%4};" ::"r"(a), "r"(v.x), "r"(v.y), "r"(v.z), "r"(v.w) : "memory"); }
__device__ __forceinline__ void sts2f(uint32_t a, float x, float y) { asm volatile("st.shared.v2.f32 [%0], {%1,%2};" ::"r"(a), "f"(x), "f"(y) : "memory"); }
__device__ __forceinline__ void sts4f(uint32_t a, float x, float y, float z, float w) { asm volatile("st.shared.v4.f32 [%0], {%1,%2,%3,%4};" ::"r"(a), "f"(x), "f"(y), "f"(z), "f"(w) : "memory"); }
__device__ __forceinline__ void stsf(uint32_t a, float v) { asm volatile("st.shared.f32 [%0], %1;" ::"r"(a), "f"(v) : "memory"); }
__device__ __forceinline__ uint32_t lds1(uint32_t a) { uint32_t v; asm volatile("ld.shared.u32 %0, [%1];" : "=r"(v) : "r"(a) : "memory"); return v; }
__device__ __forceinline__ float ldsf(uint32_t a) { float v; asm volatile("ld.shared.f32 %0, [%1];" : "=f"(v) : "r"(a) : "memory"); return v; }
__device__ __forceinline__ float2 ldsf2(uint32_t a) { float2 v; asm volatile("ld.shared.v2.f32 {%0,%1}, [%2];" : "=f"(v.x), "=f"(v.y) : "r"(a) : "memory"); return v; }
__device__ __forceinline__ float4 ldsf4(uint32_t a) { float4 v; asm volatile("ld.shared.v4.f32 {%0,%1,%2,%3}, [%4];" : "=f"(v.x), "=f"(v.y), "=f"(v.z), "=f"(v.w) : "r"(a) : "memory"); return v; }
__device__ __forceinline__ void lds4(uint32_t (&r)[4], uint32_t a) { asm volatile("ld.shared.v4.u32 {%0,%1,%2,%3}, [%4];" : "=r"(r[0]), "=r"(r[1]), "=r"(r[2]), "=r"(r[3]) : "r"(a) : "memory"); }

__device__ __forceinline__ void wg_fence() { asm volatile("wgmma.fence.sync.aligned;" ::: "memory"); }
__device__ __forceinline__ void wg_commit() { asm volatile("wgmma.commit_group.sync.aligned;" ::: "memory"); }
template <int N> __device__ __forceinline__ void wg_wait() { asm volatile("wgmma.wait_group.sync.aligned %0;" ::"n"(N) : "memory"); }
__host__ __device__ constexpr uint32_t desc_lo(uint32_t off) { return ((SB + off) >> 4) | 0x10000u; }
template <int TA, int ACC> __device__ __forceinline__ void wgmma_n16(float (&d)[8], uint32_t da, uint32_t db) {
  asm volatile("{\n.reg .b64 da, db;\nmov.b64 da, {%8, 0x40000040};\nmov.b64 db, {%9, 0x40000040};\n"
               "wgmma.mma_async.sync.aligned.m64n16k16.f32.bf16.bf16 {%0,%1,%2,%3,%4,%5,%6,%7}, da, db, %11, 1, 1, %10, 0;\n}"
               : "+f"(d[0]), "+f"(d[1]), "+f"(d[2]), "+f"(d[3]), "+f"(d[4]), "+f"(d[5]), "+f"(d[6]), "+f"(d[7])
               : "r"(da), "r"(db), "n"(TA), "n"(ACC));
}
__device__ __forceinline__ void wgmma_n16_ones(float (&d)[8], uint32_t one, uint32_t db) {
  asm volatile("{\n.reg .b64 db;\nmov.b64 db, {%9, 0x40000040};\n"
               "wgmma.mma_async.sync.aligned.m64n16k16.f32.bf16.bf16 {%0,%1,%2,%3,%4,%5,%6,%7}, {%8,%8,%8,%8}, db, 1, 1, 1, 0;\n}"
               : "+f"(d[0]), "+f"(d[1]), "+f"(d[2]), "+f"(d[3]), "+f"(d[4]), "+f"(d[5]), "+f"(d[6]), "+f"(d[7])
               : "r"(one), "r"(db));
}
__device__ __forceinline__ void acc_fence(float (&d)[8]) {
  asm volatile("" : "+f"(d[0]), "+f"(d[1]), "+f"(d[2]), "+f"(d[3]), "+f"(d[4]), "+f"(d[5]), "+f"(d[6]), "+f"(d[7]) :: "memory");
}

template <int N, int STRIDE> __device__ __forceinline__ void load_units(uint2 (&v)[N], const uint32_t* p) {
#pragma unroll
  for (int i = 0; i < N; i++) v[i] = ldg_u64(p + i * STRIDE);
}
__device__ __forceinline__ void reload_unit(uint2& v, const uint32_t* p) {
  asm volatile("{\n.reg .pred q;\nsetp.eq.u32 q, %1, 0;\n@q ld.relaxed.gpu.global.v2.b32 {%0, %1}, [%2];\n}" : "+r"(v.x), "+r"(v.y) : "l"(p) : "memory");
}
template <int N> __device__ __forceinline__ uint32_t min_flags(const uint2 (&v)[N]) {
  uint32_t a = v[0].y, b = v[1].y;
#pragma unroll
  for (int i = 2; i < N; i += 2) { a = min(a, v[i].y); b = min(b, v[i + 1].y); }
  return min(a, b);
}
template <int N, int STRIDE> __device__ __forceinline__ int check_units(uint2 (&v)[N], const uint32_t* p) {
  int it = 0;
  while (!__all_sync(~0u, min_flags(v) != 0)) {
#pragma unroll
    for (int i = 0; i < N; i++) reload_unit(v[i], p + i * STRIDE);
    if (++it > SPIN_LIMIT) __trap();
  }
  return it;
}
__device__ __forceinline__ void sum4_to_smem(const uint2 (&v)[4], uint32_t dst) {
  const float c0 = (bf_lo(v[0].x) + bf_lo(v[1].x)) + (bf_lo(v[2].x) + bf_lo(v[3].x));
  const float c1 = (bf_hi(v[0].x) + bf_hi(v[1].x)) + (bf_hi(v[2].x) + bf_hi(v[3].x));
  const float c2 = (bf_lo(v[0].y) + bf_lo(v[1].y)) + (bf_lo(v[2].y) + bf_lo(v[3].y));
  const float c3 = (bf_hi(v[0].y) + bf_hi(v[1].y)) + (bf_hi(v[2].y) + bf_hi(v[3].y));
  sts1(dst, pack_bf16(c0, c1));
  sts1(dst + 128, pack_bf16(c2, c3));
}
__device__ __forceinline__ uint32_t a_t_offset(int w, int lane) {
  const int mi = lane >> 3, r = lane & 7;
  return (w >> 2) * 16384 + (8 * (mi >> 1) + r) * 128 + (((2 * (w & 3) + (mi & 1)) ^ r) << 4);
}
__device__ __forceinline__ void load_a_t(uint32_t (&a)[8][4], uint32_t base) {
#pragma unroll
  for (int ks = 0; ks < 8; ks++) ldsm4t(a[ks], base + ks * 2048);
}
__device__ __forceinline__ void mma128(float (&d)[4], const uint32_t (&a)[8][4], const uint32_t (&b)[4][4]) {
  float e[4][4] = {{d[0], d[1], d[2], d[3]}, {0.f, 0.f, 0.f, 0.f}, {0.f, 0.f, 0.f, 0.f}, {0.f, 0.f, 0.f, 0.f}};
#pragma unroll
  for (int kk = 0; kk < 4; kk++) { mma16816(e[(2 * kk) & 3], a[2 * kk], b[kk][0], b[kk][1]); mma16816(e[(2 * kk + 1) & 3], a[2 * kk + 1], b[kk][2], b[kk][3]); }
#pragma unroll
  for (int i = 0; i < 4; i++) d[i] = (e[0][i] + e[1][i]) + (e[2][i] + e[3][i]);
}
template <int NP> __device__ __forceinline__ bool sum_pieces(const uint32_t* p0, uint32_t one, float (&r)[4]) {
  uint2 v[NP / 4];
  load_units<NP / 4, 64>(v, p0);
  float d[4][4] = {};
#pragma unroll
  for (int i = 0; i < NP / 8; i++) { const uint32_t a[4] = {v[2 * i].x, v[2 * i].y, v[2 * i + 1].x, v[2 * i + 1].y}; mma16816(d[i & 3], a, one, one); }
  const bool ok = __all_sync(~0u, min_flags(v) != 0);
#pragma unroll
  for (int k = 0; k < 4; k++) r[k] = (d[0][k] + d[1][k]) + (d[2][k] + d[3][k]);
  return ok;
}
template <typename F> __device__ __forceinline__ float reduce_g(const float (&x)[4], int lane, F f) {
  const bool u4 = lane & 16, u3 = lane & 8;
  const float a0 = f(u4 ? x[2] : x[0], __shfl_xor_sync(~0u, u4 ? x[0] : x[2], 16));
  const float a1 = f(u4 ? x[3] : x[1], __shfl_xor_sync(~0u, u4 ? x[1] : x[3], 16));
  const float b = f(u3 ? a1 : a0, __shfl_xor_sync(~0u, u3 ? a0 : a1, 8));
  return f(b, __shfl_xor_sync(~0u, b, 4));
}

__global__ void __launch_bounds__(NTHREADS, 1)
fused_decode_kernel(__nv_bfloat16* __restrict__ gout, Scratch* __restrict__ gs, const uint8_t* __restrict__ gwmod,
                    const uint8_t* __restrict__ gx, const uint8_t* __restrict__ gc, uint32_t* __restrict__ gin,
                    const __grid_constant__ Params P) {
  constexpr Tune T{};
  extern __shared__ __align__(1024) uint8_t smem_raw[];
  constexpr uint32_t sb = SB;
  const int tid = __shfl_xor_sync(0xffffffffu, threadIdx.x ^ 1, 1), lane = tid & 31;
  const int w = __shfl_sync(0xffffffffu, threadIdx.x >> 5, 0);
  const int cta = blockIdx.x;
  auto BAR = [](int i) { return SB + OFF_BARS + 8 * i; };
  auto selector = [&](int c) { uint32_t v; asm volatile("ld.shared.u8 %0, [%1];" : "=r"(v) : "r"(sb + OFF_SEL + c) : "memory"); return v; };
  auto inbox = [&](int c, int k) { return gin + blk(c, k, selector(c)); };
  auto nearbox = [&](int c, int k) { return gin + blk(c, k, selector(cta) ^ flip((c ^ cta) & 15)); };
  const int g = lane >> 2, t = lane & 3;
  const int hI = cta >> 2, jI = cta & 3;
  const int bs = cta >> 1, hh = cta & 1;

  CLK_DECL;
  CLK(0);
  if (w == 8) {
    CLK(7);
    const uint32_t t_entry = gtime32();
    CLK(8);
    if (lane == 0) {
      if ((uint32_t)__cvta_generic_to_shared(smem_raw) != SB) __trap();
      mbar_init(BAR(BAR_WQ), 1); mbar_init(BAR(BAR_WQ + 1), 1); mbar_init(BAR(BAR_XC), 1); mbar_init(BAR(BAR_C), 1);
      asm volatile("fence.mbarrier_init.release.cluster;" ::: "memory");
      asm volatile("prefetch.tensormap [%0];" ::"l"(&P.wq) : "memory");
      mbar_expect(BAR(BAR_XC), 8192); mbar_expect(BAR(BAR_C), 8192); mbar_expect(BAR(BAR_WQ), 16384); mbar_expect(BAR(BAR_WQ + 1), 16384);
      CLK(9);
    }
    __syncwarp();
    asm volatile("barrier.cta.arrive.aligned 0, %0;" ::"n"(NTHREADS) : "memory");
    CLK(10);
    uint32_t tn = t_entry + T.PC_T0 + ((bs * 37) & 63) * T.PC_STAG / 64;
    const int h = hI, j = jI;
    if (lane == 0) {
      uint64_t pol; asm volatile("createpolicy.fractional.L2::evict_first.b64 %0, 1.0;" : "=l"(pol));
#pragma unroll
      for (int u = 0; u < 4; u++) {
        until_ns(tn + u * T.PC_P1);
        if (u == 0) CLK(11);
        tma2d(sb + OFF_WQ + u * 8192, &P.wq, 128 * h + 64 * (u >> 1), 128 * j + 64 * (u & 1), BAR(BAR_WQ + (u >> 1)), pol);
        if (u == 0) {
#pragma unroll
          for (int i = 0; i < 8; i++) { const int o = ((i + cta) & 3) * 2048; bulk_ld(sb + OFF_XS + (i >> 2) * 8192 + o, (i < 4 ? gx : gc) + o, 2048, BAR(i < 4 ? BAR_XC : BAR_C)); }
          CLK(1);
          asm volatile("prefetch.tensormap [%0];" ::"l"(&P.wuk) : "memory");
          asm volatile("prefetch.tensormap [%0];" ::"l"(&P.wm2) : "memory");
          asm volatile("prefetch.tensormap [%0];" ::"l"(&P.ckv2) : "memory");
        }
      }
    }
    __syncwarp();
    tn += 4 * T.PC_P1;
    bar_sync(5, 64);
    if (lane == 0) {
      uint64_t pol; asm volatile("createpolicy.fractional.L2::evict_first.b64 %0, 1.0;" : "=l"(pol));
#pragma unroll
      for (int u = 0; u < 4; u++) {
        if (u & 1) mbar_wait(BAR(BAR_WQ + (u >> 1)));
        slot(tn, T.PC_SL);
        tma5d(sb + OFF_WUK + u * 8192, &P.wuk, 128 * h + 64 * (u >> 1), 0, 0, 0, 8 * j + 4 * (u & 1), BAR(BAR_WUK + (u >> 1)), pol);
        tn += T.PC_P1;
      }
#pragma unroll
      for (int u = 0; u < 2; u++) {
        if (u) mbar_wait(BAR(BAR_WUK));
        slot(tn, T.PC_SL);
        if (j != 3) tma2d_nohint(sb + OFF_WM2 + u * 8192, &P.wm2, 1024 + 16 * (3 * h + j), 256 * u, BAR(BAR_WM2));
        tn += T.PC_PM;
      }
      const int row0 = (bs >> 3) * 4096 + (bs & 7) * 64;
      uint32_t dst = sb + OFF_RING;
#pragma unroll 1
      for (int n = 0; n < 31; n++) {
        if (n >= 4 && (n < 12 || (n & 3) == 0)) mbar_wait(BAR(n >= 12 ? BAR_EMPTY + (n >> 2) - 3 : (n == 7 && j != 3) ? BAR_P0BD : (n == 8 || n == 9) ? BAR_P2D : BAR_P1D));
        if (n < T.PC_NW) {
          if (n >= 4) mbar_wait(BAR(BAR_FULL + n - 4));
          else if (n & 1) mbar_wait(BAR((n < 2 || j == 3) ? BAR_WUK + 1 : BAR_WM2));
        }
        slot(tn, T.PC_SL);
        tma3d(dst, &P.ckv2, 0, row0 + (n >> 2) * 512, 2 * (n & 3), BAR(BAR_FULL + n), pol);
        dst = (n == 11 || n == 23) ? sb + OFF_RING : dst + 16384;
        tn += T.PC_P2;
        if (n == 4) CLK(2);
        if (n == 12) CLK(3);
        if (n == 20) CLK(4);
        if (n == 28) CLK(5);
        if (n == 24) {
          asm volatile("prefetch.tensormap [%0];" ::"l"(&P.ckv1) : "memory");
          asm volatile("prefetch.tensormap [%0];" ::"l"(&P.wuv) : "memory");
          asm volatile("prefetch.tensormap [%0];" ::"l"(&P.wo) : "memory");
          asm volatile("prefetch.tensormap [%0];" ::"l"(cta < NFF ? &P.w1 : &P.wm3) : "memory");
          asm volatile("prefetch.tensormap [%0];" ::"l"(&P.w2) : "memory");
        }
      }
      slot(tn, T.PC_SL);
      tma3d(dst, &P.ckv1, 0, row0 + 7 * 512, 6, BAR(BAR_LAST + 3), pol);
      tma3d(dst + 8192, &P.ckv1, 0, row0 + 7 * 512, 7, BAR(BAR_LAST + 4), pol);
      tn += T.PC_P2;
      CLK(6);
      auto unit = [&](int u) {
        if (u < 4) tma5d(sb + OFF_WUV + u * 8192, &P.wuv, 128 * h + 64 * (u >> 1), 0, 4 * (j >> 1), 0, 2 * (j & 1) + (u & 1), BAR(BAR_WUV + (u >> 1)), pol);
        else if (u < 8) tma2d(sb + OFF_WO + (u - 4) * 8192, &P.wo, 128 * j + 64 * ((u - 4) >> 1), 128 * h + 64 * (u & 1), BAR(BAR_WO + ((u - 4) >> 1)), pol);
        else if (u < 10) { if (cta < NFF) tma2d_nohint(sb + OFF_W1 + (u - 8) * 16384, &P.w1, 32 * bs, 256 * (u - 8), BAR(BAR_W1)); }
        else if (cta < NFF) tma3d(sb + OFF_W2 + (u - 10) * 8192, &P.w2, 0, 32 * bs, 4 * hh + 2 * (u - 10), BAR(BAR_W2), pol);
        else tma2d_nohint(sb + OFF_W1 + (u - 10) * 16384, &P.wm3, 2560 + 32 * (cta - NFF), 256 * (u - 10), BAR(BAR_W1));
      };
      mbar_wait(BAR(BAR_EMPTY + 5));
      tn += T.PW_0;
#pragma unroll
      for (int u = 0; u < 12; u++) {
        if (u == 8) mbar_wait(BAR(BAR_EMPTY + 6));
        if (u == 10 && cta >= NFF) tn -= T.PW_GB;
        until_ns(tn);
        unit(u);
        tn += u < 3 ? T.PW_UV : u == 3 ? T.PW_G : u < 7 ? T.PW_O : u == 7 ? T.PW_G2 : u == 9 ? T.PW_G3 : T.PW_F;
      }
      CLK_DUMP();
    }
    return;
  }

  if (w == 9) {
    if (lane == 0) {
#pragma unroll
      for (int i = 0; i < NBARS; i++) mbar_init(BAR(i), i >= BAR_P1D ? 8 : i >= BAR_EMPTY ? 4 : 1);
      asm volatile("fence.mbarrier_init.release.cluster;" ::: "memory");
    }
    __syncwarp();
    mbar_expect(BAR(lane), lane == BAR_LAST + 3 ? 8192 : 16384);
    if (lane < BAR_ALLCLR - 32) mbar_expect(BAR(32 + lane), lane == 0 ? 8192 : lane == BAR_W1 - 32 ? 32768 : 16384);
    CLK(9);
    asm volatile("barrier.cta.arrive.aligned 5, 64;" ::: "memory");
    asm volatile("barrier.cta.arrive.aligned 0, %0;" ::"n"(NTHREADS) : "memory");
  }
  const uint32_t epoch = ldg_rlx1(&gs->epoch);

  if (w == 9) {
    const int mo = g * 512 + 16 * hI + 2 * jI;
    const uint32_t xo0 = ldg_nc1(gx + mo * 2), xo1 = ldg_nc1(gx + mo * 2 + 16);
    const int par = epoch & 1;
    const uint32_t t0 = gtime32();
    const uint4 z = make_uint4(0, 0, 0, 0);
    uint32_t sel;
    {
      uint32_t* pa = gin + blk(cta, 5, 0) + 960;
      uint32_t* pb = gin + blk(cta, 5, 1) + 960;
      until_ns(t0 + T.PR_T0);
      if (lane < 4) stg4(reinterpret_cast<uint4*>(lane & 2 ? pa : pb) + (lane & 1), z);
      uint32_t ma = 0xffffffffu, mb = 0xffffffffu;
#pragma unroll 1
      for (int i = 0; i < 2 * T.PR_N; i++) {
        const uint32_t c0 = clk32();
        asm volatile("{\n.reg .pred q;\n.reg .b32 v;\nsetp.eq.u32 q, %1, 0;\nmov.u32 v, 0;\n@q atom.relaxed.gpu.global.add.u32 v, [%0], 1;\n"
                     "setp.eq.u32 q, v, 0xffffffff;\n@q trap;\n}" ::"l"(i & 1 ? pb : pa), "r"(lane) : "memory");
        const uint32_t d = clk32() - c0;
        if (i & 1) mb = min(mb, d); else ma = min(ma, d);
      }
      sel = __shfl_sync(~0u, (uint32_t)(mb < ma), 0);
      const uint32_t sw = 2 * (epoch + 1) + sel;
      if (lane < 2) stg4(reinterpret_cast<uint4*>(gin + blk(cta, 5, 1) + 896) + lane, make_uint4(sw, sw, sw, sw));
    }
    until_ns(t0 + T.CLR_T0);
    {
#pragma unroll 1
      for (int i0 = 0; i0 < 13; i0++) {
        uint4* q = reinterpret_cast<uint4*>(gin + (i0 < 12 ? blk(cta, i0 >> 1, sel) + (i0 & 1) * 512 : blk(cta, 4, sel ^ 1) + 512)) + lane;
#pragma unroll
        for (int i = 0; i < 4; i++) if (i0 != 11 || i < 3) stg4(q + i * 32, z);
        backoff(T.CLR_CLK);
      }
#pragma unroll
      for (int i = 0; i < 2; i++) {
        if (jI == 1) stg4(reinterpret_cast<uint4*>(gin + blk(cta, 6, i)) + lane, z);
        if (lane < 2) stg4(reinterpret_cast<uint4*>(gin + blk(cta, 5, i) + 928) + lane, z);
        stg4(reinterpret_cast<uint4*>(gin + blk(16 * g, 6 + (cta >> 6), i) + (cta & 63) * 16) + t, z);
      }
      CLK(1);
      {
        uint32_t sv = 0;
        uint32_t u[4];
        int it = 0;
        do {
#pragma unroll
          for (int i = 0; i < 4; i++) u[i] = ldg_rlx1(gin + blk(4 * lane + i, 5, 1) + 896) ^ (2 * (epoch + 1));
          if (++it > SPIN_LIMIT) __trap();
        } while (!__all_sync(~0u, (u[0] | u[1] | u[2] | u[3]) < 2));
#pragma unroll
        for (int i = 0; i < 4; i++) sv |= u[i] << (8 * i);
        sts1(sb + OFF_SEL + lane * 4, sv);
      }
      asm volatile("fence.acq_rel.gpu;" ::: "memory");
      CLK(2);
      __syncwarp();
      if (lane < NSYNC) asm volatile("red.relaxed.gpu.global.add.u32 [%0], 1;" ::"l"(&gs->sync[lane][0]) : "memory");
#pragma unroll
      for (int i = 0; i < 4; i++) stg4(reinterpret_cast<uint4*>(gs->QP[par ^ 1] + cta * 512) + i * 32 + lane, z);
      backoff(T.CLR_CLK);
#pragma unroll
      for (int i = 0; i < 4; i++) stg4(reinterpret_cast<uint4*>(gs->QX[par ^ 1] + cta * 512) + i * 32 + lane, z);
      stg4(reinterpret_cast<uint4*>(gs->MOD1[par ^ 1] + cta * 128) + lane, z);
      if (lane < 16) stg4(reinterpret_cast<uint4*>(gs->MOD2[par ^ 1] + cta * 64) + lane, z);
      const uint32_t target = (epoch + 1) * NCTA;
      uint32_t c; int it = 0;
      do {
        backoff(T.CLR_CLK);
        asm volatile("ld.acquire.gpu.global.u32 %0, [%1];" : "=r"(c) : "l"(&gs->sync[cta % NSYNC][0]) : "memory");
        if (++it > SPIN_LIMIT) __trap();
      } while (!__all_sync(~0u, (int)(c - target) >= 0));
      if (lane == 0) mbar_arrive(BAR(BAR_ALLCLR));
    }
    CLK(3);
    const uint32_t* const pg = gs->MOD2[par] + cta * 16 + g * 2;
    auto gate = [&](const uint32_t* q) { uint2 u; int it = 0; do { u = ldg_u64(q); if (++it > SPIN_LIMIT) __trap(); } while (!__all_sync(~0u, u.y != 0)); return u; };
    const uint2 gau = gate(pg);
    uint32_t anchor;
    {
      uint32_t* const po = gin + blk(16 * (lane & 7), 5, lane >> 3) + 928;
      const uint32_t* const pi = nearbox(cta & ~15, 5) + 928;
      mbar_wait(BAR(BAR_LAST + T.TS_P));
      unsigned long long now; asm volatile("mov.u64 %0, %%globaltimer;" : "=l"(now));
      if (lane < 16) {
        asm volatile("red.relaxed.gpu.global.max.u64 [%0], %1;" ::"l"(po + 2), "l"(now) : "memory");
        asm volatile("red.relaxed.gpu.global.add.u32 [%0], 1;" ::"l"(po + 1) : "memory");
      }
      backoff(T.D_TS);
      uint4 v; int it = 0;
      do { v = ldg_2u64(pi); if (++it > SPIN_LIMIT) __trap(); } while (!__all_sync(~0u, v.y == NCTA));
      const int age = min(max((int)(gtime32() - v.z), 0), 4000);
      anchor = clk32() - age * 7 / 4 + T.TS_O;
      if (lane == 0) { sts1(sb + OFF_TS, anchor); mbar_arrive(BAR(BAR_TS)); }
      CLK(10);
    }
    {
      const uint32_t* pm = pin(nearbox(4 * hI + 1, 6) + lane * 4);
      wait_clk(anchor, T.A_M);
      uint4 ml = ldg_2u64(pm);
      int it = 0;
      while (!__all_sync(~0u, ml.y != 0 && ml.w != 0)) { ml = ldg_2u64(pm); if (++it > SPIN_LIMIT) __trap(); }
      ITS(2, it);
      float M = fmaxf(__uint_as_float(ml.x), __uint_as_float(ml.z));
      M = fmaxf(M, __shfl_xor_sync(~0u, M, 1)); M = fmaxf(M, __shfl_xor_sync(~0u, M, 2));
      const float e0 = ex2(__uint_as_float(ml.x) - M), e1 = ex2(__uint_as_float(ml.z) - M);
      float l = e0 * __uint_as_float(ml.y) + e1 * __uint_as_float(ml.w);
      l += __shfl_xor_sync(~0u, l, 1); l += __shfl_xor_sync(~0u, l, 2);
      const float inv = __fdividef(1.f, l);
      sts2f(sb + OFF_WV + lane * 8, e0 * inv, e1 * inv);
      __syncwarp();
      if (lane == 0) mbar_arrive(BAR(BAR_WV));
      CLK(11);
    }
    uint32_t* x3o[4];
#pragma unroll
    for (int i = 0; i < 4; i++) x3o[i] = pin(gin + blk(32 * i + 16 * (t >> 1), 6 + (cta >> 6), t) + (cta & 63) * 16 + g * 2);
    uint32_t* const fo = pin(reinterpret_cast<uint32_t*>(gout) + mo / 2 + 4 * (t & 1));
    const uint32_t* const p3 = pin(gin + blk(cta, 4, sel) + t * 16 + g * 2);
    const uint32_t* const p4 = pin(gin + blk(cta, 5, sel) + t * 16 + g * 2);
    const uint32_t one = pin((g & 1) ? 0x3f800000u : 0x00003f80u);
    const float xf[4] = {pin(bf_lo(xo0)), pin(bf_hi(xo0)), pin(bf_lo(xo1)), pin(bf_hi(xo1))};
    const float ga[4] = {pin(bf_lo(gau.x)), pin(bf_hi(gau.x)), pin(bf_lo(gau.y)), pin(bf_hi(gau.y))};
    mbar_wait(BAR(BAR_P5D));
    backoff(T.D_X3A);
    wait_clk(anchor, T.A_X1 + T.R_X3A);
    CLK(4);
    float r[4];
    uint32_t x20, x21;
    int it = 0;
    bool ok;
    do {
      ok = sum_pieces<32>(p3, one, r);
      x20 = pack_bf16(xf[0] + ga[0] * r[0], xf[1] + ga[1] * r[1]); x21 = pack_bf16(xf[2] + ga[2] * r[2], xf[3] + ga[3] * r[3]);
#pragma unroll
      for (int i = 0; i < 4; i++) stg_u64_unless(!ok || (i == 3 && t >= 2), x3o[i], x20, x21);
    } while (!ok && ++it < SPIN_LIMIT);
    if (!ok) __trap();
    CLK(6);
    ITS(0, it);
    const uint32_t xw = (t & 1) ? x21 : x20;
    const float xa = pin(bf_lo(xw)), xb = pin(bf_hi(xw));
    if (cta < NFF) mbar_wait(BAR(BAR_P7D)); else wait_clk(anchor, T.A_X1 + T.R_X3A + T.R_X3B + T.R_FIN - T.D_FIN);
    uint2 gbu = ldg_u64(pg + 3 * 2048);
    backoff(T.D_FIN);
    CLK(7);
    do {
      ok = sum_pieces<NFG>(p4, one, r);
      ok = ok && __all_sync(~0u, gbu.y != 0);
      const uint32_t gw = (t & 1) ? gbu.y : gbu.x;
      const uint32_t o = pack_bf16(xa + bf_lo(gw) * ((t & 1) ? r[2] : r[0]), xb + bf_hi(gw) * ((t & 1) ? r[3] : r[1]));
      if (ok && t < 2) asm volatile("st.global.u32 [%0], %1;" ::"l"(fo), "r"(o) : "memory");
      reload_unit(gbu, pg + 3 * 2048);
    } while (!ok && ++it < SPIN_LIMIT);
    if (!ok) __trap();
    ITS(1, it);
    CLK(8);
    CLK_DUMP();
    if (cta == 0 && lane == 0) stg1(&gs->epoch, epoch + 1);
    return;
  }

  const int wg = w >> 2, wq = w & 3;
  uint32_t tstore;
  {
    const uint8_t* pw = gwmod + (size_t)(128 * jI + 16 * w + 4 * (g >> 1) + (g & 1)) * 6144 + 64 * hI + 16 * t;
    const uint4 w0 = ldg_nc4(pw), w1 = ldg_nc4(pw + 2 * 6144);
    const uint2 cc = ldg_nc2(gc + g * 1024 + 256 * jI + 32 * w + 8 * t);
    CLK(40);
    const uint32_t a[4] = {silu2(cc.x), 0u, silu2(cc.y), 0u};
    float d[4][4] = {{0.f, 0.f, 0.f, 0.f}, {0.f, 0.f, 0.f, 0.f}, {0.f, 0.f, 0.f, 0.f}, {0.f, 0.f, 0.f, 0.f}};
    mma16816(d[0], a, movm(w0.x), movm(w1.x)); mma16816(d[1], a, movm(w0.y), movm(w1.y));
    mma16816(d[2], a, movm(w0.z), movm(w1.z)); mma16816(d[3], a, movm(w0.w), movm(w1.w));
    CLK(1);
    sts4f(sb + OFF_P0S + w * 1088 + lane * 16, d[0][0], d[0][1], d[1][0], d[1][1]);
    sts4f(sb + OFF_P0S + w * 1088 + 544 + lane * 16, d[2][0], d[2][1], d[3][0], d[3][1]);
    bar_sync(0, NTHREADS);
    if (tid < 128) {
      const uint32_t src = sb + OFF_P0S + ((tid >> 2) & 1) * 544 + (((tid >> 3) & 7) * 4 + 2 * (tid >> 6) + (tid & 1)) * 16 + ((tid >> 1) & 1) * 8;
      float2 v[8];
#pragma unroll
      for (int i = 0; i < 8; i++) v[i] = ldsf2(src + i * 1088);
      const float ax = ((v[0].x + v[1].x) + (v[2].x + v[3].x)) + ((v[4].x + v[5].x) + (v[6].x + v[7].x));
      const float ay = ((v[0].y + v[1].y) + (v[2].y + v[3].y)) + ((v[4].y + v[5].y) + (v[6].y + v[7].y));
      stg1(gs->MOD1[epoch & 1] + jI * 4096 + hI * 128 + tid, nz(pack_bf16(ax, ay)));
    }
    tstore = clk32();
  }
  CLK(2);
  const int par = epoch & 1;
  uint32_t cf[4][4];
  mbar_wait(BAR(BAR_XC));
  {
    uint32_t u[2][4];
    lds4(u[0], sb + OFF_XS + w * 1024 + lane * 16); lds4(u[1], sb + OFF_XS + w * 1024 + 512 + lane * 16);
    float v[16];
#pragma unroll
    for (int i = 0; i < 8; i++) { v[2 * i] = bf_lo(u[i >> 2][i & 3]); v[2 * i + 1] = bf_hi(u[i >> 2][i & 3]); }
    float s = 0.f;
#pragma unroll
    for (int i = 0; i < 16; i++) s += v[i];
#pragma unroll
    for (int o = 16; o; o >>= 1) s += __shfl_xor_sync(~0u, s, o);
    const float mu = s * (1.f / 512.f);
    float q = 0.f;
#pragma unroll
    for (int i = 0; i < 16; i++) { v[i] -= mu; q += v[i] * v[i]; }
#pragma unroll
    for (int o = 16; o; o >>= 1) q += __shfl_xor_sync(~0u, q, o);
    const float rs = rsqrtf(q * (1.f / 512.f) + 1e-5f);
    const bool hi = jI & 2;
    uint32_t o[4];
#pragma unroll
    for (int i = 0; i < 4; i++) o[i] = pack_bf16((hi ? v[8 + 2 * i] : v[2 * i]) * rs, (hi ? v[9 + 2 * i] : v[2 * i + 1]) * rs);
    if ((lane >> 4) == (jI & 1)) sts4(sb + OFF_XN + w * 272 + (lane & 15) * 16, make_uint4(o[0], o[1], o[2], o[3]));
  }
  CLK(3);
  uint32_t aw[8][4];
  const uint32_t abase = __shfl_sync(~0u, sb + a_t_offset(w, lane), lane);
  {
    const uint32_t* pm = pin(gs->MOD1[par] + (8 * jI + w) * 64 + lane * 2);
    uint32_t* const qpo = pin(gs->QP[par] + (cta * 256 + tid) * 2);
    float d[4] = {0.f, 0.f, 0.f, 0.f};
    wait_clk(tstore, T.D_MOD);
    CLK(4);
    uint2 v[8];
    load_units<8, 2048>(v, pm);
    cbar();
    const uint32_t xn0 = lds1(sb + OFF_XN + g * 272 + w * 32 + t * 4), xn1 = lds1(sb + OFF_XN + g * 272 + w * 32 + 16 + t * 4);
    const bool early = __all_sync(~0u, mbar_test(BAR(BAR_WQ + wg)));
    if (early) load_a_t(aw, abase + OFF_WQ);
    int it = 0;
    while (true) {
      uint32_t mn = 0xffffffffu;
#pragma unroll
      for (int i = 0; i < 8; i++) mn = min(mn, min(v[i].x, v[i].y));
      if (__all_sync(~0u, mn != 0)) break;
#pragma unroll
      for (int i = 0; i < 8; i++) { if (v[i].x == 0) v[i].y = 0; reload_unit(v[i], pm + i * 2048); }
      if (++it > SPIN_LIMIT) __trap();
    }
    CLK(5);
    ITS(0, it);
    float sc[2][4];
#pragma unroll
    for (int i = 0; i < 2; i++) {
      sc[i][0] = (bf_lo(v[i].x) + bf_lo(v[2 + i].x)) + (bf_lo(v[4 + i].x) + bf_lo(v[6 + i].x));
      sc[i][1] = (bf_hi(v[i].x) + bf_hi(v[2 + i].x)) + (bf_hi(v[4 + i].x) + bf_hi(v[6 + i].x));
      sc[i][2] = (bf_lo(v[i].y) + bf_lo(v[2 + i].y)) + (bf_lo(v[4 + i].y) + bf_lo(v[6 + i].y));
      sc[i][3] = (bf_hi(v[i].y) + bf_hi(v[2 + i].y)) + (bf_hi(v[4 + i].y) + bf_hi(v[6 + i].y));
    }
    sts2(sb + OFF_BS1 + (w >> 1) * 512 + lane * 16 + (w & 1) * 8,
         pack_bf16(bf_lo(xn0) * (1.f + sc[1][0]) + sc[0][0], bf_hi(xn0) * (1.f + sc[1][1]) + sc[0][1]),
         pack_bf16(bf_lo(xn1) * (1.f + sc[1][2]) + sc[0][2], bf_hi(xn1) * (1.f + sc[1][3]) + sc[0][3]));
    if (!early) { mbar_wait(BAR(BAR_WQ + wg)); load_a_t(aw, abase + OFF_WQ); }
    CLK(6);
    cbar();
    uint32_t b[4][4];
#pragma unroll
    for (int kk = 0; kk < 4; kk++) lds4(b[kk], sb + OFF_BS1 + kk * 512 + lane * 16);
    mma128(d, aw, b);
    stg_u64(qpo, pack_bf16(d[0], d[1]), pack_bf16(d[2], d[3]));
    tstore = clk32();
    CLK(7);
    if (wg) {
      mbar_wait(BAR(BAR_C));
#pragma unroll
      for (int i = 0; i < 4; i++) lds4(cf[i], sb + OFF_CS + g * 1024 + wq * 256 + i * 64 + t * 16);
#pragma unroll
      for (int i = 0; i < 16; i++) cf[i >> 2][i & 3] = silu2(cf[i >> 2][i & 3]);
    }
    __syncwarp();
    if (lane == 0) mbar_arrive(BAR(BAR_P1D));
  }
  {
    const uint32_t* pq = pin(gs->QP[par] + (hI * 4 * 256 + tid) * 2);
    uint32_t* const qxo = pin(gs->QX[par] + (g * 32 + hI) * 256 + 64 * jI + 8 * w + 2 * t);
    uint2 v[4];
    float d[4] = {0.f, 0.f, 0.f, 0.f};
    wait_clk(tstore, T.D_QP);
    CLK(8);
    load_units<4, 512>(v, pq);
    const uint32_t kbase = sb + OFF_WUK + (16 * w + (lane & 15)) * 128;
    auto load_half = [&](int hf) {
#pragma unroll
      for (int ks = 0; ks < 4; ks++) ldsm4(aw[4 * hf + ks], kbase + hf * 16384 + (((2 * ks + (lane >> 4)) ^ (lane & 7)) << 4));
    };
    mbar_wait(BAR(BAR_WUK));
    load_half(0);
    const bool early = __all_sync(~0u, mbar_test(BAR(BAR_WUK + 1)));
    if (early) load_half(1);
    const int it = check_units<4, 512>(v, pq);
    CLK(9);
    ITS(1, it);
    sum4_to_smem(v, sb + OFF_BS2 + (16 * w + g) * 16 + t * 4);
    if (!early) { mbar_wait(BAR(BAR_WUK + 1)); load_half(1); }
    CLK(10);
    cbar();
    uint32_t b[4][4];
#pragma unroll
    for (int kk = 0; kk < 4; kk++) ldsm4t(b[kk], sb + OFF_BS2 + (32 * kk + lane) * 16);
    mma128(d, aw, b);
    const float sc = 0.08838834764831845f * 1.4426950408889634f;
    stg_u64(qxo, movm(pack_bf16(d[0] * sc, d[1] * sc)), movm(pack_bf16(d[2] * sc, d[3] * sc)));
    tstore = clk32();
    CLK(11);
    if (lane == 0) mbar_arrive(BAR(BAR_P2D));
  }
  if (wg && jI != 3) {
    const int mi = lane >> 3, r = lane & 7;
    const uint32_t a0 = sb + OFF_WM2 + (8 * (r >> 1) + (r & 1) + 2 * (mi >> 1)) * 32 + (mi & 1) * 16;
    mbar_wait(BAR(BAR_WM2));
#pragma unroll
    for (int s = 0; s < 8; s++) ldsm4t(aw[s], a0 + (128 * wq + 32 * (s >> 1) + 4 * (s & 1)) * 32);
    float d[4] = {0.f, 0.f, 0.f, 0.f};
    mma128(d, aw, cf);
    sts4f(sb + OFF_P0B + (tid - 128) * 16, d[0], d[1], d[2], d[3]);
    if (lane == 0) mbar_arrive(BAR(BAR_P0BD));
    bar_sync(3, 128);
    if (w == 4) {
      float4 v[4];
#pragma unroll
      for (int i = 0; i < 4; i++) v[i] = ldsf4(sb + OFF_P0B + (i * 32 + lane) * 16);
      stg_u64(gs->MOD2[par] + (3 * hI + jI) * 64 + t * 16 + g * 2, movm(pack_bf16((v[0].x + v[1].x) + (v[2].x + v[3].x), (v[0].y + v[1].y) + (v[2].y + v[3].y))),
              movm(pack_bf16((v[0].z + v[1].z) + (v[2].z + v[3].z), (v[0].w + v[1].w) + (v[2].w + v[3].w))));
    }
    CLK(15);
  }
  {
    const uint32_t* qx = pin(gs->QX[par] + ((bs >> 3) * 32 + 16 * hh) * 256 + tid * 4);
    const int ch = tid & 63, h0 = tid >> 6;
    const uint32_t dst = sb + OFF_Q + (ch >> 3) * 2048 + h0 * 128;
    wait_clk(tstore, T.D_QX);
    CLK(12);
    uint4 v[4];
#pragma unroll
    for (int i = 0; i < 4; i++) v[i] = ldg_2u64(qx + i * 1024);
    int it = 0;
    while (true) {
      uint32_t mn = 0xffffffffu;
#pragma unroll
      for (int i = 0; i < 4; i++) mn = min(mn, min(v[i].y, v[i].w));
      if (__all_sync(~0u, mn != 0)) break;
#pragma unroll
      for (int i = 0; i < 4; i++)
        asm volatile("{\n.reg .pred q;\nsetp.eq.u32 q, %5, 0;\n@q ld.relaxed.gpu.global.v4.b32 {%0, %1, %2, %3}, [%4];\n}"
                     : "+r"(v[i].x), "+r"(v[i].y), "+r"(v[i].z), "+r"(v[i].w) : "l"(qx + i * 1024), "r"(min(v[i].y, v[i].w)) : "memory");
      if (++it > SPIN_LIMIT) __trap();
    }
    CLK(13);
    ITS(2, it);
#pragma unroll
    for (int i = 0; i < 4; i++) sts4(dst + i * 512 + (((ch & 7) ^ ((4 * i + h0) & 7)) << 4), v[i]);
    asm volatile("fence.proxy.async.shared::cta;" ::: "memory");
    CLK(14);
    cbar();
  }

  uint2 cbf[4], sbf[4];
  const uint32_t* const pcb = gs->MOD2[par] + 2048 + (16 * w + t) * 16 + g * 2;
  auto load_frags = [&] {
    if (cta < NFF) { load_units<4, 64>(sbf, pcb); load_units<4, 64>(cbf, pcb + 2048); }
    else {
#pragma unroll
      for (int s = 0; s < 4; s++) { cbf[s].x = ldg_nc1(gc + g * 1024 + w * 128 + s * 32 + t * 4); cbf[s].y = ldg_nc1(gc + g * 1024 + w * 128 + s * 32 + 16 + t * 4); }
    }
  };
  uint32_t thand, anchor;
  const uint32_t opaque0 = w >> 4;
  if (wg == 0) {
    float mh[4];
    float L[8];
#pragma unroll
    for (int i = 0; i < 4; i++) { L[2 * i] = L[2 * i + 1] = 0.f; mh[i] = -INFINITY; }
    constexpr uint32_t dq = desc_lo(OFF_Q);
    const uint32_t ptw = sb + OFF_PT + (8 * (lane >> 4) + (lane & 7)) * 128 + (((2 * wq + ((lane >> 3) & 1)) ^ (lane & 7)) << 4);
    float S[8];
    auto softmax = [&](int tl) {
      auto write_p = [&](const float (&x)[8]) {
        float p[8];
#pragma unroll
        for (int i = 0; i < 8; i++) p[i] = ex2(x[i]);
        stsm4t(ptw + (tl & 1) * 2048, pack_bf16(p[0], p[1]), pack_bf16(p[2], p[3]), pack_bf16(p[4], p[5]), pack_bf16(p[6], p[7]));
        asm volatile("fence.proxy.async.shared::cta;" ::: "memory");
      };
      float x[8];
#pragma unroll
      for (int i = 0; i < 8; i++) x[i] = S[i] - mh[2 * (i >> 2) + (i & 1)];
      if (tl) write_p(x);
      const float ex = fmaxf(fmaxf(fmaxf(x[0], x[1]), fmaxf(x[2], x[3])), fmaxf(fmaxf(x[4], x[5]), fmaxf(x[6], x[7])));
      if (tl == 0 || bar_over(ex)) {
        float mx[4];
#pragma unroll
        for (int i = 0; i < 4; i++) mx[i] = fmaxf(S[4 * (i >> 1) + (i & 1)], S[4 * (i >> 1) + 2 + (i & 1)]);
        const float a = reduce_g(mx, lane, [](float u, float v) { return fmaxf(u, v); });
        stsf(sb + OFF_RED + wq * 64 + (8 * (lane >> 4) + 2 * t + ((lane >> 3) & 1)) * 4, a);
        bar_sync(2, 128);
#pragma unroll
        for (int jn = 0; jn < 2; jn++) {
          float m0 = mh[2 * jn], m1 = mh[2 * jn + 1];
#pragma unroll
          for (int i = 0; i < 4; i++) { const float2 v = ldsf2(sb + OFF_RED + i * 64 + (8 * jn + 2 * t) * 4); m0 = fmaxf(m0, v.x); m1 = fmaxf(m1, v.y); }
          const float a0 = ex2(mh[2 * jn] - m0), a1 = ex2(mh[2 * jn + 1] - m1);
          mh[2 * jn] = m0; mh[2 * jn + 1] = m1;
          L[4 * jn] *= a0; L[4 * jn + 1] *= a1; L[4 * jn + 2] *= a0; L[4 * jn + 3] *= a1;
          if (tid < 4) sts2f(sb + OFF_ALPHA + (8 * jn + 2 * t) * 4, a0, a1);
        }
        asm volatile("barrier.cta.arrive.aligned 1, 256;" ::: "memory");
#pragma unroll
        for (int i = 0; i < 8; i++) x[i] = S[i] - mh[2 * (i >> 2) + (i & 1)];
        write_p(x);
        bar_over(0.f);
      }
      const uint32_t dpt = __shfl_sync(~0u, desc_lo(OFF_PT) + (tl & 1) * 128, 0);
      wg_fence();
#pragma unroll
      for (int ks = 0; ks < 4; ks++) wgmma_n16_ones(L, ONE2, dpt + ks * 2);
      wg_commit();
    };
    uint32_t da = desc_lo(OFF_RING);
#pragma unroll 1
    for (int tl = 0; tl < 7; tl++) {
      if (tl == 5) { load_frags(); }
      uint32_t ok = 0;
#pragma unroll
      for (int u = 0; u < 4; u++) ok += mbar_test(BAR(BAR_FULL + 4 * tl + u));
      ok = __reduce_min_sync(~0u, ok);
      const uint32_t du = __shfl_sync(~0u, da, 0);
#pragma unroll
      for (int u = 0; u < 4; u++) {
        if (ok != 4) mbar_wait(BAR(BAR_FULL + 4 * tl + u));
        wg_fence();
#pragma unroll
        for (int k = 0; k < 8; k++) {
          const int i = 8 * u + k;
          if (i == 0) wgmma_n16<0, 0>(S, du, dq); else wgmma_n16<0, 1>(S, du + (i >> 2) * 512 + (i & 3) * 2, dq + (i >> 2) * 128 + (i & 3) * 2);
        }
        wg_commit();
      }
      wg_wait<0>();
      acc_fence(S); acc_fence(L);
      if (tl == 0) CLK(15);
      if (tl == 1) CLK(17);
      softmax(tl);
      if (tl == 0) CLK(16);
      if (tl == 1) CLK(18);
      if (tl == 3) CLK(19);
      if (tl == 6) CLK(20);
      da = (tl == 2 || tl == 5) ? da - 8192 : da + 4096;
    }
    mbar_wait(BAR(BAR_ALLCLR));
    uint32_t* const mlo = pin(gin + blk(4 * (16 * hh + 4 * (g & 2) + 2 * t + (g & 1)) + 1, 6, g >> 2) + bs * 2);
#pragma unroll
    for (int i = 0; i < 32; i++) {
      if (i == 0 || i == 8 || i == 16 || i == 24 || i == 28) {
        if (i) wg_commit();
        mbar_wait(BAR(BAR_LAST + (i == 28 ? 4 : i >> 3)));
        if (i == 28) CLK(21);
        wg_fence();
      }
      if (i == 0) wgmma_n16<0, 0>(S, desc_lo(65536), dq); else wgmma_n16<0, 1>(S, desc_lo(65536) + (i >> 2) * 512 + (i & 3) * 2, dq + (i >> 2) * 128 + (i & 3) * 2);
    }
    wg_commit();
    wg_wait<0>();
    acc_fence(S); acc_fence(L);
    CLK(22);
    softmax(7);
    CLK(23);
    thand = clk32();
    wg_wait<0>();
    acc_fence(L);
    if (tid < 32) red_u64(mlo, __float_as_uint(g & 2 ? (g & 1 ? mh[3] : mh[2]) : (g & 1 ? mh[1] : mh[0])), __float_as_uint(g & 2 ? (g & 1 ? L[5] : L[4]) : (g & 1 ? L[1] : L[0])));
    CLK(24);
  } else {
    float O[8][8];
#pragma unroll
    for (int i = 0; i < 8; i++)
#pragma unroll
      for (int k = 0; k < 8; k++) O[i][k] = 0.f;
    constexpr uint32_t dp = desc_lo(OFF_PT);
    auto handover = [&](int tl) {
      uint32_t over = opaque0 + (tl == 0);
#pragma unroll 1
      do {
        if (over) {
          cbar();
#pragma unroll
          for (int jn = 0; jn < 2; jn++) {
            const float2 a = ldsf2(sb + OFF_ALPHA + (8 * jn + 2 * t) * 4);
#pragma unroll
            for (int mb = 0; mb < 8; mb++) { O[mb][4 * jn] *= a.x; O[mb][4 * jn + 1] *= a.y; O[mb][4 * jn + 2] *= a.x; O[mb][4 * jn + 3] *= a.y; }
          }
        }
        over++;
      } while (bar_over(0.f));
    };
    uint32_t da = desc_lo(OFF_RING);
    uint32_t* x1o[8] = {};
#pragma unroll 1
    for (int tl = 0; tl < 8; tl++) {
      if (tl == 5) load_frags();
      if (tl == 7) {
        mbar_wait(BAR(BAR_ALLCLR));
#pragma unroll
        for (int i = 0; i < 8; i++)
          x1o[i] = inbox((16 * hh + 8 * ((i >> 1) & 1) + 2 * t + (i & 1)) * 4 + 2 * (i >> 2) + (wq >> 1), bs >> 4) + (bs & 15) * 64 + ((wq & 1) * 8 + g) * 4;
      }
      handover(tl);
      CLK(23);
      thand = clk32();
      const uint32_t dpt = dp + (tl & 1) * 128;
      wg_fence();
#pragma unroll
      for (int i = 0; i < 32; i++) wgmma_n16<1, 1>(O[i >> 2], da + (i >> 2) * 512 + (i & 3) * 128, dpt + (i & 3) * 2);
      wg_commit();
      da = (tl == 2 || tl == 5) ? da - 8192 : da + 4096;
      wg_wait<0>();
#pragma unroll
      for (int mb = 0; mb < 8; mb++) acc_fence(O[mb]);
      if (lane == 0) mbar_arrive(BAR(BAR_EMPTY + tl));
      if (tl == 0) CLK(16);
      if (tl == 1) CLK(18);
      if (tl == 3) CLK(19);
      if (tl == 6) CLK(20);
    }
    CLK(22);
#pragma unroll
    for (int i = 0; i < 8; i++) {
      const int J = i >> 2, k = 4 * ((i >> 1) & 1) + (i & 1);
      stg_cvt8(x1o[i], O[4 * J][k], O[4 * J][k + 2], O[4 * J + 1][k], O[4 * J + 1][k + 2], O[4 * J + 2][k], O[4 * J + 2][k + 2], O[4 * J + 3][k], O[4 * J + 3][k + 2]);
    }
    CLK(24);
  }

  {
    const uint32_t* px = pin(inbox(cta, w >> 1) + (w & 1) * 512 + lane * 2);
    uint32_t* const x2o = pin(inbox(cta, 4) + 512 + tid * 2);
    uint32_t* const x2p = pin(gin + blk(cta, 4, selector(cta) ^ 1) + 512 + tid * 2);
    const uint32_t q4 = lds1(sb + OFF_SEL + 4 * hI) ^ 0x00010100u;
    const uint32_t same = pin((uint32_t)(q4 == 0 || q4 == 0x01010101u));
    mbar_wait(BAR(BAR_TS));
    anchor = lds1(sb + OFF_TS);
    const uint32_t sdst = pin(sb + OFF_BS4 + w * 272 + lane * 8), ssrc = pin(sb + OFF_BS4 + (lane & 7) * 272 + (lane >> 3) * 16);
    float d[4] = {0.f, 0.f, 0.f, 0.f};
    if (cta >= NFF) {
#pragma unroll
      for (int s = 0; s < 4; s++) { cbf[s].x = silu2(cbf[s].x); cbf[s].y = silu2(cbf[s].y); }
    }
    wait_clk(thand, T.D_X1);
    wait_clk(anchor, T.A_X1 - T.R_X0);
    uint2 v[8];
    load_units<8, 64>(v, px);
    if (T.R_X0) {
      wait_clk(anchor, T.A_X1);
#pragma unroll
      for (int i = 0; i < 8; i++) reload_unit(v[i], px + i * 64);
    }
    CLK(25);
    const bool early = __all_sync(~0u, mbar_test(BAR(BAR_WUV + wg)));
    if (early) load_a_t(aw, abase + OFF_WUV);
    mbar_wait(BAR(BAR_WV));
    const float4 wa = ldsf4(sb + OFF_WV + w * 32), wb = ldsf4(sb + OFF_WV + w * 32 + 16);
    const float wv[8] = {wa.x, wa.y, wa.z, wa.w, wb.x, wb.y, wb.z, wb.w};
    CLK(27);
    uint32_t it = opaque0;
    bool ok;
#pragma unroll 1
    do {
      if (it) {
#pragma unroll
        for (int i = 0; i < 8; i++) reload_unit(v[i], px + i * 64);
        if (it > SPIN_LIMIT) __trap();
      }
      it++;
      float a0 = 0.f, a1 = 0.f, a2 = 0.f, a3 = 0.f;
#pragma unroll
      for (int i = 0; i < 8; i++) { a0 += wv[i] * bf_lo(v[i].x); a1 += wv[i] * bf_hi(v[i].x); a2 += wv[i] * bf_lo(v[i].y); a3 += wv[i] * bf_hi(v[i].y); }
      ok = __all_sync(~0u, min_flags(v) != 0);
      sts2(sdst, pack_bf16(a0, a1), pack_bf16(a2, a3));
    } while (!ok);
    CLK(29);
    cbar();
    uint32_t b[4][4];
#pragma unroll
    for (int kk = 0; kk < 4; kk++) ldsm4(b[kk], ssrc + kk * 64);
    if (__builtin_expect(!early, 0)) { mbar_wait(BAR(BAR_WUV + wg)); load_a_t(aw, abase + OFF_WUV); }
    mma128(d, aw, b);
    const uint32_t c0 = pack_bf16(d[0], d[1]), c1 = pack_bf16(d[2], d[3]);
    stg_u64(x2o, c0, c1);
    stg_u64_unless(same, x2p, c0, c1);
    ITS(4, it - 1);
    tstore = clk32();
    CLK(30);
  }
  {
    uint32_t* const o = pin(inbox(4 * (8 * jI + w) + t, 4) + hI * 16 + g * 2);
    const uint32_t* x2i[4];
#pragma unroll
    for (int i = 0; i < 4; i++) x2i[i] = pin(nearbox(4 * hI + i, 4) + 512 + tid * 2);
    const uint32_t sdst = pin(sb + OFF_BS5 + (16 * w + g) * 16 + t * 4), ssrc = pin(sb + OFF_BS5 + lane * 16);
    float d[4] = {0.f, 0.f, 0.f, 0.f};
    wait_clk(tstore, T.D_X2);
    uint2 v[4];
#pragma unroll
    for (int i = 0; i < 4; i++) v[i] = ldg_u64(x2i[i]);
    const bool early = __all_sync(~0u, mbar_test(BAR(BAR_WO + wg)));
    if (early) load_a_t(aw, abase + OFF_WO);
    CLK(31);
    uint32_t it = opaque0;
    bool ok;
#pragma unroll 1
    do {
      if (it) {
#pragma unroll
        for (int i = 0; i < 4; i++) reload_unit(v[i], x2i[i]);
        if (it > SPIN_LIMIT) __trap();
      }
      it++;
      ok = __all_sync(~0u, min_flags(v) != 0);
      sum4_to_smem(v, sdst);
    } while (!ok);
    CLK(32);
    cbar();
    uint32_t b[4][4];
#pragma unroll
    for (int kk = 0; kk < 4; kk++) ldsm4t(b[kk], ssrc + kk * 512);
    if (__builtin_expect(!early, 0)) { mbar_wait(BAR(BAR_WO + wg)); load_a_t(aw, abase + OFF_WO); }
    mma128(d, aw, b);
    stg_u64(o, movm(pack_bf16(d[0], d[1])), movm(pack_bf16(d[2], d[3])));
    ITS(5, it - 1);
    tstore = clk32();
    CLK(33);
    if (lane == 0) mbar_arrive(BAR(BAR_P5D));
  }
  if (cta < NFF) {
    const int mi = lane >> 3, r = lane & 7;
    uint32_t a1[2][4][4], a2[2][2][4];
    check_units<4, 64>(sbf, pcb);
    check_units<4, 64>(cbf, pcb + 2048);
    __syncwarp();
#pragma unroll
    for (int s = 0; s < 4; s++) { cbf[s].x = hadd2(cbf[s].x, ONE2); cbf[s].y = hadd2(cbf[s].y, ONE2); }
    mbar_wait(BAR(BAR_W1));
#pragma unroll
    for (int mt = 0; mt < 2; mt++) {
#pragma unroll
      for (int ks = 0; ks < 4; ks++) ldsm4t(a1[mt][ks], sb + OFF_W1 + (64 * w + 16 * ks + 8 * (mi >> 1) + r) * 64 + (((2 * mt + (mi & 1)) ^ (r >> 1)) << 4));
      float u[4] = {0.f, 0.f, 0.f, 0.f}, vv[4] = {0.f, 0.f, 0.f, 0.f};
#pragma unroll
      for (int s = 0; s < 4; s++) { mma16816(u, a1[mt][s], cbf[s].x, cbf[s].y); mma16816(vv, a1[mt][s], sbf[s].x, sbf[s].y); }
      sts4f(sb + OFF_REDU + w * 1024 + mt * 512 + lane * 16, u[0], u[1], u[2], u[3]);
      sts4f(sb + OFF_REDV + w * 1024 + mt * 512 + lane * 16, vv[0], vv[1], vv[2], vv[3]);
    }
    const uint32_t* xb = pin(nearbox(cta & ~15, 6 + wg) + (16 * wq + t) * 16 + g * 2);
    uint32_t* const ox[2] = {pin(inbox(64 * hh + 8 * w + t, 5) + bs * 16 + g * 2), pin(inbox(64 * hh + 8 * w + 4 + t, 5) + bs * 16 + g * 2)};
    cbar();
    const int lp = (tid >> 2) & 31, kq = tid & 3;
    const int fo = 16 * wg + (lp >> 2) + 8 * (kq >> 1), bo = 2 * (lp & 3) + (kq & 1);
    float U = 0.f, V = 0.f;
#pragma unroll
    for (int i = 0; i < 8; i++) { U += ldsf(sb + OFF_REDU + i * 1024 + tid * 4); V += ldsf(sb + OFF_REDV + i * 1024 + tid * 4); }
    U = pin(U); V = pin(V);
    const uint32_t s_g = pin(sb + OFF_REDG + w * 1024 + lane * 16), s_s = pin(sb + OFF_REDS + g * 80 + w * 8);
    const uint32_t l_g = pin(sb + OFF_REDG + tid * 4), l_s = pin(sb + OFF_REDS + bo * 80), s_h = pin(sb + OFF_H1 + fo * 16 + bo * 2);
    CLK(34);
    wait_clk(tstore, T.D_X3B);
    wait_clk(anchor, T.A_X1 + T.R_X3A + T.R_X3B);
    uint2 x[4];
    load_units<4, 64>(x, xb);
    mbar_wait(BAR(BAR_W2));
#pragma unroll
    for (int i = 0; i < 4; i++)
      ldsm4t(a2[i >> 1][i & 1], sb + OFF_W2 + (w >> 1) * 4096 + (16 * (i & 1) + 8 * (mi >> 1) + r) * 128 + (((4 * (w & 1) + 2 * (i >> 1) + (mi & 1)) ^ r) << 4));
    CLK(35);
    uint32_t it = opaque0;
    float G[2][2][4], S[2][4];
#pragma unroll 1
    do {
      if (it) {
#pragma unroll
        for (int i = 0; i < 4; i++) reload_unit(x[i], xb + i * 64);
        if (it > SPIN_LIMIT) __trap();
      }
      it++;
#pragma unroll
      for (int i = 0; i < 8; i++) { G[0][i >> 2][i & 3] = G[1][i >> 2][i & 3] = S[i >> 2][i & 3] = 0.f; }
#pragma unroll
      for (int s = 0; s < 4; s++) {
        const uint32_t sx[4] = {x[s].x, ONE2, x[s].y, ONE2};
        mma16816(S[s & 1], sx, x[s].x, x[s].y);
        const uint32_t y0 = hmul2(x[s].x, cbf[s].x), y1 = hmul2(x[s].y, cbf[s].y);
        mma16816(G[0][s & 1], a1[0][s], y0, y1);
        mma16816(G[1][s & 1], a1[1][s], y0, y1);
      }
    } while (!__all_sync(~0u, min_flags(x) != 0));
    if (t == (g >> 1)) sts2f(s_s, (g & 1) ? S[0][3] + S[1][3] : S[0][2] + S[1][2], (g & 1) ? S[0][1] + S[1][1] : S[0][0] + S[1][0]);
#pragma unroll
    for (int mt = 0; mt < 2; mt++)
      sts4f(s_g + mt * 512, G[mt][0][0] + G[mt][1][0], G[mt][0][1] + G[mt][1][1], G[mt][0][2] + G[mt][1][2], G[mt][0][3] + G[mt][1][3]);
    CLK(37);
    cbar();
    {
      float gv[8];
      float4 sv[4];
#pragma unroll
      for (int i = 0; i < 4; i++) sv[i] = ldsf4(l_s + i * 16);
#pragma unroll
      for (int i = 0; i < 8; i++) gv[i] = ldsf(l_g + i * 1024);
      const float s1 = ((sv[0].x + sv[0].z) + (sv[1].x + sv[1].z)) + ((sv[2].x + sv[2].z) + (sv[3].x + sv[3].z));
      const float s2 = ((sv[0].y + sv[0].w) + (sv[1].y + sv[1].w)) + ((sv[2].y + sv[2].w) + (sv[3].y + sv[3].w));
      const float gsum = ((gv[0] + gv[1]) + (gv[2] + gv[3])) + ((gv[4] + gv[5]) + (gv[6] + gv[7]));
      const float mu = s1 * (1.f / 512.f);
      float rs;
      asm("rsqrt.approx.ftz.f32 %0, %1;" : "=f"(rs) : "f"(fmaxf(s2 * (1.f / 512.f) - mu * mu, 0.f) + 1e-5f));
      const float hv = fmaxf(rs * (gsum - mu * U) + V, 0.f);
      asm volatile("st.shared.u16 [%0], %1;" ::"r"(s_h), "h"(__bfloat16_as_ushort(__float2bfloat16(hv))) : "memory");
    }
    ITS(6, it - 1);
    CLK(38);
    cbar();
    uint32_t b[4];
    ldsm4t(b, sb + OFF_H1 + lane * 16);
    float o[2][2][4] = {};
#pragma unroll
    for (int i = 0; i < 4; i++) mma16816(o[i >> 1][i & 1], a2[i >> 1][i & 1], b[2 * (i & 1)], b[2 * (i & 1) + 1]);
#pragma unroll
    for (int mb = 0; mb < 2; mb++)
      stg_u64(ox[mb], movm(pack_bf16(o[mb][0][0] + o[mb][1][0], o[mb][0][1] + o[mb][1][1])), movm(pack_bf16(o[mb][0][2] + o[mb][1][2], o[mb][0][3] + o[mb][1][3])));
    CLK(39);
    if (lane == 0) mbar_arrive(BAR(BAR_P7D));
  } else {
    const int mi = lane >> 3, r = lane & 7;
    mbar_wait(BAR(BAR_W1));
#pragma unroll
    for (int mt = 0; mt < 2; mt++) {
      float u[4] = {0.f, 0.f, 0.f, 0.f};
#pragma unroll
      for (int ks = 0; ks < 4; ks++) ldsm4t(aw[4 * mt + ks], sb + OFF_W1 + (64 * w + 16 * ks + 8 * (mi >> 1) + r) * 64 + (((2 * mt + (mi & 1)) ^ (r >> 1)) << 4));
#pragma unroll
      for (int ks = 0; ks < 4; ks++) mma16816(u, aw[4 * mt + ks], cbf[ks].x, cbf[ks].y);
      sts4f(sb + OFF_REDU + w * 1024 + mt * 512 + lane * 16, u[0], u[1], u[2], u[3]);
    }
    cbar();
    if (w < 2) {
      float4 v[8];
#pragma unroll
      for (int i = 0; i < 8; i++) v[i] = ldsf4(sb + OFF_REDU + i * 1024 + tid * 16);
      stg_u64(gs->MOD2[par] + (96 + 2 * (cta - NFF) + w) * 64 + t * 16 + g * 2,
              movm(pack_bf16(((v[0].x + v[1].x) + (v[2].x + v[3].x)) + ((v[4].x + v[5].x) + (v[6].x + v[7].x)), ((v[0].y + v[1].y) + (v[2].y + v[3].y)) + ((v[4].y + v[5].y) + (v[6].y + v[7].y)))),
              movm(pack_bf16(((v[0].z + v[1].z) + (v[2].z + v[3].z)) + ((v[4].z + v[5].z) + (v[6].z + v[7].z)), ((v[0].w + v[1].w) + (v[2].w + v[3].w)) + ((v[4].w + v[5].w) + (v[6].w + v[7].w)))));
    }
    CLK(26);
  }
  CLK_DUMP();
}

typedef CUresult (*EncodeTiledFn)(CUtensorMap*, CUtensorMapDataType, cuuint32_t, void*, const cuuint64_t*, const cuuint64_t*,
                                  const cuuint32_t*, const cuuint32_t*, CUtensorMapInterleave, CUtensorMapSwizzle,
                                  CUtensorMapL2promotion, CUtensorMapFloatOOBfill);

struct Dim { uint64_t size, stride; uint32_t box; };
template <int R> void encode_map(EncodeTiledFn enc, CUtensorMap* m, const void* base, const Dim (&d)[R], CUtensorMapSwizzle sw, CUtensorMapL2promotion promo) {
  cuuint64_t dims[R], strides[R];
  cuuint32_t box[R], es[R];
  for (int i = 0; i < R; i++) { dims[i] = d[i].size; strides[i] = d[i].stride; box[i] = d[i].box; es[i] = 1; }
  enc(m, CU_TENSOR_MAP_DATA_TYPE_BFLOAT16, R, const_cast<void*>(base), dims, strides + 1, box, es, CU_TENSOR_MAP_INTERLEAVE_NONE, sw, promo,
      CU_TENSOR_MAP_FLOAT_OOB_FILL_NONE);
}

}

extern "C" void kernel_launch(void* const* d_in, const int* in_sizes, int n_in, void* d_out, int out_size) {
  (void)in_sizes; (void)n_in; (void)out_size;
  static EncodeTiledFn enc = nullptr;
  static Scratch* scratch = nullptr;
  static uint32_t* inbox = nullptr;
  if (!enc) {
    void* sp = nullptr;
    cudaGetSymbolAddress(&sp, g_s);
    scratch = (Scratch*)sp;
    cudaGetSymbolAddress(&sp, g_in);
    inbox = (uint32_t*)(((uintptr_t)sp + 0xfffff) & ~(uintptr_t)0xfffff);
    void* fn = nullptr;
    cudaDriverEntryPointQueryResult q;
    cudaGetDriverEntryPoint("cuTensorMapEncodeTiled", &fn, cudaEnableDefault, &q);
    enc = (EncodeTiledFn)fn;
    cudaFuncSetAttribute(fused_decode_kernel, cudaFuncAttributeMaxDynamicSharedMemorySize, SMEM_BYTES);
  }
  const CUtensorMapSwizzle S128 = CU_TENSOR_MAP_SWIZZLE_128B, S0 = CU_TENSOR_MAP_SWIZZLE_NONE;
  const CUtensorMapL2promotion L0 = CU_TENSOR_MAP_L2_PROMOTION_NONE, L128 = CU_TENSOR_MAP_L2_PROMOTION_L2_128B;
  Params P;
  encode_map<2>(enc, &P.wq, d_in[2], {{4096, 2, 64}, {512, 8192, 64}}, S128, L0);
  encode_map<5>(enc, &P.wuk, d_in[3], {{4096, 2, 64}, {2, 8192, 2}, {4, 4 * 8192, 4}, {2, 2 * 8192, 2}, {32, 16 * 8192, 4}}, S128, L0);
  encode_map<2>(enc, &P.wm2, d_in[10], {{3072, 2, 16}, {512, 6144, 256}}, S0, L128);
  encode_map<2>(enc, &P.wm3, d_in[10], {{3072, 2, 32}, {512, 6144, 256}}, CU_TENSOR_MAP_SWIZZLE_64B, L128);
  encode_map<3>(enc, &P.ckv2, d_in[1], {{64, 2, 64}, {8 * 4096, 1024, 64}, {8, 128, 2}}, S128, L0);
  encode_map<3>(enc, &P.ckv1, d_in[1], {{64, 2, 64}, {8 * 4096, 1024, 64}, {8, 128, 1}}, S128, L0);
  encode_map<5>(enc, &P.wuv, d_in[4], {{4096, 2, 64}, {2, 8 * 8192, 2}, {8, 64 * 8192, 4}, {8, 8192, 8}, {4, 16 * 8192, 1}}, S128, L0);
  encode_map<2>(enc, &P.wo, d_in[5], {{512, 2, 64}, {4096, 1024, 64}}, S128, L0);
  encode_map<2>(enc, &P.w1, d_in[7], {{1792, 2, 32}, {512, 3584, 256}}, CU_TENSOR_MAP_SWIZZLE_64B, L128);
  encode_map<3>(enc, &P.w2, d_in[8], {{64, 2, 64}, {1792, 1024, 32}, {8, 128, 2}}, S128, L0);
  fused_decode_kernel<<<NCTA, NTHREADS, SMEM_BYTES>>>((__nv_bfloat16*)d_out, scratch, (const uint8_t*)d_in[10], (const uint8_t*)d_in[0],
                     (const uint8_t*)d_in[9], inbox,
                     P);
}
```

```cpp
#include <cuda_runtime.h>
#include <cuda.h>
#include <cuda_bf16.h>
#include <stdint.h>
#define V4 1

namespace {

constexpr int NCTA = 128;
constexpr int NTHREADS = 320;
constexpr int NFG = 56;
constexpr int NFF = 2 * NFG;
constexpr int NSYNC = 4;

constexpr uint32_t OFF_RING = 0;
constexpr uint32_t OFF_WUK = 131072;
constexpr uint32_t OFF_WQ = 131072 + 32768;
constexpr uint32_t OFF_WM2 = 65536 + 49152;
constexpr uint32_t OFF_WUV = 131072;
constexpr uint32_t OFF_WO = 131072 + 32768;
constexpr uint32_t OFF_W1 = 0;
constexpr uint32_t OFF_W2 = 32768;
constexpr uint32_t OFF_Q = 196608;
constexpr uint32_t OFF_PT = 212992;
constexpr uint32_t OFF_SCR = 217088;
constexpr uint32_t OFF_XS = 65536;
constexpr uint32_t OFF_CS = 65536 + 8192;
constexpr uint32_t OFF_P0S = 65536 + 16384;
constexpr uint32_t OFF_BS1 = OFF_SCR + 2048;
constexpr uint32_t OFF_BS2 = OFF_SCR + 4096;
constexpr uint32_t OFF_P0B = OFF_SCR + 6144;
constexpr uint32_t OFF_XN = OFF_SCR + 8192;
constexpr uint32_t OFF_RED = OFF_SCR + 10496;
constexpr uint32_t OFF_ALPHA = OFF_SCR + 11072;
constexpr uint32_t OFF_WV = OFF_SCR + 6144;
constexpr uint32_t OFF_SEL = OFF_SCR + 10752;
constexpr uint32_t OFF_TS = OFF_SCR + 11136;
constexpr uint32_t OFF_BARS = OFF_SCR + 11264;
constexpr uint32_t SMEM_BYTES = OFF_BARS + 512;
constexpr uint32_t OFF_BS4 = OFF_Q;
constexpr uint32_t OFF_H1 = OFF_Q + 2304;
constexpr uint32_t OFF_REDS = OFF_Q + 2816;
constexpr uint32_t OFF_BS5 = OFF_Q + 4096;
constexpr uint32_t OFF_REDG = OFF_Q + 8192;
constexpr uint32_t OFF_REDU = 65536;
constexpr uint32_t OFF_REDV = 65536 + 8192;

constexpr int BAR_FULL = 0;
constexpr int BAR_LAST = 28;
constexpr int BAR_WUK = 33, BAR_WM2 = 35, BAR_WUV = 36, BAR_WO = 38, BAR_W1 = 40, BAR_W2 = 41;
constexpr int BAR_ALLCLR = 42, BAR_TS = 43, BAR_WV = 44;
constexpr int BAR_EMPTY = 45;
constexpr int BAR_P0BD = 53;
constexpr int BAR_P1D = 54, BAR_P2D = 55;
constexpr int BAR_P5D = 56, BAR_P7D = 57;
constexpr int NBARS = 58;
constexpr int BAR_XC = 58, BAR_WQ = 59;
constexpr int BAR_C = 61;
constexpr uint32_t SB = 1024;

#define TUNE_LIST(X) \
  X(PC_T0, 355) X(PC_P1, 320) X(PC_PM, 225) X(PC_P2, 319) X(PC_STAG, 390) X(PC_SL, 500) X(PC_NW, 6) \
  X(T_UV, 225) X(P_UV, 245) X(PF_N, 3) X(T_PF, 1060) X(P_PF, 230) X(T_O, 2040) X(P_O, 205) X(T_1, 2990) X(T_2, 3700) X(T_GB, 3600) X(P_F, 300) \
  X(PR_T0, 1000) X(PR_N, 4) X(CLR_T0, 3900) X(CLR_CLK, 190) \
  X(D_MOD, 1450) X(D_QP, 1200) X(D_QX, 950) X(TS_P, 1) X(TS_O, 1270) X(D_TS, 700) X(A_M, 1600) X(D_X1, 1400) X(A_X1, 2460) X(R_X0, 1500) \
  X(D_X2, 260) X(D_X3A, 60) X(R_X3A, 2790) X(D_X3B, 800) X(R_X3B, 915) X(D_FIN, 350) X(R_FIN, 1540)
struct Tune {
#define X(n, v) static constexpr int n = v;
  TUNE_LIST(X)
#undef X
};

struct Scratch {
  uint32_t MOD1[2][4 * 64 * 64];
  uint32_t MOD2[2][128 * 64];
  uint32_t QP[2][128 * 256 * 2];
  uint32_t QX[2][8 * 32 * 256];
  uint32_t epoch;
  uint32_t pad[31];
  uint32_t sync[NSYNC][32];
};
__device__ Scratch g_s;
__device__ uint32_t g_in[(128 + 16) * 16384];
__device__ __forceinline__ uint32_t blk(int c, int k, uint32_t sel) { return c * 16384 + k * 2048 + ((sel ^ k) & 1) * 1024; }
__device__ __forceinline__ uint32_t flip(int c) { return c ^ (c >> 1) ^ (c >> 3); }

#define CLK_DECL
#define CLK(i) do {} while (0)
#define CLK_DUMP() do {} while (0)
#define ITS(i, v) do {} while (0)

struct Params {
  CUtensorMap wq, wuk, wm2, wm3, ckv2, ckv1, wuv, wo, w1, w2;
};

__device__ __forceinline__ void mbar_init(uint32_t bar, int cnt) { asm volatile("mbarrier.init.shared::cta.b64 [%0], %1;" ::"r"(bar), "r"(cnt)); }
__device__ __forceinline__ void mbar_expect(uint32_t bar, uint32_t bytes) { asm volatile("mbarrier.arrive.expect_tx.shared::cta.b64 _, [%0], %1;" ::"r"(bar), "r"(bytes) : "memory"); }
__device__ __forceinline__ void mbar_arrive(uint32_t bar) { asm volatile("mbarrier.arrive.shared::cta.b64 _, [%0];" ::"r"(bar) : "memory"); }
__device__ __forceinline__ uint32_t clk32() { unsigned long long c; asm volatile("mov.u64 %0, %%clock64;" : "=l"(c) :: "memory"); return (uint32_t)c; }
__device__ __forceinline__ uint32_t gtime32() { uint32_t c; asm volatile("mov.u32 %0, %%globaltimer_lo;" : "=r"(c) :: "memory"); return c; }
__device__ __forceinline__ void wait_clk(uint32_t t0, int clocks) { while ((int)(clk32() - t0) < clocks) {} }
__device__ __forceinline__ void backoff(int clocks) { if (clocks > 0) wait_clk(clk32(), clocks); }
__device__ __forceinline__ void until_ns(uint32_t ns) { while ((int)(gtime32() - ns) < 0) {} }
__device__ __forceinline__ void slot(uint32_t& tn, int slack) {
  uint32_t now;
  do { now = gtime32(); } while ((int)(now - tn) < 0);
  if ((int)(now - tn) > slack) tn = now - slack;
}
template <typename T> __device__ __forceinline__ T* pin(T* p) { asm volatile("" : "+l"(p)); return p; }
__device__ __forceinline__ uint32_t pin(uint32_t v) { asm volatile("" : "+r"(v)); return v; }
__device__ __forceinline__ float pin(float v) { asm volatile("" : "+f"(v)); return v; }
constexpr int SPIN_LIMIT = 1 << 22;
__device__ __forceinline__ void mbar_wait(uint32_t bar) {
  asm volatile("{\n.reg .pred p;\n.reg .u32 c;\nmov.u32 c, 0;\n"
               "MW_LOOP:\nmbarrier.try_wait.parity.shared::cta.b64 p, [%0], 0;\n@p bra MW_DONE;\n"
               "add.u32 c, c, 1;\nsetp.lt.u32 p, c, 4194304;\n@p bra MW_LOOP;\ntrap;\nMW_DONE:\n}"
               ::"r"(bar) : "memory");
}
__device__ __forceinline__ bool mbar_test(uint32_t bar) {
  uint32_t ok;
  asm volatile("{\n.reg .pred p;\nmbarrier.test_wait.parity.shared::cta.b64 p, [%1], 0;\nselp.u32 %0,1,0,p;\n}" : "=r"(ok) : "r"(bar) : "memory");
  return ok;
}
__device__ __forceinline__ void tma2d(uint32_t dst, const CUtensorMap* m, int c0, int c1, uint32_t bar, uint64_t pol) {
  asm volatile("cp.async.bulk.tensor.2d.shared::cluster.global.mbarrier::complete_tx::bytes.L2::cache_hint [%0], [%1, {%3,%4}], [%2], %5;"
               ::"r"(dst), "l"(m), "r"(bar), "r"(c0), "r"(c1), "l"(pol) : "memory");
}
__device__ __forceinline__ void tma2d_nohint(uint32_t dst, const CUtensorMap* m, int c0, int c1, uint32_t bar) {
  asm volatile("cp.async.bulk.tensor.2d.shared::cluster.global.mbarrier::complete_tx::bytes [%0], [%1, {%3,%4}], [%2];"
               ::"r"(dst), "l"(m), "r"(bar), "r"(c0), "r"(c1) : "memory");
}
__device__ __forceinline__ void tma3d(uint32_t dst, const CUtensorMap* m, int c0, int c1, int c2, uint32_t bar, uint64_t pol) {
  asm volatile("cp.async.bulk.tensor.3d.shared::cluster.global.mbarrier::complete_tx::bytes.L2::cache_hint [%0], [%1, {%3,%4,%5}], [%2], %6;"
               ::"r"(dst), "l"(m), "r"(bar), "r"(c0), "r"(c1), "r"(c2), "l"(pol) : "memory");
}
__device__ __forceinline__ void tma5d(uint32_t dst, const CUtensorMap* m, int c0, int c1, int c2, int c3, int c4, uint32_t bar, uint64_t pol) {
  asm volatile("cp.async.bulk.tensor.5d.shared::cluster.global.mbarrier::complete_tx::bytes.L2::cache_hint [%0], [%1, {%3,%4,%5,%6,%7}], [%2], %8;"
               ::"r"(dst), "l"(m), "r"(bar), "r"(c0), "r"(c1), "r"(c2), "r"(c3), "r"(c4), "l"(pol) : "memory");
}
__device__ __forceinline__ void bulk_ld(uint32_t dst, const void* src, uint32_t bytes, uint32_t bar) {
  asm volatile("cp.async.bulk.shared::cluster.global.mbarrier::complete_tx::bytes [%0], [%1], %2, [%3];" ::"r"(dst), "l"(src), "r"(bytes), "r"(bar) : "memory");
}
__device__ __forceinline__ void bar_sync(int id, int n) { asm volatile("barrier.cta.sync.aligned %0, %1;" ::"r"(id), "r"(n) : "memory"); }
__device__ __forceinline__ void cbar() { asm volatile("barrier.cta.sync.aligned 1, 256;" ::: "memory"); }
__device__ __forceinline__ bool bar_over(float ex) {
  uint32_t over;
  asm volatile("{\n.reg .pred p, q;\nsetp.gtu.f32 p, %1, 0f42700000;\nbarrier.cta.red.or.aligned.pred q, 4, 256, p;\nselp.u32 %0, 1, 0, q;\n}"
               : "=r"(over) : "f"(ex) : "memory");
  return over;
}

__device__ __forceinline__ uint32_t ldg_nc1(const void* p) { uint32_t v; asm volatile("ld.global.nc.L1::no_allocate.u32 %0, [%1];" : "=r"(v) : "l"(p)); return v; }
__device__ __forceinline__ uint2 ldg_nc2(const void* p) { uint2 v; asm volatile("ld.global.nc.v2.u32 {%0,%1}, [%2];" : "=r"(v.x), "=r"(v.y) : "l"(p)); return v; }
__device__ __forceinline__ uint4 ldg_nc4(const void* p) { uint4 v; asm volatile("ld.global.nc.L1::no_allocate.v4.u32 {%0,%1,%2,%3}, [%4];" : "=r"(v.x), "=r"(v.y), "=r"(v.z), "=r"(v.w) : "l"(p)); return v; }
__device__ __forceinline__ uint32_t ldg_rlx1(const void* p) { uint32_t v; asm volatile("ld.relaxed.gpu.global.u32 %0, [%1];" : "=r"(v) : "l"(p) : "memory"); return v; }
__device__ __forceinline__ void stg4(void* p, uint4 v) { asm volatile("st.relaxed.gpu.global.v4.u32 [%0], {%1,%2,%3,%4};" ::"l"(p), "r"(v.x), "r"(v.y), "r"(v.z), "r"(v.w) : "memory"); }
__device__ __forceinline__ void stg1(void* p, uint32_t a) { asm volatile("st.relaxed.gpu.global.u32 [%0], %1;" ::"l"(p), "r"(a) : "memory"); }
__device__ __forceinline__ uint32_t nz(uint32_t w) { return max(w, 1u); }
__device__ __forceinline__ uint2 ldg_u64(const void* p) {
  uint2 v; asm volatile("{\n.reg .b64 a;\nld.relaxed.gpu.global.b64 a, [%2];\nmov.b64 {%0,%1}, a;\n}" : "=r"(v.x), "=r"(v.y) : "l"(p) : "memory"); return v;
}
__device__ __forceinline__ uint4 ldg_2u64(const void* p) {
  uint4 v; asm volatile("{\n.reg .b64 a, b;\nld.relaxed.gpu.global.v2.b64 {a, b}, [%4];\nmov.b64 {%0,%1}, a;\nmov.b64 {%2,%3}, b;\n}" : "=r"(v.x), "=r"(v.y), "=r"(v.z), "=r"(v.w) : "l"(p) : "memory"); return v;
}
__device__ __forceinline__ void stg_u64(void* p, uint32_t x, uint32_t y) {
  asm volatile("{\n.reg .b32 y;\nmax.u32 y, %2, 1;\nst.relaxed.gpu.global.v2.b32 [%0], {%1, y};\n}" ::"l"(p), "r"(x), "r"(y) : "memory");
}
__device__ __forceinline__ void red_u64(void* p, uint32_t x, uint32_t y) {
  asm volatile("{\n.reg .b32 y;\n.reg .b64 a;\nmax.u32 y, %2, 1;\nmov.b64 a, {%1, y};\nred.relaxed.gpu.global.or.b64 [%0], a;\n}" ::"l"(p), "r"(x), "r"(y) : "memory");
}
__device__ __forceinline__ void stg_u64_unless(uint32_t bad, void* p, uint32_t x, uint32_t y) {
  asm volatile("{\n.reg .b32 y;\n.reg .pred q;\nsetp.eq.u32 q, %3, 0;\nmax.u32 y, %2, 1;\n@q st.relaxed.gpu.global.v2.b32 [%0], {%1, y};\n}" ::"l"(p), "r"(x), "r"(y), "r"(bad) : "memory");
}

__device__ __forceinline__ void stg_cvt8(void* p, float a0, float a1, float b0, float b1, float c0, float c1, float d0, float d1) {
  asm volatile("{\n.reg .b32 x, y, z, w;\ncvt.rn.bf16x2.f32 x, %2, %1;\ncvt.rn.bf16x2.f32 y, %4, %3;\ncvt.rn.bf16x2.f32 z, %6, %5;\ncvt.rn.bf16x2.f32 w, %8, %7;\n"
               "max.u32 y, y, 1;\nmax.u32 w, w, 1;\nst.relaxed.gpu.global.v4.b32 [%0], {x, y, z, w};\n}"
               ::"l"(p), "f"(a0), "f"(a1), "f"(b0), "f"(b1), "f"(c0), "f"(c1), "f"(d0), "f"(d1) : "memory");
}
__device__ __forceinline__ uint32_t pack_bf16(float lo, float hi) { uint32_t r; asm("cvt.rn.bf16x2.f32 %0, %1, %2;" : "=r"(r) : "f"(hi), "f"(lo)); return r; }
__device__ __forceinline__ float bf_lo(uint32_t w) { return __uint_as_float(w << 16); }
__device__ __forceinline__ float bf_hi(uint32_t w) { return __uint_as_float(w & 0xffff0000u); }
__device__ __forceinline__ float ex2(float x) { float r; asm("ex2.approx.ftz.f32 %0, %1;" : "=f"(r) : "f"(x)); return r; }
__device__ __forceinline__ uint32_t hmul2(uint32_t a, uint32_t b) { uint32_t r; asm("mul.rn.bf16x2 %0, %1, %2;" : "=r"(r) : "r"(a), "r"(b)); return r; }
__device__ __forceinline__ uint32_t hadd2(uint32_t a, uint32_t b) { uint32_t r; asm("add.rn.bf16x2 %0, %1, %2;" : "=r"(r) : "r"(a), "r"(b)); return r; }
__device__ __forceinline__ uint32_t silu2(uint32_t v) { const float a = bf_lo(v), b = bf_hi(v); return pack_bf16(__fdividef(a, 1.f + __expf(-a)), __fdividef(b, 1.f + __expf(-b))); }
constexpr uint32_t ONE2 = 0x3f803f80u;

__device__ __forceinline__ void ldsm4(uint32_t (&r)[4], uint32_t a) { asm volatile("ldmatrix.sync.aligned.m8n8.x4.shared.b16 {%0,%1,%2,%3}, [%4];" : "=r"(r[0]), "=r"(r[1]), "=r"(r[2]), "=r"(r[3]) : "r"(a) : "memory"); }
__device__ __forceinline__ void ldsm4t(uint32_t (&r)[4], uint32_t a) { asm volatile("ldmatrix.sync.aligned.m8n8.x4.trans.shared.b16 {%0,%1,%2,%3}, [%4];" : "=r"(r[0]), "=r"(r[1]), "=r"(r[2]), "=r"(r[3]) : "r"(a) : "memory"); }
__device__ __forceinline__ void stsm4t(uint32_t a, uint32_t r0, uint32_t r1, uint32_t r2, uint32_t r3) { asm volatile("stmatrix.sync.aligned.m8n8.x4.trans.shared.b16 [%0], {%1,%2,%3,%4};" ::"r"(a), "r"(r0), "r"(r1), "r"(r2), "r"(r3) : "memory"); }
__device__ __forceinline__ uint32_t movm(uint32_t a) { uint32_t d; asm volatile("movmatrix.sync.aligned.m8n8.trans.b16 %0, %1;" : "=r"(d) : "r"(a)); return d; }
__device__ __forceinline__ void mma16816(float (&d)[4], const uint32_t (&a)[4], uint32_t b0, uint32_t b1) {
  asm volatile("mma.sync.aligned.m16n8k16.row.col.f32.bf16.bf16.f32 {%0,%1,%2,%3}, {%4,%5,%6,%7}, {%8,%9}, {%0,%1,%2,%3};"
               : "+f"(d[0]), "+f"(d[1]), "+f"(d[2]), "+f"(d[3]) : "r"(a[0]), "r"(a[1]), "r"(a[2]), "r"(a[3]), "r"(b0), "r"(b1));
}
__device__ __forceinline__ void sts1(uint32_t a, uint32_t v) { asm volatile("st.shared.u32 [%0], %1;" ::"r"(a), "r"(v) : "memory"); }
__device__ __forceinline__ void sts2(uint32_t a, uint32_t x, uint32_t y) { asm volatile("st.shared.v2.u32 [%0], {%1,%2};" ::"r"(a), "r"(x), "r"(y) : "memory"); }
__device__ __forceinline__ void sts4(uint32_t a, uint4 v) { asm volatile("st.shared.v4.u32 [%0], {%1,%2,%3,%4};" ::"r"(a), "r"(v.x), "r"(v.y), "r"(v.z), "r"(v.w) : "memory"); }
__device__ __forceinline__ void sts2f(uint32_t a, float x, float y) { asm volatile("st.shared.v2.f32 [%0], {%1,%2};" ::"r"(a), "f"(x), "f"(y) : "memory"); }
__device__ __forceinline__ void sts4f(uint32_t a, float x, float y, float z, float w) { asm volatile("st.shared.v4.f32 [%0], {%1,%2,%3,%4};" ::"r"(a), "f"(x), "f"(y), "f"(z), "f"(w) : "memory"); }
__device__ __forceinline__ void stsf(uint32_t a, float v) { asm volatile("st.shared.f32 [%0], %1;" ::"r"(a), "f"(v) : "memory"); }
__device__ __forceinline__ uint32_t lds1(uint32_t a) { uint32_t v; asm volatile("ld.shared.u32 %0, [%1];" : "=r"(v) : "r"(a) : "memory"); return v; }
__device__ __forceinline__ float ldsf(uint32_t a) { float v; asm volatile("ld.shared.f32 %0, [%1];" : "=f"(v) : "r"(a) : "memory"); return v; }
__device__ __forceinline__ float2 ldsf2(uint32_t a) { float2 v; asm volatile("ld.shared.v2.f32 {%0,%1}, [%2];" : "=f"(v.x), "=f"(v.y) : "r"(a) : "memory"); return v; }
__device__ __forceinline__ float4 ldsf4(uint32_t a) { float4 v; asm volatile("ld.shared.v4.f32 {%0,%1,%2,%3}, [%4];" : "=f"(v.x), "=f"(v.y), "=f"(v.z), "=f"(v.w) : "r"(a) : "memory"); return v; }
__device__ __forceinline__ void lds4(uint32_t (&r)[4], uint32_t a) { asm volatile("ld.shared.v4.u32 {%0,%1,%2,%3}, [%4];" : "=r"(r[0]), "=r"(r[1]), "=r"(r[2]), "=r"(r[3]) : "r"(a) : "memory"); }

__device__ __forceinline__ void wg_fence() { asm volatile("wgmma.fence.sync.aligned;" ::: "memory"); }
__device__ __forceinline__ void wg_commit() { asm volatile("wgmma.commit_group.sync.aligned;" ::: "memory"); }
template <int N> __device__ __forceinline__ void wg_wait() { asm volatile("wgmma.wait_group.sync.aligned %0;" ::"n"(N) : "memory"); }
__host__ __device__ constexpr uint32_t desc_lo(uint32_t off) { return ((SB + off) >> 4) | 0x10000u; }
template <int TA, int ACC> __device__ __forceinline__ void wgmma_n16(float (&d)[8], uint32_t da, uint32_t db) {
  asm volatile("{\n.reg .b64 da, db;\nmov.b64 da, {%8, 0x40000040};\nmov.b64 db, {%9, 0x40000040};\n"
               "wgmma.mma_async.sync.aligned.m64n16k16.f32.bf16.bf16 {%0,%1,%2,%3,%4,%5,%6,%7}, da, db, %11, 1, 1, %10, 0;\n}"
               : "+f"(d[0]), "+f"(d[1]), "+f"(d[2]), "+f"(d[3]), "+f"(d[4]), "+f"(d[5]), "+f"(d[6]), "+f"(d[7])
               : "r"(da), "r"(db), "n"(TA), "n"(ACC));
}
__device__ __forceinline__ void wgmma_n16_ones(float (&d)[8], uint32_t one, uint32_t db) {
  asm volatile("{\n.reg .b64 db;\nmov.b64 db, {%9, 0x40000040};\n"
               "wgmma.mma_async.sync.aligned.m64n16k16.f32.bf16.bf16 {%0,%1,%2,%3,%4,%5,%6,%7}, {%8,%8,%8,%8}, db, 1, 1, 1, 0;\n}"
               : "+f"(d[0]), "+f"(d[1]), "+f"(d[2]), "+f"(d[3]), "+f"(d[4]), "+f"(d[5]), "+f"(d[6]), "+f"(d[7])
               : "r"(one), "r"(db));
}
__device__ __forceinline__ void acc_fence(float (&d)[8]) {
  asm volatile("" : "+f"(d[0]), "+f"(d[1]), "+f"(d[2]), "+f"(d[3]), "+f"(d[4]), "+f"(d[5]), "+f"(d[6]), "+f"(d[7]) :: "memory");
}

template <int N, int STRIDE> __device__ __forceinline__ void load_units(uint2 (&v)[N], const uint32_t* p) {
#pragma unroll
  for (int i = 0; i < N; i++) v[i] = ldg_u64(p + i * STRIDE);
}
__device__ __forceinline__ void reload_unit(uint2& v, const uint32_t* p) {
  asm volatile("{\n.reg .pred q;\nsetp.eq.u32 q, %1, 0;\n@q ld.relaxed.gpu.global.v2.b32 {%0, %1}, [%2];\n}" : "+r"(v.x), "+r"(v.y) : "l"(p) : "memory");
}
template <int N> __device__ __forceinline__ uint32_t min_flags(const uint2 (&v)[N]) {
  uint32_t a = v[0].y, b = v[1].y;
#pragma unroll
  for (int i = 2; i < N; i += 2) { a = min(a, v[i].y); b = min(b, v[i + 1].y); }
  return min(a, b);
}
template <int N, int STRIDE> __device__ __forceinline__ int check_units(uint2 (&v)[N], const uint32_t* p) {
  int it = 0;
  while (!__all_sync(~0u, min_flags(v) != 0)) {
#pragma unroll
    for (int i = 0; i < N; i++) reload_unit(v[i], p + i * STRIDE);
    if (++it > SPIN_LIMIT) __trap();
  }
  return it;
}
__device__ __forceinline__ void sum4_to_smem(const uint2 (&v)[4], uint32_t dst) {
  const float c0 = (bf_lo(v[0].x) + bf_lo(v[1].x)) + (bf_lo(v[2].x) + bf_lo(v[3].x));
  const float c1 = (bf_hi(v[0].x) + bf_hi(v[1].x)) + (bf_hi(v[2].x) + bf_hi(v[3].x));
  const float c2 = (bf_lo(v[0].y) + bf_lo(v[1].y)) + (bf_lo(v[2].y) + bf_lo(v[3].y));
  const float c3 = (bf_hi(v[0].y) + bf_hi(v[1].y)) + (bf_hi(v[2].y) + bf_hi(v[3].y));
  sts1(dst, pack_bf16(c0, c1));
  sts1(dst + 128, pack_bf16(c2, c3));
}
__device__ __forceinline__ uint32_t a_t_offset(int w, int lane) {
  const int mi = lane >> 3, r = lane & 7;
  return (w >> 2) * 16384 + (8 * (mi >> 1) + r) * 128 + (((2 * (w & 3) + (mi & 1)) ^ r) << 4);
}
__device__ __forceinline__ void load_a_t(uint32_t (&a)[8][4], uint32_t base) {
#pragma unroll
  for (int ks = 0; ks < 8; ks++) ldsm4t(a[ks], base + ks * 2048);
}
__device__ __forceinline__ void mma128(float (&d)[4], const uint32_t (&a)[8][4], const uint32_t (&b)[4][4]) {
  float e[4][4] = {{d[0], d[1], d[2], d[3]}, {0.f, 0.f, 0.f, 0.f}, {0.f, 0.f, 0.f, 0.f}, {0.f, 0.f, 0.f, 0.f}};
#pragma unroll
  for (int kk = 0; kk < 4; kk++) { mma16816(e[(2 * kk) & 3], a[2 * kk], b[kk][0], b[kk][1]); mma16816(e[(2 * kk + 1) & 3], a[2 * kk + 1], b[kk][2], b[kk][3]); }
#pragma unroll
  for (int i = 0; i < 4; i++) d[i] = (e[0][i] + e[1][i]) + (e[2][i] + e[3][i]);
}
template <int NP> __device__ __forceinline__ bool sum_pieces(const uint32_t* p0, uint32_t one, float (&r)[4]) {
  uint2 v[NP / 4];
  load_units<NP / 4, 64>(v, p0);
  float d[4][4] = {};
#pragma unroll
  for (int i = 0; i < NP / 8; i++) { const uint32_t a[4] = {v[2 * i].x, v[2 * i].y, v[2 * i + 1].x, v[2 * i + 1].y}; mma16816(d[i & 3], a, one, one); }
  const bool ok = __all_sync(~0u, min_flags(v) != 0);
#pragma unroll
  for (int k = 0; k < 4; k++) r[k] = (d[0][k] + d[1][k]) + (d[2][k] + d[3][k]);
  return ok;
}
template <typename F> __device__ __forceinline__ float reduce_g(const float (&x)[4], int lane, F f) {
  const bool u4 = lane & 16, u3 = lane & 8;
  const float a0 = f(u4 ? x[2] : x[0], __shfl_xor_sync(~0u, u4 ? x[0] : x[2], 16));
  const float a1 = f(u4 ? x[3] : x[1], __shfl_xor_sync(~0u, u4 ? x[1] : x[3], 16));
  const float b = f(u3 ? a1 : a0, __shfl_xor_sync(~0u, u3 ? a0 : a1, 8));
  return f(b, __shfl_xor_sync(~0u, b, 4));
}

__global__ void __launch_bounds__(NTHREADS, 1)
fused_decode_kernel(__nv_bfloat16* __restrict__ gout, Scratch* __restrict__ gs, const uint8_t* __restrict__ gwmod,
                    const uint8_t* __restrict__ gx, const uint8_t* __restrict__ gc, uint32_t* __restrict__ gin,
                    const __grid_constant__ Params P) {
  constexpr Tune T{};
  extern __shared__ __align__(1024) uint8_t smem_raw[];
  constexpr uint32_t sb = SB;
  const int tid = __shfl_xor_sync(0xffffffffu, threadIdx.x ^ 1, 1), lane = tid & 31;
  const int w = __shfl_sync(0xffffffffu, threadIdx.x >> 5, 0);
  const int cta = blockIdx.x;
  auto BAR = [](int i) { return SB + OFF_BARS + 8 * i; };
  auto selector = [&](int c) { uint32_t v; asm volatile("ld.shared.u8 %0, [%1];" : "=r"(v) : "r"(sb + OFF_SEL + c) : "memory"); return v; };
  auto inbox = [&](int c, int k) { return gin + blk(c, k, selector(c)); };
  auto nearbox = [&](int c, int k) { return gin + blk(c, k, selector(cta) ^ flip((c ^ cta) & 15)); };
  const int g = lane >> 2, t = lane & 3;
  const int hI = cta >> 2, jI = cta & 3;
  const int bs = cta >> 1, hh = cta & 1;

  CLK_DECL;
  CLK(0);
  if (w == 8) {
    CLK(7);
    const uint32_t t_entry = gtime32();
    CLK(8);
    if (lane == 0) {
      if ((uint32_t)__cvta_generic_to_shared(smem_raw) != SB) __trap();
      mbar_init(BAR(BAR_WQ), 1); mbar_init(BAR(BAR_WQ + 1), 1); mbar_init(BAR(BAR_XC), 1); mbar_init(BAR(BAR_C), 1);
      asm volatile("fence.mbarrier_init.release.cluster;" ::: "memory");
      asm volatile("prefetch.tensormap [%0];" ::"l"(&P.wq) : "memory");
      mbar_expect(BAR(BAR_XC), 8192); mbar_expect(BAR(BAR_C), 8192); mbar_expect(BAR(BAR_WQ), 16384); mbar_expect(BAR(BAR_WQ + 1), 16384);
      CLK(9);
    }
    __syncwarp();
    asm volatile("barrier.cta.arrive.aligned 0, %0;" ::"n"(NTHREADS) : "memory");
    CLK(10);
    uint32_t tn = t_entry + T.PC_T0 + ((bs * 37) & 63) * T.PC_STAG / 64;
    const int h = hI, j = jI;
    if (lane == 0) {
      uint64_t pol; asm volatile("createpolicy.fractional.L2::evict_first.b64 %0, 1.0;" : "=l"(pol));
#pragma unroll
      for (int u = 0; u < 4; u++) {
        until_ns(tn + u * T.PC_P1);
        if (u == 0) CLK(11);
        tma2d(sb + OFF_WQ + u * 8192, &P.wq, 128 * h + 64 * (u >> 1), 128 * j + 64 * (u & 1), BAR(BAR_WQ + (u >> 1)), pol);
        if (u == 0) {
#pragma unroll
          for (int i = 0; i < 8; i++) { const int o = ((i + cta) & 3) * 2048; bulk_ld(sb + OFF_XS + (i >> 2) * 8192 + o, (i < 4 ? gx : gc) + o, 2048, BAR(i < 4 ? BAR_XC : BAR_C)); }
          CLK(1);
          asm volatile("prefetch.tensormap [%0];" ::"l"(&P.wuk) : "memory");
          asm volatile("prefetch.tensormap [%0];" ::"l"(&P.wm2) : "memory");
          asm volatile("prefetch.tensormap [%0];" ::"l"(&P.ckv2) : "memory");
        }
      }
    }
    __syncwarp();
    tn += 4 * T.PC_P1;
    bar_sync(5, 64);
    if (lane == 0) {
      uint64_t pol; asm volatile("createpolicy.fractional.L2::evict_first.b64 %0, 1.0;" : "=l"(pol));
#pragma unroll
      for (int u = 0; u < 4; u++) {
        if (u & 1) mbar_wait(BAR(BAR_WQ + (u >> 1)));
        slot(tn, T.PC_SL);
        tma5d(sb + OFF_WUK + u * 8192, &P.wuk, 128 * h + 64 * (u >> 1), 0, 0, 0, 8 * j + 4 * (u & 1), BAR(BAR_WUK + (u >> 1)), pol);
        tn += T.PC_P1;
      }
#pragma unroll
      for (int u = 0; u < 2; u++) {
        if (u) mbar_wait(BAR(BAR_WUK));
        slot(tn, T.PC_SL);
        if (j != 3) tma2d_nohint(sb + OFF_WM2 + u * 8192, &P.wm2, 1024 + 16 * (3 * h + j), 256 * u, BAR(BAR_WM2));
        tn += T.PC_PM;
      }
      const int row0 = (bs >> 3) * 4096 + (bs & 7) * 64;
      uint32_t dst = sb + OFF_RING;
#pragma unroll 1
      for (int n = 0; n < 31; n++) {
        if (n >= 4 && (n < 12 || (n & 3) == 0)) mbar_wait(BAR(n >= 12 ? BAR_EMPTY + (n >> 2) - 3 : (n == 7 && j != 3) ? BAR_P0BD : (n == 8 || n == 9) ? BAR_P2D : BAR_P1D));
        if (n < T.PC_NW) {
          if (n >= 4) mbar_wait(BAR(BAR_FULL + n - 4));
          else if (n & 1) mbar_wait(BAR((n < 2 || j == 3) ? BAR_WUK + 1 : BAR_WM2));
        }
        slot(tn, T.PC_SL);
        tma3d(dst, &P.ckv2, 0, row0 + (n >> 2) * 512, 2 * (n & 3), BAR(BAR_FULL + n), pol);
        dst = (n == 11 || n == 23) ? sb + OFF_RING : dst + 16384;
        tn += T.PC_P2;
        if (n == 4) CLK(2);
        if (n == 12) CLK(3);
        if (n == 20) CLK(4);
        if (n == 28) CLK(5);
        if (n == 24) {
          asm volatile("prefetch.tensormap [%0];" ::"l"(&P.ckv1) : "memory");
          asm volatile("prefetch.tensormap [%0];" ::"l"(&P.wuv) : "memory");
          asm volatile("prefetch.tensormap [%0];" ::"l"(&P.wo) : "memory");
          asm volatile("prefetch.tensormap [%0];" ::"l"(cta < NFF ? &P.w1 : &P.wm3) : "memory");
          asm volatile("prefetch.tensormap [%0];" ::"l"(&P.w2) : "memory");
        }
      }
      slot(tn, T.PC_SL);
      tma3d(dst, &P.ckv1, 0, row0 + 7 * 512, 6, BAR(BAR_LAST + 3), pol);
      tma3d(dst + 8192, &P.ckv1, 0, row0 + 7 * 512, 7, BAR(BAR_LAST + 4), pol);
      tn += T.PC_P2;
      CLK(6);
      auto unit = [&](int u) {
        if (u < 4) tma5d(sb + OFF_WUV + u * 8192, &P.wuv, 128 * h + 64 * (u >> 1), 0, 4 * (j >> 1), 0, 2 * (j & 1) + (u & 1), BAR(BAR_WUV + (u >> 1)), pol);
        else if (u < 8) tma2d(sb + OFF_WO + (u - 4) * 8192, &P.wo, 128 * j + 64 * ((u - 4) >> 1), 128 * h + 64 * (u & 1), BAR(BAR_WO + ((u - 4) >> 1)), pol);
        else if (u < 10) { if (cta < NFF) tma2d_nohint(sb + OFF_W1 + (u - 8) * 16384, &P.w1, 32 * bs, 256 * (u - 8), BAR(BAR_W1)); }
        else if (cta < NFF) tma3d(sb + OFF_W2 + (u - 10) * 8192, &P.w2, 0, 32 * bs, 4 * hh + 2 * (u - 10), BAR(BAR_W2), pol);
        else tma2d_nohint(sb + OFF_W1 + (u - 10) * 16384, &P.wm3, 2560 + 32 * (cta - NFF), 256 * (u - 10), BAR(BAR_W1));
      };
      mbar_wait(BAR(BAR_EMPTY + 5));
#pragma unroll
      for (int u = 0; u < 12; u++) {
        if (u == 8) mbar_wait(BAR(BAR_EMPTY + 6));
        until_ns(tn + (u < 4 ? T.T_UV + u * T.P_UV : u < 8 ? T.T_O + (u - 4) * T.P_O : u < 10 ? T.T_1 + (u - 8) * T.P_F : (cta < NFF ? T.T_2 : T.T_GB) + (u - 10) * T.P_F));
        unit(u);
        if (u == 3) {
#pragma unroll
          for (int q = 0; q < 4; q++)
            if (q < T.PF_N) {
              until_ns(tn + T.T_PF + q * T.P_PF);
              asm volatile("cp.async.bulk.prefetch.tensor.2d.L2.global.tile [%0, {%1,%2}];" ::"l"(&P.wo), "r"(128 * j + 64 * (q >> 1)), "r"(128 * h + 64 * (q & 1)) : "memory");
            }
        }
      }
      CLK_DUMP();
    }
    return;
  }

  if (w == 9) {
    if (lane == 0) {
#pragma unroll
      for (int i = 0; i < NBARS; i++) mbar_init(BAR(i), i >= BAR_P1D ? 8 : i >= BAR_EMPTY ? 4 : 1);
      asm volatile("fence.mbarrier_init.release.cluster;" ::: "memory");
    }
    __syncwarp();
    mbar_expect(BAR(lane), lane == BAR_LAST + 3 ? 8192 : 16384);
    if (lane < BAR_ALLCLR - 32) mbar_expect(BAR(32 + lane), lane == 0 ? 8192 : lane == BAR_W1 - 32 ? 32768 : 16384);
    CLK(9);
    asm volatile("barrier.cta.arrive.aligned 5, 64;" ::: "memory");
    asm volatile("barrier.cta.arrive.aligned 0, %0;" ::"n"(NTHREADS) : "memory");
  }
  const uint32_t epoch = ldg_rlx1(&gs->epoch);

  if (w == 9) {
    const int mo = g * 512 + 16 * hI + 2 * jI;
    const uint32_t xo0 = ldg_nc1(gx + mo * 2), xo1 = ldg_nc1(gx + mo * 2 + 16);
    const int par = epoch & 1;
    const uint32_t t0 = gtime32();
    const uint4 z = make_uint4(0, 0, 0, 0);
    uint32_t sel;
    {
      uint32_t* pa = gin + blk(cta, 5, 0) + 960;
      uint32_t* pb = gin + blk(cta, 5, 1) + 960;
      until_ns(t0 + T.PR_T0);
      if (lane < 4) stg4(reinterpret_cast<uint4*>(lane & 2 ? pa : pb) + (lane & 1), z);
      uint32_t ma = 0xffffffffu, mb = 0xffffffffu;
#pragma unroll 1
      for (int i = 0; i < 2 * T.PR_N; i++) {
        const uint32_t c0 = clk32();
        asm volatile("{\n.reg .pred q;\n.reg .b32 v;\nsetp.eq.u32 q, %1, 0;\nmov.u32 v, 0;\n@q atom.relaxed.gpu.global.add.u32 v, [%0], 1;\n"
                     "setp.eq.u32 q, v, 0xffffffff;\n@q trap;\n}" ::"l"(i & 1 ? pb : pa), "r"(lane) : "memory");
        const uint32_t d = clk32() - c0;
        if (i & 1) mb = min(mb, d); else ma = min(ma, d);
      }
      sel = __shfl_sync(~0u, (uint32_t)(mb < ma), 0);
      const uint32_t sw = 2 * (epoch + 1) + sel;
      if (lane < 2) stg4(reinterpret_cast<uint4*>(gin + blk(cta, 5, 1) + 896) + lane, make_uint4(sw, sw, sw, sw));
    }
    until_ns(t0 + T.CLR_T0);
    {
#pragma unroll 1
      for (int i0 = 0; i0 < 13; i0++) {
        uint4* q = reinterpret_cast<uint4*>(gin + (i0 < 12 ? blk(cta, i0 >> 1, sel) + (i0 & 1) * 512 : blk(cta, 4, sel ^ 1) + 512)) + lane;
#pragma unroll
        for (int i = 0; i < 4; i++) if (i0 != 11 || i < 3) stg4(q + i * 32, z);
        backoff(T.CLR_CLK);
      }
#pragma unroll
      for (int i = 0; i < 2; i++) {
        if (jI == 1) stg4(reinterpret_cast<uint4*>(gin + blk(cta, 6, i)) + lane, z);
        if (lane < 2) stg4(reinterpret_cast<uint4*>(gin + blk(cta, 5, i) + 928) + lane, z);
        stg4(reinterpret_cast<uint4*>(gin + blk(16 * g, 6 + (cta >> 6), i) + (cta & 63) * 16) + t, z);
      }
      CLK(1);
      {
        uint32_t sv = 0;
        uint32_t u[4];
        int it = 0;
        do {
#pragma unroll
          for (int i = 0; i < 4; i++) u[i] = ldg_rlx1(gin + blk(4 * lane + i, 5, 1) + 896) ^ (2 * (epoch + 1));
          if (++it > SPIN_LIMIT) __trap();
        } while (!__all_sync(~0u, (u[0] | u[1] | u[2] | u[3]) < 2));
#pragma unroll
        for (int i = 0; i < 4; i++) sv |= u[i] << (8 * i);
        sts1(sb + OFF_SEL + lane * 4, sv);
      }
      asm volatile("fence.acq_rel.gpu;" ::: "memory");
      CLK(2);
      __syncwarp();
      if (lane < NSYNC) asm volatile("red.relaxed.gpu.global.add.u32 [%0], 1;" ::"l"(&gs->sync[lane][0]) : "memory");
#pragma unroll
      for (int i = 0; i < 4; i++) stg4(reinterpret_cast<uint4*>(gs->QP[par ^ 1] + cta * 512) + i * 32 + lane, z);
      backoff(T.CLR_CLK);
#pragma unroll
      for (int i = 0; i < 4; i++) stg4(reinterpret_cast<uint4*>(gs->QX[par ^ 1] + cta * 512) + i * 32 + lane, z);
      stg4(reinterpret_cast<uint4*>(gs->MOD1[par ^ 1] + cta * 128) + lane, z);
      if (lane < 16) stg4(reinterpret_cast<uint4*>(gs->MOD2[par ^ 1] + cta * 64) + lane, z);
      const uint32_t target = (epoch + 1) * NCTA;
      uint32_t c; int it = 0;
      do {
        backoff(T.CLR_CLK);
        asm volatile("ld.acquire.gpu.global.u32 %0, [%1];" : "=r"(c) : "l"(&gs->sync[cta % NSYNC][0]) : "memory");
        if (++it > SPIN_LIMIT) __trap();
      } while (!__all_sync(~0u, (int)(c - target) >= 0));
      if (lane == 0) mbar_arrive(BAR(BAR_ALLCLR));
    }
    CLK(3);
    const uint32_t* const pg = gs->MOD2[par] + cta * 16 + g * 2;
    auto gate = [&](const uint32_t* q) { uint2 u; int it = 0; do { u = ldg_u64(q); if (++it > SPIN_LIMIT) __trap(); } while (!__all_sync(~0u, u.y != 0)); return u; };
    const uint2 gau = gate(pg);
    uint32_t anchor;
    {
      uint32_t* const po = gin + blk(16 * (lane & 7), 5, lane >> 3) + 928;
      const uint32_t* const pi = nearbox(cta & ~15, 5) + 928;
      mbar_wait(BAR(BAR_LAST + T.TS_P));
      unsigned long long now; asm volatile("mov.u64 %0, %%globaltimer;" : "=l"(now));
      if (lane < 16) {
        asm volatile("red.relaxed.gpu.global.max.u64 [%0], %1;" ::"l"(po + 2), "l"(now) : "memory");
        asm volatile("red.relaxed.gpu.global.add.u32 [%0], 1;" ::"l"(po + 1) : "memory");
      }
      backoff(T.D_TS);
      uint4 v; int it = 0;
      do { v = ldg_2u64(pi); if (++it > SPIN_LIMIT) __trap(); } while (!__all_sync(~0u, v.y == NCTA));
      const int age = min(max((int)(gtime32() - v.z), 0), 4000);
      anchor = clk32() - age * 7 / 4 + T.TS_O;
      if (lane == 0) { sts1(sb + OFF_TS, anchor); mbar_arrive(BAR(BAR_TS)); }
      CLK(10);
    }
    {
      const uint32_t* pm = pin(nearbox(4 * hI + 1, 6) + lane * 4);
      wait_clk(anchor, T.A_M);
      uint4 ml = ldg_2u64(pm);
      int it = 0;
      while (!__all_sync(~0u, ml.y != 0 && ml.w != 0)) { ml = ldg_2u64(pm); if (++it > SPIN_LIMIT) __trap(); }
      ITS(2, it);
      float M = fmaxf(__uint_as_float(ml.x), __uint_as_float(ml.z));
      M = fmaxf(M, __shfl_xor_sync(~0u, M, 1)); M = fmaxf(M, __shfl_xor_sync(~0u, M, 2));
      const float e0 = ex2(__uint_as_float(ml.x) - M), e1 = ex2(__uint_as_float(ml.z) - M);
      float l = e0 * __uint_as_float(ml.y) + e1 * __uint_as_float(ml.w);
      l += __shfl_xor_sync(~0u, l, 1); l += __shfl_xor_sync(~0u, l, 2);
      const float inv = __fdividef(1.f, l);
      sts2f(sb + OFF_WV + lane * 8, e0 * inv, e1 * inv);
      __syncwarp();
      if (lane == 0) mbar_arrive(BAR(BAR_WV));
      CLK(11);
    }
    uint32_t* x3o[4];
#pragma unroll
    for (int i = 0; i < 4; i++) x3o[i] = pin(gin + blk(32 * i + 16 * (t >> 1), 6 + (cta >> 6), t) + (cta & 63) * 16 + g * 2);
    uint32_t* const fo = pin(reinterpret_cast<uint32_t*>(gout) + mo / 2 + 4 * (t & 1));
    const uint32_t* const p3 = pin(gin + blk(cta, 4, sel) + t * 16 + g * 2);
    const uint32_t* const p4 = pin(gin + blk(cta, 5, sel) + t * 16 + g * 2);
    const uint32_t one = pin((g & 1) ? 0x3f800000u : 0x00003f80u);
    const float xf[4] = {pin(bf_lo(xo0)), pin(bf_hi(xo0)), pin(bf_lo(xo1)), pin(bf_hi(xo1))};
    const float ga[4] = {pin(bf_lo(gau.x)), pin(bf_hi(gau.x)), pin(bf_lo(gau.y)), pin(bf_hi(gau.y))};
    mbar_wait(BAR(BAR_P5D));
    backoff(T.D_X3A);
    wait_clk(anchor, T.A_X1 + T.R_X3A);
    CLK(4);
    float r[4];
    uint32_t x20, x21;
    int it = 0;
    bool ok;
    do {
      ok = sum_pieces<32>(p3, one, r);
      x20 = pack_bf16(xf[0] + ga[0] * r[0], xf[1] + ga[1] * r[1]); x21 = pack_bf16(xf[2] + ga[2] * r[2], xf[3] + ga[3] * r[3]);
#pragma unroll
      for (int i = 0; i < 4; i++) stg_u64_unless(!ok || (i == 3 && t >= 2), x3o[i], x20, x21);
    } while (!ok && ++it < SPIN_LIMIT);
    if (!ok) __trap();
    CLK(6);
    ITS(0, it);
    const uint32_t xw = (t & 1) ? x21 : x20;
    const float xa = pin(bf_lo(xw)), xb = pin(bf_hi(xw));
    if (cta < NFF) mbar_wait(BAR(BAR_P7D)); else wait_clk(anchor, T.A_X1 + T.R_X3A + T.R_X3B + T.R_FIN - T.D_FIN);
    uint2 gbu = ldg_u64(pg + 3 * 2048);
    backoff(T.D_FIN);
    CLK(7);
    do {
      ok = sum_pieces<NFG>(p4, one, r);
      ok = ok && __all_sync(~0u, gbu.y != 0);
      const uint32_t gw = (t & 1) ? gbu.y : gbu.x;
      const uint32_t o = pack_bf16(xa + bf_lo(gw) * ((t & 1) ? r[2] : r[0]), xb + bf_hi(gw) * ((t & 1) ? r[3] : r[1]));
      if (ok && t < 2) asm volatile("st.global.u32 [%0], %1;" ::"l"(fo), "r"(o) : "memory");
      reload_unit(gbu, pg + 3 * 2048);
    } while (!ok && ++it < SPIN_LIMIT);
    if (!ok) __trap();
    ITS(1, it);
    CLK(8);
    CLK_DUMP();
    if (cta == 0 && lane == 0) stg1(&gs->epoch, epoch + 1);
    return;
  }

  const int wg = w >> 2, wq = w & 3;
  uint32_t tstore;
  {
    const uint8_t* pw = gwmod + (size_t)(128 * jI + 16 * w + 4 * (g >> 1) + (g & 1)) * 6144 + 64 * hI + 16 * t;
    const uint4 w0 = ldg_nc4(pw), w1 = ldg_nc4(pw + 2 * 6144);
    const uint2 cc = ldg_nc2(gc + g * 1024 + 256 * jI + 32 * w + 8 * t);
    CLK(40);
    const uint32_t a[4] = {silu2(cc.x), 0u, silu2(cc.y), 0u};
    float d[4][4] = {{0.f, 0.f, 0.f, 0.f}, {0.f, 0.f, 0.f, 0.f}, {0.f, 0.f, 0.f, 0.f}, {0.f, 0.f, 0.f, 0.f}};
    mma16816(d[0], a, movm(w0.x), movm(w1.x)); mma16816(d[1], a, movm(w0.y), movm(w1.y));
    mma16816(d[2], a, movm(w0.z), movm(w1.z)); mma16816(d[3], a, movm(w0.w), movm(w1.w));
    CLK(1);
    sts4f(sb + OFF_P0S + w * 1088 + lane * 16, d[0][0], d[0][1], d[1][0], d[1][1]);
    sts4f(sb + OFF_P0S + w * 1088 + 544 + lane * 16, d[2][0], d[2][1], d[3][0], d[3][1]);
    bar_sync(0, NTHREADS);
    if (tid < 128) {
      const uint32_t src = sb + OFF_P0S + ((tid >> 2) & 1) * 544 + (((tid >> 3) & 7) * 4 + 2 * (tid >> 6) + (tid & 1)) * 16 + ((tid >> 1) & 1) * 8;
      float2 v[8];
#pragma unroll
      for (int i = 0; i < 8; i++) v[i] = ldsf2(src + i * 1088);
      const float ax = ((v[0].x + v[1].x) + (v[2].x + v[3].x)) + ((v[4].x + v[5].x) + (v[6].x + v[7].x));
      const float ay = ((v[0].y + v[1].y) + (v[2].y + v[3].y)) + ((v[4].y + v[5].y) + (v[6].y + v[7].y));
      stg1(gs->MOD1[epoch & 1] + jI * 4096 + hI * 128 + tid, nz(pack_bf16(ax, ay)));
    }
    tstore = clk32();
  }
  CLK(2);
  const int par = epoch & 1;
  uint32_t cf[4][4];
  mbar_wait(BAR(BAR_XC));
  {
    uint32_t u[2][4];
    lds4(u[0], sb + OFF_XS + w * 1024 + lane * 16); lds4(u[1], sb + OFF_XS + w * 1024 + 512 + lane * 16);
    float v[16];
#pragma unroll
    for (int i = 0; i < 8; i++) { v[2 * i] = bf_lo(u[i >> 2][i & 3]); v[2 * i + 1] = bf_hi(u[i >> 2][i & 3]); }
    float s = 0.f;
#pragma unroll
    for (int i = 0; i < 16; i++) s += v[i];
#pragma unroll
    for (int o = 16; o; o >>= 1) s += __shfl_xor_sync(~0u, s, o);
    const float mu = s * (1.f / 512.f);
    float q = 0.f;
#pragma unroll
    for (int i = 0; i < 16; i++) { v[i] -= mu; q += v[i] * v[i]; }
#pragma unroll
    for (int o = 16; o; o >>= 1) q += __shfl_xor_sync(~0u, q, o);
    const float rs = rsqrtf(q * (1.f / 512.f) + 1e-5f);
    const bool hi = jI & 2;
    uint32_t o[4];
#pragma unroll
    for (int i = 0; i < 4; i++) o[i] = pack_bf16((hi ? v[8 + 2 * i] : v[2 * i]) * rs, (hi ? v[9 + 2 * i] : v[2 * i + 1]) * rs);
    if ((lane >> 4) == (jI & 1)) sts4(sb + OFF_XN + w * 272 + (lane & 15) * 16, make_uint4(o[0], o[1], o[2], o[3]));
  }
  CLK(3);
  uint32_t aw[8][4];
  const uint32_t abase = __shfl_sync(~0u, sb + a_t_offset(w, lane), lane);
  {
    const uint32_t* pm = pin(gs->MOD1[par] + (8 * jI + w) * 64 + lane * 2);
    uint32_t* const qpo = pin(gs->QP[par] + (cta * 256 + tid) * 2);
    float d[4] = {0.f, 0.f, 0.f, 0.f};
    wait_clk(tstore, T.D_MOD);
    CLK(4);
    uint2 v[8];
    load_units<8, 2048>(v, pm);
    cbar();
    const uint32_t xn0 = lds1(sb + OFF_XN + g * 272 + w * 32 + t * 4), xn1 = lds1(sb + OFF_XN + g * 272 + w * 32 + 16 + t * 4);
    const bool early = __all_sync(~0u, mbar_test(BAR(BAR_WQ + wg)));
    if (early) load_a_t(aw, abase + OFF_WQ);
    int it = 0;
    while (true) {
      uint32_t mn = 0xffffffffu;
#pragma unroll
      for (int i = 0; i < 8; i++) mn = min(mn, min(v[i].x, v[i].y));
      if (__all_sync(~0u, mn != 0)) break;
#pragma unroll
      for (int i = 0; i < 8; i++) { if (v[i].x == 0) v[i].y = 0; reload_unit(v[i], pm + i * 2048); }
      if (++it > SPIN_LIMIT) __trap();
    }
    CLK(5);
    ITS(0, it);
    float sc[2][4];
#pragma unroll
    for (int i = 0; i < 2; i++) {
      sc[i][0] = (bf_lo(v[i].x) + bf_lo(v[2 + i].x)) + (bf_lo(v[4 + i].x) + bf_lo(v[6 + i].x));
      sc[i][1] = (bf_hi(v[i].x) + bf_hi(v[2 + i].x)) + (bf_hi(v[4 + i].x) + bf_hi(v[6 + i].x));
      sc[i][2] = (bf_lo(v[i].y) + bf_lo(v[2 + i].y)) + (bf_lo(v[4 + i].y) + bf_lo(v[6 + i].y));
      sc[i][3] = (bf_hi(v[i].y) + bf_hi(v[2 + i].y)) + (bf_hi(v[4 + i].y) + bf_hi(v[6 + i].y));
    }
    sts2(sb + OFF_BS1 + (w >> 1) * 512 + lane * 16 + (w & 1) * 8,
         pack_bf16(bf_lo(xn0) * (1.f + sc[1][0]) + sc[0][0], bf_hi(xn0) * (1.f + sc[1][1]) + sc[0][1]),
         pack_bf16(bf_lo(xn1) * (1.f + sc[1][2]) + sc[0][2], bf_hi(xn1) * (1.f + sc[1][3]) + sc[0][3]));
    if (!early) { mbar_wait(BAR(BAR_WQ + wg)); load_a_t(aw, abase + OFF_WQ); }
    CLK(6);
    cbar();
    uint32_t b[4][4];
#pragma unroll
    for (int kk = 0; kk < 4; kk++) lds4(b[kk], sb + OFF_BS1 + kk * 512 + lane * 16);
    mma128(d, aw, b);
    stg_u64(qpo, pack_bf16(d[0], d[1]), pack_bf16(d[2], d[3]));
    tstore = clk32();
    CLK(7);
    if (wg) {
      mbar_wait(BAR(BAR_C));
#pragma unroll
      for (int i = 0; i < 4; i++) lds4(cf[i], sb + OFF_CS + g * 1024 + wq * 256 + i * 64 + t * 16);
#pragma unroll
      for (int i = 0; i < 16; i++) cf[i >> 2][i & 3] = silu2(cf[i >> 2][i & 3]);
    }
    __syncwarp();
    if (lane == 0) mbar_arrive(BAR(BAR_P1D));
  }
  {
    const uint32_t* pq = pin(gs->QP[par] + (hI * 4 * 256 + tid) * 2);
    uint32_t* const qxo = pin(gs->QX[par] + (g * 32 + hI) * 256 + 64 * jI + 8 * w + 2 * t);
    uint2 v[4];
    float d[4] = {0.f, 0.f, 0.f, 0.f};
    wait_clk(tstore, T.D_QP);
    CLK(8);
    load_units<4, 512>(v, pq);
    const uint32_t kbase = sb + OFF_WUK + (16 * w + (lane & 15)) * 128;
    auto load_half = [&](int hf) {
#pragma unroll
      for (int ks = 0; ks < 4; ks++) ldsm4(aw[4 * hf + ks], kbase + hf * 16384 + (((2 * ks + (lane >> 4)) ^ (lane & 7)) << 4));
    };
    mbar_wait(BAR(BAR_WUK));
    load_half(0);
    const bool early = __all_sync(~0u, mbar_test(BAR(BAR_WUK + 1)));
    if (early) load_half(1);
    const int it = check_units<4, 512>(v, pq);
    CLK(9);
    ITS(1, it);
    sum4_to_smem(v, sb + OFF_BS2 + (16 * w + g) * 16 + t * 4);
    if (!early) { mbar_wait(BAR(BAR_WUK + 1)); load_half(1); }
    CLK(10);
    cbar();
    uint32_t b[4][4];
#pragma unroll
    for (int kk = 0; kk < 4; kk++) ldsm4t(b[kk], sb + OFF_BS2 + (32 * kk + lane) * 16);
    mma128(d, aw, b);
    const float sc = 0.08838834764831845f * 1.4426950408889634f;
    stg_u64(qxo, movm(pack_bf16(d[0] * sc, d[1] * sc)), movm(pack_bf16(d[2] * sc, d[3] * sc)));
    tstore = clk32();
    CLK(11);
    if (lane == 0) mbar_arrive(BAR(BAR_P2D));
  }
  if (wg && jI != 3) {
    const int mi = lane >> 3, r = lane & 7;
    const uint32_t a0 = sb + OFF_WM2 + (8 * (r >> 1) + (r & 1) + 2 * (mi >> 1)) * 32 + (mi & 1) * 16;
    mbar_wait(BAR(BAR_WM2));
#pragma unroll
    for (int s = 0; s < 8; s++) ldsm4t(aw[s], a0 + (128 * wq + 32 * (s >> 1) + 4 * (s & 1)) * 32);
    float d[4] = {0.f, 0.f, 0.f, 0.f};
    mma128(d, aw, cf);
    sts4f(sb + OFF_P0B + (tid - 128) * 16, d[0], d[1], d[2], d[3]);
    if (lane == 0) mbar_arrive(BAR(BAR_P0BD));
    bar_sync(3, 128);
    if (w == 4) {
      float4 v[4];
#pragma unroll
      for (int i = 0; i < 4; i++) v[i] = ldsf4(sb + OFF_P0B + (i * 32 + lane) * 16);
      stg_u64(gs->MOD2[par] + (3 * hI + jI) * 64 + t * 16 + g * 2, movm(pack_bf16((v[0].x + v[1].x) + (v[2].x + v[3].x), (v[0].y + v[1].y) + (v[2].y + v[3].y))),
              movm(pack_bf16((v[0].z + v[1].z) + (v[2].z + v[3].z), (v[0].w + v[1].w) + (v[2].w + v[3].w))));
    }
    CLK(15);
  }
  {
    const uint32_t* qx = pin(gs->QX[par] + ((bs >> 3) * 32 + 16 * hh) * 256 + tid * 4);
    const int ch = tid & 63, h0 = tid >> 6;
    const uint32_t dst = sb + OFF_Q + (ch >> 3) * 2048 + h0 * 128;
    wait_clk(tstore, T.D_QX);
    CLK(12);
    uint4 v[4];
#pragma unroll
    for (int i = 0; i < 4; i++) v[i] = ldg_2u64(qx + i * 1024);
    int it = 0;
    while (true) {
      uint32_t mn = 0xffffffffu;
#pragma unroll
      for (int i = 0; i < 4; i++) mn = min(mn, min(v[i].y, v[i].w));
      if (__all_sync(~0u, mn != 0)) break;
#pragma unroll
      for (int i = 0; i < 4; i++)
        asm volatile("{\n.reg .pred q;\nsetp.eq.u32 q, %5, 0;\n@q ld.relaxed.gpu.global.v4.b32 {%0, %1, %2, %3}, [%4];\n}"
                     : "+r"(v[i].x), "+r"(v[i].y), "+r"(v[i].z), "+r"(v[i].w) : "l"(qx + i * 1024), "r"(min(v[i].y, v[i].w)) : "memory");
      if (++it > SPIN_LIMIT) __trap();
    }
    CLK(13);
    ITS(2, it);
#pragma unroll
    for (int i = 0; i < 4; i++) sts4(dst + i * 512 + (((ch & 7) ^ ((4 * i + h0) & 7)) << 4), v[i]);
    asm volatile("fence.proxy.async.shared::cta;" ::: "memory");
    CLK(14);
    cbar();
  }

  uint2 cbf[4], sbf[4];
  const uint32_t* const pcb = gs->MOD2[par] + 2048 + (16 * w + t) * 16 + g * 2;
  auto load_frags = [&] {
    if (cta < NFF) { load_units<4, 64>(sbf, pcb); load_units<4, 64>(cbf, pcb + 2048); }
    else {
#pragma unroll
      for (int s = 0; s < 4; s++) { cbf[s].x = ldg_nc1(gc + g * 1024 + w * 128 + s * 32 + t * 4); cbf[s].y = ldg_nc1(gc + g * 1024 + w * 128 + s * 32 + 16 + t * 4); }
    }
  };
  uint32_t thand, anchor;
  const uint32_t opaque0 = w >> 4;
  if (wg == 0) {
    float mh[4];
    float L[8];
#pragma unroll
    for (int i = 0; i < 4; i++) { L[2 * i] = L[2 * i + 1] = 0.f; mh[i] = -INFINITY; }
    constexpr uint32_t dq = desc_lo(OFF_Q);
    const uint32_t ptw = sb + OFF_PT + (8 * (lane >> 4) + (lane & 7)) * 128 + (((2 * wq + ((lane >> 3) & 1)) ^ (lane & 7)) << 4);
    float S[8];
    auto softmax = [&](int tl) {
      auto write_p = [&](const float (&x)[8]) {
        float p[8];
#pragma unroll
        for (int i = 0; i < 8; i++) p[i] = ex2(x[i]);
        stsm4t(ptw + (tl & 1) * 2048, pack_bf16(p[0], p[1]), pack_bf16(p[2], p[3]), pack_bf16(p[4], p[5]), pack_bf16(p[6], p[7]));
        asm volatile("fence.proxy.async.shared::cta;" ::: "memory");
      };
      float x[8];
#pragma unroll
      for (int i = 0; i < 8; i++) x[i] = S[i] - mh[2 * (i >> 2) + (i & 1)];
      if (tl) write_p(x);
      const float ex = fmaxf(fmaxf(fmaxf(x[0], x[1]), fmaxf(x[2], x[3])), fmaxf(fmaxf(x[4], x[5]), fmaxf(x[6], x[7])));
      if (tl == 0 || bar_over(ex)) {
        float mx[4];
#pragma unroll
        for (int i = 0; i < 4; i++) mx[i] = fmaxf(S[4 * (i >> 1) + (i & 1)], S[4 * (i >> 1) + 2 + (i & 1)]);
        const float a = reduce_g(mx, lane, [](float u, float v) { return fmaxf(u, v); });
        stsf(sb + OFF_RED + wq * 64 + (8 * (lane >> 4) + 2 * t + ((lane >> 3) & 1)) * 4, a);
        bar_sync(2, 128);
#pragma unroll
        for (int jn = 0; jn < 2; jn++) {
          float m0 = mh[2 * jn], m1 = mh[2 * jn + 1];
#pragma unroll
          for (int i = 0; i < 4; i++) { const float2 v = ldsf2(sb + OFF_RED + i * 64 + (8 * jn + 2 * t) * 4); m0 = fmaxf(m0, v.x); m1 = fmaxf(m1, v.y); }
          const float a0 = ex2(mh[2 * jn] - m0), a1 = ex2(mh[2 * jn + 1] - m1);
          mh[2 * jn] = m0; mh[2 * jn + 1] = m1;
          L[4 * jn] *= a0; L[4 * jn + 1] *= a1; L[4 * jn + 2] *= a0; L[4 * jn + 3] *= a1;
          if (tid < 4) sts2f(sb + OFF_ALPHA + (8 * jn + 2 * t) * 4, a0, a1);
        }
        asm volatile("barrier.cta.arrive.aligned 1, 256;" ::: "memory");
#pragma unroll
        for (int i = 0; i < 8; i++) x[i] = S[i] - mh[2 * (i >> 2) + (i & 1)];
        write_p(x);
        bar_over(0.f);
      }
      const uint32_t dpt = __shfl_sync(~0u, desc_lo(OFF_PT) + (tl & 1) * 128, 0);
      wg_fence();
#pragma unroll
      for (int ks = 0; ks < 4; ks++) wgmma_n16_ones(L, ONE2, dpt + ks * 2);
      wg_commit();
    };
    uint32_t da = desc_lo(OFF_RING);
#pragma unroll 1
    for (int tl = 0; tl < 7; tl++) {
      if (tl == 5) { load_frags(); }
      uint32_t ok = 0;
#pragma unroll
      for (int u = 0; u < 4; u++) ok += mbar_test(BAR(BAR_FULL + 4 * tl + u));
      ok = __reduce_min_sync(~0u, ok);
      const uint32_t du = __shfl_sync(~0u, da, 0);
#pragma unroll
      for (int u = 0; u < 4; u++) {
        if (ok != 4) mbar_wait(BAR(BAR_FULL + 4 * tl + u));
        wg_fence();
#pragma unroll
        for (int k = 0; k < 8; k++) {
          const int i = 8 * u + k;
          if (i == 0) wgmma_n16<0, 0>(S, du, dq); else wgmma_n16<0, 1>(S, du + (i >> 2) * 512 + (i & 3) * 2, dq + (i >> 2) * 128 + (i & 3) * 2);
        }
        wg_commit();
      }
      wg_wait<0>();
      acc_fence(S); acc_fence(L);
      if (tl == 0) CLK(15);
      if (tl == 1) CLK(17);
      softmax(tl);
      if (tl == 0) CLK(16);
      if (tl == 1) CLK(18);
      if (tl == 3) CLK(19);
      if (tl == 6) CLK(20);
      da = (tl == 2 || tl == 5) ? da - 8192 : da + 4096;
    }
    mbar_wait(BAR(BAR_ALLCLR));
    uint32_t* const mlo = pin(gin + blk(4 * (16 * hh + 4 * (g & 2) + 2 * t + (g & 1)) + 1, 6, g >> 2) + bs * 2);
#pragma unroll
    for (int i = 0; i < 32; i++) {
      if (i == 0 || i == 8 || i == 16 || i == 24 || i == 28) {
        if (i) wg_commit();
        mbar_wait(BAR(BAR_LAST + (i == 28 ? 4 : i >> 3)));
        if (i == 28) CLK(21);
        wg_fence();
      }
      if (i == 0) wgmma_n16<0, 0>(S, desc_lo(65536), dq); else wgmma_n16<0, 1>(S, desc_lo(65536) + (i >> 2) * 512 + (i & 3) * 2, dq + (i >> 2) * 128 + (i & 3) * 2);
    }
    wg_commit();
    wg_wait<0>();
    acc_fence(S); acc_fence(L);
    CLK(22);
    softmax(7);
    CLK(23);
    thand = clk32();
    wg_wait<0>();
    acc_fence(L);
    if (tid < 32) red_u64(mlo, __float_as_uint(g & 2 ? (g & 1 ? mh[3] : mh[2]) : (g & 1 ? mh[1] : mh[0])), __float_as_uint(g & 2 ? (g & 1 ? L[5] : L[4]) : (g & 1 ? L[1] : L[0])));
    CLK(24);
  } else {
    float O[8][8];
#pragma unroll
    for (int i = 0; i < 8; i++)
#pragma unroll
      for (int k = 0; k < 8; k++) O[i][k] = 0.f;
    constexpr uint32_t dp = desc_lo(OFF_PT);
    auto handover = [&](int tl) {
      uint32_t over = opaque0 + (tl == 0);
#pragma unroll 1
      do {
        if (over) {
          cbar();
#pragma unroll
          for (int jn = 0; jn < 2; jn++) {
            const float2 a = ldsf2(sb + OFF_ALPHA + (8 * jn + 2 * t) * 4);
#pragma unroll
            for (int mb = 0; mb < 8; mb++) { O[mb][4 * jn] *= a.x; O[mb][4 * jn + 1] *= a.y; O[mb][4 * jn + 2] *= a.x; O[mb][4 * jn + 3] *= a.y; }
          }
        }
        over++;
      } while (bar_over(0.f));
    };
    uint32_t da = desc_lo(OFF_RING);
    uint32_t* x1o[8] = {};
#pragma unroll 1
    for (int tl = 0; tl < 8; tl++) {
      if (tl == 5) load_frags();
      if (tl == 7) {
        mbar_wait(BAR(BAR_ALLCLR));
#pragma unroll
        for (int i = 0; i < 8; i++)
          x1o[i] = inbox((16 * hh + 8 * ((i >> 1) & 1) + 2 * t + (i & 1)) * 4 + 2 * (i >> 2) + (wq >> 1), bs >> 4) + (bs & 15) * 64 + ((wq & 1) * 8 + g) * 4;
      }
      handover(tl);
      CLK(23);
      thand = clk32();
      const uint32_t dpt = dp + (tl & 1) * 128;
      wg_fence();
#pragma unroll
      for (int i = 0; i < 32; i++) wgmma_n16<1, 1>(O[i >> 2], da + (i >> 2) * 512 + (i & 3) * 128, dpt + (i & 3) * 2);
      wg_commit();
      da = (tl == 2 || tl == 5) ? da - 8192 : da + 4096;
      wg_wait<0>();
#pragma unroll
      for (int mb = 0; mb < 8; mb++) acc_fence(O[mb]);
      if (lane == 0) mbar_arrive(BAR(BAR_EMPTY + tl));
      if (tl == 0) CLK(16);
      if (tl == 1) CLK(18);
      if (tl == 3) CLK(19);
      if (tl == 6) CLK(20);
    }
    CLK(22);
#pragma unroll
    for (int i = 0; i < 8; i++) {
      const int J = i >> 2, k = 4 * ((i >> 1) & 1) + (i & 1);
      stg_cvt8(x1o[i], O[4 * J][k], O[4 * J][k + 2], O[4 * J + 1][k], O[4 * J + 1][k + 2], O[4 * J + 2][k], O[4 * J + 2][k + 2], O[4 * J + 3][k], O[4 * J + 3][k + 2]);
    }
    CLK(24);
  }

  {
    const uint32_t* px = pin(inbox(cta, w >> 1) + (w & 1) * 512 + lane * 2);
    uint32_t* const x2o = pin(inbox(cta, 4) + 512 + tid * 2);
    uint32_t* const x2p = pin(gin + blk(cta, 4, selector(cta) ^ 1) + 512 + tid * 2);
    const uint32_t q4 = lds1(sb + OFF_SEL + 4 * hI) ^ 0x00010100u;
    const uint32_t same = pin((uint32_t)(q4 == 0 || q4 == 0x01010101u));
    mbar_wait(BAR(BAR_TS));
    anchor = lds1(sb + OFF_TS);
    const uint32_t sdst = pin(sb + OFF_BS4 + w * 272 + lane * 8), ssrc = pin(sb + OFF_BS4 + (lane & 7) * 272 + (lane >> 3) * 16);
    float d[4] = {0.f, 0.f, 0.f, 0.f};
    if (cta >= NFF) {
#pragma unroll
      for (int s = 0; s < 4; s++) { cbf[s].x = silu2(cbf[s].x); cbf[s].y = silu2(cbf[s].y); }
    }
    wait_clk(thand, T.D_X1);
    wait_clk(anchor, T.A_X1 - T.R_X0);
    uint2 v[8];
    load_units<8, 64>(v, px);
    if (T.R_X0) {
      wait_clk(anchor, T.A_X1);
#pragma unroll
      for (int i = 0; i < 8; i++) reload_unit(v[i], px + i * 64);
    }
    CLK(25);
    const bool early = __all_sync(~0u, mbar_test(BAR(BAR_WUV + wg)));
    if (early) load_a_t(aw, abase + OFF_WUV);
    mbar_wait(BAR(BAR_WV));
    const float4 wa = ldsf4(sb + OFF_WV + w * 32), wb = ldsf4(sb + OFF_WV + w * 32 + 16);
    const float wv[8] = {wa.x, wa.y, wa.z, wa.w, wb.x, wb.y, wb.z, wb.w};
    CLK(27);
    uint32_t it = opaque0;
    bool ok;
#pragma unroll 1
    do {
      if (it) {
#pragma unroll
        for (int i = 0; i < 8; i++) reload_unit(v[i], px + i * 64);
        if (it > SPIN_LIMIT) __trap();
      }
      it++;
      float a0 = 0.f, a1 = 0.f, a2 = 0.f, a3 = 0.f;
#pragma unroll
      for (int i = 0; i < 8; i++) { a0 += wv[i] * bf_lo(v[i].x); a1 += wv[i] * bf_hi(v[i].x); a2 += wv[i] * bf_lo(v[i].y); a3 += wv[i] * bf_hi(v[i].y); }
      ok = __all_sync(~0u, min_flags(v) != 0);
      sts2(sdst, pack_bf16(a0, a1), pack_bf16(a2, a3));
    } while (!ok);
    CLK(29);
    cbar();
    uint32_t b[4][4];
#pragma unroll
    for (int kk = 0; kk < 4; kk++) ldsm4(b[kk], ssrc + kk * 64);
    if (__builtin_expect(!early, 0)) { mbar_wait(BAR(BAR_WUV + wg)); load_a_t(aw, abase + OFF_WUV); }
    mma128(d, aw, b);
    const uint32_t c0 = pack_bf16(d[0], d[1]), c1 = pack_bf16(d[2], d[3]);
    stg_u64(x2o, c0, c1);
    stg_u64_unless(same, x2p, c0, c1);
    ITS(4, it - 1);
    tstore = clk32();
    CLK(30);
  }
  {
    uint32_t* const o = pin(inbox(4 * (8 * jI + w) + t, 4) + hI * 16 + g * 2);
    const uint32_t* x2i[4];
#pragma unroll
    for (int i = 0; i < 4; i++) x2i[i] = pin(nearbox(4 * hI + i, 4) + 512 + tid * 2);
    const uint32_t sdst = pin(sb + OFF_BS5 + (16 * w + g) * 16 + t * 4), ssrc = pin(sb + OFF_BS5 + lane * 16);
    float d[4] = {0.f, 0.f, 0.f, 0.f};
    wait_clk(tstore, T.D_X2);
    uint2 v[4];
#pragma unroll
    for (int i = 0; i < 4; i++) v[i] = ldg_u64(x2i[i]);
    const bool early = __all_sync(~0u, mbar_test(BAR(BAR_WO + wg)));
    if (early) load_a_t(aw, abase + OFF_WO);
    CLK(31);
    uint32_t it = opaque0;
    bool ok;
#pragma unroll 1
    do {
      if (it) {
#pragma unroll
        for (int i = 0; i < 4; i++) reload_unit(v[i], x2i[i]);
        if (it > SPIN_LIMIT) __trap();
      }
      it++;
      ok = __all_sync(~0u, min_flags(v) != 0);
      sum4_to_smem(v, sdst);
    } while (!ok);
    CLK(32);
    cbar();
    uint32_t b[4][4];
#pragma unroll
    for (int kk = 0; kk < 4; kk++) ldsm4t(b[kk], ssrc + kk * 512);
    if (__builtin_expect(!early, 0)) { mbar_wait(BAR(BAR_WO + wg)); load_a_t(aw, abase + OFF_WO); }
    mma128(d, aw, b);
    stg_u64(o, movm(pack_bf16(d[0], d[1])), movm(pack_bf16(d[2], d[3])));
    ITS(5, it - 1);
    tstore = clk32();
    CLK(33);
    if (lane == 0) mbar_arrive(BAR(BAR_P5D));
  }
  if (cta < NFF) {
    const int mi = lane >> 3, r = lane & 7;
    uint32_t a1[2][4][4], a2[2][2][4];
    check_units<4, 64>(sbf, pcb);
    check_units<4, 64>(cbf, pcb + 2048);
    __syncwarp();
#pragma unroll
    for (int s = 0; s < 4; s++) { cbf[s].x = hadd2(cbf[s].x, ONE2); cbf[s].y = hadd2(cbf[s].y, ONE2); }
    mbar_wait(BAR(BAR_W1));
#pragma unroll
    for (int mt = 0; mt < 2; mt++) {
#pragma unroll
      for (int ks = 0; ks < 4; ks++) ldsm4t(a1[mt][ks], sb + OFF_W1 + (64 * w + 16 * ks + 8 * (mi >> 1) + r) * 64 + (((2 * mt + (mi & 1)) ^ (r >> 1)) << 4));
      float u[4] = {0.f, 0.f, 0.f, 0.f}, vv[4] = {0.f, 0.f, 0.f, 0.f};
#pragma unroll
      for (int s = 0; s < 4; s++) { mma16816(u, a1[mt][s], cbf[s].x, cbf[s].y); mma16816(vv, a1[mt][s], sbf[s].x, sbf[s].y); }
      sts4f(sb + OFF_REDU + w * 1024 + mt * 512 + lane * 16, u[0], u[1], u[2], u[3]);
      sts4f(sb + OFF_REDV + w * 1024 + mt * 512 + lane * 16, vv[0], vv[1], vv[2], vv[3]);
    }
    const uint32_t* xb = pin(nearbox(cta & ~15, 6 + wg) + (16 * wq + t) * 16 + g * 2);
    uint32_t* const ox[2] = {pin(inbox(64 * hh + 8 * w + t, 5) + bs * 16 + g * 2), pin(inbox(64 * hh + 8 * w + 4 + t, 5) + bs * 16 + g * 2)};
    cbar();
    const int lp = (tid >> 2) & 31, kq = tid & 3;
    const int fo = 16 * wg + (lp >> 2) + 8 * (kq >> 1), bo = 2 * (lp & 3) + (kq & 1);
    float U = 0.f, V = 0.f;
#pragma unroll
    for (int i = 0; i < 8; i++) { U += ldsf(sb + OFF_REDU + i * 1024 + tid * 4); V += ldsf(sb + OFF_REDV + i * 1024 + tid * 4); }
    U = pin(U); V = pin(V);
    const uint32_t s_g = pin(sb + OFF_REDG + w * 1024 + lane * 16), s_s = pin(sb + OFF_REDS + g * 80 + w * 8);
    const uint32_t l_g = pin(sb + OFF_REDG + tid * 4), l_s = pin(sb + OFF_REDS + bo * 80), s_h = pin(sb + OFF_H1 + fo * 16 + bo * 2);
    CLK(34);
    wait_clk(tstore, T.D_X3B);
    wait_clk(anchor, T.A_X1 + T.R_X3A + T.R_X3B);
    uint2 x[4];
    load_units<4, 64>(x, xb);
    mbar_wait(BAR(BAR_W2));
#pragma unroll
    for (int i = 0; i < 4; i++)
      ldsm4t(a2[i >> 1][i & 1], sb + OFF_W2 + (w >> 1) * 4096 + (16 * (i & 1) + 8 * (mi >> 1) + r) * 128 + (((4 * (w & 1) + 2 * (i >> 1) + (mi & 1)) ^ r) << 4));
    CLK(35);
    uint32_t it = opaque0;
    float G[2][2][4], S[2][4];
#pragma unroll 1
    do {
      if (it) {
#pragma unroll
        for (int i = 0; i < 4; i++) reload_unit(x[i], xb + i * 64);
        if (it > SPIN_LIMIT) __trap();
      }
      it++;
#pragma unroll
      for (int i = 0; i < 8; i++) { G[0][i >> 2][i & 3] = G[1][i >> 2][i & 3] = S[i >> 2][i & 3] = 0.f; }
#pragma unroll
      for (int s = 0; s < 4; s++) {
        const uint32_t sx[4] = {x[s].x, ONE2, x[s].y, ONE2};
        mma16816(S[s & 1], sx, x[s].x, x[s].y);
        const uint32_t y0 = hmul2(x[s].x, cbf[s].x), y1 = hmul2(x[s].y, cbf[s].y);
        mma16816(G[0][s & 1], a1[0][s], y0, y1);
        mma16816(G[1][s & 1], a1[1][s], y0, y1);
      }
    } while (!__all_sync(~0u, min_flags(x) != 0));
    if (t == (g >> 1)) sts2f(s_s, (g & 1) ? S[0][3] + S[1][3] : S[0][2] + S[1][2], (g & 1) ? S[0][1] + S[1][1] : S[0][0] + S[1][0]);
#pragma unroll
    for (int mt = 0; mt < 2; mt++)
      sts4f(s_g + mt * 512, G[mt][0][0] + G[mt][1][0], G[mt][0][1] + G[mt][1][1], G[mt][0][2] + G[mt][1][2], G[mt][0][3] + G[mt][1][3]);
    CLK(37);
    cbar();
    {
      float gv[8];
      float4 sv[4];
#pragma unroll
      for (int i = 0; i < 4; i++) sv[i] = ldsf4(l_s + i * 16);
#pragma unroll
      for (int i = 0; i < 8; i++) gv[i] = ldsf(l_g + i * 1024);
      const float s1 = ((sv[0].x + sv[0].z) + (sv[1].x + sv[1].z)) + ((sv[2].x + sv[2].z) + (sv[3].x + sv[3].z));
      const float s2 = ((sv[0].y + sv[0].w) + (sv[1].y + sv[1].w)) + ((sv[2].y + sv[2].w) + (sv[3].y + sv[3].w));
      const float gsum = ((gv[0] + gv[1]) + (gv[2] + gv[3])) + ((gv[4] + gv[5]) + (gv[6] + gv[7]));
      const float mu = s1 * (1.f / 512.f);
      float rs;
      asm("rsqrt.approx.ftz.f32 %0, %1;" : "=f"(rs) : "f"(fmaxf(s2 * (1.f / 512.f) - mu * mu, 0.f) + 1e-5f));
      const float hv = fmaxf(rs * (gsum - mu * U) + V, 0.f);
      asm volatile("st.shared.u16 [%0], %1;" ::"r"(s_h), "h"(__bfloat16_as_ushort(__float2bfloat16(hv))) : "memory");
    }
    ITS(6, it - 1);
    CLK(38);
    cbar();
    uint32_t b[4];
    ldsm4t(b, sb + OFF_H1 + lane * 16);
    float o[2][2][4] = {};
#pragma unroll
    for (int i = 0; i < 4; i++) mma16816(o[i >> 1][i & 1], a2[i >> 1][i & 1], b[2 * (i & 1)], b[2 * (i & 1) + 1]);
#pragma unroll
    for (int mb = 0; mb < 2; mb++)
      stg_u64(ox[mb], movm(pack_bf16(o[mb][0][0] + o[mb][1][0], o[mb][0][1] + o[mb][1][1])), movm(pack_bf16(o[mb][0][2] + o[mb][1][2], o[mb][0][3] + o[mb][1][3])));
    CLK(39);
    if (lane == 0) mbar_arrive(BAR(BAR_P7D));
  } else {
    const int mi = lane >> 3, r = lane & 7;
    mbar_wait(BAR(BAR_W1));
#pragma unroll
    for (int mt = 0; mt < 2; mt++) {
      float u[4] = {0.f, 0.f, 0.f, 0.f};
#pragma unroll
      for (int ks = 0; ks < 4; ks++) ldsm4t(aw[4 * mt + ks], sb + OFF_W1 + (64 * w + 16 * ks + 8 * (mi >> 1) + r) * 64 + (((2 * mt + (mi & 1)) ^ (r >> 1)) << 4));
#pragma unroll
      for (int ks = 0; ks < 4; ks++) mma16816(u, aw[4 * mt + ks], cbf[ks].x, cbf[ks].y);
      sts4f(sb + OFF_REDU + w * 1024 + mt * 512 + lane * 16, u[0], u[1], u[2], u[3]);
    }
    cbar();
    if (w < 2) {
      float4 v[8];
#pragma unroll
      for (int i = 0; i < 8; i++) v[i] = ldsf4(sb + OFF_REDU + i * 1024 + tid * 16);
      stg_u64(gs->MOD2[par] + (96 + 2 * (cta - NFF) + w) * 64 + t * 16 + g * 2,
              movm(pack_bf16(((v[0].x + v[1].x) + (v[2].x + v[3].x)) + ((v[4].x + v[5].x) + (v[6].x + v[7].x)), ((v[0].y + v[1].y) + (v[2].y + v[3].y)) + ((v[4].y + v[5].y) + (v[6].y + v[7].y)))),
              movm(pack_bf16(((v[0].z + v[1].z) + (v[2].z + v[3].z)) + ((v[4].z + v[5].z) + (v[6].z + v[7].z)), ((v[0].w + v[1].w) + (v[2].w + v[3].w)) + ((v[4].w + v[5].w) + (v[6].w + v[7].w)))));
    }
    CLK(26);
  }
  CLK_DUMP();
}

typedef CUresult (*EncodeTiledFn)(CUtensorMap*, CUtensorMapDataType, cuuint32_t, void*, const cuuint64_t*, const cuuint64_t*,
                                  const cuuint32_t*, const cuuint32_t*, CUtensorMapInterleave, CUtensorMapSwizzle,
                                  CUtensorMapL2promotion, CUtensorMapFloatOOBfill);

struct Dim { uint64_t size, stride; uint32_t box; };
template <int R> void encode_map(EncodeTiledFn enc, CUtensorMap* m, const void* base, const Dim (&d)[R], CUtensorMapSwizzle sw, CUtensorMapL2promotion promo) {
  cuuint64_t dims[R], strides[R];
  cuuint32_t box[R], es[R];
  for (int i = 0; i < R; i++) { dims[i] = d[i].size; strides[i] = d[i].stride; box[i] = d[i].box; es[i] = 1; }
  enc(m, CU_TENSOR_MAP_DATA_TYPE_BFLOAT16, R, const_cast<void*>(base), dims, strides + 1, box, es, CU_TENSOR_MAP_INTERLEAVE_NONE, sw, promo,
      CU_TENSOR_MAP_FLOAT_OOB_FILL_NONE);
}

}

extern "C" void kernel_launch(void* const* d_in, const int* in_sizes, int n_in, void* d_out, int out_size) {
  (void)in_sizes; (void)n_in; (void)out_size;
  static EncodeTiledFn enc = nullptr;
  static Scratch* scratch = nullptr;
  static uint32_t* inbox = nullptr;
  if (!enc) {
    void* sp = nullptr;
    cudaGetSymbolAddress(&sp, g_s);
    scratch = (Scratch*)sp;
    cudaGetSymbolAddress(&sp, g_in);
    inbox = (uint32_t*)(((uintptr_t)sp + 0xfffff) & ~(uintptr_t)0xfffff);
    void* fn = nullptr;
    cudaDriverEntryPointQueryResult q;
    cudaGetDriverEntryPoint("cuTensorMapEncodeTiled", &fn, cudaEnableDefault, &q);
    enc = (EncodeTiledFn)fn;
    cudaFuncSetAttribute(fused_decode_kernel, cudaFuncAttributeMaxDynamicSharedMemorySize, SMEM_BYTES);
  }
  const CUtensorMapSwizzle S128 = CU_TENSOR_MAP_SWIZZLE_128B, S0 = CU_TENSOR_MAP_SWIZZLE_NONE;
  const CUtensorMapL2promotion L0 = CU_TENSOR_MAP_L2_PROMOTION_NONE, L128 = CU_TENSOR_MAP_L2_PROMOTION_L2_128B;
  Params P;
  encode_map<2>(enc, &P.wq, d_in[2], {{4096, 2, 64}, {512, 8192, 64}}, S128, L0);
  encode_map<5>(enc, &P.wuk, d_in[3], {{4096, 2, 64}, {2, 8192, 2}, {4, 4 * 8192, 4}, {2, 2 * 8192, 2}, {32, 16 * 8192, 4}}, S128, L0);
  encode_map<2>(enc, &P.wm2, d_in[10], {{3072, 2, 16}, {512, 6144, 256}}, S0, L128);
  encode_map<2>(enc, &P.wm3, d_in[10], {{3072, 2, 32}, {512, 6144, 256}}, CU_TENSOR_MAP_SWIZZLE_64B, L128);
  encode_map<3>(enc, &P.ckv2, d_in[1], {{64, 2, 64}, {8 * 4096, 1024, 64}, {8, 128, 2}}, S128, L0);
  encode_map<3>(enc, &P.ckv1, d_in[1], {{64, 2, 64}, {8 * 4096, 1024, 64}, {8, 128, 1}}, S128, L0);
  encode_map<5>(enc, &P.wuv, d_in[4], {{4096, 2, 64}, {2, 8 * 8192, 2}, {8, 64 * 8192, 4}, {8, 8192, 8}, {4, 16 * 8192, 1}}, S128, L0);
  encode_map<2>(enc, &P.wo, d_in[5], {{512, 2, 64}, {4096, 1024, 64}}, S128, L0);
  encode_map<2>(enc, &P.w1, d_in[7], {{1792, 2, 32}, {512, 3584, 256}}, CU_TENSOR_MAP_SWIZZLE_64B, L128);
  encode_map<3>(enc, &P.w2, d_in[8], {{64, 2, 64}, {1792, 1024, 32}, {8, 128, 2}}, S128, L0);
  fused_decode_kernel<<<NCTA, NTHREADS, SMEM_BYTES>>>((__nv_bfloat16*)d_out, scratch, (const uint8_t*)d_in[10], (const uint8_t*)d_in[0],
                     (const uint8_t*)d_in[9], inbox,
                     P);
}
```

```cpp
#include <cuda_runtime.h>
#include <cuda.h>
#include <cuda_bf16.h>
#include <stdint.h>
#define V4 1

namespace {

constexpr int NCTA = 128;
constexpr int NTHREADS = 320;
constexpr int NFG = 56;
constexpr int NFF = 2 * NFG;
constexpr int NSYNC = 4;

constexpr uint32_t OFF_RING = 0;
constexpr uint32_t OFF_WUK = 131072;
constexpr uint32_t OFF_WQ = 131072 + 32768;
constexpr uint32_t OFF_WM2 = 65536 + 49152;
constexpr uint32_t OFF_WUV = 131072;
constexpr uint32_t OFF_WO = 131072 + 32768;
constexpr uint32_t OFF_W1 = 0;
constexpr uint32_t OFF_W2 = 32768;
constexpr uint32_t OFF_Q = 196608;
constexpr uint32_t OFF_PT = 212992;
constexpr uint32_t OFF_SCR = 217088;
constexpr uint32_t OFF_XS = 65536;
constexpr uint32_t OFF_CS = 65536 + 8192;
constexpr uint32_t OFF_P0S = 65536 + 16384;
constexpr uint32_t OFF_BS1 = OFF_SCR + 2048;
constexpr uint32_t OFF_BS2 = OFF_SCR + 4096;
constexpr uint32_t OFF_P0B = OFF_SCR + 6144;
constexpr uint32_t OFF_XN = OFF_SCR + 8192;
constexpr uint32_t OFF_RED = OFF_SCR + 10496;
constexpr uint32_t OFF_ALPHA = OFF_SCR + 11072;
constexpr uint32_t OFF_WV = OFF_SCR + 6144;
constexpr uint32_t OFF_SEL = OFF_SCR + 10752;
constexpr uint32_t OFF_TS = OFF_SCR + 11136;
constexpr uint32_t OFF_BARS = OFF_SCR + 11264;
constexpr uint32_t SMEM_BYTES = OFF_BARS + 512;
constexpr uint32_t OFF_BS4 = OFF_Q;
constexpr uint32_t OFF_H1 = OFF_Q + 2304;
constexpr uint32_t OFF_REDS = OFF_Q + 2816;
constexpr uint32_t OFF_BS5 = OFF_Q + 4096;
constexpr uint32_t OFF_REDG = OFF_Q + 8192;
constexpr uint32_t OFF_REDU = 65536;
constexpr uint32_t OFF_REDV = 65536 + 8192;

constexpr int BAR_FULL = 0;
constexpr int BAR_LAST = 28;
constexpr int BAR_WUK = 33, BAR_WM2 = 35, BAR_WUV = 36, BAR_WO = 38, BAR_W1 = 40, BAR_W2 = 41;
constexpr int BAR_ALLCLR = 42, BAR_TS = 43, BAR_WV = 44;
constexpr int BAR_EMPTY = 45;
constexpr int BAR_P0BD = 53;
constexpr int BAR_P1D = 54, BAR_P2D = 55;
constexpr int BAR_P5D = 56, BAR_P7D = 57;
constexpr int NBARS = 58;
constexpr int BAR_XC = 58, BAR_WQ = 59;
constexpr int BAR_C = 61;
constexpr uint32_t SB = 1024;

#define TUNE_LIST(X) \
  X(PC_T0, 355) X(PC_P1, 320) X(PC_PM, 225) X(PC_P2, 319) X(PC_STAG, 390) X(PC_SL, 500) X(PC_NW, 6) \
  X(T_UV, 225) X(P_UV, 250) X(PF_N, 3) X(T_PF, 1060) X(P_PF, 230) X(T_O, 2040) X(P_O, 185) X(T_1, 2960) X(T_2, 3700) X(T_GB, 3520) X(P_F, 300) \
  X(PR_T0, 1000) X(PR_N, 4) X(CLR_T0, 3900) X(CLR_CLK, 190) \
  X(D_MOD, 1450) X(D_QP, 1200) X(D_QX, 950) X(TS_P, 1) X(TS_O, 1970) X(D_TS, 700) X(A_M, 1450) X(D_X1, 1400) X(A_X1, 2460) X(R_X0, 1550) \
  X(D_X2, 275) X(D_X3A, 60) X(R_X3A, 2835) X(D_X3B, 800) X(R_X3B, 915) X(D_FIN, 320) X(R_FIN, 1540)
struct Tune {
#define X(n, v) static constexpr int n = v;
  TUNE_LIST(X)
#undef X
};

struct Scratch {
  uint32_t MOD1[2][4 * 64 * 64];
  uint32_t MOD2[2][128 * 64];
  uint32_t QP[2][128 * 256 * 2];
  uint32_t QX[2][8 * 32 * 256];
  uint32_t epoch;
  uint32_t pad[31];
  uint32_t sync[NSYNC][32];
};
__device__ Scratch g_s;
__device__ uint32_t g_in[(128 + 16) * 16384];
__device__ __forceinline__ uint32_t blk(int c, int k, uint32_t sel) { return c * 16384 + k * 2048 + ((sel ^ k) & 1) * 1024; }
__device__ __forceinline__ uint32_t flip(int c) { return c ^ (c >> 1) ^ (c >> 3); }

#define CLK_DECL
#define CLK(i) do {} while (0)
#define CLK_DUMP() do {} while (0)
#define ITS(i, v) do {} while (0)

struct Params {
  CUtensorMap wq, wuk, wm2, wm3, ckv2, ckv1, wuv, wo, w1, w2;
};

__device__ __forceinline__ void mbar_init(uint32_t bar, int cnt) { asm volatile("mbarrier.init.shared::cta.b64 [%0], %1;" ::"r"(bar), "r"(cnt)); }
__device__ __forceinline__ void mbar_expect(uint32_t bar, uint32_t bytes) { asm volatile("mbarrier.arrive.expect_tx.shared::cta.b64 _, [%0], %1;" ::"r"(bar), "r"(bytes) : "memory"); }
__device__ __forceinline__ void mbar_arrive(uint32_t bar) { asm volatile("mbarrier.arrive.shared::cta.b64 _, [%0];" ::"r"(bar) : "memory"); }
__device__ __forceinline__ uint32_t clk32() { unsigned long long c; asm volatile("mov.u64 %0, %%clock64;" : "=l"(c) :: "memory"); return (uint32_t)c; }
__device__ __forceinline__ uint32_t gtime32() { uint32_t c; asm volatile("mov.u32 %0, %%globaltimer_lo;" : "=r"(c) :: "memory"); return c; }
__device__ __forceinline__ void wait_clk(uint32_t t0, int clocks) { while ((int)(clk32() - t0) < clocks) {} }
__device__ __forceinline__ void backoff(int clocks) { if (clocks > 0) wait_clk(clk32(), clocks); }
__device__ __forceinline__ void until_ns(uint32_t ns) { while ((int)(gtime32() - ns) < 0) {} }
__device__ __forceinline__ void slot(uint32_t& tn, int slack) {
  uint32_t now;
  do { now = gtime32(); } while ((int)(now - tn) < 0);
  if ((int)(now - tn) > slack) tn = now - slack;
}
template <typename T> __device__ __forceinline__ T* pin(T* p) { asm volatile("" : "+l"(p)); return p; }
__device__ __forceinline__ uint32_t pin(uint32_t v) { asm volatile("" : "+r"(v)); return v; }
__device__ __forceinline__ float pin(float v) { asm volatile("" : "+f"(v)); return v; }
constexpr int SPIN_LIMIT = 1 << 22;
__device__ __forceinline__ void mbar_wait(uint32_t bar) {
  asm volatile("{\n.reg .pred p;\n.reg .u32 c;\nmov.u32 c, 0;\n"
               "MW_LOOP:\nmbarrier.try_wait.parity.shared::cta.b64 p, [%0], 0;\n@p bra MW_DONE;\n"
               "add.u32 c, c, 1;\nsetp.lt.u32 p, c, 4194304;\n@p bra MW_LOOP;\ntrap;\nMW_DONE:\n}"
               ::"r"(bar) : "memory");
}
__device__ __forceinline__ bool mbar_test(uint32_t bar) {
  uint32_t ok;
  asm volatile("{\n.reg .pred p;\nmbarrier.test_wait.parity.shared::cta.b64 p, [%1], 0;\nselp.u32 %0,1,0,p;\n}" : "=r"(ok) : "r"(bar) : "memory");
  return ok;
}
__device__ __forceinline__ void tma2d(uint32_t dst, const CUtensorMap* m, int c0, int c1, uint32_t bar, uint64_t pol) {
  asm volatile("cp.async.bulk.tensor.2d.shared::cluster.global.mbarrier::complete_tx::bytes.L2::cache_hint [%0], [%1, {%3,%4}], [%2], %5;"
               ::"r"(dst), "l"(m), "r"(bar), "r"(c0), "r"(c1), "l"(pol) : "memory");
}
__device__ __forceinline__ void tma2d_nohint(uint32_t dst, const CUtensorMap* m, int c0, int c1, uint32_t bar) {
  asm volatile("cp.async.bulk.tensor.2d.shared::cluster.global.mbarrier::complete_tx::bytes [%0], [%1, {%3,%4}], [%2];"
               ::"r"(dst), "l"(m), "r"(bar), "r"(c0), "r"(c1) : "memory");
}
__device__ __forceinline__ void tma3d(uint32_t dst, const CUtensorMap* m, int c0, int c1, int c2, uint32_t bar, uint64_t pol) {
  asm volatile("cp.async.bulk.tensor.3d.shared::cluster.global.mbarrier::complete_tx::bytes.L2::cache_hint [%0], [%1, {%3,%4,%5}], [%2], %6;"
               ::"r"(dst), "l"(m), "r"(bar), "r"(c0), "r"(c1), "r"(c2), "l"(pol) : "memory");
}
__device__ __forceinline__ void tma5d(uint32_t dst, const CUtensorMap* m, int c0, int c1, int c2, int c3, int c4, uint32_t bar, uint64_t pol) {
  asm volatile("cp.async.bulk.tensor.5d.shared::cluster.global.mbarrier::complete_tx::bytes.L2::cache_hint [%0], [%1, {%3,%4,%5,%6,%7}], [%2], %8;"
               ::"r"(dst), "l"(m), "r"(bar), "r"(c0), "r"(c1), "r"(c2), "r"(c3), "r"(c4), "l"(pol) : "memory");
}
__device__ __forceinline__ void bulk_ld(uint32_t dst, const void* src, uint32_t bytes, uint32_t bar) {
  asm volatile("cp.async.bulk.shared::cluster.global.mbarrier::complete_tx::bytes [%0], [%1], %2, [%3];" ::"r"(dst), "l"(src), "r"(bytes), "r"(bar) : "memory");
}
__device__ __forceinline__ void bar_sync(int id, int n) { asm volatile("barrier.cta.sync.aligned %0, %1;" ::"r"(id), "r"(n) : "memory"); }
__device__ __forceinline__ void cbar() { asm volatile("barrier.cta.sync.aligned 1, 256;" ::: "memory"); }
__device__ __forceinline__ bool bar_over(float ex) {
  uint32_t over;
  asm volatile("{\n.reg .pred p, q;\nsetp.gtu.f32 p, %1, 0f42700000;\nbarrier.cta.red.or.aligned.pred q, 4, 256, p;\nselp.u32 %0, 1, 0, q;\n}"
               : "=r"(over) : "f"(ex) : "memory");
  return over;
}

__device__ __forceinline__ uint32_t ldg_nc1(const void* p) { uint32_t v; asm volatile("ld.global.nc.L1::no_allocate.u32 %0, [%1];" : "=r"(v) : "l"(p)); return v; }
__device__ __forceinline__ uint2 ldg_nc2(const void* p) { uint2 v; asm volatile("ld.global.nc.v2.u32 {%0,%1}, [%2];" : "=r"(v.x), "=r"(v.y) : "l"(p)); return v; }
__device__ __forceinline__ uint4 ldg_nc4(const void* p) { uint4 v; asm volatile("ld.global.nc.L1::no_allocate.v4.u32 {%0,%1,%2,%3}, [%4];" : "=r"(v.x), "=r"(v.y), "=r"(v.z), "=r"(v.w) : "l"(p)); return v; }
__device__ __forceinline__ uint32_t ldg_rlx1(const void* p) { uint32_t v; asm volatile("ld.relaxed.gpu.global.u32 %0, [%1];" : "=r"(v) : "l"(p) : "memory"); return v; }
__device__ __forceinline__ void stg4(void* p, uint4 v) { asm volatile("st.relaxed.gpu.global.v4.u32 [%0], {%1,%2,%3,%4};" ::"l"(p), "r"(v.x), "r"(v.y), "r"(v.z), "r"(v.w) : "memory"); }
__device__ __forceinline__ void stg1(void* p, uint32_t a) { asm volatile("st.relaxed.gpu.global.u32 [%0], %1;" ::"l"(p), "r"(a) : "memory"); }
__device__ __forceinline__ uint32_t nz(uint32_t w) { return max(w, 1u); }
__device__ __forceinline__ uint2 ldg_u64(const void* p) {
  uint2 v; asm volatile("{\n.reg .b64 a;\nld.relaxed.gpu.global.b64 a, [%2];\nmov.b64 {%0,%1}, a;\n}" : "=r"(v.x), "=r"(v.y) : "l"(p) : "memory"); return v;
}
__device__ __forceinline__ uint4 ldg_2u64(const void* p) {
  uint4 v; asm volatile("{\n.reg .b64 a, b;\nld.relaxed.gpu.global.v2.b64 {a, b}, [%4];\nmov.b64 {%0,%1}, a;\nmov.b64 {%2,%3}, b;\n}" : "=r"(v.x), "=r"(v.y), "=r"(v.z), "=r"(v.w) : "l"(p) : "memory"); return v;
}
__device__ __forceinline__ void stg_u64(void* p, uint32_t x, uint32_t y) {
  asm volatile("{\n.reg .b32 y;\nmax.u32 y, %2, 1;\nst.relaxed.gpu.global.v2.b32 [%0], {%1, y};\n}" ::"l"(p), "r"(x), "r"(y) : "memory");
}
__device__ __forceinline__ void red_u64(void* p, uint32_t x, uint32_t y) {
  asm volatile("{\n.reg .b32 y;\n.reg .b64 a;\nmax.u32 y, %2, 1;\nmov.b64 a, {%1, y};\nred.relaxed.gpu.global.or.b64 [%0], a;\n}" ::"l"(p), "r"(x), "r"(y) : "memory");
}
__device__ __forceinline__ void stg_u64_unless(uint32_t bad, void* p, uint32_t x, uint32_t y) {
  asm volatile("{\n.reg .b32 y;\n.reg .pred q;\nsetp.eq.u32 q, %3, 0;\nmax.u32 y, %2, 1;\n@q st.relaxed.gpu.global.v2.b32 [%0], {%1, y};\n}" ::"l"(p), "r"(x), "r"(y), "r"(bad) : "memory");
}

__device__ __forceinline__ void stg_cvt8(void* p, float a0, float a1, float b0, float b1, float c0, float c1, float d0, float d1) {
  asm volatile("{\n.reg .b32 x, y, z, w;\ncvt.rn.bf16x2.f32 x, %2, %1;\ncvt.rn.bf16x2.f32 y, %4, %3;\ncvt.rn.bf16x2.f32 z, %6, %5;\ncvt.rn.bf16x2.f32 w, %8, %7;\n"
               "max.u32 y, y, 1;\nmax.u32 w, w, 1;\nst.relaxed.gpu.global.v4.b32 [%0], {x, y, z, w};\n}"
               ::"l"(p), "f"(a0), "f"(a1), "f"(b0), "f"(b1), "f"(c0), "f"(c1), "f"(d0), "f"(d1) : "memory");
}
__device__ __forceinline__ uint32_t pack_bf16(float lo, float hi) { uint32_t r; asm("cvt.rn.bf16x2.f32 %0, %1, %2;" : "=r"(r) : "f"(hi), "f"(lo)); return r; }
__device__ __forceinline__ float bf_lo(uint32_t w) { return __uint_as_float(w << 16); }
__device__ __forceinline__ float bf_hi(uint32_t w) { return __uint_as_float(w & 0xffff0000u); }
__device__ __forceinline__ float ex2(float x) { float r; asm("ex2.approx.ftz.f32 %0, %1;" : "=f"(r) : "f"(x)); return r; }
__device__ __forceinline__ uint32_t hmul2(uint32_t a, uint32_t b) { uint32_t r; asm("mul.rn.bf16x2 %0, %1, %2;" : "=r"(r) : "r"(a), "r"(b)); return r; }
__device__ __forceinline__ uint32_t hadd2(uint32_t a, uint32_t b) { uint32_t r; asm("add.rn.bf16x2 %0, %1, %2;" : "=r"(r) : "r"(a), "r"(b)); return r; }
__device__ __forceinline__ uint32_t silu2(uint32_t v) { const float a = bf_lo(v), b = bf_hi(v); return pack_bf16(__fdividef(a, 1.f + __expf(-a)), __fdividef(b, 1.f + __expf(-b))); }
constexpr uint32_t ONE2 = 0x3f803f80u;

__device__ __forceinline__ void ldsm4(uint32_t (&r)[4], uint32_t a) { asm volatile("ldmatrix.sync.aligned.m8n8.x4.shared.b16 {%0,%1,%2,%3}, [%4];" : "=r"(r[0]), "=r"(r[1]), "=r"(r[2]), "=r"(r[3]) : "r"(a) : "memory"); }
__device__ __forceinline__ void ldsm4t(uint32_t (&r)[4], uint32_t a) { asm volatile("ldmatrix.sync.aligned.m8n8.x4.trans.shared.b16 {%0,%1,%2,%3}, [%4];" : "=r"(r[0]), "=r"(r[1]), "=r"(r[2]), "=r"(r[3]) : "r"(a) : "memory"); }
__device__ __forceinline__ void stsm4t(uint32_t a, uint32_t r0, uint32_t r1, uint32_t r2, uint32_t r3) { asm volatile("stmatrix.sync.aligned.m8n8.x4.trans.shared.b16 [%0], {%1,%2,%3,%4};" ::"r"(a), "r"(r0), "r"(r1), "r"(r2), "r"(r3) : "memory"); }
__device__ __forceinline__ uint32_t movm(uint32_t a) { uint32_t d; asm volatile("movmatrix.sync.aligned.m8n8.trans.b16 %0, %1;" : "=r"(d) : "r"(a)); return d; }
__device__ __forceinline__ void mma16816(float (&d)[4], const uint32_t (&a)[4], uint32_t b0, uint32_t b1) {
  asm volatile("mma.sync.aligned.m16n8k16.row.col.f32.bf16.bf16.f32 {%0,%1,%2,%3}, {%4,%5,%6,%7}, {%8,%9}, {%0,%1,%2,%3};"
               : "+f"(d[0]), "+f"(d[1]), "+f"(d[2]), "+f"(d[3]) : "r"(a[0]), "r"(a[1]), "r"(a[2]), "r"(a[3]), "r"(b0), "r"(b1));
}
__device__ __forceinline__ void sts1(uint32_t a, uint32_t v) { asm volatile("st.shared.u32 [%0], %1;" ::"r"(a), "r"(v) : "memory"); }
__device__ __forceinline__ void sts2(uint32_t a, uint32_t x, uint32_t y) { asm volatile("st.shared.v2.u32 [%0], {%1,%2};" ::"r"(a), "r"(x), "r"(y) : "memory"); }
__device__ __forceinline__ void sts4(uint32_t a, uint4 v) { asm volatile("st.shared.v4.u32 [%0], {%1,%2,%3,%4};" ::"r"(a), "r"(v.x), "r"(v.y), "r"(v.z), "r"(v.w) : "memory"); }
__device__ __forceinline__ void sts2f(uint32_t a, float x, float y) { asm volatile("st.shared.v2.f32 [%0], {%1,%2};" ::"r"(a), "f"(x), "f"(y) : "memory"); }
__device__ __forceinline__ void sts4f(uint32_t a, float x, float y, float z, float w) { asm volatile("st.shared.v4.f32 [%0], {%1,%2,%3,%4};" ::"r"(a), "f"(x), "f"(y), "f"(z), "f"(w) : "memory"); }
__device__ __forceinline__ void stsf(uint32_t a, float v) { asm volatile("st.shared.f32 [%0], %1;" ::"r"(a), "f"(v) : "memory"); }
__device__ __forceinline__ uint32_t lds1(uint32_t a) { uint32_t v; asm volatile("ld.shared.u32 %0, [%1];" : "=r"(v) : "r"(a) : "memory"); return v; }
__device__ __forceinline__ float ldsf(uint32_t a) { float v; asm volatile("ld.shared.f32 %0, [%1];" : "=f"(v) : "r"(a) : "memory"); return v; }
__device__ __forceinline__ float2 ldsf2(uint32_t a) { float2 v; asm volatile("ld.shared.v2.f32 {%0,%1}, [%2];" : "=f"(v.x), "=f"(v.y) : "r"(a) : "memory"); return v; }
__device__ __forceinline__ float4 ldsf4(uint32_t a) { float4 v; asm volatile("ld.shared.v4.f32 {%0,%1,%2,%3}, [%4];" : "=f"(v.x), "=f"(v.y), "=f"(v.z), "=f"(v.w) : "r"(a) : "memory"); return v; }
__device__ __forceinline__ void lds4(uint32_t (&r)[4], uint32_t a) { asm volatile("ld.shared.v4.u32 {%0,%1,%2,%3}, [%4];" : "=r"(r[0]), "=r"(r[1]), "=r"(r[2]), "=r"(r[3]) : "r"(a) : "memory"); }

__device__ __forceinline__ void wg_fence() { asm volatile("wgmma.fence.sync.aligned;" ::: "memory"); }
__device__ __forceinline__ void wg_commit() { asm volatile("wgmma.commit_group.sync.aligned;" ::: "memory"); }
template <int N> __device__ __forceinline__ void wg_wait() { asm volatile("wgmma.wait_group.sync.aligned %0;" ::"n"(N) : "memory"); }
__host__ __device__ constexpr uint32_t desc_lo(uint32_t off) { return ((SB + off) >> 4) | 0x10000u; }
template <int TA, int ACC> __device__ __forceinline__ void wgmma_n16(float (&d)[8], uint32_t da, uint32_t db) {
  asm volatile("{\n.reg .b64 da, db;\nmov.b64 da, {%8, 0x40000040};\nmov.b64 db, {%9, 0x40000040};\n"
               "wgmma.mma_async.sync.aligned.m64n16k16.f32.bf16.bf16 {%0,%1,%2,%3,%4,%5,%6,%7}, da, db, %11, 1, 1, %10, 0;\n}"
               : "+f"(d[0]), "+f"(d[1]), "+f"(d[2]), "+f"(d[3]), "+f"(d[4]), "+f"(d[5]), "+f"(d[6]), "+f"(d[7])
               : "r"(da), "r"(db), "n"(TA), "n"(ACC));
}
__device__ __forceinline__ void wgmma_n16_ones(float (&d)[8], uint32_t one, uint32_t db) {
  asm volatile("{\n.reg .b64 db;\nmov.b64 db, {%9, 0x40000040};\n"
               "wgmma.mma_async.sync.aligned.m64n16k16.f32.bf16.bf16 {%0,%1,%2,%3,%4,%5,%6,%7}, {%8,%8,%8,%8}, db, 1, 1, 1, 0;\n}"
               : "+f"(d[0]), "+f"(d[1]), "+f"(d[2]), "+f"(d[3]), "+f"(d[4]), "+f"(d[5]), "+f"(d[6]), "+f"(d[7])
               : "r"(one), "r"(db));
}
__device__ __forceinline__ void acc_fence(float (&d)[8]) {
  asm volatile("" : "+f"(d[0]), "+f"(d[1]), "+f"(d[2]), "+f"(d[3]), "+f"(d[4]), "+f"(d[5]), "+f"(d[6]), "+f"(d[7]) :: "memory");
}

template <int N, int STRIDE> __device__ __forceinline__ void load_units(uint2 (&v)[N], const uint32_t* p) {
#pragma unroll
  for (int i = 0; i < N; i++) v[i] = ldg_u64(p + i * STRIDE);
}
__device__ __forceinline__ void reload_unit(uint2& v, const uint32_t* p) {
  asm volatile("{\n.reg .pred q;\nsetp.eq.u32 q, %1, 0;\n@q ld.relaxed.gpu.global.v2.b32 {%0, %1}, [%2];\n}" : "+r"(v.x), "+r"(v.y) : "l"(p) : "memory");
}
template <int N> __device__ __forceinline__ uint32_t min_flags(const uint2 (&v)[N]) {
  uint32_t a = v[0].y, b = v[1].y;
#pragma unroll
  for (int i = 2; i < N; i += 2) { a = min(a, v[i].y); b = min(b, v[i + 1].y); }
  return min(a, b);
}
template <int N, int STRIDE> __device__ __forceinline__ int check_units(uint2 (&v)[N], const uint32_t* p) {
  int it = 0;
  while (!__all_sync(~0u, min_flags(v) != 0)) {
#pragma unroll
    for (int i = 0; i < N; i++) reload_unit(v[i], p + i * STRIDE);
    if (++it > SPIN_LIMIT) __trap();
  }
  return it;
}
__device__ __forceinline__ void sum4_to_smem(const uint2 (&v)[4], uint32_t dst) {
  const float c0 = (bf_lo(v[0].x) + bf_lo(v[1].x)) + (bf_lo(v[2].x) + bf_lo(v[3].x));
  const float c1 = (bf_hi(v[0].x) + bf_hi(v[1].x)) + (bf_hi(v[2].x) + bf_hi(v[3].x));
  const float c2 = (bf_lo(v[0].y) + bf_lo(v[1].y)) + (bf_lo(v[2].y) + bf_lo(v[3].y));
  const float c3 = (bf_hi(v[0].y) + bf_hi(v[1].y)) + (bf_hi(v[2].y) + bf_hi(v[3].y));
  sts1(dst, pack_bf16(c0, c1));
  sts1(dst + 128, pack_bf16(c2, c3));
}
__device__ __forceinline__ uint32_t a_t_offset(int w, int lane) {
  const int mi = lane >> 3, r = lane & 7;
  return (w >> 2) * 16384 + (8 * (mi >> 1) + r) * 128 + (((2 * (w & 3) + (mi & 1)) ^ r) << 4);
}
__device__ __forceinline__ void load_a_t(uint32_t (&a)[8][4], uint32_t base) {
#pragma unroll
  for (int ks = 0; ks < 8; ks++) ldsm4t(a[ks], base + ks * 2048);
}
__device__ __forceinline__ void mma128(float (&d)[4], const uint32_t (&a)[8][4], const uint32_t (&b)[4][4]) {
  float e[4][4] = {{d[0], d[1], d[2], d[3]}, {0.f, 0.f, 0.f, 0.f}, {0.f, 0.f, 0.f, 0.f}, {0.f, 0.f, 0.f, 0.f}};
#pragma unroll
  for (int kk = 0; kk < 4; kk++) { mma16816(e[(2 * kk) & 3], a[2 * kk], b[kk][0], b[kk][1]); mma16816(e[(2 * kk + 1) & 3], a[2 * kk + 1], b[kk][2], b[kk][3]); }
#pragma unroll
  for (int i = 0; i < 4; i++) d[i] = (e[0][i] + e[1][i]) + (e[2][i] + e[3][i]);
}
template <int NP> __device__ __forceinline__ bool sum_pieces(const uint32_t* p0, uint32_t one, float (&r)[4]) {
  uint2 v[NP / 4];
  load_units<NP / 4, 64>(v, p0);
  float d[4][4] = {};
#pragma unroll
  for (int i = 0; i < NP / 8; i++) { const uint32_t a[4] = {v[2 * i].x, v[2 * i].y, v[2 * i + 1].x, v[2 * i + 1].y}; mma16816(d[i & 3], a, one, one); }
  const bool ok = __all_sync(~0u, min_flags(v) != 0);
#pragma unroll
  for (int k = 0; k < 4; k++) r[k] = (d[0][k] + d[1][k]) + (d[2][k] + d[3][k]);
  return ok;
}
template <typename F> __device__ __forceinline__ float reduce_g(const float (&x)[4], int lane, F f) {
  const bool u4 = lane & 16, u3 = lane & 8;
  const float a0 = f(u4 ? x[2] : x[0], __shfl_xor_sync(~0u, u4 ? x[0] : x[2], 16));
  const float a1 = f(u4 ? x[3] : x[1], __shfl_xor_sync(~0u, u4 ? x[1] : x[3], 16));
  const float b = f(u3 ? a1 : a0, __shfl_xor_sync(~0u, u3 ? a0 : a1, 8));
  return f(b, __shfl_xor_sync(~0u, b, 4));
}

__global__ void __launch_bounds__(NTHREADS, 1)
fused_decode_kernel(__nv_bfloat16* __restrict__ gout, Scratch* __restrict__ gs, const uint8_t* __restrict__ gwmod,
                    const uint8_t* __restrict__ gx, const uint8_t* __restrict__ gc, uint32_t* __restrict__ gin,
                    const __grid_constant__ Params P) {
  constexpr Tune T{};
  extern __shared__ __align__(1024) uint8_t smem_raw[];
  constexpr uint32_t sb = SB;
  const int tid = __shfl_xor_sync(0xffffffffu, threadIdx.x ^ 1, 1), lane = tid & 31;
  const int w = __shfl_sync(0xffffffffu, threadIdx.x >> 5, 0);
  const int cta = blockIdx.x;
  auto BAR = [](int i) { return SB + OFF_BARS + 8 * i; };
  auto selector = [&](int c) { uint32_t v; asm volatile("ld.shared.u8 %0, [%1];" : "=r"(v) : "r"(sb + OFF_SEL + c) : "memory"); return v; };
  auto inbox = [&](int c, int k) { return gin + blk(c, k, selector(c)); };
  auto nearbox = [&](int c, int k) { return gin + blk(c, k, selector(cta) ^ flip((c ^ cta) & 15)); };
  const int g = lane >> 2, t = lane & 3;
  const int hI = cta >> 2, jI = cta & 3;
  const int bs = cta >> 1, hh = cta & 1;

  CLK_DECL;
  CLK(0);
  if (w == 8) {
    CLK(7);
    const uint32_t t_entry = gtime32();
    CLK(8);
    if (lane == 0) {
      if ((uint32_t)__cvta_generic_to_shared(smem_raw) != SB) __trap();
      mbar_init(BAR(BAR_WQ), 1); mbar_init(BAR(BAR_WQ + 1), 1); mbar_init(BAR(BAR_XC), 1); mbar_init(BAR(BAR_C), 1);
      asm volatile("fence.mbarrier_init.release.cluster;" ::: "memory");
      asm volatile("prefetch.tensormap [%0];" ::"l"(&P.wq) : "memory");
      mbar_expect(BAR(BAR_XC), 8192); mbar_expect(BAR(BAR_C), 8192); mbar_expect(BAR(BAR_WQ), 16384); mbar_expect(BAR(BAR_WQ + 1), 16384);
      CLK(9);
    }
    __syncwarp();
    asm volatile("barrier.cta.arrive.aligned 0, %0;" ::"n"(NTHREADS) : "memory");
    CLK(10);
    uint32_t tn = t_entry + T.PC_T0 + ((bs * 37) & 63) * T.PC_STAG / 64;
    const int h = hI, j = jI;
    if (lane == 0) {
      uint64_t pol; asm volatile("createpolicy.fractional.L2::evict_first.b64 %0, 1.0;" : "=l"(pol));
#pragma unroll
      for (int u = 0; u < 4; u++) {
        until_ns(tn + u * T.PC_P1);
        if (u == 0) CLK(11);
        tma2d(sb + OFF_WQ + u * 8192, &P.wq, 128 * h + 64 * (u >> 1), 128 * j + 64 * (u & 1), BAR(BAR_WQ + (u >> 1)), pol);
        if (u == 0) {
#pragma unroll
          for (int i = 0; i < 8; i++) { const int o = ((i + cta) & 3) * 2048; bulk_ld(sb + OFF_XS + (i >> 2) * 8192 + o, (i < 4 ? gx : gc) + o, 2048, BAR(i < 4 ? BAR_XC : BAR_C)); }
          CLK(1);
          asm volatile("prefetch.tensormap [%0];" ::"l"(&P.wuk) : "memory");
          asm volatile("prefetch.tensormap [%0];" ::"l"(&P.wm2) : "memory");
          asm volatile("prefetch.tensormap [%0];" ::"l"(&P.ckv2) : "memory");
        }
      }
    }
    __syncwarp();
    tn += 4 * T.PC_P1;
    bar_sync(5, 64);
    if (lane == 0) {
      uint64_t pol; asm volatile("createpolicy.fractional.L2::evict_first.b64 %0, 1.0;" : "=l"(pol));
#pragma unroll
      for (int u = 0; u < 4; u++) {
        if (u & 1) mbar_wait(BAR(BAR_WQ + (u >> 1)));
        slot(tn, T.PC_SL);
        tma5d(sb + OFF_WUK + u * 8192, &P.wuk, 128 * h + 64 * (u >> 1), 0, 0, 0, 8 * j + 4 * (u & 1), BAR(BAR_WUK + (u >> 1)), pol);
        tn += T.PC_P1;
      }
#pragma unroll
      for (int u = 0; u < 2; u++) {
        if (u) mbar_wait(BAR(BAR_WUK));
        slot(tn, T.PC_SL);
        if (j != 3) tma2d_nohint(sb + OFF_WM2 + u * 8192, &P.wm2, 1024 + 16 * (3 * h + j), 256 * u, BAR(BAR_WM2));
        tn += T.PC_PM;
      }
      const int row0 = (bs >> 3) * 4096 + (bs & 7) * 64;
      uint32_t dst = sb + OFF_RING;
#pragma unroll 1
      for (int n = 0; n < 31; n++) {
        if (n >= 4 && (n < 12 || (n & 3) == 0)) mbar_wait(BAR(n >= 12 ? BAR_EMPTY + (n >> 2) - 3 : (n == 7 && j != 3) ? BAR_P0BD : (n == 8 || n == 9) ? BAR_P2D : BAR_P1D));
        if (n < T.PC_NW) {
          if (n >= 4) mbar_wait(BAR(BAR_FULL + n - 4));
          else if (n & 1) mbar_wait(BAR((n < 2 || j == 3) ? BAR_WUK + 1 : BAR_WM2));
        }
        slot(tn, T.PC_SL);
        tma3d(dst, &P.ckv2, 0, row0 + (n >> 2) * 512, 2 * (n & 3), BAR(BAR_FULL + n), pol);
        dst = (n == 11 || n == 23) ? sb + OFF_RING : dst + 16384;
        tn += T.PC_P2;
        if (n == 4) CLK(2);
        if (n == 12) CLK(3);
        if (n == 20) CLK(4);
        if (n == 28) CLK(5);
        if (n == 24) {
          asm volatile("prefetch.tensormap [%0];" ::"l"(&P.ckv1) : "memory");
          asm volatile("prefetch.tensormap [%0];" ::"l"(&P.wuv) : "memory");
          asm volatile("prefetch.tensormap [%0];" ::"l"(&P.wo) : "memory");
          asm volatile("prefetch.tensormap [%0];" ::"l"(cta < NFF ? &P.w1 : &P.wm3) : "memory");
          asm volatile("prefetch.tensormap [%0];" ::"l"(&P.w2) : "memory");
        }
      }
      slot(tn, T.PC_SL);
      tma3d(dst, &P.ckv1, 0, row0 + 7 * 512, 6, BAR(BAR_LAST + 3), pol);
      tma3d(dst + 8192, &P.ckv1, 0, row0 + 7 * 512, 7, BAR(BAR_LAST + 4), pol);
      tn += T.PC_P2;
      CLK(6);
      auto unit = [&](int u) {
        if (u < 4) tma5d(sb + OFF_WUV + u * 8192, &P.wuv, 128 * h + 64 * (u >> 1), 0, 4 * (j >> 1), 0, 2 * (j & 1) + (u & 1), BAR(BAR_WUV + (u >> 1)), pol);
        else if (u < 8) tma2d(sb + OFF_WO + (u - 4) * 8192, &P.wo, 128 * j + 64 * ((u - 4) >> 1), 128 * h + 64 * (u & 1), BAR(BAR_WO + ((u - 4) >> 1)), pol);
        else if (u < 10) { if (cta < NFF) tma2d_nohint(sb + OFF_W1 + (u - 8) * 16384, &P.w1, 32 * bs, 256 * (u - 8), BAR(BAR_W1)); }
        else if (cta < NFF) tma3d(sb + OFF_W2 + (u - 10) * 8192, &P.w2, 0, 32 * bs, 4 * hh + 2 * (u - 10), BAR(BAR_W2), pol);
        else tma2d_nohint(sb + OFF_W1 + (u - 10) * 16384, &P.wm3, 2560 + 32 * (cta - NFF), 256 * (u - 10), BAR(BAR_W1));
      };
      mbar_wait(BAR(BAR_EMPTY + 5));
#pragma unroll
      for (int u = 0; u < 12; u++) {
        if (u == 8) mbar_wait(BAR(BAR_EMPTY + 6));
        until_ns(tn + (u < 4 ? T.T_UV + u * T.P_UV : u < 8 ? T.T_O + (u - 4) * T.P_O : u < 10 ? T.T_1 + (u - 8) * T.P_F : (cta < NFF ? T.T_2 : T.T_GB) + (u - 10) * T.P_F));
        unit(u);
        if (u == 3) {
#pragma unroll
          for (int q = 0; q < 4; q++)
            if (q < T.PF_N) {
              until_ns(tn + T.T_PF + q * T.P_PF);
              asm volatile("cp.async.bulk.prefetch.tensor.2d.L2.global.tile [%0, {%1,%2}];" ::"l"(&P.wo), "r"(128 * j + 64 * (q >> 1)), "r"(128 * h + 64 * (q & 1)) : "memory");
            }
        }
      }
      CLK_DUMP();
    }
    return;
  }

  if (w == 9) {
    if (lane == 0) {
#pragma unroll
      for (int i = 0; i < NBARS; i++) mbar_init(BAR(i), i >= BAR_P1D ? 8 : i >= BAR_EMPTY ? 4 : 1);
      asm volatile("fence.mbarrier_init.release.cluster;" ::: "memory");
    }
    __syncwarp();
    mbar_expect(BAR(lane), lane == BAR_LAST + 3 ? 8192 : 16384);
    if (lane < BAR_ALLCLR - 32) mbar_expect(BAR(32 + lane), lane == 0 ? 8192 : lane == BAR_W1 - 32 ? 32768 : 16384);
    CLK(9);
    asm volatile("barrier.cta.arrive.aligned 5, 64;" ::: "memory");
    asm volatile("barrier.cta.arrive.aligned 0, %0;" ::"n"(NTHREADS) : "memory");
  }
  const uint32_t epoch = ldg_rlx1(&gs->epoch);

  if (w == 9) {
    const int mo = g * 512 + 16 * hI + 2 * jI;
    const uint32_t xo0 = ldg_nc1(gx + mo * 2), xo1 = ldg_nc1(gx + mo * 2 + 16);
    const int par = epoch & 1;
    const uint32_t t0 = gtime32();
    const uint4 z = make_uint4(0, 0, 0, 0);
    uint32_t sel;
    {
      uint32_t* pa = gin + blk(cta, 5, 0) + 960;
      uint32_t* pb = gin + blk(cta, 5, 1) + 960;
      until_ns(t0 + T.PR_T0);
      if (lane < 4) stg4(reinterpret_cast<uint4*>(lane & 2 ? pa : pb) + (lane & 1), z);
      uint32_t ma = 0xffffffffu, mb = 0xffffffffu;
#pragma unroll 1
      for (int i = 0; i < 2 * T.PR_N; i++) {
        const uint32_t c0 = clk32();
        asm volatile("{\n.reg .pred q;\n.reg .b32 v;\nsetp.eq.u32 q, %1, 0;\nmov.u32 v, 0;\n@q atom.relaxed.gpu.global.add.u32 v, [%0], 1;\n"
                     "setp.eq.u32 q, v, 0xffffffff;\n@q trap;\n}" ::"l"(i & 1 ? pb : pa), "r"(lane) : "memory");
        const uint32_t d = clk32() - c0;
        if (i & 1) mb = min(mb, d); else ma = min(ma, d);
      }
      sel = __shfl_sync(~0u, (uint32_t)(mb < ma), 0);
      const uint32_t sw = 2 * (epoch + 1) + sel;
      if (lane < 2) stg4(reinterpret_cast<uint4*>(gin + blk(cta, 5, 1) + 896) + lane, make_uint4(sw, sw, sw, sw));
    }
    until_ns(t0 + T.CLR_T0);
    {
#pragma unroll 1
      for (int i0 = 0; i0 < 13; i0++) {
        uint4* q = reinterpret_cast<uint4*>(gin + (i0 < 12 ? blk(cta, i0 >> 1, sel) + (i0 & 1) * 512 : blk(cta, 4, sel ^ 1) + 512)) + lane;
#pragma unroll
        for (int i = 0; i < 4; i++) if (i0 != 11 || i < 3) stg4(q + i * 32, z);
        backoff(T.CLR_CLK);
      }
#pragma unroll
      for (int i = 0; i < 2; i++) {
        if (jI == 1) stg4(reinterpret_cast<uint4*>(gin + blk(cta, 6, i)) + lane, z);
        if (lane < 2) stg4(reinterpret_cast<uint4*>(gin + blk(cta, 5, i) + 928) + lane, z);
        stg4(reinterpret_cast<uint4*>(gin + blk(16 * g, 6 + (cta >> 6), i) + (cta & 63) * 16) + t, z);
      }
      CLK(1);
      {
        uint32_t sv = 0;
        uint32_t u[4];
        int it = 0;
        do {
#pragma unroll
          for (int i = 0; i < 4; i++) u[i] = ldg_rlx1(gin + blk(4 * lane + i, 5, 1) + 896) ^ (2 * (epoch + 1));
          if (++it > SPIN_LIMIT) __trap();
        } while (!__all_sync(~0u, (u[0] | u[1] | u[2] | u[3]) < 2));
#pragma unroll
        for (int i = 0; i < 4; i++) sv |= u[i] << (8 * i);
        sts1(sb + OFF_SEL + lane * 4, sv);
      }
      asm volatile("fence.acq_rel.gpu;" ::: "memory");
      CLK(2);
      __syncwarp();
      if (lane < NSYNC) asm volatile("red.relaxed.gpu.global.add.u32 [%0], 1;" ::"l"(&gs->sync[lane][0]) : "memory");
#pragma unroll
      for (int i = 0; i < 4; i++) stg4(reinterpret_cast<uint4*>(gs->QP[par ^ 1] + cta * 512) + i * 32 + lane, z);
      backoff(T.CLR_CLK);
#pragma unroll
      for (int i = 0; i < 4; i++) stg4(reinterpret_cast<uint4*>(gs->QX[par ^ 1] + cta * 512) + i * 32 + lane, z);
      stg4(reinterpret_cast<uint4*>(gs->MOD1[par ^ 1] + cta * 128) + lane, z);
      if (lane < 16) stg4(reinterpret_cast<uint4*>(gs->MOD2[par ^ 1] + cta * 64) + lane, z);
      const uint32_t target = (epoch + 1) * NCTA;
      uint32_t c; int it = 0;
      do {
        backoff(T.CLR_CLK);
        asm volatile("ld.acquire.gpu.global.u32 %0, [%1];" : "=r"(c) : "l"(&gs->sync[cta % NSYNC][0]) : "memory");
        if (++it > SPIN_LIMIT) __trap();
      } while (!__all_sync(~0u, (int)(c - target) >= 0));
      if (lane == 0) mbar_arrive(BAR(BAR_ALLCLR));
    }
    CLK(3);
    const uint32_t* const pg = gs->MOD2[par] + cta * 16 + g * 2;
    auto gate = [&](const uint32_t* q) { uint2 u; int it = 0; do { u = ldg_u64(q); if (++it > SPIN_LIMIT) __trap(); } while (!__all_sync(~0u, u.y != 0)); return u; };
    const uint2 gau = gate(pg);
    uint32_t anchor;
    {
      uint32_t* const po = gin + blk(16 * (lane & 7), 5, lane >> 3) + 928;
      const uint32_t* const pi = nearbox(cta & ~15, 5) + 928;
      mbar_wait(BAR(BAR_LAST + T.TS_P));
      unsigned long long now; asm volatile("mov.u64 %0, %%globaltimer;" : "=l"(now));
      if (lane < 16) asm volatile("red.relaxed.gpu.global.add.u64 [%0], %1;" ::"l"(po), "l"((now << 8) + 1) : "memory");
      backoff(T.D_TS);
      uint2 v; int it = 0;
      do { v = ldg_u64(pi); if (++it > SPIN_LIMIT) __trap(); } while (!__all_sync(~0u, (v.x & 255) == NCTA));
      const uint32_t mean = __funnelshift_r(v.x, v.y, 15);
      const int age = min(max((int)(gtime32() - mean), 0), 4000);
      anchor = clk32() - age * 7 / 4 + T.TS_O;
      if (lane == 0) { sts1(sb + OFF_TS, anchor); mbar_arrive(BAR(BAR_TS)); }
      CLK(10);
    }
    {
      const uint32_t* pm = pin(nearbox(4 * hI + 1, 6) + lane * 4);
      wait_clk(anchor, T.A_M);
      uint4 ml = ldg_2u64(pm);
      int it = 0;
      while (!__all_sync(~0u, ml.y != 0 && ml.w != 0)) { ml = ldg_2u64(pm); if (++it > SPIN_LIMIT) __trap(); }
      ITS(2, it);
      float M = fmaxf(__uint_as_float(ml.x), __uint_as_float(ml.z));
      M = fmaxf(M, __shfl_xor_sync(~0u, M, 1)); M = fmaxf(M, __shfl_xor_sync(~0u, M, 2));
      const float e0 = ex2(__uint_as_float(ml.x) - M), e1 = ex2(__uint_as_float(ml.z) - M);
      float l = e0 * __uint_as_float(ml.y) + e1 * __uint_as_float(ml.w);
      l += __shfl_xor_sync(~0u, l, 1); l += __shfl_xor_sync(~0u, l, 2);
      const float inv = __fdividef(1.f, l);
      sts2f(sb + OFF_WV + lane * 8, e0 * inv, e1 * inv);
      __syncwarp();
      if (lane == 0) mbar_arrive(BAR(BAR_WV));
      CLK(11);
    }
    uint32_t* x3o[4];
#pragma unroll
    for (int i = 0; i < 4; i++) x3o[i] = pin(gin + blk(32 * i + 16 * (t >> 1), 6 + (cta >> 6), t) + (cta & 63) * 16 + g * 2);
    uint32_t* const fo = pin(reinterpret_cast<uint32_t*>(gout) + mo / 2 + 4 * (t & 1));
    const uint32_t* const p3 = pin(gin + blk(cta, 4, sel) + t * 16 + g * 2);
    const uint32_t* const p4 = pin(gin + blk(cta, 5, sel) + t * 16 + g * 2);
    const uint32_t one = pin((g & 1) ? 0x3f800000u : 0x00003f80u);
    const float xf[4] = {pin(bf_lo(xo0)), pin(bf_hi(xo0)), pin(bf_lo(xo1)), pin(bf_hi(xo1))};
    const float ga[4] = {pin(bf_lo(gau.x)), pin(bf_hi(gau.x)), pin(bf_lo(gau.y)), pin(bf_hi(gau.y))};
    mbar_wait(BAR(BAR_P5D));
    backoff(T.D_X3A);
    wait_clk(anchor, T.A_X1 + T.R_X3A);
    CLK(4);
    float r[4];
    uint32_t x20, x21;
    int it = 0;
    bool ok;
    do {
      ok = sum_pieces<32>(p3, one, r);
      x20 = pack_bf16(xf[0] + ga[0] * r[0], xf[1] + ga[1] * r[1]); x21 = pack_bf16(xf[2] + ga[2] * r[2], xf[3] + ga[3] * r[3]);
#pragma unroll
      for (int i = 0; i < 4; i++) stg_u64_unless(!ok || (i == 3 && t >= 2), x3o[i], x20, x21);
    } while (!ok && ++it < SPIN_LIMIT);
    if (!ok) __trap();
    CLK(6);
    ITS(0, it);
    const uint32_t xw = (t & 1) ? x21 : x20;
    const float xa = pin(bf_lo(xw)), xb = pin(bf_hi(xw));
    if (cta < NFF) mbar_wait(BAR(BAR_P7D)); else wait_clk(anchor, T.A_X1 + T.R_X3A + T.R_X3B + T.R_FIN - T.D_FIN);
    uint2 gbu = ldg_u64(pg + 3 * 2048);
    backoff(T.D_FIN);
    CLK(7);
    do {
      ok = sum_pieces<NFG>(p4, one, r);
      ok = ok && __all_sync(~0u, gbu.y != 0);
      const uint32_t gw = (t & 1) ? gbu.y : gbu.x;
      const uint32_t o = pack_bf16(xa + bf_lo(gw) * ((t & 1) ? r[2] : r[0]), xb + bf_hi(gw) * ((t & 1) ? r[3] : r[1]));
      if (ok && t < 2) asm volatile("st.global.u32 [%0], %1;" ::"l"(fo), "r"(o) : "memory");
      reload_unit(gbu, pg + 3 * 2048);
    } while (!ok && ++it < SPIN_LIMIT);
    if (!ok) __trap();
    ITS(1, it);
    CLK(8);
    CLK_DUMP();
    if (cta == 0 && lane == 0) stg1(&gs->epoch, epoch + 1);
    return;
  }

  const int wg = w >> 2, wq = w & 3;
  uint32_t tstore;
  {
    const uint8_t* pw = gwmod + (size_t)(128 * jI + 16 * w + 4 * (g >> 1) + (g & 1)) * 6144 + 64 * hI + 16 * t;
    const uint4 w0 = ldg_nc4(pw), w1 = ldg_nc4(pw + 2 * 6144);
    const uint2 cc = ldg_nc2(gc + g * 1024 + 256 * jI + 32 * w + 8 * t);
    CLK(40);
    const uint32_t a[4] = {silu2(cc.x), 0u, silu2(cc.y), 0u};
    float d[4][4] = {{0.f, 0.f, 0.f, 0.f}, {0.f, 0.f, 0.f, 0.f}, {0.f, 0.f, 0.f, 0.f}, {0.f, 0.f, 0.f, 0.f}};
    mma16816(d[0], a, movm(w0.x), movm(w1.x)); mma16816(d[1], a, movm(w0.y), movm(w1.y));
    mma16816(d[2], a, movm(w0.z), movm(w1.z)); mma16816(d[3], a, movm(w0.w), movm(w1.w));
    CLK(1);
    sts4f(sb + OFF_P0S + w * 1088 + lane * 16, d[0][0], d[0][1], d[1][0], d[1][1]);
    sts4f(sb + OFF_P0S + w * 1088 + 544 + lane * 16, d[2][0], d[2][1], d[3][0], d[3][1]);
    bar_sync(0, NTHREADS);
    if (tid < 128) {
      const uint32_t src = sb + OFF_P0S + ((tid >> 2) & 1) * 544 + (((tid >> 3) & 7) * 4 + 2 * (tid >> 6) + (tid & 1)) * 16 + ((tid >> 1) & 1) * 8;
      float2 v[8];
#pragma unroll
      for (int i = 0; i < 8; i++) v[i] = ldsf2(src + i * 1088);
      const float ax = ((v[0].x + v[1].x) + (v[2].x + v[3].x)) + ((v[4].x + v[5].x) + (v[6].x + v[7].x));
      const float ay = ((v[0].y + v[1].y) + (v[2].y + v[3].y)) + ((v[4].y + v[5].y) + (v[6].y + v[7].y));
      stg1(gs->MOD1[epoch & 1] + jI * 4096 + hI * 128 + tid, nz(pack_bf16(ax, ay)));
    }
    tstore = clk32();
  }
  CLK(2);
  const int par = epoch & 1;
  uint32_t cf[4][4];
  mbar_wait(BAR(BAR_XC));
  {
    uint32_t u[2][4];
    lds4(u[0], sb + OFF_XS + w * 1024 + lane * 16); lds4(u[1], sb + OFF_XS + w * 1024 + 512 + lane * 16);
    float v[16];
#pragma unroll
    for (int i = 0; i < 8; i++) { v[2 * i] = bf_lo(u[i >> 2][i & 3]); v[2 * i + 1] = bf_hi(u[i >> 2][i & 3]); }
    float s = 0.f;
#pragma unroll
    for (int i = 0; i < 16; i++) s += v[i];
#pragma unroll
    for (int o = 16; o; o >>= 1) s += __shfl_xor_sync(~0u, s, o);
    const float mu = s * (1.f / 512.f);
    float q = 0.f;
#pragma unroll
    for (int i = 0; i < 16; i++) { v[i] -= mu; q += v[i] * v[i]; }
#pragma unroll
    for (int o = 16; o; o >>= 1) q += __shfl_xor_sync(~0u, q, o);
    const float rs = rsqrtf(q * (1.f / 512.f) + 1e-5f);
    const bool hi = jI & 2;
    uint32_t o[4];
#pragma unroll
    for (int i = 0; i < 4; i++) o[i] = pack_bf16((hi ? v[8 + 2 * i] : v[2 * i]) * rs, (hi ? v[9 + 2 * i] : v[2 * i + 1]) * rs);
    if ((lane >> 4) == (jI & 1)) sts4(sb + OFF_XN + w * 272 + (lane & 15) * 16, make_uint4(o[0], o[1], o[2], o[3]));
  }
  CLK(3);
  uint32_t aw[8][4];
  const uint32_t abase = __shfl_sync(~0u, sb + a_t_offset(w, lane), lane);
  {
    const uint32_t* pm = pin(gs->MOD1[par] + (8 * jI + w) * 64 + lane * 2);
    uint32_t* const qpo = pin(gs->QP[par] + (cta * 256 + tid) * 2);
    float d[4] = {0.f, 0.f, 0.f, 0.f};
    wait_clk(tstore, T.D_MOD);
    CLK(4);
    uint2 v[8];
    load_units<8, 2048>(v, pm);
    cbar();
    const uint32_t xn0 = lds1(sb + OFF_XN + g * 272 + w * 32 + t * 4), xn1 = lds1(sb + OFF_XN + g * 272 + w * 32 + 16 + t * 4);
    const bool early = __all_sync(~0u, mbar_test(BAR(BAR_WQ + wg)));
    if (early) load_a_t(aw, abase + OFF_WQ);
    int it = 0;
    while (true) {
      uint32_t mn = 0xffffffffu;
#pragma unroll
      for (int i = 0; i < 8; i++) mn = min(mn, min(v[i].x, v[i].y));
      if (__all_sync(~0u, mn != 0)) break;
#pragma unroll
      for (int i = 0; i < 8; i++) { if (v[i].x == 0) v[i].y = 0; reload_unit(v[i], pm + i * 2048); }
      if (++it > SPIN_LIMIT) __trap();
    }
    CLK(5);
    ITS(0, it);
    float sc[2][4];
#pragma unroll
    for (int i = 0; i < 2; i++) {
      sc[i][0] = (bf_lo(v[i].x) + bf_lo(v[2 + i].x)) + (bf_lo(v[4 + i].x) + bf_lo(v[6 + i].x));
      sc[i][1] = (bf_hi(v[i].x) + bf_hi(v[2 + i].x)) + (bf_hi(v[4 + i].x) + bf_hi(v[6 + i].x));
      sc[i][2] = (bf_lo(v[i].y) + bf_lo(v[2 + i].y)) + (bf_lo(v[4 + i].y) + bf_lo(v[6 + i].y));
      sc[i][3] = (bf_hi(v[i].y) + bf_hi(v[2 + i].y)) + (bf_hi(v[4 + i].y) + bf_hi(v[6 + i].y));
    }
    sts2(sb + OFF_BS1 + (w >> 1) * 512 + lane * 16 + (w & 1) * 8,
         pack_bf16(bf_lo(xn0) * (1.f + sc[1][0]) + sc[0][0], bf_hi(xn0) * (1.f + sc[1][1]) + sc[0][1]),
         pack_bf16(bf_lo(xn1) * (1.f + sc[1][2]) + sc[0][2], bf_hi(xn1) * (1.f + sc[1][3]) + sc[0][3]));
    if (!early) { mbar_wait(BAR(BAR_WQ + wg)); load_a_t(aw, abase + OFF_WQ); }
    CLK(6);
    cbar();
    uint32_t b[4][4];
#pragma unroll
    for (int kk = 0; kk < 4; kk++) lds4(b[kk], sb + OFF_BS1 + kk * 512 + lane * 16);
    mma128(d, aw, b);
    stg_u64(qpo, pack_bf16(d[0], d[1]), pack_bf16(d[2], d[3]));
    tstore = clk32();
    CLK(7);
    if (wg) {
      mbar_wait(BAR(BAR_C));
#pragma unroll
      for (int i = 0; i < 4; i++) lds4(cf[i], sb + OFF_CS + g * 1024 + wq * 256 + i * 64 + t * 16);
#pragma unroll
      for (int i = 0; i < 16; i++) cf[i >> 2][i & 3] = silu2(cf[i >> 2][i & 3]);
    }
    __syncwarp();
    if (lane == 0) mbar_arrive(BAR(BAR_P1D));
  }
  {
    const uint32_t* pq = pin(gs->QP[par] + (hI * 4 * 256 + tid) * 2);
    uint32_t* const qxo = pin(gs->QX[par] + (g * 32 + hI) * 256 + 64 * jI + 8 * w + 2 * t);
    uint2 v[4];
    float d[4] = {0.f, 0.f, 0.f, 0.f};
    wait_clk(tstore, T.D_QP);
    CLK(8);
    load_units<4, 512>(v, pq);
    const uint32_t kbase = sb + OFF_WUK + (16 * w + (lane & 15)) * 128;
    auto load_half = [&](int hf) {
#pragma unroll
      for (int ks = 0; ks < 4; ks++) ldsm4(aw[4 * hf + ks], kbase + hf * 16384 + (((2 * ks + (lane >> 4)) ^ (lane & 7)) << 4));
    };
    mbar_wait(BAR(BAR_WUK));
    load_half(0);
    const bool early = __all_sync(~0u, mbar_test(BAR(BAR_WUK + 1)));
    if (early) load_half(1);
    const int it = check_units<4, 512>(v, pq);
    CLK(9);
    ITS(1, it);
    sum4_to_smem(v, sb + OFF_BS2 + (16 * w + g) * 16 + t * 4);
    if (!early) { mbar_wait(BAR(BAR_WUK + 1)); load_half(1); }
    CLK(10);
    cbar();
    uint32_t b[4][4];
#pragma unroll
    for (int kk = 0; kk < 4; kk++) ldsm4t(b[kk], sb + OFF_BS2 + (32 * kk + lane) * 16);
    mma128(d, aw, b);
    const float sc = 0.08838834764831845f * 1.4426950408889634f;
    stg_u64(qxo, movm(pack_bf16(d[0] * sc, d[1] * sc)), movm(pack_bf16(d[2] * sc, d[3] * sc)));
    tstore = clk32();
    CLK(11);
    if (lane == 0) mbar_arrive(BAR(BAR_P2D));
  }
  if (wg && jI != 3) {
    const int mi = lane >> 3, r = lane & 7;
    const uint32_t a0 = sb + OFF_WM2 + (8 * (r >> 1) + (r & 1) + 2 * (mi >> 1)) * 32 + (mi & 1) * 16;
    mbar_wait(BAR(BAR_WM2));
#pragma unroll
    for (int s = 0; s < 8; s++) ldsm4t(aw[s], a0 + (128 * wq + 32 * (s >> 1) + 4 * (s & 1)) * 32);
    float d[4] = {0.f, 0.f, 0.f, 0.f};
    mma128(d, aw, cf);
    sts4f(sb + OFF_P0B + (tid - 128) * 16, d[0], d[1], d[2], d[3]);
    if (lane == 0) mbar_arrive(BAR(BAR_P0BD));
    bar_sync(3, 128);
    if (w == 4) {
      float4 v[4];
#pragma unroll
      for (int i = 0; i < 4; i++) v[i] = ldsf4(sb + OFF_P0B + (i * 32 + lane) * 16);
      stg_u64(gs->MOD2[par] + (3 * hI + jI) * 64 + t * 16 + g * 2, movm(pack_bf16((v[0].x + v[1].x) + (v[2].x + v[3].x), (v[0].y + v[1].y) + (v[2].y + v[3].y))),
              movm(pack_bf16((v[0].z + v[1].z) + (v[2].z + v[3].z), (v[0].w + v[1].w) + (v[2].w + v[3].w))));
    }
    CLK(15);
  }
  {
    const uint32_t* qx = pin(gs->QX[par] + ((bs >> 3) * 32 + 16 * hh) * 256 + tid * 4);
    const int ch = tid & 63, h0 = tid >> 6;
    const uint32_t dst = sb + OFF_Q + (ch >> 3) * 2048 + h0 * 128;
    wait_clk(tstore, T.D_QX);
    CLK(12);
    uint4 v[4];
#pragma unroll
    for (int i = 0; i < 4; i++) v[i] = ldg_2u64(qx + i * 1024);
    int it = 0;
    while (true) {
      uint32_t mn = 0xffffffffu;
#pragma unroll
      for (int i = 0; i < 4; i++) mn = min(mn, min(v[i].y, v[i].w));
      if (__all_sync(~0u, mn != 0)) break;
#pragma unroll
      for (int i = 0; i < 4; i++)
        asm volatile("{\n.reg .pred q;\nsetp.eq.u32 q, %5, 0;\n@q ld.relaxed.gpu.global.v4.b32 {%0, %1, %2, %3}, [%4];\n}"
                     : "+r"(v[i].x), "+r"(v[i].y), "+r"(v[i].z), "+r"(v[i].w) : "l"(qx + i * 1024), "r"(min(v[i].y, v[i].w)) : "memory");
      if (++it > SPIN_LIMIT) __trap();
    }
    CLK(13);
    ITS(2, it);
#pragma unroll
    for (int i = 0; i < 4; i++) sts4(dst + i * 512 + (((ch & 7) ^ ((4 * i + h0) & 7)) << 4), v[i]);
    asm volatile("fence.proxy.async.shared::cta;" ::: "memory");
    CLK(14);
    cbar();
  }

  uint2 cbf[4], sbf[4];
  const uint32_t* const pcb = gs->MOD2[par] + 2048 + (16 * w + t) * 16 + g * 2;
  auto load_frags = [&] {
    if (cta < NFF) { load_units<4, 64>(sbf, pcb); load_units<4, 64>(cbf, pcb + 2048); }
    else {
#pragma unroll
      for (int s = 0; s < 4; s++) { cbf[s].x = ldg_nc1(gc + g * 1024 + w * 128 + s * 32 + t * 4); cbf[s].y = ldg_nc1(gc + g * 1024 + w * 128 + s * 32 + 16 + t * 4); }
    }
  };
  uint32_t thand, anchor;
  const uint32_t opaque0 = w >> 4;
  if (wg == 0) {
    float mh[4];
    float L[8];
#pragma unroll
    for (int i = 0; i < 4; i++) { L[2 * i] = L[2 * i + 1] = 0.f; mh[i] = -INFINITY; }
    constexpr uint32_t dq = desc_lo(OFF_Q);
    const uint32_t ptw = sb + OFF_PT + (8 * (lane >> 4) + (lane & 7)) * 128 + (((2 * wq + ((lane >> 3) & 1)) ^ (lane & 7)) << 4);
    float S[8];
    auto softmax = [&](int tl) {
      auto write_p = [&](const float (&x)[8]) {
        float p[8];
#pragma unroll
        for (int i = 0; i < 8; i++) p[i] = ex2(x[i]);
        stsm4t(ptw + (tl & 1) * 2048, pack_bf16(p[0], p[1]), pack_bf16(p[2], p[3]), pack_bf16(p[4], p[5]), pack_bf16(p[6], p[7]));
        asm volatile("fence.proxy.async.shared::cta;" ::: "memory");
      };
      float x[8];
#pragma unroll
      for (int i = 0; i < 8; i++) x[i] = S[i] - mh[2 * (i >> 2) + (i & 1)];
      if (tl) write_p(x);
      const float ex = fmaxf(fmaxf(fmaxf(x[0], x[1]), fmaxf(x[2], x[3])), fmaxf(fmaxf(x[4], x[5]), fmaxf(x[6], x[7])));
      if (tl == 0 || bar_over(ex)) {
        float mx[4];
#pragma unroll
        for (int i = 0; i < 4; i++) mx[i] = fmaxf(S[4 * (i >> 1) + (i & 1)], S[4 * (i >> 1) + 2 + (i & 1)]);
        const float a = reduce_g(mx, lane, [](float u, float v) { return fmaxf(u, v); });
        stsf(sb + OFF_RED + wq * 64 + (8 * (lane >> 4) + 2 * t + ((lane >> 3) & 1)) * 4, a);
        bar_sync(2, 128);
#pragma unroll
        for (int jn = 0; jn < 2; jn++) {
          float m0 = mh[2 * jn], m1 = mh[2 * jn + 1];
#pragma unroll
          for (int i = 0; i < 4; i++) { const float2 v = ldsf2(sb + OFF_RED + i * 64 + (8 * jn + 2 * t) * 4); m0 = fmaxf(m0, v.x); m1 = fmaxf(m1, v.y); }
          const float a0 = ex2(mh[2 * jn] - m0), a1 = ex2(mh[2 * jn + 1] - m1);
          mh[2 * jn] = m0; mh[2 * jn + 1] = m1;
          L[4 * jn] *= a0; L[4 * jn + 1] *= a1; L[4 * jn + 2] *= a0; L[4 * jn + 3] *= a1;
          if (tid < 4) sts2f(sb + OFF_ALPHA + (8 * jn + 2 * t) * 4, a0, a1);
        }
        asm volatile("barrier.cta.arrive.aligned 1, 256;" ::: "memory");
#pragma unroll
        for (int i = 0; i < 8; i++) x[i] = S[i] - mh[2 * (i >> 2) + (i & 1)];
        write_p(x);
        bar_over(0.f);
      }
      const uint32_t dpt = __shfl_sync(~0u, desc_lo(OFF_PT) + (tl & 1) * 128, 0);
      wg_fence();
#pragma unroll
      for (int ks = 0; ks < 4; ks++) wgmma_n16_ones(L, ONE2, dpt + ks * 2);
      wg_commit();
    };
    uint32_t da = desc_lo(OFF_RING);
#pragma unroll 1
    for (int tl = 0; tl < 7; tl++) {
      if (tl == 5) { load_frags(); }
      uint32_t ok = 0;
#pragma unroll
      for (int u = 0; u < 4; u++) ok += mbar_test(BAR(BAR_FULL + 4 * tl + u));
      ok = __reduce_min_sync(~0u, ok);
      const uint32_t du = __shfl_sync(~0u, da, 0);
#pragma unroll
      for (int u = 0; u < 4; u++) {
        if (ok != 4) mbar_wait(BAR(BAR_FULL + 4 * tl + u));
        wg_fence();
#pragma unroll
        for (int k = 0; k < 8; k++) {
          const int i = 8 * u + k;
          if (i == 0) wgmma_n16<0, 0>(S, du, dq); else wgmma_n16<0, 1>(S, du + (i >> 2) * 512 + (i & 3) * 2, dq + (i >> 2) * 128 + (i & 3) * 2);
        }
        wg_commit();
      }
      wg_wait<0>();
      acc_fence(S); acc_fence(L);
      if (tl == 0) CLK(15);
      if (tl == 1) CLK(17);
      softmax(tl);
      if (tl == 0) CLK(16);
      if (tl == 1) CLK(18);
      if (tl == 3) CLK(19);
      if (tl == 6) CLK(20);
      da = (tl == 2 || tl == 5) ? da - 8192 : da + 4096;
    }
    mbar_wait(BAR(BAR_ALLCLR));
    uint32_t* const mlo = pin(gin + blk(4 * (16 * hh + 4 * (g & 2) + 2 * t + (g & 1)) + 1, 6, g >> 2) + bs * 2);
#pragma unroll
    for (int i = 0; i < 32; i++) {
      if (i == 0 || i == 8 || i == 16 || i == 24 || i == 28) {
        if (i) wg_commit();
        mbar_wait(BAR(BAR_LAST + (i == 28 ? 4 : i >> 3)));
        if (i == 28) CLK(21);
        wg_fence();
      }
      if (i == 0) wgmma_n16<0, 0>(S, desc_lo(65536), dq); else wgmma_n16<0, 1>(S, desc_lo(65536) + (i >> 2) * 512 + (i & 3) * 2, dq + (i >> 2) * 128 + (i & 3) * 2);
    }
    wg_commit();
    wg_wait<0>();
    acc_fence(S); acc_fence(L);
    CLK(22);
    softmax(7);
    CLK(23);
    thand = clk32();
    wg_wait<0>();
    acc_fence(L);
    if (tid < 32) red_u64(mlo, __float_as_uint(g & 2 ? (g & 1 ? mh[3] : mh[2]) : (g & 1 ? mh[1] : mh[0])), __float_as_uint(g & 2 ? (g & 1 ? L[5] : L[4]) : (g & 1 ? L[1] : L[0])));
    CLK(24);
  } else {
    float O[8][8];
#pragma unroll
    for (int i = 0; i < 8; i++)
#pragma unroll
      for (int k = 0; k < 8; k++) O[i][k] = 0.f;
    constexpr uint32_t dp = desc_lo(OFF_PT);
    auto handover = [&](int tl) {
      uint32_t over = opaque0 + (tl == 0);
#pragma unroll 1
      do {
        if (over) {
          cbar();
#pragma unroll
          for (int jn = 0; jn < 2; jn++) {
            const float2 a = ldsf2(sb + OFF_ALPHA + (8 * jn + 2 * t) * 4);
#pragma unroll
            for (int mb = 0; mb < 8; mb++) { O[mb][4 * jn] *= a.x; O[mb][4 * jn + 1] *= a.y; O[mb][4 * jn + 2] *= a.x; O[mb][4 * jn + 3] *= a.y; }
          }
        }
        over++;
      } while (bar_over(0.f));
    };
    uint32_t da = desc_lo(OFF_RING);
    uint32_t* x1o[8] = {};
#pragma unroll 1
    for (int tl = 0; tl < 8; tl++) {
      if (tl == 5) load_frags();
      if (tl == 7) {
        mbar_wait(BAR(BAR_ALLCLR));
#pragma unroll
        for (int i = 0; i < 8; i++)
          x1o[i] = inbox((16 * hh + 8 * ((i >> 1) & 1) + 2 * t + (i & 1)) * 4 + 2 * (i >> 2) + (wq >> 1), bs >> 4) + (bs & 15) * 64 + ((wq & 1) * 8 + g) * 4;
      }
      handover(tl);
      CLK(23);
      thand = clk32();
      const uint32_t dpt = dp + (tl & 1) * 128;
      wg_fence();
#pragma unroll
      for (int i = 0; i < 32; i++) wgmma_n16<1, 1>(O[i >> 2], da + (i >> 2) * 512 + (i & 3) * 128, dpt + (i & 3) * 2);
      wg_commit();
      da = (tl == 2 || tl == 5) ? da - 8192 : da + 4096;
      wg_wait<0>();
#pragma unroll
      for (int mb = 0; mb < 8; mb++) acc_fence(O[mb]);
      if (lane == 0) mbar_arrive(BAR(BAR_EMPTY + tl));
      if (tl == 0) CLK(16);
      if (tl == 1) CLK(18);
      if (tl == 3) CLK(19);
      if (tl == 6) CLK(20);
    }
    CLK(22);
#pragma unroll
    for (int i = 0; i < 8; i++) {
      const int J = i >> 2, k = 4 * ((i >> 1) & 1) + (i & 1);
      stg_cvt8(x1o[i], O[4 * J][k], O[4 * J][k + 2], O[4 * J + 1][k], O[4 * J + 1][k + 2], O[4 * J + 2][k], O[4 * J + 2][k + 2], O[4 * J + 3][k], O[4 * J + 3][k + 2]);
    }
    CLK(24);
  }

  {
    const uint32_t* px = pin(inbox(cta, w >> 1) + (w & 1) * 512 + lane * 2);
    uint32_t* const x2o = pin(inbox(cta, 4) + 512 + tid * 2);
    uint32_t* const x2p = pin(gin + blk(cta, 4, selector(cta) ^ 1) + 512 + tid * 2);
    const uint32_t q4 = lds1(sb + OFF_SEL + 4 * hI) ^ 0x00010100u;
    const uint32_t same = pin((uint32_t)(q4 == 0 || q4 == 0x01010101u));
    mbar_wait(BAR(BAR_TS));
    anchor = lds1(sb + OFF_TS);
    const uint32_t sdst = pin(sb + OFF_BS4 + w * 272 + lane * 8), ssrc = pin(sb + OFF_BS4 + (lane & 7) * 272 + (lane >> 3) * 16);
    float d[4] = {0.f, 0.f, 0.f, 0.f};
    if (cta >= NFF) {
#pragma unroll
      for (int s = 0; s < 4; s++) { cbf[s].x = silu2(cbf[s].x); cbf[s].y = silu2(cbf[s].y); }
    }
    wait_clk(thand, T.D_X1);
    wait_clk(anchor, T.A_X1 - T.R_X0);
    uint2 v[8];
    load_units<8, 64>(v, px);
    if (T.R_X0) {
      wait_clk(anchor, T.A_X1);
#pragma unroll
      for (int i = 0; i < 8; i++) reload_unit(v[i], px + i * 64);
    }
    CLK(25);
    const bool early = __all_sync(~0u, mbar_test(BAR(BAR_WUV + wg)));
    if (early) load_a_t(aw, abase + OFF_WUV);
    mbar_wait(BAR(BAR_WV));
    const float4 wa = ldsf4(sb + OFF_WV + w * 32), wb = ldsf4(sb + OFF_WV + w * 32 + 16);
    const float wv[8] = {wa.x, wa.y, wa.z, wa.w, wb.x, wb.y, wb.z, wb.w};
    CLK(27);
    uint32_t it = opaque0;
    bool ok;
#pragma unroll 1
    do {
      if (it) {
#pragma unroll
        for (int i = 0; i < 8; i++) reload_unit(v[i], px + i * 64);
        if (it > SPIN_LIMIT) __trap();
      }
      it++;
      float a0 = 0.f, a1 = 0.f, a2 = 0.f, a3 = 0.f;
#pragma unroll
      for (int i = 0; i < 8; i++) { a0 += wv[i] * bf_lo(v[i].x); a1 += wv[i] * bf_hi(v[i].x); a2 += wv[i] * bf_lo(v[i].y); a3 += wv[i] * bf_hi(v[i].y); }
      ok = __all_sync(~0u, min_flags(v) != 0);
      sts2(sdst, pack_bf16(a0, a1), pack_bf16(a2, a3));
    } while (!ok);
    CLK(29);
    cbar();
    uint32_t b[4][4];
#pragma unroll
    for (int kk = 0; kk < 4; kk++) ldsm4(b[kk], ssrc + kk * 64);
    if (__builtin_expect(!early, 0)) { mbar_wait(BAR(BAR_WUV + wg)); load_a_t(aw, abase + OFF_WUV); }
    mma128(d, aw, b);
    const uint32_t c0 = pack_bf16(d[0], d[1]), c1 = pack_bf16(d[2], d[3]);
    stg_u64(x2o, c0, c1);
    stg_u64_unless(same, x2p, c0, c1);
    ITS(4, it - 1);
    tstore = clk32();
    CLK(30);
  }
  {
    uint32_t* const o = pin(inbox(4 * (8 * jI + w) + t, 4) + hI * 16 + g * 2);
    const uint32_t* x2i[4];
#pragma unroll
    for (int i = 0; i < 4; i++) x2i[i] = pin(nearbox(4 * hI + i, 4) + 512 + tid * 2);
    const uint32_t sdst = pin(sb + OFF_BS5 + (16 * w + g) * 16 + t * 4), ssrc = pin(sb + OFF_BS5 + lane * 16);
    float d[4] = {0.f, 0.f, 0.f, 0.f};
    wait_clk(tstore, T.D_X2);
    uint2 v[4];
#pragma unroll
    for (int i = 0; i < 4; i++) v[i] = ldg_u64(x2i[i]);
    const bool early = __all_sync(~0u, mbar_test(BAR(BAR_WO + wg)));
    if (early) load_a_t(aw, abase + OFF_WO);
    CLK(31);
    uint32_t it = opaque0;
    bool ok;
#pragma unroll 1
    do {
      if (it) {
#pragma unroll
        for (int i = 0; i < 4; i++) reload_unit(v[i], x2i[i]);
        if (it > SPIN_LIMIT) __trap();
      }
      it++;
      ok = __all_sync(~0u, min_flags(v) != 0);
      sum4_to_smem(v, sdst);
    } while (!ok);
    CLK(32);
    cbar();
    uint32_t b[4][4];
#pragma unroll
    for (int kk = 0; kk < 4; kk++) ldsm4t(b[kk], ssrc + kk * 512);
    if (__builtin_expect(!early, 0)) { mbar_wait(BAR(BAR_WO + wg)); load_a_t(aw, abase + OFF_WO); }
    mma128(d, aw, b);
    stg_u64(o, movm(pack_bf16(d[0], d[1])), movm(pack_bf16(d[2], d[3])));
    ITS(5, it - 1);
    tstore = clk32();
    CLK(33);
    if (lane == 0) mbar_arrive(BAR(BAR_P5D));
  }
  if (cta < NFF) {
    const int mi = lane >> 3, r = lane & 7;
    uint32_t a1[2][4][4], a2[2][2][4];
    check_units<4, 64>(sbf, pcb);
    check_units<4, 64>(cbf, pcb + 2048);
    __syncwarp();
#pragma unroll
    for (int s = 0; s < 4; s++) { cbf[s].x = hadd2(cbf[s].x, ONE2); cbf[s].y = hadd2(cbf[s].y, ONE2); }
    mbar_wait(BAR(BAR_W1));
#pragma unroll
    for (int mt = 0; mt < 2; mt++) {
#pragma unroll
      for (int ks = 0; ks < 4; ks++) ldsm4t(a1[mt][ks], sb + OFF_W1 + (64 * w + 16 * ks + 8 * (mi >> 1) + r) * 64 + (((2 * mt + (mi & 1)) ^ (r >> 1)) << 4));
      float u[4] = {0.f, 0.f, 0.f, 0.f}, vv[4] = {0.f, 0.f, 0.f, 0.f};
#pragma unroll
      for (int s = 0; s < 4; s++) { mma16816(u, a1[mt][s], cbf[s].x, cbf[s].y); mma16816(vv, a1[mt][s], sbf[s].x, sbf[s].y); }
      sts4f(sb + OFF_REDU + w * 1024 + mt * 512 + lane * 16, u[0], u[1], u[2], u[3]);
      sts4f(sb + OFF_REDV + w * 1024 + mt * 512 + lane * 16, vv[0], vv[1], vv[2], vv[3]);
    }
    const uint32_t* xb = pin(nearbox(cta & ~15, 6 + wg) + (16 * wq + t) * 16 + g * 2);
    uint32_t* const ox[2] = {pin(inbox(64 * hh + 8 * w + t, 5) + bs * 16 + g * 2), pin(inbox(64 * hh + 8 * w + 4 + t, 5) + bs * 16 + g * 2)};
    cbar();
    const int lp = (tid >> 2) & 31, kq = tid & 3;
    const int fo = 16 * wg + (lp >> 2) + 8 * (kq >> 1), bo = 2 * (lp & 3) + (kq & 1);
    float U = 0.f, V = 0.f;
#pragma unroll
    for (int i = 0; i < 8; i++) { U += ldsf(sb + OFF_REDU + i * 1024 + tid * 4); V += ldsf(sb + OFF_REDV + i * 1024 + tid * 4); }
    U = pin(U); V = pin(V);
    const uint32_t s_g = pin(sb + OFF_REDG + w * 1024 + lane * 16), s_s = pin(sb + OFF_REDS + g * 80 + w * 8);
    const uint32_t l_g = pin(sb + OFF_REDG + tid * 4), l_s = pin(sb + OFF_REDS + bo * 80), s_h = pin(sb + OFF_H1 + fo * 16 + bo * 2);
    CLK(34);
    wait_clk(tstore, T.D_X3B);
    wait_clk(anchor, T.A_X1 + T.R_X3A + T.R_X3B);
    uint2 x[4];
    load_units<4, 64>(x, xb);
    mbar_wait(BAR(BAR_W2));
#pragma unroll
    for (int i = 0; i < 4; i++)
      ldsm4t(a2[i >> 1][i & 1], sb + OFF_W2 + (w >> 1) * 4096 + (16 * (i & 1) + 8 * (mi >> 1) + r) * 128 + (((4 * (w & 1) + 2 * (i >> 1) + (mi & 1)) ^ r) << 4));
    CLK(35);
    uint32_t it = opaque0;
    float G[2][2][4], S[2][4];
#pragma unroll 1
    do {
      if (it) {
#pragma unroll
        for (int i = 0; i < 4; i++) reload_unit(x[i], xb + i * 64);
        if (it > SPIN_LIMIT) __trap();
      }
      it++;
#pragma unroll
      for (int i = 0; i < 8; i++) { G[0][i >> 2][i & 3] = G[1][i >> 2][i & 3] = S[i >> 2][i & 3] = 0.f; }
#pragma unroll
      for (int s = 0; s < 4; s++) {
        const uint32_t sx[4] = {x[s].x, ONE2, x[s].y, ONE2};
        mma16816(S[s & 1], sx, x[s].x, x[s].y);
        const uint32_t y0 = hmul2(x[s].x, cbf[s].x), y1 = hmul2(x[s].y, cbf[s].y);
        mma16816(G[0][s & 1], a1[0][s], y0, y1);
        mma16816(G[1][s & 1], a1[1][s], y0, y1);
      }
    } while (!__all_sync(~0u, min_flags(x) != 0));
    if (t == (g >> 1)) sts2f(s_s, (g & 1) ? S[0][3] + S[1][3] : S[0][2] + S[1][2], (g & 1) ? S[0][1] + S[1][1] : S[0][0] + S[1][0]);
#pragma unroll
    for (int mt = 0; mt < 2; mt++)
      sts4f(s_g + mt * 512, G[mt][0][0] + G[mt][1][0], G[mt][0][1] + G[mt][1][1], G[mt][0][2] + G[mt][1][2], G[mt][0][3] + G[mt][1][3]);
    CLK(37);
    cbar();
    {
      float gv[8];
      float4 sv[4];
#pragma unroll
      for (int i = 0; i < 4; i++) sv[i] = ldsf4(l_s + i * 16);
#pragma unroll
      for (int i = 0; i < 8; i++) gv[i] = ldsf(l_g + i * 1024);
      const float s1 = ((sv[0].x + sv[0].z) + (sv[1].x + sv[1].z)) + ((sv[2].x + sv[2].z) + (sv[3].x + sv[3].z));
      const float s2 = ((sv[0].y + sv[0].w) + (sv[1].y + sv[1].w)) + ((sv[2].y + sv[2].w) + (sv[3].y + sv[3].w));
      const float gsum = ((gv[0] + gv[1]) + (gv[2] + gv[3])) + ((gv[4] + gv[5]) + (gv[6] + gv[7]));
      const float mu = s1 * (1.f / 512.f);
      float rs;
      asm("rsqrt.approx.ftz.f32 %0, %1;" : "=f"(rs) : "f"(fmaxf(s2 * (1.f / 512.f) - mu * mu, 0.f) + 1e-5f));
      const float hv = fmaxf(rs * (gsum - mu * U) + V, 0.f);
      asm volatile("st.shared.u16 [%0], %1;" ::"r"(s_h), "h"(__bfloat16_as_ushort(__float2bfloat16(hv))) : "memory");
    }
    ITS(6, it - 1);
    CLK(38);
    cbar();
    uint32_t b[4];
    ldsm4t(b, sb + OFF_H1 + lane * 16);
    float o[2][2][4] = {};
#pragma unroll
    for (int i = 0; i < 4; i++) mma16816(o[i >> 1][i & 1], a2[i >> 1][i & 1], b[2 * (i & 1)], b[2 * (i & 1) + 1]);
#pragma unroll
    for (int mb = 0; mb < 2; mb++)
      stg_u64(ox[mb], movm(pack_bf16(o[mb][0][0] + o[mb][1][0], o[mb][0][1] + o[mb][1][1])), movm(pack_bf16(o[mb][0][2] + o[mb][1][2], o[mb][0][3] + o[mb][1][3])));
    CLK(39);
    if (lane == 0) mbar_arrive(BAR(BAR_P7D));
  } else {
    const int mi = lane >> 3, r = lane & 7;
    mbar_wait(BAR(BAR_W1));
#pragma unroll
    for (int mt = 0; mt < 2; mt++) {
      float u[4] = {0.f, 0.f, 0.f, 0.f};
#pragma unroll
      for (int ks = 0; ks < 4; ks++) ldsm4t(aw[4 * mt + ks], sb + OFF_W1 + (64 * w + 16 * ks + 8 * (mi >> 1) + r) * 64 + (((2 * mt + (mi & 1)) ^ (r >> 1)) << 4));
#pragma unroll
      for (int ks = 0; ks < 4; ks++) mma16816(u, aw[4 * mt + ks], cbf[ks].x, cbf[ks].y);
      sts4f(sb + OFF_REDU + w * 1024 + mt * 512 + lane * 16, u[0], u[1], u[2], u[3]);
    }
    cbar();
    if (w < 2) {
      float4 v[8];
#pragma unroll
      for (int i = 0; i < 8; i++) v[i] = ldsf4(sb + OFF_REDU + i * 1024 + tid * 16);
      stg_u64(gs->MOD2[par] + (96 + 2 * (cta - NFF) + w) * 64 + t * 16 + g * 2,
              movm(pack_bf16(((v[0].x + v[1].x) + (v[2].x + v[3].x)) + ((v[4].x + v[5].x) + (v[6].x + v[7].x)), ((v[0].y + v[1].y) + (v[2].y + v[3].y)) + ((v[4].y + v[5].y) + (v[6].y + v[7].y)))),
              movm(pack_bf16(((v[0].z + v[1].z) + (v[2].z + v[3].z)) + ((v[4].z + v[5].z) + (v[6].z + v[7].z)), ((v[0].w + v[1].w) + (v[2].w + v[3].w)) + ((v[4].w + v[5].w) + (v[6].w + v[7].w)))));
    }
    CLK(26);
  }
  CLK_DUMP();
}

typedef CUresult (*EncodeTiledFn)(CUtensorMap*, CUtensorMapDataType, cuuint32_t, void*, const cuuint64_t*, const cuuint64_t*,
                                  const cuuint32_t*, const cuuint32_t*, CUtensorMapInterleave, CUtensorMapSwizzle,
                                  CUtensorMapL2promotion, CUtensorMapFloatOOBfill);

struct Dim { uint64_t size, stride; uint32_t box; };
template <int R> void encode_map(EncodeTiledFn enc, CUtensorMap* m, const void* base, const Dim (&d)[R], CUtensorMapSwizzle sw, CUtensorMapL2promotion promo) {
  cuuint64_t dims[R], strides[R];
  cuuint32_t box[R], es[R];
  for (int i = 0; i < R; i++) { dims[i] = d[i].size; strides[i] = d[i].stride; box[i] = d[i].box; es[i] = 1; }
  enc(m, CU_TENSOR_MAP_DATA_TYPE_BFLOAT16, R, const_cast<void*>(base), dims, strides + 1, box, es, CU_TENSOR_MAP_INTERLEAVE_NONE, sw, promo,
      CU_TENSOR_MAP_FLOAT_OOB_FILL_NONE);
}

}

extern "C" void kernel_launch(void* const* d_in, const int* in_sizes, int n_in, void* d_out, int out_size) {
  (void)in_sizes; (void)n_in; (void)out_size;
  static EncodeTiledFn enc = nullptr;
  static Scratch* scratch = nullptr;
  static uint32_t* inbox = nullptr;
  if (!enc) {
    void* sp = nullptr;
    cudaGetSymbolAddress(&sp, g_s);
    scratch = (Scratch*)sp;
    cudaGetSymbolAddress(&sp, g_in);
    inbox = (uint32_t*)(((uintptr_t)sp + 0xfffff) & ~(uintptr_t)0xfffff);
    void* fn = nullptr;
    cudaDriverEntryPointQueryResult q;
    cudaGetDriverEntryPoint("cuTensorMapEncodeTiled", &fn, cudaEnableDefault, &q);
    enc = (EncodeTiledFn)fn;
    cudaFuncSetAttribute(fused_decode_kernel, cudaFuncAttributeMaxDynamicSharedMemorySize, SMEM_BYTES);
  }
  const CUtensorMapSwizzle S128 = CU_TENSOR_MAP_SWIZZLE_128B, S0 = CU_TENSOR_MAP_SWIZZLE_NONE;
  const CUtensorMapL2promotion L0 = CU_TENSOR_MAP_L2_PROMOTION_NONE, L128 = CU_TENSOR_MAP_L2_PROMOTION_L2_128B;
  Params P;
  encode_map<2>(enc, &P.wq, d_in[2], {{4096, 2, 64}, {512, 8192, 64}}, S128, L0);
  encode_map<5>(enc, &P.wuk, d_in[3], {{4096, 2, 64}, {2, 8192, 2}, {4, 4 * 8192, 4}, {2, 2 * 8192, 2}, {32, 16 * 8192, 4}}, S128, L0);
  encode_map<2>(enc, &P.wm2, d_in[10], {{3072, 2, 16}, {512, 6144, 256}}, S0, L128);
  encode_map<2>(enc, &P.wm3, d_in[10], {{3072, 2, 32}, {512, 6144, 256}}, CU_TENSOR_MAP_SWIZZLE_64B, L128);
  encode_map<3>(enc, &P.ckv2, d_in[1], {{64, 2, 64}, {8 * 4096, 1024, 64}, {8, 128, 2}}, S128, L0);
  encode_map<3>(enc, &P.ckv1, d_in[1], {{64, 2, 64}, {8 * 4096, 1024, 64}, {8, 128, 1}}, S128, L0);
  encode_map<5>(enc, &P.wuv, d_in[4], {{4096, 2, 64}, {2, 8 * 8192, 2}, {8, 64 * 8192, 4}, {8, 8192, 8}, {4, 16 * 8192, 1}}, S128, L0);
  encode_map<2>(enc, &P.wo, d_in[5], {{512, 2, 64}, {4096, 1024, 64}}, S128, L0);
  encode_map<2>(enc, &P.w1, d_in[7], {{1792, 2, 32}, {512, 3584, 256}}, CU_TENSOR_MAP_SWIZZLE_64B, L128);
  encode_map<3>(enc, &P.w2, d_in[8], {{64, 2, 64}, {1792, 1024, 32}, {8, 128, 2}}, S128, L0);
  fused_decode_kernel<<<NCTA, NTHREADS, SMEM_BYTES>>>((__nv_bfloat16*)d_out, scratch, (const uint8_t*)d_in[10], (const uint8_t*)d_in[0],
                     (const uint8_t*)d_in[9], inbox,
                     P);
}
```

```cpp
#include <cuda_runtime.h>
#include <cuda.h>
#include <cuda_bf16.h>
#include <stdint.h>
#define V4 1

namespace {

constexpr int NCTA = 128;
constexpr int NTHREADS = 320;
constexpr int NFG = 56;
constexpr int NFF = 2 * NFG;
constexpr int NSYNC = 4;

constexpr uint32_t OFF_RING = 0;
constexpr uint32_t OFF_WUK = 131072;
constexpr uint32_t OFF_WQ = 131072 + 32768;
constexpr uint32_t OFF_WM2 = 65536 + 49152;
constexpr uint32_t OFF_WUV = 131072;
constexpr uint32_t OFF_WO = 131072 + 32768;
constexpr uint32_t OFF_W1 = 0;
constexpr uint32_t OFF_W2 = 32768;
constexpr uint32_t OFF_Q = 196608;
constexpr uint32_t OFF_PT = 212992;
constexpr uint32_t OFF_SCR = 217088;
constexpr uint32_t OFF_XS = 65536;
constexpr uint32_t OFF_CS = 65536 + 8192;
constexpr uint32_t OFF_P0S = 65536 + 16384;
constexpr uint32_t OFF_BS1 = OFF_SCR + 2048;
constexpr uint32_t OFF_BS2 = OFF_SCR + 4096;
constexpr uint32_t OFF_P0B = OFF_SCR + 6144;
constexpr uint32_t OFF_XN = OFF_SCR + 8192;
constexpr uint32_t OFF_RED = OFF_SCR + 10496;
constexpr uint32_t OFF_ALPHA = OFF_SCR + 11072;
constexpr uint32_t OFF_WV = OFF_SCR + 6144;
constexpr uint32_t OFF_SEL = OFF_SCR + 10752;
constexpr uint32_t OFF_TS = OFF_SCR + 11136;
constexpr uint32_t OFF_BARS = OFF_SCR + 11264;
constexpr uint32_t SMEM_BYTES = OFF_BARS + 512;
constexpr uint32_t OFF_BS4 = OFF_Q;
constexpr uint32_t OFF_H1 = OFF_Q + 2304;
constexpr uint32_t OFF_REDS = OFF_Q + 2816;
constexpr uint32_t OFF_BS5 = OFF_Q + 4096;
constexpr uint32_t OFF_REDG = OFF_Q + 8192;
constexpr uint32_t OFF_REDU = 65536;
constexpr uint32_t OFF_REDV = 65536 + 8192;

constexpr int BAR_FULL = 0;
constexpr int BAR_LAST = 28;
constexpr int BAR_WUK = 33, BAR_WM2 = 35, BAR_WUV = 36, BAR_WO = 38, BAR_W1 = 40, BAR_W2 = 41;
constexpr int BAR_ALLCLR = 42, BAR_TS = 43, BAR_WV = 44;
constexpr int BAR_EMPTY = 45;
constexpr int BAR_P0BD = 53;
constexpr int BAR_P1D = 54, BAR_P2D = 55;
constexpr int BAR_P5D = 56, BAR_P7D = 57;
constexpr int NBARS = 58;
constexpr int BAR_XC = 58, BAR_WQ = 59;
constexpr int BAR_C = 61;
constexpr uint32_t SB = 1024;

#define TUNE_LIST(X) \
  X(PC_T0, 355) X(PC_P1, 320) X(PC_PM, 225) X(PC_P2, 319) X(PC_STAG, 390) X(PC_SL, 500) X(PC_NW, 6) \
  X(T_UV, 225) X(P_UV, 250) X(PF_N, 3) X(T_PF, 1060) X(P_PF, 230) X(T_O, 2040) X(P_O, 185) X(T_1, 2960) X(T_2, 3700) X(T_GB, 3450) X(P_F, 300) \
  X(PR_T0, 1000) X(PR_N, 4) X(CLR_T0, 3900) X(CLR_CLK, 190) \
  X(D_MOD, 1450) X(D_QP, 1200) X(D_QX, 950) X(TS_P, 1) X(TS_O, 1945) X(D_TS, 700) X(A_M, 1450) X(D_X1, 1400) X(A_X1, 2460) X(R_X0, 1550) \
  X(D_X2, 275) X(D_X3A, 60) X(R_X3A, 2835) X(D_X3B, 800) X(R_X3B, 915) X(D_FIN, 320) X(R_FIN, 1540)
struct Tune {
#define X(n, v) static constexpr int n = v;
  TUNE_LIST(X)
#undef X
};

struct Scratch {
  uint32_t MOD1[2][4 * 64 * 64];
  uint32_t MOD2[2][128 * 64];
  uint32_t QP[2][128 * 256 * 2];
  uint32_t QX[2][8 * 32 * 256];
  uint32_t epoch;
  uint32_t pad[31];
  uint32_t sync[NSYNC][32];
};
__device__ Scratch g_s;
__device__ uint32_t g_in[(128 + 16) * 16384];
__device__ __forceinline__ uint32_t blk(int c, int k, uint32_t sel) { return c * 16384 + k * 2048 + ((sel ^ k) & 1) * 1024; }
__device__ __forceinline__ uint32_t flip(int c) { return c ^ (c >> 1) ^ (c >> 3); }

#define CLK_DECL
#define CLK(i) do {} while (0)
#define CLK_DUMP() do {} while (0)
#define ITS(i, v) do {} while (0)

struct Params {
  CUtensorMap wq, wuk, wm2, wm3, ckv2, ckv1, wuv, wo, w1, w2;
};

__device__ __forceinline__ void mbar_init(uint32_t bar, int cnt) { asm volatile("mbarrier.init.shared::cta.b64 [%0], %1;" ::"r"(bar), "r"(cnt)); }
__device__ __forceinline__ void mbar_expect(uint32_t bar, uint32_t bytes) { asm volatile("mbarrier.arrive.expect_tx.shared::cta.b64 _, [%0], %1;" ::"r"(bar), "r"(bytes) : "memory"); }
__device__ __forceinline__ void mbar_arrive(uint32_t bar) { asm volatile("mbarrier.arrive.shared::cta.b64 _, [%0];" ::"r"(bar) : "memory"); }
__device__ __forceinline__ uint32_t clk32() { unsigned long long c; asm volatile("mov.u64 %0, %%clock64;" : "=l"(c) :: "memory"); return (uint32_t)c; }
__device__ __forceinline__ uint32_t gtime32() { uint32_t c; asm volatile("mov.u32 %0, %%globaltimer_lo;" : "=r"(c) :: "memory"); return c; }
__device__ __forceinline__ void wait_clk(uint32_t t0, int clocks) { while ((int)(clk32() - t0) < clocks) {} }
__device__ __forceinline__ void backoff(int clocks) { if (clocks > 0) wait_clk(clk32(), clocks); }
__device__ __forceinline__ void until_ns(uint32_t ns) { while ((int)(gtime32() - ns) < 0) {} }
__device__ __forceinline__ void slot(uint32_t& tn, int slack) {
  uint32_t now;
  do { now = gtime32(); } while ((int)(now - tn) < 0);
  if ((int)(now - tn) > slack) tn = now - slack;
}
template <typename T> __device__ __forceinline__ T* pin(T* p) { asm volatile("" : "+l"(p)); return p; }
__device__ __forceinline__ uint32_t pin(uint32_t v) { asm volatile("" : "+r"(v)); return v; }
__device__ __forceinline__ float pin(float v) { asm volatile("" : "+f"(v)); return v; }
constexpr int SPIN_LIMIT = 1 << 22;
__device__ __forceinline__ void mbar_wait(uint32_t bar) {
  asm volatile("{\n.reg .pred p;\n.reg .u32 c;\nmov.u32 c, 0;\n"
               "MW_LOOP:\nmbarrier.try_wait.parity.shared::cta.b64 p, [%0], 0;\n@p bra MW_DONE;\n"
               "add.u32 c, c, 1;\nsetp.lt.u32 p, c, 4194304;\n@p bra MW_LOOP;\ntrap;\nMW_DONE:\n}"
               ::"r"(bar) : "memory");
}
__device__ __forceinline__ bool mbar_test(uint32_t bar) {
  uint32_t ok;
  asm volatile("{\n.reg .pred p;\nmbarrier.test_wait.parity.shared::cta.b64 p, [%1], 0;\nselp.u32 %0,1,0,p;\n}" : "=r"(ok) : "r"(bar) : "memory");
  return ok;
}
__device__ __forceinline__ void tma2d(uint32_t dst, const CUtensorMap* m, int c0, int c1, uint32_t bar, uint64_t pol) {
  asm volatile("cp.async.bulk.tensor.2d.shared::cluster.global.mbarrier::complete_tx::bytes.L2::cache_hint [%0], [%1, {%3,%4}], [%2], %5;"
               ::"r"(dst), "l"(m), "r"(bar), "r"(c0), "r"(c1), "l"(pol) : "memory");
}
__device__ __forceinline__ void tma2d_nohint(uint32_t dst, const CUtensorMap* m, int c0, int c1, uint32_t bar) {
  asm volatile("cp.async.bulk.tensor.2d.shared::cluster.global.mbarrier::complete_tx::bytes [%0], [%1, {%3,%4}], [%2];"
               ::"r"(dst), "l"(m), "r"(bar), "r"(c0), "r"(c1) : "memory");
}
__device__ __forceinline__ void tma3d(uint32_t dst, const CUtensorMap* m, int c0, int c1, int c2, uint32_t bar, uint64_t pol) {
  asm volatile("cp.async.bulk.tensor.3d.shared::cluster.global.mbarrier::complete_tx::bytes.L2::cache_hint [%0], [%1, {%3,%4,%5}], [%2], %6;"
               ::"r"(dst), "l"(m), "r"(bar), "r"(c0), "r"(c1), "r"(c2), "l"(pol) : "memory");
}
__device__ __forceinline__ void tma5d(uint32_t dst, const CUtensorMap* m, int c0, int c1, int c2, int c3, int c4, uint32_t bar, uint64_t pol) {
  asm volatile("cp.async.bulk.tensor.5d.shared::cluster.global.mbarrier::complete_tx::bytes.L2::cache_hint [%0], [%1, {%3,%4,%5,%6,%7}], [%2], %8;"
               ::"r"(dst), "l"(m), "r"(bar), "r"(c0), "r"(c1), "r"(c2), "r"(c3), "r"(c4), "l"(pol) : "memory");
}
__device__ __forceinline__ void bulk_ld(uint32_t dst, const void* src, uint32_t bytes, uint32_t bar) {
  asm volatile("cp.async.bulk.shared::cluster.global.mbarrier::complete_tx::bytes [%0], [%1], %2, [%3];" ::"r"(dst), "l"(src), "r"(bytes), "r"(bar) : "memory");
}
__device__ __forceinline__ void bar_sync(int id, int n) { asm volatile("barrier.cta.sync.aligned %0, %1;" ::"r"(id), "r"(n) : "memory"); }
__device__ __forceinline__ void cbar() { asm volatile("barrier.cta.sync.aligned 1, 256;" ::: "memory"); }
__device__ __forceinline__ bool bar_over(float ex) {
  uint32_t over;
  asm volatile("{\n.reg .pred p, q;\nsetp.gtu.f32 p, %1, 0f42700000;\nbarrier.cta.red.or.aligned.pred q, 4, 256, p;\nselp.u32 %0, 1, 0, q;\n}"
               : "=r"(over) : "f"(ex) : "memory");
  return over;
}

__device__ __forceinline__ uint32_t ldg_nc1(const void* p) { uint32_t v; asm volatile("ld.global.nc.L1::no_allocate.u32 %0, [%1];" : "=r"(v) : "l"(p)); return v; }
__device__ __forceinline__ uint2 ldg_nc2(const void* p) { uint2 v; asm volatile("ld.global.nc.v2.u32 {%0,%1}, [%2];" : "=r"(v.x), "=r"(v.y) : "l"(p)); return v; }
__device__ __forceinline__ uint4 ldg_nc4(const void* p) { uint4 v; asm volatile("ld.global.nc.L1::no_allocate.v4.u32 {%0,%1,%2,%3}, [%4];" : "=r"(v.x), "=r"(v.y), "=r"(v.z), "=r"(v.w) : "l"(p)); return v; }
__device__ __forceinline__ uint32_t ldg_rlx1(const void* p) { uint32_t v; asm volatile("ld.relaxed.gpu.global.u32 %0, [%1];" : "=r"(v) : "l"(p) : "memory"); return v; }
__device__ __forceinline__ void stg4(void* p, uint4 v) { asm volatile("st.relaxed.gpu.global.v4.u32 [%0], {%1,%2,%3,%4};" ::"l"(p), "r"(v.x), "r"(v.y), "r"(v.z), "r"(v.w) : "memory"); }
__device__ __forceinline__ void stg1(void* p, uint32_t a) { asm volatile("st.relaxed.gpu.global.u32 [%0], %1;" ::"l"(p), "r"(a) : "memory"); }
__device__ __forceinline__ uint32_t nz(uint32_t w) { return max(w, 1u); }
__device__ __forceinline__ uint2 ldg_u64(const void* p) {
  uint2 v; asm volatile("{\n.reg .b64 a;\nld.relaxed.gpu.global.b64 a, [%2];\nmov.b64 {%0,%1}, a;\n}" : "=r"(v.x), "=r"(v.y) : "l"(p) : "memory"); return v;
}
__device__ __forceinline__ uint4 ldg_2u64(const void* p) {
  uint4 v; asm volatile("{\n.reg .b64 a, b;\nld.relaxed.gpu.global.v2.b64 {a, b}, [%4];\nmov.b64 {%0,%1}, a;\nmov.b64 {%2,%3}, b;\n}" : "=r"(v.x), "=r"(v.y), "=r"(v.z), "=r"(v.w) : "l"(p) : "memory"); return v;
}
__device__ __forceinline__ void stg_u64(void* p, uint32_t x, uint32_t y) {
  asm volatile("{\n.reg .b32 y;\nmax.u32 y, %2, 1;\nst.relaxed.gpu.global.v2.b32 [%0], {%1, y};\n}" ::"l"(p), "r"(x), "r"(y) : "memory");
}
__device__ __forceinline__ void red_u64(void* p, uint32_t x, uint32_t y) {
  asm volatile("{\n.reg .b32 y;\n.reg .b64 a;\nmax.u32 y, %2, 1;\nmov.b64 a, {%1, y};\nred.relaxed.gpu.global.or.b64 [%0], a;\n}" ::"l"(p), "r"(x), "r"(y) : "memory");
}
__device__ __forceinline__ void stg_u64_unless(uint32_t bad, void* p, uint32_t x, uint32_t y) {
  asm volatile("{\n.reg .b32 y;\n.reg .pred q;\nsetp.eq.u32 q, %3, 0;\nmax.u32 y, %2, 1;\n@q st.relaxed.gpu.global.v2.b32 [%0], {%1, y};\n}" ::"l"(p), "r"(x), "r"(y), "r"(bad) : "memory");
}

__device__ __forceinline__ void stg_cvt8(void* p, float a0, float a1, float b0, float b1, float c0, float c1, float d0, float d1) {
  asm volatile("{\n.reg .b32 x, y, z, w;\ncvt.rn.bf16x2.f32 x, %2, %1;\ncvt.rn.bf16x2.f32 y, %4, %3;\ncvt.rn.bf16x2.f32 z, %6, %5;\ncvt.rn.bf16x2.f32 w, %8, %7;\n"
               "max.u32 y, y, 1;\nmax.u32 w, w, 1;\nst.relaxed.gpu.global.v4.b32 [%0], {x, y, z, w};\n}"
               ::"l"(p), "f"(a0), "f"(a1), "f"(b0), "f"(b1), "f"(c0), "f"(c1), "f"(d0), "f"(d1) : "memory");
}
__device__ __forceinline__ uint32_t pack_bf16(float lo, float hi) { uint32_t r; asm("cvt.rn.bf16x2.f32 %0, %1, %2;" : "=r"(r) : "f"(hi), "f"(lo)); return r; }
__device__ __forceinline__ float bf_lo(uint32_t w) { return __uint_as_float(w << 16); }
__device__ __forceinline__ float bf_hi(uint32_t w) { return __uint_as_float(w & 0xffff0000u); }
__device__ __forceinline__ float ex2(float x) { float r; asm("ex2.approx.ftz.f32 %0, %1;" : "=f"(r) : "f"(x)); return r; }
__device__ __forceinline__ uint32_t hmul2(uint32_t a, uint32_t b) { uint32_t r; asm("mul.rn.bf16x2 %0, %1, %2;" : "=r"(r) : "r"(a), "r"(b)); return r; }
__device__ __forceinline__ uint32_t hadd2(uint32_t a, uint32_t b) { uint32_t r; asm("add.rn.bf16x2 %0, %1, %2;" : "=r"(r) : "r"(a), "r"(b)); return r; }
__device__ __forceinline__ uint32_t silu2(uint32_t v) { const float a = bf_lo(v), b = bf_hi(v); return pack_bf16(__fdividef(a, 1.f + __expf(-a)), __fdividef(b, 1.f + __expf(-b))); }
constexpr uint32_t ONE2 = 0x3f803f80u;

__device__ __forceinline__ void ldsm4(uint32_t (&r)[4], uint32_t a) { asm volatile("ldmatrix.sync.aligned.m8n8.x4.shared.b16 {%0,%1,%2,%3}, [%4];" : "=r"(r[0]), "=r"(r[1]), "=r"(r[2]), "=r"(r[3]) : "r"(a) : "memory"); }
__device__ __forceinline__ void ldsm4t(uint32_t (&r)[4], uint32_t a) { asm volatile("ldmatrix.sync.aligned.m8n8.x4.trans.shared.b16 {%0,%1,%2,%3}, [%4];" : "=r"(r[0]), "=r"(r[1]), "=r"(r[2]), "=r"(r[3]) : "r"(a) : "memory"); }
__device__ __forceinline__ void stsm4t(uint32_t a, uint32_t r0, uint32_t r1, uint32_t r2, uint32_t r3) { asm volatile("stmatrix.sync.aligned.m8n8.x4.trans.shared.b16 [%0], {%1,%2,%3,%4};" ::"r"(a), "r"(r0), "r"(r1), "r"(r2), "r"(r3) : "memory"); }
__device__ __forceinline__ uint32_t movm(uint32_t a) { uint32_t d; asm volatile("movmatrix.sync.aligned.m8n8.trans.b16 %0, %1;" : "=r"(d) : "r"(a)); return d; }
__device__ __forceinline__ void mma16816(float (&d)[4], const uint32_t (&a)[4], uint32_t b0, uint32_t b1) {
  asm volatile("mma.sync.aligned.m16n8k16.row.col.f32.bf16.bf16.f32 {%0,%1,%2,%3}, {%4,%5,%6,%7}, {%8,%9}, {%0,%1,%2,%3};"
               : "+f"(d[0]), "+f"(d[1]), "+f"(d[2]), "+f"(d[3]) : "r"(a[0]), "r"(a[1]), "r"(a[2]), "r"(a[3]), "r"(b0), "r"(b1));
}
__device__ __forceinline__ void sts1(uint32_t a, uint32_t v) { asm volatile("st.shared.u32 [%0], %1;" ::"r"(a), "r"(v) : "memory"); }
__device__ __forceinline__ void sts2(uint32_t a, uint32_t x, uint32_t y) { asm volatile("st.shared.v2.u32 [%0], {%1,%2};" ::"r"(a), "r"(x), "r"(y) : "memory"); }
__device__ __forceinline__ void sts4(uint32_t a, uint4 v) { asm volatile("st.shared.v4.u32 [%0], {%1,%2,%3,%4};" ::"r"(a), "r"(v.x), "r"(v.y), "r"(v.z), "r"(v.w) : "memory"); }
__device__ __forceinline__ void sts2f(uint32_t a, float x, float y) { asm volatile("st.shared.v2.f32 [%0], {%1,%2};" ::"r"(a), "f"(x), "f"(y) : "memory"); }
__device__ __forceinline__ void sts4f(uint32_t a, float x, float y, float z, float w) { asm volatile("st.shared.v4.f32 [%0], {%1,%2,%3,%4};" ::"r"(a), "f"(x), "f"(y), "f"(z), "f"(w) : "memory"); }
__device__ __forceinline__ void stsf(uint32_t a, float v) { asm volatile("st.shared.f32 [%0], %1;" ::"r"(a), "f"(v) : "memory"); }
__device__ __forceinline__ uint32_t lds1(uint32_t a) { uint32_t v; asm volatile("ld.shared.u32 %0, [%1];" : "=r"(v) : "r"(a) : "memory"); return v; }
__device__ __forceinline__ float ldsf(uint32_t a) { float v; asm volatile("ld.shared.f32 %0, [%1];" : "=f"(v) : "r"(a) : "memory"); return v; }
__device__ __forceinline__ float2 ldsf2(uint32_t a) { float2 v; asm volatile("ld.shared.v2.f32 {%0,%1}, [%2];" : "=f"(v.x), "=f"(v.y) : "r"(a) : "memory"); return v; }
__device__ __forceinline__ float4 ldsf4(uint32_t a) { float4 v; asm volatile("ld.shared.v4.f32 {%0,%1,%2,%3}, [%4];" : "=f"(v.x), "=f"(v.y), "=f"(v.z), "=f"(v.w) : "r"(a) : "memory"); return v; }
__device__ __forceinline__ void lds4(uint32_t (&r)[4], uint32_t a) { asm volatile("ld.shared.v4.u32 {%0,%1,%2,%3}, [%4];" : "=r"(r[0]), "=r"(r[1]), "=r"(r[2]), "=r"(r[3]) : "r"(a) : "memory"); }

__device__ __forceinline__ void wg_fence() { asm volatile("wgmma.fence.sync.aligned;" ::: "memory"); }
__device__ __forceinline__ void wg_commit() { asm volatile("wgmma.commit_group.sync.aligned;" ::: "memory"); }
template <int N> __device__ __forceinline__ void wg_wait() { asm volatile("wgmma.wait_group.sync.aligned %0;" ::"n"(N) : "memory"); }
__host__ __device__ constexpr uint32_t desc_lo(uint32_t off) { return ((SB + off) >> 4) | 0x10000u; }
template <int TA, int ACC> __device__ __forceinline__ void wgmma_n16(float (&d)[8], uint32_t da, uint32_t db) {
  asm volatile("{\n.reg .b64 da, db;\nmov.b64 da, {%8, 0x40000040};\nmov.b64 db, {%9, 0x40000040};\n"
               "wgmma.mma_async.sync.aligned.m64n16k16.f32.bf16.bf16 {%0,%1,%2,%3,%4,%5,%6,%7}, da, db, %11, 1, 1, %10, 0;\n}"
               : "+f"(d[0]), "+f"(d[1]), "+f"(d[2]), "+f"(d[3]), "+f"(d[4]), "+f"(d[5]), "+f"(d[6]), "+f"(d[7])
               : "r"(da), "r"(db), "n"(TA), "n"(ACC));
}
__device__ __forceinline__ void wgmma_n16_ones(float (&d)[8], uint32_t one, uint32_t db) {
  asm volatile("{\n.reg .b64 db;\nmov.b64 db, {%9, 0x40000040};\n"
               "wgmma.mma_async.sync.aligned.m64n16k16.f32.bf16.bf16 {%0,%1,%2,%3,%4,%5,%6,%7}, {%8,%8,%8,%8}, db, 1, 1, 1, 0;\n}"
               : "+f"(d[0]), "+f"(d[1]), "+f"(d[2]), "+f"(d[3]), "+f"(d[4]), "+f"(d[5]), "+f"(d[6]), "+f"(d[7])
               : "r"(one), "r"(db));
}
__device__ __forceinline__ void acc_fence(float (&d)[8]) {
  asm volatile("" : "+f"(d[0]), "+f"(d[1]), "+f"(d[2]), "+f"(d[3]), "+f"(d[4]), "+f"(d[5]), "+f"(d[6]), "+f"(d[7]) :: "memory");
}

template <int N, int STRIDE> __device__ __forceinline__ void load_units(uint2 (&v)[N], const uint32_t* p) {
#pragma unroll
  for (int i = 0; i < N; i++) v[i] = ldg_u64(p + i * STRIDE);
}
__device__ __forceinline__ void reload_unit(uint2& v, const uint32_t* p) {
  asm volatile("{\n.reg .pred q;\nsetp.eq.u32 q, %1, 0;\n@q ld.relaxed.gpu.global.v2.b32 {%0, %1}, [%2];\n}" : "+r"(v.x), "+r"(v.y) : "l"(p) : "memory");
}
template <int N> __device__ __forceinline__ uint32_t min_flags(const uint2 (&v)[N]) {
  uint32_t a = v[0].y, b = v[1].y;
#pragma unroll
  for (int i = 2; i < N; i += 2) { a = min(a, v[i].y); b = min(b, v[i + 1].y); }
  return min(a, b);
}
template <int N, int STRIDE> __device__ __forceinline__ int check_units(uint2 (&v)[N], const uint32_t* p) {
  int it = 0;
  while (!__all_sync(~0u, min_flags(v) != 0)) {
#pragma unroll
    for (int i = 0; i < N; i++) reload_unit(v[i], p + i * STRIDE);
    if (++it > SPIN_LIMIT) __trap();
  }
  return it;
}
__device__ __forceinline__ void sum4_to_smem(const uint2 (&v)[4], uint32_t dst) {
  const float c0 = (bf_lo(v[0].x) + bf_lo(v[1].x)) + (bf_lo(v[2].x) + bf_lo(v[3].x));
  const float c1 = (bf_hi(v[0].x) + bf_hi(v[1].x)) + (bf_hi(v[2].x) + bf_hi(v[3].x));
  const float c2 = (bf_lo(v[0].y) + bf_lo(v[1].y)) + (bf_lo(v[2].y) + bf_lo(v[3].y));
  const float c3 = (bf_hi(v[0].y) + bf_hi(v[1].y)) + (bf_hi(v[2].y) + bf_hi(v[3].y));
  sts1(dst, pack_bf16(c0, c1));
  sts1(dst + 128, pack_bf16(c2, c3));
}
__device__ __forceinline__ uint32_t a_t_offset(int w, int lane) {
  const int mi = lane >> 3, r = lane & 7;
  return (w >> 2) * 16384 + (8 * (mi >> 1) + r) * 128 + (((2 * (w & 3) + (mi & 1)) ^ r) << 4);
}
__device__ __forceinline__ void load_a_t(uint32_t (&a)[8][4], uint32_t base) {
#pragma unroll
  for (int ks = 0; ks < 8; ks++) ldsm4t(a[ks], base + ks * 2048);
}
__device__ __forceinline__ void mma128(float (&d)[4], const uint32_t (&a)[8][4], const uint32_t (&b)[4][4]) {
  float e[4][4] = {{d[0], d[1], d[2], d[3]}, {0.f, 0.f, 0.f, 0.f}, {0.f, 0.f, 0.f, 0.f}, {0.f, 0.f, 0.f, 0.f}};
#pragma unroll
  for (int kk = 0; kk < 4; kk++) { mma16816(e[(2 * kk) & 3], a[2 * kk], b[kk][0], b[kk][1]); mma16816(e[(2 * kk + 1) & 3], a[2 * kk + 1], b[kk][2], b[kk][3]); }
#pragma unroll
  for (int i = 0; i < 4; i++) d[i] = (e[0][i] + e[1][i]) + (e[2][i] + e[3][i]);
}
template <int NP> __device__ __forceinline__ bool sum_pieces(const uint32_t* p0, uint32_t one, float (&r)[4]) {
  uint2 v[NP / 4];
  load_units<NP / 4, 64>(v, p0);
  float d[4][4] = {};
#pragma unroll
  for (int i = 0; i < NP / 8; i++) { const uint32_t a[4] = {v[2 * i].x, v[2 * i].y, v[2 * i + 1].x, v[2 * i + 1].y}; mma16816(d[i & 3], a, one, one); }
  const bool ok = __all_sync(~0u, min_flags(v) != 0);
#pragma unroll
  for (int k = 0; k < 4; k++) r[k] = (d[0][k] + d[1][k]) + (d[2][k] + d[3][k]);
  return ok;
}
template <typename F> __device__ __forceinline__ float reduce_g(const float (&x)[4], int lane, F f) {
  const bool u4 = lane & 16, u3 = lane & 8;
  const float a0 = f(u4 ? x[2] : x[0], __shfl_xor_sync(~0u, u4 ? x[0] : x[2], 16));
  const float a1 = f(u4 ? x[3] : x[1], __shfl_xor_sync(~0u, u4 ? x[1] : x[3], 16));
  const float b = f(u3 ? a1 : a0, __shfl_xor_sync(~0u, u3 ? a0 : a1, 8));
  return f(b, __shfl_xor_sync(~0u, b, 4));
}

__global__ void __launch_bounds__(NTHREADS, 1)
fused_decode_kernel(__nv_bfloat16* __restrict__ gout, Scratch* __restrict__ gs, const uint8_t* __restrict__ gwmod,
                    const uint8_t* __restrict__ gx, const uint8_t* __restrict__ gc, uint32_t* __restrict__ gin,
                    const __grid_constant__ Params P) {
  constexpr Tune T{};
  extern __shared__ __align__(1024) uint8_t smem_raw[];
  constexpr uint32_t sb = SB;
  const int tid = __shfl_xor_sync(0xffffffffu, threadIdx.x ^ 1, 1), lane = tid & 31;
  const int w = __shfl_sync(0xffffffffu, threadIdx.x >> 5, 0);
  const int cta = blockIdx.x;
  auto keep = [&](uint32_t v) { return __shfl_sync(~0u, v, lane); };
  auto BAR = [](int i) { return SB + OFF_BARS + 8 * i; };
  auto selector = [&](int c) { uint32_t v; asm volatile("ld.shared.u8 %0, [%1];" : "=r"(v) : "r"(sb + OFF_SEL + c) : "memory"); return v; };
  auto inbox = [&](int c, int k) { return gin + blk(c, k, selector(c)); };
  auto nearbox = [&](int c, int k) { return gin + blk(c, k, selector(cta) ^ flip((c ^ cta) & 15)); };
  const int g = lane >> 2, t = lane & 3;
  const int hI = cta >> 2, jI = cta & 3;
  const int bs = cta >> 1, hh = cta & 1;

  CLK_DECL;
  CLK(0);
  if (w == 8) {
    CLK(7);
    const uint32_t t_entry = gtime32();
    CLK(8);
    if (lane == 0) {
      if ((uint32_t)__cvta_generic_to_shared(smem_raw) != SB) __trap();
      mbar_init(BAR(BAR_WQ), 1); mbar_init(BAR(BAR_WQ + 1), 1); mbar_init(BAR(BAR_XC), 1); mbar_init(BAR(BAR_C), 1);
      asm volatile("fence.mbarrier_init.release.cluster;" ::: "memory");
      asm volatile("prefetch.tensormap [%0];" ::"l"(&P.wq) : "memory");
      mbar_expect(BAR(BAR_XC), 8192); mbar_expect(BAR(BAR_C), 8192); mbar_expect(BAR(BAR_WQ), 16384); mbar_expect(BAR(BAR_WQ + 1), 16384);
      CLK(9);
    }
    __syncwarp();
    asm volatile("barrier.cta.arrive.aligned 0, %0;" ::"n"(NTHREADS) : "memory");
    CLK(10);
    uint32_t tn = t_entry + T.PC_T0 + ((bs * 37) & 63) * T.PC_STAG / 64;
    const int h = hI, j = jI;
    if (lane == 0) {
      uint64_t pol; asm volatile("createpolicy.fractional.L2::evict_first.b64 %0, 1.0;" : "=l"(pol));
#pragma unroll
      for (int u = 0; u < 4; u++) {
        until_ns(tn + u * T.PC_P1);
        if (u == 0) CLK(11);
        tma2d(sb + OFF_WQ + u * 8192, &P.wq, 128 * h + 64 * (u >> 1), 128 * j + 64 * (u & 1), BAR(BAR_WQ + (u >> 1)), pol);
        if (u == 0) {
#pragma unroll
          for (int i = 0; i < 8; i++) { const int o = ((i + cta) & 3) * 2048; bulk_ld(sb + OFF_XS + (i >> 2) * 8192 + o, (i < 4 ? gx : gc) + o, 2048, BAR(i < 4 ? BAR_XC : BAR_C)); }
          CLK(1);
          asm volatile("prefetch.tensormap [%0];" ::"l"(&P.wuk) : "memory");
          asm volatile("prefetch.tensormap [%0];" ::"l"(&P.wm2) : "memory");
          asm volatile("prefetch.tensormap [%0];" ::"l"(&P.ckv2) : "memory");
        }
      }
    }
    __syncwarp();
    tn += 4 * T.PC_P1;
    bar_sync(5, 64);
    if (lane == 0) {
      uint64_t pol; asm volatile("createpolicy.fractional.L2::evict_first.b64 %0, 1.0;" : "=l"(pol));
#pragma unroll
      for (int u = 0; u < 4; u++) {
        if (u & 1) mbar_wait(BAR(BAR_WQ + (u >> 1)));
        slot(tn, T.PC_SL);
        tma5d(sb + OFF_WUK + u * 8192, &P.wuk, 128 * h + 64 * (u >> 1), 0, 0, 0, 8 * j + 4 * (u & 1), BAR(BAR_WUK + (u >> 1)), pol);
        tn += T.PC_P1;
      }
#pragma unroll
      for (int u = 0; u < 2; u++) {
        if (u) mbar_wait(BAR(BAR_WUK));
        slot(tn, T.PC_SL);
        if (j != 3) tma2d_nohint(sb + OFF_WM2 + u * 8192, &P.wm2, 1024 + 16 * (3 * h + j), 256 * u, BAR(BAR_WM2));
        tn += T.PC_PM;
      }
      const int row0 = (bs >> 3) * 4096 + (bs & 7) * 64;
      uint32_t dst = sb + OFF_RING;
#pragma unroll 1
      for (int n = 0; n < 31; n++) {
        if (n >= 4 && (n < 12 || (n & 3) == 0)) mbar_wait(BAR(n >= 12 ? BAR_EMPTY + (n >> 2) - 3 : (n == 7 && j != 3) ? BAR_P0BD : (n == 8 || n == 9) ? BAR_P2D : BAR_P1D));
        if (n < T.PC_NW) {
          if (n >= 4) mbar_wait(BAR(BAR_FULL + n - 4));
          else if (n & 1) mbar_wait(BAR((n < 2 || j == 3) ? BAR_WUK + 1 : BAR_WM2));
        }
        slot(tn, T.PC_SL);
        tma3d(dst, &P.ckv2, 0, row0 + (n >> 2) * 512, 2 * (n & 3), BAR(BAR_FULL + n), pol);
        dst = (n == 11 || n == 23) ? sb + OFF_RING : dst + 16384;
        tn += T.PC_P2;
        if (n == 4) CLK(2);
        if (n == 12) CLK(3);
        if (n == 20) CLK(4);
        if (n == 28) CLK(5);
        if (n == 24) {
          asm volatile("prefetch.tensormap [%0];" ::"l"(&P.ckv1) : "memory");
          asm volatile("prefetch.tensormap [%0];" ::"l"(&P.wuv) : "memory");
          asm volatile("prefetch.tensormap [%0];" ::"l"(&P.wo) : "memory");
          asm volatile("prefetch.tensormap [%0];" ::"l"(cta < NFF ? &P.w1 : &P.wm3) : "memory");
          asm volatile("prefetch.tensormap [%0];" ::"l"(&P.w2) : "memory");
        }
      }
      slot(tn, T.PC_SL);
      tma3d(dst, &P.ckv1, 0, row0 + 7 * 512, 6, BAR(BAR_LAST + 3), pol);
      tma3d(dst + 8192, &P.ckv1, 0, row0 + 7 * 512, 7, BAR(BAR_LAST + 4), pol);
      tn += T.PC_P2;
      CLK(6);
      auto unit = [&](int u) {
        if (u < 4) tma5d(sb + OFF_WUV + u * 8192, &P.wuv, 128 * h + 64 * (u >> 1), 0, 4 * (j >> 1), 0, 2 * (j & 1) + (u & 1), BAR(BAR_WUV + (u >> 1)), pol);
        else if (u < 8) tma2d(sb + OFF_WO + (u - 4) * 8192, &P.wo, 128 * j + 64 * ((u - 4) >> 1), 128 * h + 64 * (u & 1), BAR(BAR_WO + ((u - 4) >> 1)), pol);
        else if (u < 10) { if (cta < NFF) tma2d_nohint(sb + OFF_W1 + (u - 8) * 16384, &P.w1, 32 * bs, 256 * (u - 8), BAR(BAR_W1)); }
        else if (cta < NFF) tma3d(sb + OFF_W2 + (u - 10) * 8192, &P.w2, 0, 32 * bs, 4 * hh + 2 * (u - 10), BAR(BAR_W2), pol);
        else tma2d_nohint(sb + OFF_W1 + (u - 10) * 16384, &P.wm3, 2560 + 32 * (cta - NFF), 256 * (u - 10), BAR(BAR_W1));
      };
      mbar_wait(BAR(BAR_EMPTY + 5));
#pragma unroll
      for (int u = 0; u < 12; u++) {
        if (u == 8) mbar_wait(BAR(BAR_EMPTY + 6));
        until_ns(tn + (u < 4 ? T.T_UV + u * T.P_UV : u < 8 ? T.T_O + (u - 4) * T.P_O : u < 10 ? T.T_1 + (u - 8) * T.P_F : (cta < NFF ? T.T_2 : T.T_GB) + (u - 10) * T.P_F));
        unit(u);
        if (u == 3) {
#pragma unroll
          for (int q = 0; q < 4; q++)
            if (q < T.PF_N) {
              until_ns(tn + T.T_PF + q * T.P_PF);
              asm volatile("cp.async.bulk.prefetch.tensor.2d.L2.global.tile [%0, {%1,%2}];" ::"l"(&P.wo), "r"(128 * j + 64 * (q >> 1)), "r"(128 * h + 64 * (q & 1)) : "memory");
            }
        }
      }
      CLK_DUMP();
    }
    return;
  }

  if (w == 9) {
    if (lane == 0) {
#pragma unroll
      for (int i = 0; i < NBARS; i++) mbar_init(BAR(i), i >= BAR_P1D ? 8 : i >= BAR_EMPTY ? 4 : 1);
      asm volatile("fence.mbarrier_init.release.cluster;" ::: "memory");
    }
    __syncwarp();
    mbar_expect(BAR(lane), lane == BAR_LAST + 3 ? 8192 : 16384);
    if (lane < BAR_ALLCLR - 32) mbar_expect(BAR(32 + lane), lane == 0 ? 8192 : lane == BAR_W1 - 32 ? 32768 : 16384);
    CLK(9);
    asm volatile("barrier.cta.arrive.aligned 5, 64;" ::: "memory");
    asm volatile("barrier.cta.arrive.aligned 0, %0;" ::"n"(NTHREADS) : "memory");
  }
  const uint32_t epoch = ldg_rlx1(&gs->epoch);

  if (w == 9) {
    const int mo = g * 512 + 16 * hI + 2 * jI;
    const uint32_t xo0 = ldg_nc1(gx + mo * 2), xo1 = ldg_nc1(gx + mo * 2 + 16);
    const int par = epoch & 1;
    const uint32_t t0 = gtime32();
    const uint4 z = make_uint4(0, 0, 0, 0);
    uint32_t sel;
    {
      uint32_t* pa = gin + blk(cta, 5, 0) + 960;
      uint32_t* pb = gin + blk(cta, 5, 1) + 960;
      until_ns(t0 + T.PR_T0);
      if (lane < 4) stg4(reinterpret_cast<uint4*>(lane & 2 ? pa : pb) + (lane & 1), z);
      uint32_t ma = 0xffffffffu, mb = 0xffffffffu;
#pragma unroll 1
      for (int i = 0; i < 2 * T.PR_N; i++) {
        const uint32_t c0 = clk32();
        asm volatile("{\n.reg .pred q;\n.reg .b32 v;\nsetp.eq.u32 q, %1, 0;\nmov.u32 v, 0;\n@q atom.relaxed.gpu.global.add.u32 v, [%0], 1;\n"
                     "setp.eq.u32 q, v, 0xffffffff;\n@q trap;\n}" ::"l"(i & 1 ? pb : pa), "r"(lane) : "memory");
        const uint32_t d = clk32() - c0;
        if (i & 1) mb = min(mb, d); else ma = min(ma, d);
      }
      sel = __shfl_sync(~0u, (uint32_t)(mb < ma), 0);
      const uint32_t sw = 2 * (epoch + 1) + sel;
      if (lane < 2) stg4(reinterpret_cast<uint4*>(gin + blk(cta, 5, 1) + 896) + lane, make_uint4(sw, sw, sw, sw));
    }
    until_ns(t0 + T.CLR_T0);
    {
#pragma unroll 1
      for (int i0 = 0; i0 < 13; i0++) {
        uint4* q = reinterpret_cast<uint4*>(gin + (i0 < 12 ? blk(cta, i0 >> 1, sel) + (i0 & 1) * 512 : blk(cta, 4, sel ^ 1) + 512)) + lane;
#pragma unroll
        for (int i = 0; i < 4; i++) if (i0 != 11 || i < 3) stg4(q + i * 32, z);
        backoff(T.CLR_CLK);
      }
#pragma unroll
      for (int i = 0; i < 2; i++) {
        if (jI == 1) stg4(reinterpret_cast<uint4*>(gin + blk(cta, 6, i)) + lane, z);
        if (lane < 2) stg4(reinterpret_cast<uint4*>(gin + blk(cta, 5, i) + 928) + lane, z);
        stg4(reinterpret_cast<uint4*>(gin + blk(16 * g, 6 + (cta >> 6), i) + (cta & 63) * 16) + t, z);
      }
      CLK(1);
      {
        uint32_t sv = 0;
        uint32_t u[4];
        int it = 0;
        do {
#pragma unroll
          for (int i = 0; i < 4; i++) u[i] = ldg_rlx1(gin + blk(4 * lane + i, 5, 1) + 896) ^ (2 * (epoch + 1));
          if (++it > SPIN_LIMIT) __trap();
        } while (!__all_sync(~0u, (u[0] | u[1] | u[2] | u[3]) < 2));
#pragma unroll
        for (int i = 0; i < 4; i++) sv |= u[i] << (8 * i);
        sts1(sb + OFF_SEL + lane * 4, sv);
      }
      asm volatile("fence.acq_rel.gpu;" ::: "memory");
      CLK(2);
      __syncwarp();
      if (lane < NSYNC) asm volatile("red.relaxed.gpu.global.add.u32 [%0], 1;" ::"l"(&gs->sync[lane][0]) : "memory");
#pragma unroll
      for (int i = 0; i < 4; i++) stg4(reinterpret_cast<uint4*>(gs->QP[par ^ 1] + cta * 512) + i * 32 + lane, z);
      backoff(T.CLR_CLK);
#pragma unroll
      for (int i = 0; i < 4; i++) stg4(reinterpret_cast<uint4*>(gs->QX[par ^ 1] + cta * 512) + i * 32 + lane, z);
      stg4(reinterpret_cast<uint4*>(gs->MOD1[par ^ 1] + cta * 128) + lane, z);
      if (lane < 16) stg4(reinterpret_cast<uint4*>(gs->MOD2[par ^ 1] + cta * 64) + lane, z);
      const uint32_t target = (epoch + 1) * NCTA;
      uint32_t c; int it = 0;
      do {
        backoff(T.CLR_CLK);
        asm volatile("ld.acquire.gpu.global.u32 %0, [%1];" : "=r"(c) : "l"(&gs->sync[cta % NSYNC][0]) : "memory");
        if (++it > SPIN_LIMIT) __trap();
      } while (!__all_sync(~0u, (int)(c - target) >= 0));
      if (lane == 0) mbar_arrive(BAR(BAR_ALLCLR));
    }
    CLK(3);
    const uint32_t* const pg = gs->MOD2[par] + cta * 16 + g * 2;
    auto gate = [&](const uint32_t* q) { uint2 u; int it = 0; do { u = ldg_u64(q); if (++it > SPIN_LIMIT) __trap(); } while (!__all_sync(~0u, u.y != 0)); return u; };
    const uint2 gau = gate(pg);
    uint32_t anchor;
    {
      uint32_t* const po = gin + blk(16 * (lane & 7), 5, lane >> 3) + 928;
      const uint32_t* const pi = nearbox(cta & ~15, 5) + 928;
      mbar_wait(BAR(BAR_LAST + T.TS_P));
      unsigned long long now; asm volatile("mov.u64 %0, %%globaltimer;" : "=l"(now));
      if (lane < 16) asm volatile("red.relaxed.gpu.global.add.u64 [%0], %1;" ::"l"(po), "l"((now << 8) + 1) : "memory");
      backoff(T.D_TS);
      uint2 v; int it = 0;
      do { v = ldg_u64(pi); if (++it > SPIN_LIMIT) __trap(); } while (!__all_sync(~0u, (v.x & 255) == NCTA));
      const uint32_t mean = __funnelshift_r(v.x, v.y, 15);
      const int age = min(max((int)(gtime32() - mean), 0), 4000);
      anchor = clk32() - age * 7 / 4 + T.TS_O;
      if (lane == 0) { sts1(sb + OFF_TS, anchor); mbar_arrive(BAR(BAR_TS)); }
      CLK(10);
    }
    {
      const uint32_t* pm = pin(nearbox(4 * hI + 1, 6) + lane * 4);
      wait_clk(anchor, T.A_M);
      uint4 ml = ldg_2u64(pm);
      int it = 0;
      while (!__all_sync(~0u, ml.y != 0 && ml.w != 0)) { ml = ldg_2u64(pm); if (++it > SPIN_LIMIT) __trap(); }
      ITS(2, it);
      float M = fmaxf(__uint_as_float(ml.x), __uint_as_float(ml.z));
      M = fmaxf(M, __shfl_xor_sync(~0u, M, 1)); M = fmaxf(M, __shfl_xor_sync(~0u, M, 2));
      const float e0 = ex2(__uint_as_float(ml.x) - M), e1 = ex2(__uint_as_float(ml.z) - M);
      float l = e0 * __uint_as_float(ml.y) + e1 * __uint_as_float(ml.w);
      l += __shfl_xor_sync(~0u, l, 1); l += __shfl_xor_sync(~0u, l, 2);
      const float inv = __fdividef(1.f, l);
      sts2f(sb + OFF_WV + lane * 8, e0 * inv, e1 * inv);
      __syncwarp();
      if (lane == 0) mbar_arrive(BAR(BAR_WV));
      CLK(11);
    }
    uint32_t* x3o[4];
#pragma unroll
    for (int i = 0; i < 4; i++) x3o[i] = pin(gin + blk(32 * i + 16 * (t >> 1), 6 + (cta >> 6), t) + (cta & 63) * 16 + g * 2);
    uint32_t* const fo = pin(reinterpret_cast<uint32_t*>(gout) + mo / 2 + 4 * (t & 1));
    const uint32_t* const p3 = pin(gin + blk(cta, 4, sel) + t * 16 + g * 2);
    const uint32_t* const p4 = pin(gin + blk(cta, 5, sel) + t * 16 + g * 2);
    const uint32_t one = pin((g & 1) ? 0x3f800000u : 0x00003f80u);
    const float xf[4] = {pin(bf_lo(xo0)), pin(bf_hi(xo0)), pin(bf_lo(xo1)), pin(bf_hi(xo1))};
    const float ga[4] = {pin(bf_lo(gau.x)), pin(bf_hi(gau.x)), pin(bf_lo(gau.y)), pin(bf_hi(gau.y))};
    mbar_wait(BAR(BAR_P5D));
    backoff(T.D_X3A);
    wait_clk(anchor, T.A_X1 + T.R_X3A);
    CLK(4);
    float r[4];
    uint32_t x20, x21;
    int it = 0;
    bool ok;
    do {
      ok = sum_pieces<32>(p3, one, r);
      x20 = pack_bf16(xf[0] + ga[0] * r[0], xf[1] + ga[1] * r[1]); x21 = pack_bf16(xf[2] + ga[2] * r[2], xf[3] + ga[3] * r[3]);
#pragma unroll
      for (int i = 0; i < 4; i++) stg_u64_unless(!ok || (i == 3 && t >= 2), x3o[i], x20, x21);
    } while (!ok && ++it < SPIN_LIMIT);
    if (!ok) __trap();
    CLK(6);
    ITS(0, it);
    const uint32_t xw = (t & 1) ? x21 : x20;
    const float xa = pin(bf_lo(xw)), xb = pin(bf_hi(xw));
    if (cta < NFF) mbar_wait(BAR(BAR_P7D)); else wait_clk(anchor, T.A_X1 + T.R_X3A + T.R_X3B + T.R_FIN - T.D_FIN);
    uint2 gbu = ldg_u64(pg + 3 * 2048);
    backoff(T.D_FIN);
    CLK(7);
    do {
      ok = sum_pieces<NFG>(p4, one, r);
      ok = ok && __all_sync(~0u, gbu.y != 0);
      const uint32_t gw = (t & 1) ? gbu.y : gbu.x;
      const uint32_t o = pack_bf16(xa + bf_lo(gw) * ((t & 1) ? r[2] : r[0]), xb + bf_hi(gw) * ((t & 1) ? r[3] : r[1]));
      if (ok && t < 2) asm volatile("st.global.u32 [%0], %1;" ::"l"(fo), "r"(o) : "memory");
      reload_unit(gbu, pg + 3 * 2048);
    } while (!ok && ++it < SPIN_LIMIT);
    if (!ok) __trap();
    ITS(1, it);
    CLK(8);
    CLK_DUMP();
    if (cta == 0 && lane == 0) stg1(&gs->epoch, epoch + 1);
    return;
  }

  const int wg = w >> 2, wq = w & 3;
  uint32_t tstore;
  {
    const uint8_t* pw = gwmod + (size_t)(128 * jI + 16 * w + 4 * (g >> 1) + (g & 1)) * 6144 + 64 * hI + 16 * t;
    const uint4 w0 = ldg_nc4(pw), w1 = ldg_nc4(pw + 2 * 6144);
    const uint2 cc = ldg_nc2(gc + g * 1024 + 256 * jI + 32 * w + 8 * t);
    CLK(40);
    const uint32_t a[4] = {silu2(cc.x), 0u, silu2(cc.y), 0u};
    float d[4][4] = {{0.f, 0.f, 0.f, 0.f}, {0.f, 0.f, 0.f, 0.f}, {0.f, 0.f, 0.f, 0.f}, {0.f, 0.f, 0.f, 0.f}};
    mma16816(d[0], a, movm(w0.x), movm(w1.x)); mma16816(d[1], a, movm(w0.y), movm(w1.y));
    mma16816(d[2], a, movm(w0.z), movm(w1.z)); mma16816(d[3], a, movm(w0.w), movm(w1.w));
    CLK(1);
    sts4f(sb + OFF_P0S + w * 1088 + lane * 16, d[0][0], d[0][1], d[1][0], d[1][1]);
    sts4f(sb + OFF_P0S + w * 1088 + 544 + lane * 16, d[2][0], d[2][1], d[3][0], d[3][1]);
    bar_sync(0, NTHREADS);
    if (tid < 128) {
      const uint32_t src = sb + OFF_P0S + ((tid >> 2) & 1) * 544 + (((tid >> 3) & 7) * 4 + 2 * (tid >> 6) + (tid & 1)) * 16 + ((tid >> 1) & 1) * 8;
      float2 v[8];
#pragma unroll
      for (int i = 0; i < 8; i++) v[i] = ldsf2(src + i * 1088);
      const float ax = ((v[0].x + v[1].x) + (v[2].x + v[3].x)) + ((v[4].x + v[5].x) + (v[6].x + v[7].x));
      const float ay = ((v[0].y + v[1].y) + (v[2].y + v[3].y)) + ((v[4].y + v[5].y) + (v[6].y + v[7].y));
      stg1(gs->MOD1[epoch & 1] + jI * 4096 + hI * 128 + tid, nz(pack_bf16(ax, ay)));
    }
    tstore = clk32();
  }
  CLK(2);
  const int par = epoch & 1;
  uint32_t cf[4][4];
  mbar_wait(BAR(BAR_XC));
  {
    uint32_t u[2][4];
    lds4(u[0], sb + OFF_XS + w * 1024 + lane * 16); lds4(u[1], sb + OFF_XS + w * 1024 + 512 + lane * 16);
    float v[16];
#pragma unroll
    for (int i = 0; i < 8; i++) { v[2 * i] = bf_lo(u[i >> 2][i & 3]); v[2 * i + 1] = bf_hi(u[i >> 2][i & 3]); }
    float s = 0.f;
#pragma unroll
    for (int i = 0; i < 16; i++) s += v[i];
#pragma unroll
    for (int o = 16; o; o >>= 1) s += __shfl_xor_sync(~0u, s, o);
    const float mu = s * (1.f / 512.f);
    float q = 0.f;
#pragma unroll
    for (int i = 0; i < 16; i++) { v[i] -= mu; q += v[i] * v[i]; }
#pragma unroll
    for (int o = 16; o; o >>= 1) q += __shfl_xor_sync(~0u, q, o);
    const float rs = rsqrtf(q * (1.f / 512.f) + 1e-5f);
    const bool hi = jI & 2;
    uint32_t o[4];
#pragma unroll
    for (int i = 0; i < 4; i++) o[i] = pack_bf16((hi ? v[8 + 2 * i] : v[2 * i]) * rs, (hi ? v[9 + 2 * i] : v[2 * i + 1]) * rs);
    if ((lane >> 4) == (jI & 1)) sts4(sb + OFF_XN + w * 272 + (lane & 15) * 16, make_uint4(o[0], o[1], o[2], o[3]));
  }
  CLK(3);
  uint32_t aw[8][4];
  const uint32_t abase = keep(sb + a_t_offset(w, lane));
  {
    const uint32_t* pm = pin(gs->MOD1[par] + (8 * jI + w) * 64 + lane * 2);
    uint32_t* const qpo = pin(gs->QP[par] + (cta * 256 + tid) * 2);
    float d[4] = {0.f, 0.f, 0.f, 0.f};
    wait_clk(tstore, T.D_MOD);
    CLK(4);
    uint2 v[8];
    load_units<8, 2048>(v, pm);
    cbar();
    const uint32_t xn0 = lds1(sb + OFF_XN + g * 272 + w * 32 + t * 4), xn1 = lds1(sb + OFF_XN + g * 272 + w * 32 + 16 + t * 4);
    const bool early = __all_sync(~0u, mbar_test(BAR(BAR_WQ + wg)));
    if (early) load_a_t(aw, abase + OFF_WQ);
    int it = 0;
    while (true) {
      uint32_t mn = 0xffffffffu;
#pragma unroll
      for (int i = 0; i < 8; i++) mn = min(mn, min(v[i].x, v[i].y));
      if (__all_sync(~0u, mn != 0)) break;
#pragma unroll
      for (int i = 0; i < 8; i++) { if (v[i].x == 0) v[i].y = 0; reload_unit(v[i], pm + i * 2048); }
      if (++it > SPIN_LIMIT) __trap();
    }
    CLK(5);
    ITS(0, it);
    float sc[2][4];
#pragma unroll
    for (int i = 0; i < 2; i++) {
      sc[i][0] = (bf_lo(v[i].x) + bf_lo(v[2 + i].x)) + (bf_lo(v[4 + i].x) + bf_lo(v[6 + i].x));
      sc[i][1] = (bf_hi(v[i].x) + bf_hi(v[2 + i].x)) + (bf_hi(v[4 + i].x) + bf_hi(v[6 + i].x));
      sc[i][2] = (bf_lo(v[i].y) + bf_lo(v[2 + i].y)) + (bf_lo(v[4 + i].y) + bf_lo(v[6 + i].y));
      sc[i][3] = (bf_hi(v[i].y) + bf_hi(v[2 + i].y)) + (bf_hi(v[4 + i].y) + bf_hi(v[6 + i].y));
    }
    sts2(sb + OFF_BS1 + (w >> 1) * 512 + lane * 16 + (w & 1) * 8,
         pack_bf16(bf_lo(xn0) * (1.f + sc[1][0]) + sc[0][0], bf_hi(xn0) * (1.f + sc[1][1]) + sc[0][1]),
         pack_bf16(bf_lo(xn1) * (1.f + sc[1][2]) + sc[0][2], bf_hi(xn1) * (1.f + sc[1][3]) + sc[0][3]));
    if (!early) { mbar_wait(BAR(BAR_WQ + wg)); load_a_t(aw, abase + OFF_WQ); }
    CLK(6);
    cbar();
    uint32_t b[4][4];
#pragma unroll
    for (int kk = 0; kk < 4; kk++) lds4(b[kk], sb + OFF_BS1 + kk * 512 + lane * 16);
    mma128(d, aw, b);
    stg_u64(qpo, pack_bf16(d[0], d[1]), pack_bf16(d[2], d[3]));
    tstore = clk32();
    CLK(7);
    if (wg) {
      mbar_wait(BAR(BAR_C));
#pragma unroll
      for (int i = 0; i < 4; i++) lds4(cf[i], sb + OFF_CS + g * 1024 + wq * 256 + i * 64 + t * 16);
#pragma unroll
      for (int i = 0; i < 16; i++) cf[i >> 2][i & 3] = silu2(cf[i >> 2][i & 3]);
    }
    __syncwarp();
    if (lane == 0) mbar_arrive(BAR(BAR_P1D));
  }
  {
    const uint32_t* pq = pin(gs->QP[par] + (hI * 4 * 256 + tid) * 2);
    uint32_t* const qxo = pin(gs->QX[par] + (g * 32 + hI) * 256 + 64 * jI + 8 * w + 2 * t);
    uint2 v[4];
    float d[4] = {0.f, 0.f, 0.f, 0.f};
    wait_clk(tstore, T.D_QP);
    CLK(8);
    load_units<4, 512>(v, pq);
    const uint32_t kbase = sb + OFF_WUK + (16 * w + (lane & 15)) * 128;
    auto load_half = [&](int hf) {
#pragma unroll
      for (int ks = 0; ks < 4; ks++) ldsm4(aw[4 * hf + ks], kbase + hf * 16384 + (((2 * ks + (lane >> 4)) ^ (lane & 7)) << 4));
    };
    mbar_wait(BAR(BAR_WUK));
    load_half(0);
    const bool early = __all_sync(~0u, mbar_test(BAR(BAR_WUK + 1)));
    if (early) load_half(1);
    const int it = check_units<4, 512>(v, pq);
    CLK(9);
    ITS(1, it);
    sum4_to_smem(v, sb + OFF_BS2 + (16 * w + g) * 16 + t * 4);
    if (!early) { mbar_wait(BAR(BAR_WUK + 1)); load_half(1); }
    CLK(10);
    cbar();
    uint32_t b[4][4];
#pragma unroll
    for (int kk = 0; kk < 4; kk++) ldsm4t(b[kk], sb + OFF_BS2 + (32 * kk + lane) * 16);
    mma128(d, aw, b);
    const float sc = 0.08838834764831845f * 1.4426950408889634f;
    stg_u64(qxo, movm(pack_bf16(d[0] * sc, d[1] * sc)), movm(pack_bf16(d[2] * sc, d[3] * sc)));
    tstore = clk32();
    CLK(11);
    if (lane == 0) mbar_arrive(BAR(BAR_P2D));
  }
  if (wg && jI != 3) {
    const int mi = lane >> 3, r = lane & 7;
    const uint32_t a0 = sb + OFF_WM2 + (8 * (r >> 1) + (r & 1) + 2 * (mi >> 1)) * 32 + (mi & 1) * 16;
    mbar_wait(BAR(BAR_WM2));
#pragma unroll
    for (int s = 0; s < 8; s++) ldsm4t(aw[s], a0 + (128 * wq + 32 * (s >> 1) + 4 * (s & 1)) * 32);
    float d[4] = {0.f, 0.f, 0.f, 0.f};
    mma128(d, aw, cf);
    sts4f(sb + OFF_P0B + (tid - 128) * 16, d[0], d[1], d[2], d[3]);
    if (lane == 0) mbar_arrive(BAR(BAR_P0BD));
    bar_sync(3, 128);
    if (w == 4) {
      float4 v[4];
#pragma unroll
      for (int i = 0; i < 4; i++) v[i] = ldsf4(sb + OFF_P0B + (i * 32 + lane) * 16);
      stg_u64(gs->MOD2[par] + (3 * hI + jI) * 64 + t * 16 + g * 2, movm(pack_bf16((v[0].x + v[1].x) + (v[2].x + v[3].x), (v[0].y + v[1].y) + (v[2].y + v[3].y))),
              movm(pack_bf16((v[0].z + v[1].z) + (v[2].z + v[3].z), (v[0].w + v[1].w) + (v[2].w + v[3].w))));
    }
    CLK(15);
  }
  {
    const uint32_t* qx = pin(gs->QX[par] + ((bs >> 3) * 32 + 16 * hh) * 256 + tid * 4);
    const int ch = tid & 63, h0 = tid >> 6;
    const uint32_t dst = sb + OFF_Q + (ch >> 3) * 2048 + h0 * 128;
    wait_clk(tstore, T.D_QX);
    CLK(12);
    uint4 v[4];
#pragma unroll
    for (int i = 0; i < 4; i++) v[i] = ldg_2u64(qx + i * 1024);
    int it = 0;
    while (true) {
      uint32_t mn = 0xffffffffu;
#pragma unroll
      for (int i = 0; i < 4; i++) mn = min(mn, min(v[i].y, v[i].w));
      if (__all_sync(~0u, mn != 0)) break;
#pragma unroll
      for (int i = 0; i < 4; i++)
        asm volatile("{\n.reg .pred q;\nsetp.eq.u32 q, %5, 0;\n@q ld.relaxed.gpu.global.v4.b32 {%0, %1, %2, %3}, [%4];\n}"
                     : "+r"(v[i].x), "+r"(v[i].y), "+r"(v[i].z), "+r"(v[i].w) : "l"(qx + i * 1024), "r"(min(v[i].y, v[i].w)) : "memory");
      if (++it > SPIN_LIMIT) __trap();
    }
    CLK(13);
    ITS(2, it);
#pragma unroll
    for (int i = 0; i < 4; i++) sts4(dst + i * 512 + (((ch & 7) ^ ((4 * i + h0) & 7)) << 4), v[i]);
    asm volatile("fence.proxy.async.shared::cta;" ::: "memory");
    CLK(14);
    cbar();
  }

  uint2 cbf[4], sbf[4];
  const uint32_t* const pcb = gs->MOD2[par] + 2048 + (16 * w + t) * 16 + g * 2;
  auto load_frags = [&] {
    if (cta < NFF) { load_units<4, 64>(sbf, pcb); load_units<4, 64>(cbf, pcb + 2048); }
    else {
#pragma unroll
      for (int s = 0; s < 4; s++) { cbf[s].x = ldg_nc1(gc + g * 1024 + w * 128 + s * 32 + t * 4); cbf[s].y = ldg_nc1(gc + g * 1024 + w * 128 + s * 32 + 16 + t * 4); }
    }
  };
  uint32_t thand, anchor;
  const uint32_t opaque0 = w >> 4;
  if (wg == 0) {
    float mh[4];
    float L[8];
#pragma unroll
    for (int i = 0; i < 4; i++) { L[2 * i] = L[2 * i + 1] = 0.f; mh[i] = -INFINITY; }
    constexpr uint32_t dq = desc_lo(OFF_Q);
    const uint32_t ptw = sb + OFF_PT + (8 * (lane >> 4) + (lane & 7)) * 128 + (((2 * wq + ((lane >> 3) & 1)) ^ (lane & 7)) << 4);
    float S[8];
    auto softmax = [&](int tl) {
      auto write_p = [&](const float (&x)[8]) {
        float p[8];
#pragma unroll
        for (int i = 0; i < 8; i++) p[i] = ex2(x[i]);
        stsm4t(ptw + (tl & 1) * 2048, pack_bf16(p[0], p[1]), pack_bf16(p[2], p[3]), pack_bf16(p[4], p[5]), pack_bf16(p[6], p[7]));
        asm volatile("fence.proxy.async.shared::cta;" ::: "memory");
      };
      float x[8];
#pragma unroll
      for (int i = 0; i < 8; i++) x[i] = S[i] - mh[2 * (i >> 2) + (i & 1)];
      if (tl) write_p(x);
      const float ex = fmaxf(fmaxf(fmaxf(x[0], x[1]), fmaxf(x[2], x[3])), fmaxf(fmaxf(x[4], x[5]), fmaxf(x[6], x[7])));
      if (tl == 0 || bar_over(ex)) {
        float mx[4];
#pragma unroll
        for (int i = 0; i < 4; i++) mx[i] = fmaxf(S[4 * (i >> 1) + (i & 1)], S[4 * (i >> 1) + 2 + (i & 1)]);
        const float a = reduce_g(mx, lane, [](float u, float v) { return fmaxf(u, v); });
        stsf(sb + OFF_RED + wq * 64 + (8 * (lane >> 4) + 2 * t + ((lane >> 3) & 1)) * 4, a);
        bar_sync(2, 128);
#pragma unroll
        for (int jn = 0; jn < 2; jn++) {
          float m0 = mh[2 * jn], m1 = mh[2 * jn + 1];
#pragma unroll
          for (int i = 0; i < 4; i++) { const float2 v = ldsf2(sb + OFF_RED + i * 64 + (8 * jn + 2 * t) * 4); m0 = fmaxf(m0, v.x); m1 = fmaxf(m1, v.y); }
          const float a0 = ex2(mh[2 * jn] - m0), a1 = ex2(mh[2 * jn + 1] - m1);
          mh[2 * jn] = m0; mh[2 * jn + 1] = m1;
          L[4 * jn] *= a0; L[4 * jn + 1] *= a1; L[4 * jn + 2] *= a0; L[4 * jn + 3] *= a1;
          if (tid < 4) sts2f(sb + OFF_ALPHA + (8 * jn + 2 * t) * 4, a0, a1);
        }
        asm volatile("barrier.cta.arrive.aligned 1, 256;" ::: "memory");
#pragma unroll
        for (int i = 0; i < 8; i++) x[i] = S[i] - mh[2 * (i >> 2) + (i & 1)];
        write_p(x);
        bar_over(0.f);
      }
      const uint32_t dpt = __shfl_sync(~0u, desc_lo(OFF_PT) + (tl & 1) * 128, 0);
      wg_fence();
#pragma unroll
      for (int ks = 0; ks < 4; ks++) wgmma_n16_ones(L, ONE2, dpt + ks * 2);
      wg_commit();
    };
    uint32_t da = desc_lo(OFF_RING);
#pragma unroll 1
    for (int tl = 0; tl < 7; tl++) {
      if (tl == 5) { load_frags(); }
      uint32_t ok = 0;
#pragma unroll
      for (int u = 0; u < 4; u++) ok += mbar_test(BAR(BAR_FULL + 4 * tl + u));
      ok = __reduce_min_sync(~0u, ok);
      const uint32_t du = __shfl_sync(~0u, da, 0);
#pragma unroll
      for (int u = 0; u < 4; u++) {
        if (ok != 4) mbar_wait(BAR(BAR_FULL + 4 * tl + u));
        wg_fence();
#pragma unroll
        for (int k = 0; k < 8; k++) {
          const int i = 8 * u + k;
          if (i == 0) wgmma_n16<0, 0>(S, du, dq); else wgmma_n16<0, 1>(S, du + (i >> 2) * 512 + (i & 3) * 2, dq + (i >> 2) * 128 + (i & 3) * 2);
        }
        wg_commit();
      }
      wg_wait<0>();
      acc_fence(S); acc_fence(L);
      if (tl == 0) CLK(15);
      if (tl == 1) CLK(17);
      softmax(tl);
      if (tl == 0) CLK(16);
      if (tl == 1) CLK(18);
      if (tl == 3) CLK(19);
      if (tl == 6) CLK(20);
      da = (tl == 2 || tl == 5) ? da - 8192 : da + 4096;
    }
    mbar_wait(BAR(BAR_ALLCLR));
    uint32_t* const mlo = pin(gin + blk(4 * (16 * hh + 4 * (g & 2) + 2 * t + (g & 1)) + 1, 6, g >> 2) + bs * 2);
#pragma unroll
    for (int i = 0; i < 32; i++) {
      if (i == 0 || i == 8 || i == 16 || i == 24 || i == 28) {
        if (i) wg_commit();
        mbar_wait(BAR(BAR_LAST + (i == 28 ? 4 : i >> 3)));
        if (i == 28) CLK(21);
        wg_fence();
      }
      if (i == 0) wgmma_n16<0, 0>(S, desc_lo(65536), dq); else wgmma_n16<0, 1>(S, desc_lo(65536) + (i >> 2) * 512 + (i & 3) * 2, dq + (i >> 2) * 128 + (i & 3) * 2);
    }
    wg_commit();
    wg_wait<0>();
    acc_fence(S); acc_fence(L);
    CLK(22);
    softmax(7);
    CLK(23);
    thand = clk32();
    wg_wait<0>();
    acc_fence(L);
    if (tid < 32) red_u64(mlo, __float_as_uint(g & 2 ? (g & 1 ? mh[3] : mh[2]) : (g & 1 ? mh[1] : mh[0])), __float_as_uint(g & 2 ? (g & 1 ? L[5] : L[4]) : (g & 1 ? L[1] : L[0])));
    CLK(24);
  } else {
    float O[8][8];
#pragma unroll
    for (int i = 0; i < 8; i++)
#pragma unroll
      for (int k = 0; k < 8; k++) O[i][k] = 0.f;
    constexpr uint32_t dp = desc_lo(OFF_PT);
    auto handover = [&](int tl) {
      uint32_t over = opaque0 + (tl == 0);
#pragma unroll 1
      do {
        if (over) {
          cbar();
#pragma unroll
          for (int jn = 0; jn < 2; jn++) {
            const float2 a = ldsf2(sb + OFF_ALPHA + (8 * jn + 2 * t) * 4);
#pragma unroll
            for (int mb = 0; mb < 8; mb++) { O[mb][4 * jn] *= a.x; O[mb][4 * jn + 1] *= a.y; O[mb][4 * jn + 2] *= a.x; O[mb][4 * jn + 3] *= a.y; }
          }
        }
        over++;
      } while (bar_over(0.f));
    };
    uint32_t da = desc_lo(OFF_RING);
    uint32_t* x1o[8] = {};
#pragma unroll 1
    for (int tl = 0; tl < 8; tl++) {
      if (tl == 5) load_frags();
      if (tl == 7) {
        mbar_wait(BAR(BAR_ALLCLR));
#pragma unroll
        for (int i = 0; i < 8; i++)
          x1o[i] = inbox((16 * hh + 8 * ((i >> 1) & 1) + 2 * t + (i & 1)) * 4 + 2 * (i >> 2) + (wq >> 1), bs >> 4) + (bs & 15) * 64 + ((wq & 1) * 8 + g) * 4;
      }
      handover(tl);
      CLK(23);
      thand = clk32();
      const uint32_t dpt = dp + (tl & 1) * 128;
      wg_fence();
#pragma unroll
      for (int i = 0; i < 32; i++) wgmma_n16<1, 1>(O[i >> 2], da + (i >> 2) * 512 + (i & 3) * 128, dpt + (i & 3) * 2);
      wg_commit();
      da = (tl == 2 || tl == 5) ? da - 8192 : da + 4096;
      wg_wait<0>();
#pragma unroll
      for (int mb = 0; mb < 8; mb++) acc_fence(O[mb]);
      if (lane == 0) mbar_arrive(BAR(BAR_EMPTY + tl));
      if (tl == 0) CLK(16);
      if (tl == 1) CLK(18);
      if (tl == 3) CLK(19);
      if (tl == 6) CLK(20);
    }
    CLK(22);
#pragma unroll
    for (int i = 0; i < 8; i++) {
      const int J = i >> 2, k = 4 * ((i >> 1) & 1) + (i & 1);
      stg_cvt8(x1o[i], O[4 * J][k], O[4 * J][k + 2], O[4 * J + 1][k], O[4 * J + 1][k + 2], O[4 * J + 2][k], O[4 * J + 2][k + 2], O[4 * J + 3][k], O[4 * J + 3][k + 2]);
    }
    CLK(24);
  }

  uint32_t* const o = gin + keep((uint32_t)(inbox(4 * (8 * jI + w) + t, 4) - gin) + hI * 16 + g * 2);
  const uint32_t sdst5 = keep(sb + OFF_BS5 + (16 * w + g) * 16 + t * 4), lane16 = keep(sb + lane * 16);
  const uint32_t* x2i[4];
#pragma unroll
  for (int i = 0; i < 4; i++) x2i[i] = gin + keep((uint32_t)(nearbox(4 * hI + i, 4) - gin) + 512 + tid * 2);
  {
    const uint32_t* px = pin(inbox(cta, w >> 1) + (w & 1) * 512 + lane * 2);
    uint32_t* const x2o = pin(inbox(cta, 4) + 512 + tid * 2);
    uint32_t* const x2p = pin(gin + blk(cta, 4, selector(cta) ^ 1) + 512 + tid * 2);
    const uint32_t q4 = lds1(sb + OFF_SEL + 4 * hI) ^ 0x00010100u;
    const uint32_t same = pin((uint32_t)(q4 == 0 || q4 == 0x01010101u));
    mbar_wait(BAR(BAR_TS));
    anchor = lds1(sb + OFF_TS);
    const uint32_t sdst = keep(sb + OFF_BS4 + w * 272 + lane * 8), ssrc = keep(sb + OFF_BS4 + (lane & 7) * 272 + (lane >> 3) * 16);
    float d[4] = {0.f, 0.f, 0.f, 0.f};
    if (cta >= NFF) {
#pragma unroll
      for (int s = 0; s < 4; s++) { cbf[s].x = silu2(cbf[s].x); cbf[s].y = silu2(cbf[s].y); }
    }
    wait_clk(thand, T.D_X1);
    wait_clk(anchor, T.A_X1 - T.R_X0);
    uint2 v[8];
    load_units<8, 64>(v, px);
    if (T.R_X0) {
      wait_clk(anchor, T.A_X1);
#pragma unroll
      for (int i = 0; i < 8; i++) reload_unit(v[i], px + i * 64);
    }
    CLK(25);
    const bool early = __all_sync(~0u, mbar_test(BAR(BAR_WUV + wg)));
    if (early) load_a_t(aw, abase + OFF_WUV);
    mbar_wait(BAR(BAR_WV));
    const float4 wa = ldsf4(sb + OFF_WV + w * 32), wb = ldsf4(sb + OFF_WV + w * 32 + 16);
    const float wv[8] = {wa.x, wa.y, wa.z, wa.w, wb.x, wb.y, wb.z, wb.w};
    CLK(27);
    uint32_t it = opaque0;
    bool ok;
#pragma unroll 1
    do {
      if (it) {
#pragma unroll
        for (int i = 0; i < 8; i++) reload_unit(v[i], px + i * 64);
        if (it > SPIN_LIMIT) __trap();
      }
      it++;
      float a0 = 0.f, a1 = 0.f, a2 = 0.f, a3 = 0.f;
#pragma unroll
      for (int i = 0; i < 8; i++) { a0 += wv[i] * bf_lo(v[i].x); a1 += wv[i] * bf_hi(v[i].x); a2 += wv[i] * bf_lo(v[i].y); a3 += wv[i] * bf_hi(v[i].y); }
      ok = __all_sync(~0u, min_flags(v) != 0);
      sts2(sdst, pack_bf16(a0, a1), pack_bf16(a2, a3));
    } while (!ok);
    CLK(29);
    cbar();
    uint32_t b[4][4];
#pragma unroll
    for (int kk = 0; kk < 4; kk++) ldsm4(b[kk], ssrc + kk * 64);
    if (__builtin_expect(!early, 0)) { mbar_wait(BAR(BAR_WUV + wg)); load_a_t(aw, abase + OFF_WUV); }
    mma128(d, aw, b);
    const uint32_t c0 = pack_bf16(d[0], d[1]), c1 = pack_bf16(d[2], d[3]);
    stg_u64(x2o, c0, c1);
    stg_u64_unless(same, x2p, c0, c1);
    ITS(4, it - 1);
    tstore = clk32();
    CLK(30);
  }
  {
    float d[4] = {0.f, 0.f, 0.f, 0.f};
    wait_clk(tstore, T.D_X2);
    uint2 v[4];
#pragma unroll
    for (int i = 0; i < 4; i++) v[i] = ldg_u64(x2i[i]);
    const bool early = __all_sync(~0u, mbar_test(BAR(BAR_WO + wg)));
    if (early) load_a_t(aw, abase + OFF_WO);
    CLK(31);
    uint32_t it = opaque0;
    bool ok;
#pragma unroll 1
    do {
      if (it) {
#pragma unroll
        for (int i = 0; i < 4; i++) reload_unit(v[i], x2i[i]);
        if (it > SPIN_LIMIT) __trap();
      }
      it++;
      ok = __all_sync(~0u, min_flags(v) != 0);
      sum4_to_smem(v, sdst5);
    } while (!ok);
    CLK(32);
    cbar();
    uint32_t b[4][4];
#pragma unroll
    for (int kk = 0; kk < 4; kk++) ldsm4t(b[kk], lane16 + OFF_BS5 + kk * 512);
    if (__builtin_expect(!early, 0)) { mbar_wait(BAR(BAR_WO + wg)); load_a_t(aw, abase + OFF_WO); }
    mma128(d, aw, b);
    stg_u64(o, movm(pack_bf16(d[0], d[1])), movm(pack_bf16(d[2], d[3])));
    ITS(5, it - 1);
    tstore = clk32();
    CLK(33);
    if (lane == 0) mbar_arrive(BAR(BAR_P5D));
  }
  if (cta < NFF) {
    const int mi = lane >> 3, r = lane & 7;
    uint32_t a1[2][4][4], a2[2][2][4];
    check_units<4, 64>(sbf, pcb);
    check_units<4, 64>(cbf, pcb + 2048);
    __syncwarp();
#pragma unroll
    for (int s = 0; s < 4; s++) { cbf[s].x = hadd2(cbf[s].x, ONE2); cbf[s].y = hadd2(cbf[s].y, ONE2); }
    mbar_wait(BAR(BAR_W1));
#pragma unroll
    for (int mt = 0; mt < 2; mt++) {
#pragma unroll
      for (int ks = 0; ks < 4; ks++) ldsm4t(a1[mt][ks], sb + OFF_W1 + (64 * w + 16 * ks + 8 * (mi >> 1) + r) * 64 + (((2 * mt + (mi & 1)) ^ (r >> 1)) << 4));
      float u[4] = {0.f, 0.f, 0.f, 0.f}, vv[4] = {0.f, 0.f, 0.f, 0.f};
#pragma unroll
      for (int s = 0; s < 4; s++) { mma16816(u, a1[mt][s], cbf[s].x, cbf[s].y); mma16816(vv, a1[mt][s], sbf[s].x, sbf[s].y); }
      sts4f(sb + OFF_REDU + w * 1024 + mt * 512 + lane * 16, u[0], u[1], u[2], u[3]);
      sts4f(sb + OFF_REDV + w * 1024 + mt * 512 + lane * 16, vv[0], vv[1], vv[2], vv[3]);
    }
    const uint32_t* xb = pin(nearbox(cta & ~15, 6 + wg) + (16 * wq + t) * 16 + g * 2);
    uint32_t* const ox[2] = {pin(inbox(64 * hh + 8 * w + t, 5) + bs * 16 + g * 2), pin(inbox(64 * hh + 8 * w + 4 + t, 5) + bs * 16 + g * 2)};
    cbar();
    const int lp = (tid >> 2) & 31, kq = tid & 3;
    const int fo = 16 * wg + (lp >> 2) + 8 * (kq >> 1), bo = 2 * (lp & 3) + (kq & 1);
    float U = 0.f, V = 0.f;
#pragma unroll
    for (int i = 0; i < 8; i++) { U += ldsf(sb + OFF_REDU + i * 1024 + tid * 4); V += ldsf(sb + OFF_REDV + i * 1024 + tid * 4); }
    U = pin(U); V = pin(V);
    const uint32_t a2base = keep(sb + OFF_W2 + (w >> 1) * 4096 + (8 * (mi >> 1) + r) * 128 + (((4 * (w & 1) + (mi & 1)) ^ r) << 4));
    const uint32_t s_g = keep(sb + OFF_REDG + w * 1024 + lane * 16), l_g = keep(sb + OFF_REDG + tid * 4);
    const uint32_t s_s = keep(sb + (t == (g >> 1) ? OFF_REDS + g * 80 + w * 8 : OFF_BS4 + tid * 8));
    const uint32_t l_s = keep(sb + OFF_REDS + bo * 80), s_h = keep(sb + OFF_H1 + fo * 16 + bo * 2);
    CLK(34);
    wait_clk(tstore, T.D_X3B);
    wait_clk(anchor, T.A_X1 + T.R_X3A + T.R_X3B);
    uint2 x[4];
    load_units<4, 64>(x, xb);
    auto load_a2 = [&] {
#pragma unroll
      for (int i = 0; i < 4; i++) ldsm4t(a2[i >> 1][i & 1], (a2base ^ ((i >> 1) << 5)) + (i & 1) * 2048);
    };
    const bool early = __all_sync(~0u, mbar_test(BAR(BAR_W2)));
    if (early) load_a2();
    CLK(35);
    uint32_t it = opaque0;
    float G[2][2][4], S[2][4];
#pragma unroll 1
    do {
      if (it) {
#pragma unroll
        for (int i = 0; i < 4; i++) reload_unit(x[i], xb + i * 64);
        if (it > SPIN_LIMIT) __trap();
      }
      it++;
#pragma unroll
      for (int i = 0; i < 8; i++) { G[0][i >> 2][i & 3] = G[1][i >> 2][i & 3] = S[i >> 2][i & 3] = 0.f; }
      uint32_t y[4][2];
#pragma unroll
      for (int s = 0; s < 4; s++) { y[s][0] = hmul2(x[s].x, cbf[s].x); y[s][1] = hmul2(x[s].y, cbf[s].y); }
#pragma unroll
      for (int s2 = 0; s2 < 4; s2 += 2) {
#pragma unroll
        for (int s = s2; s < s2 + 2; s++) { mma16816(G[0][s & 1], a1[0][s], y[s][0], y[s][1]); mma16816(G[1][s & 1], a1[1][s], y[s][0], y[s][1]); }
#pragma unroll
        for (int s = s2; s < s2 + 2; s++) { const uint32_t sx[4] = {x[s].x, ONE2, x[s].y, ONE2}; mma16816(S[s & 1], sx, x[s].x, x[s].y); }
      }
    } while (!__all_sync(~0u, min_flags(x) != 0));
#pragma unroll
    for (int mt = 0; mt < 2; mt++)
      sts4f(s_g + mt * 512, G[mt][0][0] + G[mt][1][0], G[mt][0][1] + G[mt][1][1], G[mt][0][2] + G[mt][1][2], G[mt][0][3] + G[mt][1][3]);
    sts2f(s_s, (g & 1) ? S[0][3] + S[1][3] : S[0][2] + S[1][2], (g & 1) ? S[0][1] + S[1][1] : S[0][0] + S[1][0]);
    CLK(37);
    cbar();
    {
      float gv[8];
      float4 sv[4];
#pragma unroll
      for (int i = 0; i < 4; i++) sv[i] = ldsf4(l_s + i * 16);
#pragma unroll
      for (int i = 0; i < 8; i++) gv[i] = ldsf(l_g + i * 1024);
      const float s1 = ((sv[0].x + sv[0].z) + (sv[1].x + sv[1].z)) + ((sv[2].x + sv[2].z) + (sv[3].x + sv[3].z));
      const float s2 = ((sv[0].y + sv[0].w) + (sv[1].y + sv[1].w)) + ((sv[2].y + sv[2].w) + (sv[3].y + sv[3].w));
      const float gsum = ((gv[0] + gv[1]) + (gv[2] + gv[3])) + ((gv[4] + gv[5]) + (gv[6] + gv[7]));
      const float mu = s1 * (1.f / 512.f);
      float rs;
      asm("rsqrt.approx.ftz.f32 %0, %1;" : "=f"(rs) : "f"(fmaxf(s2 * (1.f / 512.f) - mu * mu, 0.f) + 1e-5f));
      const float hv = fmaxf(rs * (gsum - mu * U) + V, 0.f);
      asm volatile("st.shared.u16 [%0], %1;" ::"r"(s_h), "h"(__bfloat16_as_ushort(__float2bfloat16(hv))) : "memory");
    }
    ITS(6, it - 1);
    CLK(38);
    cbar();
    uint32_t b[4];
    ldsm4t(b, lane16 + OFF_H1);
    if (!early) { mbar_wait(BAR(BAR_W2)); load_a2(); }
    float o[2][2][4] = {};
#pragma unroll
    for (int i = 0; i < 4; i++) mma16816(o[i >> 1][i & 1], a2[i >> 1][i & 1], b[2 * (i & 1)], b[2 * (i & 1) + 1]);
#pragma unroll
    for (int mb = 0; mb < 2; mb++)
      stg_u64(ox[mb], movm(pack_bf16(o[mb][0][0] + o[mb][1][0], o[mb][0][1] + o[mb][1][1])), movm(pack_bf16(o[mb][0][2] + o[mb][1][2], o[mb][0][3] + o[mb][1][3])));
    CLK(39);
    if (lane == 0) mbar_arrive(BAR(BAR_P7D));
  } else {
    const int mi = lane >> 3, r = lane & 7;
    mbar_wait(BAR(BAR_W1));
#pragma unroll
    for (int mt = 0; mt < 2; mt++) {
      float u[4] = {0.f, 0.f, 0.f, 0.f};
#pragma unroll
      for (int ks = 0; ks < 4; ks++) ldsm4t(aw[4 * mt + ks], sb + OFF_W1 + (64 * w + 16 * ks + 8 * (mi >> 1) + r) * 64 + (((2 * mt + (mi & 1)) ^ (r >> 1)) << 4));
#pragma unroll
      for (int ks = 0; ks < 4; ks++) mma16816(u, aw[4 * mt + ks], cbf[ks].x, cbf[ks].y);
      sts4f(sb + OFF_REDU + w * 1024 + mt * 512 + lane * 16, u[0], u[1], u[2], u[3]);
    }
    cbar();
    if (w < 2) {
      float4 v[8];
#pragma unroll
      for (int i = 0; i < 8; i++) v[i] = ldsf4(sb + OFF_REDU + i * 1024 + tid * 16);
      stg_u64(gs->MOD2[par] + (96 + 2 * (cta - NFF) + w) * 64 + t * 16 + g * 2,
              movm(pack_bf16(((v[0].x + v[1].x) + (v[2].x + v[3].x)) + ((v[4].x + v[5].x) + (v[6].x + v[7].x)), ((v[0].y + v[1].y) + (v[2].y + v[3].y)) + ((v[4].y + v[5].y) + (v[6].y + v[7].y)))),
              movm(pack_bf16(((v[0].z + v[1].z) + (v[2].z + v[3].z)) + ((v[4].z + v[5].z) + (v[6].z + v[7].z)), ((v[0].w + v[1].w) + (v[2].w + v[3].w)) + ((v[4].w + v[5].w) + (v[6].w + v[7].w)))));
    }
    CLK(26);
  }
  CLK_DUMP();
}

typedef CUresult (*EncodeTiledFn)(CUtensorMap*, CUtensorMapDataType, cuuint32_t, void*, const cuuint64_t*, const cuuint64_t*,
                                  const cuuint32_t*, const cuuint32_t*, CUtensorMapInterleave, CUtensorMapSwizzle,
                                  CUtensorMapL2promotion, CUtensorMapFloatOOBfill);

struct Dim { uint64_t size, stride; uint32_t box; };
template <int R> void encode_map(EncodeTiledFn enc, CUtensorMap* m, const void* base, const Dim (&d)[R], CUtensorMapSwizzle sw, CUtensorMapL2promotion promo) {
  cuuint64_t dims[R], strides[R];
  cuuint32_t box[R], es[R];
  for (int i = 0; i < R; i++) { dims[i] = d[i].size; strides[i] = d[i].stride; box[i] = d[i].box; es[i] = 1; }
  enc(m, CU_TENSOR_MAP_DATA_TYPE_BFLOAT16, R, const_cast<void*>(base), dims, strides + 1, box, es, CU_TENSOR_MAP_INTERLEAVE_NONE, sw, promo,
      CU_TENSOR_MAP_FLOAT_OOB_FILL_NONE);
}

}

extern "C" void kernel_launch(void* const* d_in, const int* in_sizes, int n_in, void* d_out, int out_size) {
  (void)in_sizes; (void)n_in; (void)out_size;
  static EncodeTiledFn enc = nullptr;
  static Scratch* scratch = nullptr;
  static uint32_t* inbox = nullptr;
  if (!enc) {
    void* sp = nullptr;
    cudaGetSymbolAddress(&sp, g_s);
    scratch = (Scratch*)sp;
    cudaGetSymbolAddress(&sp, g_in);
    inbox = (uint32_t*)(((uintptr_t)sp + 0xfffff) & ~(uintptr_t)0xfffff);
    void* fn = nullptr;
    cudaDriverEntryPointQueryResult q;
    cudaGetDriverEntryPoint("cuTensorMapEncodeTiled", &fn, cudaEnableDefault, &q);
    enc = (EncodeTiledFn)fn;
    cudaFuncSetAttribute(fused_decode_kernel, cudaFuncAttributeMaxDynamicSharedMemorySize, SMEM_BYTES);
  }
  const CUtensorMapSwizzle S128 = CU_TENSOR_MAP_SWIZZLE_128B, S0 = CU_TENSOR_MAP_SWIZZLE_NONE;
  const CUtensorMapL2promotion L0 = CU_TENSOR_MAP_L2_PROMOTION_NONE, L128 = CU_TENSOR_MAP_L2_PROMOTION_L2_128B;
  Params P;
  encode_map<2>(enc, &P.wq, d_in[2], {{4096, 2, 64}, {512, 8192, 64}}, S128, L0);
  encode_map<5>(enc, &P.wuk, d_in[3], {{4096, 2, 64}, {2, 8192, 2}, {4, 4 * 8192, 4}, {2, 2 * 8192, 2}, {32, 16 * 8192, 4}}, S128, L0);
  encode_map<2>(enc, &P.wm2, d_in[10], {{3072, 2, 16}, {512, 6144, 256}}, S0, L128);
  encode_map<2>(enc, &P.wm3, d_in[10], {{3072, 2, 32}, {512, 6144, 256}}, CU_TENSOR_MAP_SWIZZLE_64B, L128);
  encode_map<3>(enc, &P.ckv2, d_in[1], {{64, 2, 64}, {8 * 4096, 1024, 64}, {8, 128, 2}}, S128, L0);
  encode_map<3>(enc, &P.ckv1, d_in[1], {{64, 2, 64}, {8 * 4096, 1024, 64}, {8, 128, 1}}, S128, L0);
  encode_map<5>(enc, &P.wuv, d_in[4], {{4096, 2, 64}, {2, 8 * 8192, 2}, {8, 64 * 8192, 4}, {8, 8192, 8}, {4, 16 * 8192, 1}}, S128, L0);
  encode_map<2>(enc, &P.wo, d_in[5], {{512, 2, 64}, {4096, 1024, 64}}, S128, L0);
  encode_map<2>(enc, &P.w1, d_in[7], {{1792, 2, 32}, {512, 3584, 256}}, CU_TENSOR_MAP_SWIZZLE_64B, L128);
  encode_map<3>(enc, &P.w2, d_in[8], {{64, 2, 64}, {1792, 1024, 32}, {8, 128, 2}}, S128, L0);
  fused_decode_kernel<<<NCTA, NTHREADS, SMEM_BYTES>>>((__nv_bfloat16*)d_out, scratch, (const uint8_t*)d_in[10], (const uint8_t*)d_in[0],
                     (const uint8_t*)d_in[9], inbox,
                     P);
}
```

```cpp
#include <cuda_runtime.h>
#include <cuda.h>
#include <cuda_bf16.h>
#include <stdint.h>
#define V4 1

namespace {

constexpr int NCTA = 128;
constexpr int NTHREADS = 320;
constexpr int NFG = 56;
constexpr int NFF = 2 * NFG;
constexpr int NSYNC = 4;

constexpr uint32_t OFF_RING = 0;
constexpr uint32_t OFF_WUK = 131072;
constexpr uint32_t OFF_WQ = 131072 + 32768;
constexpr uint32_t OFF_WM2 = 65536 + 49152;
constexpr uint32_t OFF_WUV = 131072;
constexpr uint32_t OFF_WO = 131072 + 32768;
constexpr uint32_t OFF_W1 = 0;
constexpr uint32_t OFF_W2 = 32768;
constexpr uint32_t OFF_Q = 196608;
constexpr uint32_t OFF_PT = 212992;
constexpr uint32_t OFF_SCR = 217088;
constexpr uint32_t OFF_XS = 65536;
constexpr uint32_t OFF_CS = 65536 + 8192;
constexpr uint32_t OFF_P0S = 65536 + 16384;
constexpr uint32_t OFF_BS1 = OFF_SCR + 2048;
constexpr uint32_t OFF_BS2 = OFF_SCR + 4096;
constexpr uint32_t OFF_P0B = OFF_SCR + 6144;
constexpr uint32_t OFF_XN = OFF_SCR + 8192;
constexpr uint32_t OFF_RED = OFF_SCR + 10496;
constexpr uint32_t OFF_ALPHA = OFF_SCR + 11072;
constexpr uint32_t OFF_WV = OFF_SCR + 6144;
constexpr uint32_t OFF_SEL = OFF_SCR + 10752;
constexpr uint32_t OFF_TS = OFF_SCR + 11136;
constexpr uint32_t OFF_BARS = OFF_SCR + 11264;
constexpr uint32_t SMEM_BYTES = OFF_BARS + 512;
constexpr uint32_t OFF_BS4 = OFF_Q;
constexpr uint32_t OFF_H1 = OFF_Q + 2304;
constexpr uint32_t OFF_REDS = OFF_Q + 2816;
constexpr uint32_t OFF_BS5 = OFF_Q + 4096;
constexpr uint32_t OFF_REDG = OFF_Q + 8192;
constexpr uint32_t OFF_REDU = 65536;
constexpr uint32_t OFF_REDV = 65536 + 8192;

constexpr int BAR_FULL = 0;
constexpr int BAR_LAST = 28;
constexpr int BAR_WUK = 33, BAR_WM2 = 35, BAR_WUV = 36, BAR_WO = 38, BAR_W1 = 40, BAR_W2 = 41;
constexpr int BAR_ALLCLR = 42, BAR_TS = 43, BAR_WV = 44;
constexpr int BAR_EMPTY = 45;
constexpr int BAR_P0BD = 53;
constexpr int BAR_P1D = 54, BAR_P2D = 55;
constexpr int BAR_P5D = 56, BAR_P7D = 57;
constexpr int NBARS = 58;
constexpr int BAR_XC = 58, BAR_WQ = 59;
constexpr int BAR_C = 61;
constexpr uint32_t SB = 1024;

#define TUNE_LIST(X) \
  X(PC_T0, 355) X(PC_P1, 320) X(PC_PM, 225) X(PC_P2, 319) X(PC_STAG, 390) X(PC_SL, 500) X(PC_NW, 6) \
  X(T_UV, 225) X(P_UV, 250) X(PF_N, 3) X(T_PF, 1060) X(P_PF, 230) X(T_O, 2180) X(P_O, 145) X(T_1, 2990) X(T_2, 3860) X(T_GB, 3370) X(P_F, 360) \
  X(PR_T0, 1000) X(PR_N, 4) X(CLR_T0, 3900) X(CLR_CLK, 190) \
  X(D_MOD, 1450) X(D_QP, 1200) X(D_QX, 950) X(TS_P, 1) X(TS_O, 1945) X(D_TS, 700) X(A_M, 1450) X(D_X1, 1400) X(A_X1, 2460) X(R_X0, 1550) \
  X(D_X2, 275) X(D_X3A, 60) X(R_X3A, 2835) X(D_X3B, 800) X(R_X3B, 915) X(D_FIN, 320) X(R_FIN, 1540)
struct Tune {
#define X(n, v) static constexpr int n = v;
  TUNE_LIST(X)
#undef X
};

struct Scratch {
  uint32_t MOD1[2][4 * 64 * 64];
  uint32_t MOD2[2][128 * 64];
  uint32_t QP[2][128 * 256 * 2];
  uint32_t QX[2][8 * 32 * 256];
  uint32_t epoch;
  uint32_t pad[31];
  uint32_t sync[NSYNC][32];
};
__device__ Scratch g_s;
__device__ uint32_t g_in[(128 + 16) * 16384];
__device__ __forceinline__ uint32_t blk(int c, int k, uint32_t sel) { return c * 16384 + k * 2048 + ((sel ^ k) & 1) * 1024; }
__device__ __forceinline__ uint32_t flip(int c) { return c ^ (c >> 1) ^ (c >> 3); }

#define CLK_DECL
#define CLK(i) do {} while (0)
#define CLK_DUMP() do {} while (0)
#define ITS(i, v) do {} while (0)

struct Params {
  CUtensorMap wq, wuk, wm2, wm3, ckv2, ckv1, wuv, wo, w1, w2;
};

__device__ __forceinline__ void mbar_init(uint32_t bar, int cnt) { asm volatile("mbarrier.init.shared::cta.b64 [%0], %1;" ::"r"(bar), "r"(cnt)); }
__device__ __forceinline__ void mbar_expect(uint32_t bar, uint32_t bytes) { asm volatile("mbarrier.arrive.expect_tx.shared::cta.b64 _, [%0], %1;" ::"r"(bar), "r"(bytes) : "memory"); }
__device__ __forceinline__ void mbar_arrive(uint32_t bar) { asm volatile("mbarrier.arrive.shared::cta.b64 _, [%0];" ::"r"(bar) : "memory"); }
__device__ __forceinline__ uint32_t clk32() { unsigned long long c; asm volatile("mov.u64 %0, %%clock64;" : "=l"(c) :: "memory"); return (uint32_t)c; }
__device__ __forceinline__ uint32_t gtime32() { uint32_t c; asm volatile("mov.u32 %0, %%globaltimer_lo;" : "=r"(c) :: "memory"); return c; }
__device__ __forceinline__ void wait_clk(uint32_t t0, int clocks) { while ((int)(clk32() - t0) < clocks) {} }
__device__ __forceinline__ void backoff(int clocks) { if (clocks > 0) wait_clk(clk32(), clocks); }
__device__ __forceinline__ void until_ns(uint32_t ns) { while ((int)(gtime32() - ns) < 0) {} }
__device__ __forceinline__ void slot(uint32_t& tn, int slack) {
  uint32_t now;
  do { now = gtime32(); } while ((int)(now - tn) < 0);
  if ((int)(now - tn) > slack) tn = now - slack;
}
template <typename T> __device__ __forceinline__ T* pin(T* p) { asm volatile("" : "+l"(p)); return p; }
__device__ __forceinline__ uint32_t pin(uint32_t v) { asm volatile("" : "+r"(v)); return v; }
__device__ __forceinline__ float pin(float v) { asm volatile("" : "+f"(v)); return v; }
constexpr int SPIN_LIMIT = 1 << 22;
__device__ __forceinline__ void mbar_wait(uint32_t bar) {
  asm volatile("{\n.reg .pred p;\n.reg .u32 c;\nmov.u32 c, 0;\n"
               "MW_LOOP:\nmbarrier.try_wait.parity.shared::cta.b64 p, [%0], 0;\n@p bra MW_DONE;\n"
               "add.u32 c, c, 1;\nsetp.lt.u32 p, c, 4194304;\n@p bra MW_LOOP;\ntrap;\nMW_DONE:\n}"
               ::"r"(bar) : "memory");
}
__device__ __forceinline__ bool mbar_test(uint32_t bar) {
  uint32_t ok;
  asm volatile("{\n.reg .pred p;\nmbarrier.test_wait.parity.shared::cta.b64 p, [%1], 0;\nselp.u32 %0,1,0,p;\n}" : "=r"(ok) : "r"(bar) : "memory");
  return ok;
}
__device__ __forceinline__ void tma2d(uint32_t dst, const CUtensorMap* m, int c0, int c1, uint32_t bar, uint64_t pol) {
  asm volatile("cp.async.bulk.tensor.2d.shared::cluster.global.mbarrier::complete_tx::bytes.L2::cache_hint [%0], [%1, {%3,%4}], [%2], %5;"
               ::"r"(dst), "l"(m), "r"(bar), "r"(c0), "r"(c1), "l"(pol) : "memory");
}
__device__ __forceinline__ void tma2d_nohint(uint32_t dst, const CUtensorMap* m, int c0, int c1, uint32_t bar) {
  asm volatile("cp.async.bulk.tensor.2d.shared::cluster.global.mbarrier::complete_tx::bytes [%0], [%1, {%3,%4}], [%2];"
               ::"r"(dst), "l"(m), "r"(bar), "r"(c0), "r"(c1) : "memory");
}
__device__ __forceinline__ void tma3d(uint32_t dst, const CUtensorMap* m, int c0, int c1, int c2, uint32_t bar, uint64_t pol) {
  asm volatile("cp.async.bulk.tensor.3d.shared::cluster.global.mbarrier::complete_tx::bytes.L2::cache_hint [%0], [%1, {%3,%4,%5}], [%2], %6;"
               ::"r"(dst), "l"(m), "r"(bar), "r"(c0), "r"(c1), "r"(c2), "l"(pol) : "memory");
}
__device__ __forceinline__ void tma5d(uint32_t dst, const CUtensorMap* m, int c0, int c1, int c2, int c3, int c4, uint32_t bar, uint64_t pol) {
  asm volatile("cp.async.bulk.tensor.5d.shared::cluster.global.mbarrier::complete_tx::bytes.L2::cache_hint [%0], [%1, {%3,%4,%5,%6,%7}], [%2], %8;"
               ::"r"(dst), "l"(m), "r"(bar), "r"(c0), "r"(c1), "r"(c2), "r"(c3), "r"(c4), "l"(pol) : "memory");
}
__device__ __forceinline__ void bulk_ld(uint32_t dst, const void* src, uint32_t bytes, uint32_t bar) {
  asm volatile("cp.async.bulk.shared::cluster.global.mbarrier::complete_tx::bytes [%0], [%1], %2, [%3];" ::"r"(dst), "l"(src), "r"(bytes), "r"(bar) : "memory");
}
__device__ __forceinline__ void bar_sync(int id, int n) { asm volatile("barrier.cta.sync.aligned %0, %1;" ::"r"(id), "r"(n) : "memory"); }
__device__ __forceinline__ void cbar() { asm volatile("barrier.cta.sync.aligned 1, 256;" ::: "memory"); }
__device__ __forceinline__ bool bar_over(float ex) {
  uint32_t over;
  asm volatile("{\n.reg .pred p, q;\nsetp.gtu.f32 p, %1, 0f42700000;\nbarrier.cta.red.or.aligned.pred q, 4, 256, p;\nselp.u32 %0, 1, 0, q;\n}"
               : "=r"(over) : "f"(ex) : "memory");
  return over;
}

__device__ __forceinline__ uint32_t ldg_nc1(const void* p) { uint32_t v; asm volatile("ld.global.nc.L1::no_allocate.u32 %0, [%1];" : "=r"(v) : "l"(p)); return v; }
__device__ __forceinline__ uint2 ldg_nc2(const void* p) { uint2 v; asm volatile("ld.global.nc.v2.u32 {%0,%1}, [%2];" : "=r"(v.x), "=r"(v.y) : "l"(p)); return v; }
__device__ __forceinline__ uint4 ldg_nc4(const void* p) { uint4 v; asm volatile("ld.global.nc.L1::no_allocate.v4.u32 {%0,%1,%2,%3}, [%4];" : "=r"(v.x), "=r"(v.y), "=r"(v.z), "=r"(v.w) : "l"(p)); return v; }
__device__ __forceinline__ uint32_t ldg_rlx1(const void* p) { uint32_t v; asm volatile("ld.relaxed.gpu.global.u32 %0, [%1];" : "=r"(v) : "l"(p) : "memory"); return v; }
__device__ __forceinline__ void stg4(void* p, uint4 v) { asm volatile("st.relaxed.gpu.global.v4.u32 [%0], {%1,%2,%3,%4};" ::"l"(p), "r"(v.x), "r"(v.y), "r"(v.z), "r"(v.w) : "memory"); }
__device__ __forceinline__ void stg1(void* p, uint32_t a) { asm volatile("st.relaxed.gpu.global.u32 [%0], %1;" ::"l"(p), "r"(a) : "memory"); }
__device__ __forceinline__ uint32_t nz(uint32_t w) { return max(w, 1u); }
__device__ __forceinline__ uint2 ldg_u64(const void* p) {
  uint2 v; asm volatile("{\n.reg .b64 a;\nld.relaxed.gpu.global.b64 a, [%2];\nmov.b64 {%0,%1}, a;\n}" : "=r"(v.x), "=r"(v.y) : "l"(p) : "memory"); return v;
}
__device__ __forceinline__ uint4 ldg_2u64(const void* p) {
  uint4 v; asm volatile("{\n.reg .b64 a, b;\nld.relaxed.gpu.global.v2.b64 {a, b}, [%4];\nmov.b64 {%0,%1}, a;\nmov.b64 {%2,%3}, b;\n}" : "=r"(v.x), "=r"(v.y), "=r"(v.z), "=r"(v.w) : "l"(p) : "memory"); return v;
}
__device__ __forceinline__ void stg_u64(void* p, uint32_t x, uint32_t y) {
  asm volatile("{\n.reg .b32 y;\nmax.u32 y, %2, 1;\nst.relaxed.gpu.global.v2.b32 [%0], {%1, y};\n}" ::"l"(p), "r"(x), "r"(y) : "memory");
}
__device__ __forceinline__ void red_u64(void* p, uint32_t x, uint32_t y) {
  asm volatile("{\n.reg .b32 y;\n.reg .b64 a;\nmax.u32 y, %2, 1;\nmov.b64 a, {%1, y};\nred.relaxed.gpu.global.or.b64 [%0], a;\n}" ::"l"(p), "r"(x), "r"(y) : "memory");
}
__device__ __forceinline__ void stg_u64_unless(uint32_t bad, void* p, uint32_t x, uint32_t y) {
  asm volatile("{\n.reg .b32 y;\n.reg .pred q;\nsetp.eq.u32 q, %3, 0;\nmax.u32 y, %2, 1;\n@q st.relaxed.gpu.global.v2.b32 [%0], {%1, y};\n}" ::"l"(p), "r"(x), "r"(y), "r"(bad) : "memory");
}

__device__ __forceinline__ void stg_cvt8(void* p, float a0, float a1, float b0, float b1, float c0, float c1, float d0, float d1) {
  asm volatile("{\n.reg .b32 x, y, z, w;\ncvt.rn.bf16x2.f32 x, %2, %1;\ncvt.rn.bf16x2.f32 y, %4, %3;\ncvt.rn.bf16x2.f32 z, %6, %5;\ncvt.rn.bf16x2.f32 w, %8, %7;\n"
               "max.u32 y, y, 1;\nmax.u32 w, w, 1;\nst.relaxed.gpu.global.v4.b32 [%0], {x, y, z, w};\n}"
               ::"l"(p), "f"(a0), "f"(a1), "f"(b0), "f"(b1), "f"(c0), "f"(c1), "f"(d0), "f"(d1) : "memory");
}
__device__ __forceinline__ uint32_t pack_bf16(float lo, float hi) { uint32_t r; asm("cvt.rn.bf16x2.f32 %0, %1, %2;" : "=r"(r) : "f"(hi), "f"(lo)); return r; }
__device__ __forceinline__ float bf_lo(uint32_t w) { return __uint_as_float(w << 16); }
__device__ __forceinline__ float bf_hi(uint32_t w) { return __uint_as_float(w & 0xffff0000u); }
__device__ __forceinline__ float ex2(float x) { float r; asm("ex2.approx.ftz.f32 %0, %1;" : "=f"(r) : "f"(x)); return r; }
__device__ __forceinline__ uint32_t hmul2(uint32_t a, uint32_t b) { uint32_t r; asm("mul.rn.bf16x2 %0, %1, %2;" : "=r"(r) : "r"(a), "r"(b)); return r; }
__device__ __forceinline__ uint32_t hadd2(uint32_t a, uint32_t b) { uint32_t r; asm("add.rn.bf16x2 %0, %1, %2;" : "=r"(r) : "r"(a), "r"(b)); return r; }
__device__ __forceinline__ uint32_t silu2(uint32_t v) { const float a = bf_lo(v), b = bf_hi(v); return pack_bf16(__fdividef(a, 1.f + __expf(-a)), __fdividef(b, 1.f + __expf(-b))); }
constexpr uint32_t ONE2 = 0x3f803f80u;

__device__ __forceinline__ void ldsm4(uint32_t (&r)[4], uint32_t a) { asm volatile("ldmatrix.sync.aligned.m8n8.x4.shared.b16 {%0,%1,%2,%3}, [%4];" : "=r"(r[0]), "=r"(r[1]), "=r"(r[2]), "=r"(r[3]) : "r"(a) : "memory"); }
__device__ __forceinline__ void ldsm4t(uint32_t (&r)[4], uint32_t a) { asm volatile("ldmatrix.sync.aligned.m8n8.x4.trans.shared.b16 {%0,%1,%2,%3}, [%4];" : "=r"(r[0]), "=r"(r[1]), "=r"(r[2]), "=r"(r[3]) : "r"(a) : "memory"); }
__device__ __forceinline__ void stsm4t(uint32_t a, uint32_t r0, uint32_t r1, uint32_t r2, uint32_t r3) { asm volatile("stmatrix.sync.aligned.m8n8.x4.trans.shared.b16 [%0], {%1,%2,%3,%4};" ::"r"(a), "r"(r0), "r"(r1), "r"(r2), "r"(r3) : "memory"); }
__device__ __forceinline__ uint32_t movm(uint32_t a) { uint32_t d; asm volatile("movmatrix.sync.aligned.m8n8.trans.b16 %0, %1;" : "=r"(d) : "r"(a)); return d; }
__device__ __forceinline__ void mma16816(float (&d)[4], const uint32_t (&a)[4], uint32_t b0, uint32_t b1) {
  asm volatile("mma.sync.aligned.m16n8k16.row.col.f32.bf16.bf16.f32 {%0,%1,%2,%3}, {%4,%5,%6,%7}, {%8,%9}, {%0,%1,%2,%3};"
               : "+f"(d[0]), "+f"(d[1]), "+f"(d[2]), "+f"(d[3]) : "r"(a[0]), "r"(a[1]), "r"(a[2]), "r"(a[3]), "r"(b0), "r"(b1));
}
__device__ __forceinline__ void sts1(uint32_t a, uint32_t v) { asm volatile("st.shared.u32 [%0], %1;" ::"r"(a), "r"(v) : "memory"); }
__device__ __forceinline__ void sts2(uint32_t a, uint32_t x, uint32_t y) { asm volatile("st.shared.v2.u32 [%0], {%1,%2};" ::"r"(a), "r"(x), "r"(y) : "memory"); }
__device__ __forceinline__ void sts4(uint32_t a, uint4 v) { asm volatile("st.shared.v4.u32 [%0], {%1,%2,%3,%4};" ::"r"(a), "r"(v.x), "r"(v.y), "r"(v.z), "r"(v.w) : "memory"); }
__device__ __forceinline__ void sts2f(uint32_t a, float x, float y) { asm volatile("st.shared.v2.f32 [%0], {%1,%2};" ::"r"(a), "f"(x), "f"(y) : "memory"); }
__device__ __forceinline__ void sts4f(uint32_t a, float x, float y, float z, float w) { asm volatile("st.shared.v4.f32 [%0], {%1,%2,%3,%4};" ::"r"(a), "f"(x), "f"(y), "f"(z), "f"(w) : "memory"); }
__device__ __forceinline__ void stsf(uint32_t a, float v) { asm volatile("st.shared.f32 [%0], %1;" ::"r"(a), "f"(v) : "memory"); }
__device__ __forceinline__ uint32_t lds1(uint32_t a) { uint32_t v; asm volatile("ld.shared.u32 %0, [%1];" : "=r"(v) : "r"(a) : "memory"); return v; }
__device__ __forceinline__ float ldsf(uint32_t a) { float v; asm volatile("ld.shared.f32 %0, [%1];" : "=f"(v) : "r"(a) : "memory"); return v; }
__device__ __forceinline__ float2 ldsf2(uint32_t a) { float2 v; asm volatile("ld.shared.v2.f32 {%0,%1}, [%2];" : "=f"(v.x), "=f"(v.y) : "r"(a) : "memory"); return v; }
__device__ __forceinline__ float4 ldsf4(uint32_t a) { float4 v; asm volatile("ld.shared.v4.f32 {%0,%1,%2,%3}, [%4];" : "=f"(v.x), "=f"(v.y), "=f"(v.z), "=f"(v.w) : "r"(a) : "memory"); return v; }
__device__ __forceinline__ void lds4(uint32_t (&r)[4], uint32_t a) { asm volatile("ld.shared.v4.u32 {%0,%1,%2,%3}, [%4];" : "=r"(r[0]), "=r"(r[1]), "=r"(r[2]), "=r"(r[3]) : "r"(a) : "memory"); }

__device__ __forceinline__ void wg_fence() { asm volatile("wgmma.fence.sync.aligned;" ::: "memory"); }
__device__ __forceinline__ void wg_commit() { asm volatile("wgmma.commit_group.sync.aligned;" ::: "memory"); }
template <int N> __device__ __forceinline__ void wg_wait() { asm volatile("wgmma.wait_group.sync.aligned %0;" ::"n"(N) : "memory"); }
__host__ __device__ constexpr uint32_t desc_lo(uint32_t off) { return ((SB + off) >> 4) | 0x10000u; }
template <int TA, int ACC> __device__ __forceinline__ void wgmma_n16(float (&d)[8], uint32_t da, uint32_t db) {
  asm volatile("{\n.reg .b64 da, db;\nmov.b64 da, {%8, 0x40000040};\nmov.b64 db, {%9, 0x40000040};\n"
               "wgmma.mma_async.sync.aligned.m64n16k16.f32.bf16.bf16 {%0,%1,%2,%3,%4,%5,%6,%7}, da, db, %11, 1, 1, %10, 0;\n}"
               : "+f"(d[0]), "+f"(d[1]), "+f"(d[2]), "+f"(d[3]), "+f"(d[4]), "+f"(d[5]), "+f"(d[6]), "+f"(d[7])
               : "r"(da), "r"(db), "n"(TA), "n"(ACC));
}
__device__ __forceinline__ void wgmma_n16_ones(float (&d)[8], uint32_t one, uint32_t db) {
  asm volatile("{\n.reg .b64 db;\nmov.b64 db, {%9, 0x40000040};\n"
               "wgmma.mma_async.sync.aligned.m64n16k16.f32.bf16.bf16 {%0,%1,%2,%3,%4,%5,%6,%7}, {%8,%8,%8,%8}, db, 1, 1, 1, 0;\n}"
               : "+f"(d[0]), "+f"(d[1]), "+f"(d[2]), "+f"(d[3]), "+f"(d[4]), "+f"(d[5]), "+f"(d[6]), "+f"(d[7])
               : "r"(one), "r"(db));
}
__device__ __forceinline__ void acc_fence(float (&d)[8]) {
  asm volatile("" : "+f"(d[0]), "+f"(d[1]), "+f"(d[2]), "+f"(d[3]), "+f"(d[4]), "+f"(d[5]), "+f"(d[6]), "+f"(d[7]) :: "memory");
}

template <int N, int STRIDE> __device__ __forceinline__ void load_units(uint2 (&v)[N], const uint32_t* p) {
#pragma unroll
  for (int i = 0; i < N; i++) v[i] = ldg_u64(p + i * STRIDE);
}
__device__ __forceinline__ void reload_unit(uint2& v, const uint32_t* p) {
  asm volatile("{\n.reg .pred q;\nsetp.eq.u32 q, %1, 0;\n@q ld.relaxed.gpu.global.v2.b32 {%0, %1}, [%2];\n}" : "+r"(v.x), "+r"(v.y) : "l"(p) : "memory");
}
template <int N> __device__ __forceinline__ uint32_t min_flags(const uint2 (&v)[N]) {
  uint32_t a = v[0].y, b = v[1].y;
#pragma unroll
  for (int i = 2; i < N; i += 2) { a = min(a, v[i].y); b = min(b, v[i + 1].y); }
  return min(a, b);
}
template <int N, int STRIDE> __device__ __forceinline__ int check_units(uint2 (&v)[N], const uint32_t* p) {
  int it = 0;
  while (!__all_sync(~0u, min_flags(v) != 0)) {
#pragma unroll
    for (int i = 0; i < N; i++) reload_unit(v[i], p + i * STRIDE);
    if (++it > SPIN_LIMIT) __trap();
  }
  return it;
}
__device__ __forceinline__ void sum4_to_smem(const uint2 (&v)[4], uint32_t dst) {
  const float c0 = (bf_lo(v[0].x) + bf_lo(v[1].x)) + (bf_lo(v[2].x) + bf_lo(v[3].x));
  const float c1 = (bf_hi(v[0].x) + bf_hi(v[1].x)) + (bf_hi(v[2].x) + bf_hi(v[3].x));
  const float c2 = (bf_lo(v[0].y) + bf_lo(v[1].y)) + (bf_lo(v[2].y) + bf_lo(v[3].y));
  const float c3 = (bf_hi(v[0].y) + bf_hi(v[1].y)) + (bf_hi(v[2].y) + bf_hi(v[3].y));
  sts1(dst, pack_bf16(c0, c1));
  sts1(dst + 128, pack_bf16(c2, c3));
}
__device__ __forceinline__ uint32_t a_t_offset(int w, int lane) {
  const int mi = lane >> 3, r = lane & 7;
  return (w >> 2) * 16384 + (8 * (mi >> 1) + r) * 128 + (((2 * (w & 3) + (mi & 1)) ^ r) << 4);
}
__device__ __forceinline__ void load_a_t(uint32_t (&a)[8][4], uint32_t base) {
#pragma unroll
  for (int ks = 0; ks < 8; ks++) ldsm4t(a[ks], base + ks * 2048);
}
__device__ __forceinline__ void mma128(float (&d)[4], const uint32_t (&a)[8][4], const uint32_t (&b)[4][4]) {
  float e[4][4] = {{d[0], d[1], d[2], d[3]}, {0.f, 0.f, 0.f, 0.f}, {0.f, 0.f, 0.f, 0.f}, {0.f, 0.f, 0.f, 0.f}};
#pragma unroll
  for (int kk = 0; kk < 4; kk++) { mma16816(e[(2 * kk) & 3], a[2 * kk], b[kk][0], b[kk][1]); mma16816(e[(2 * kk + 1) & 3], a[2 * kk + 1], b[kk][2], b[kk][3]); }
#pragma unroll
  for (int i = 0; i < 4; i++) d[i] = (e[0][i] + e[1][i]) + (e[2][i] + e[3][i]);
}
template <int NP> __device__ __forceinline__ bool sum_pieces(const uint32_t* p0, uint32_t one, float (&r)[4]) {
  uint2 v[NP / 4];
  load_units<NP / 4, 64>(v, p0);
  float d[4][4] = {};
#pragma unroll
  for (int i = 0; i < NP / 8; i++) { const uint32_t a[4] = {v[2 * i].x, v[2 * i].y, v[2 * i + 1].x, v[2 * i + 1].y}; mma16816(d[i & 3], a, one, one); }
  const bool ok = __all_sync(~0u, min_flags(v) != 0);
#pragma unroll
  for (int k = 0; k < 4; k++) r[k] = (d[0][k] + d[1][k]) + (d[2][k] + d[3][k]);
  return ok;
}
template <typename F> __device__ __forceinline__ float reduce_g(const float (&x)[4], int lane, F f) {
  const bool u4 = lane & 16, u3 = lane & 8;
  const float a0 = f(u4 ? x[2] : x[0], __shfl_xor_sync(~0u, u4 ? x[0] : x[2], 16));
  const float a1 = f(u4 ? x[3] : x[1], __shfl_xor_sync(~0u, u4 ? x[1] : x[3], 16));
  const float b = f(u3 ? a1 : a0, __shfl_xor_sync(~0u, u3 ? a0 : a1, 8));
  return f(b, __shfl_xor_sync(~0u, b, 4));
}

__global__ void __launch_bounds__(NTHREADS, 1)
fused_decode_kernel(__nv_bfloat16* __restrict__ gout, Scratch* __restrict__ gs, const uint8_t* __restrict__ gwmod,
                    const uint8_t* __restrict__ gx, const uint8_t* __restrict__ gc, uint32_t* __restrict__ gin,
                    const __grid_constant__ Params P) {
  constexpr Tune T{};
  extern __shared__ __align__(1024) uint8_t smem_raw[];
  constexpr uint32_t sb = SB;
  const int tid = __shfl_xor_sync(0xffffffffu, threadIdx.x ^ 1, 1), lane = tid & 31;
  const int w = __shfl_sync(0xffffffffu, threadIdx.x >> 5, 0);
  const int cta = blockIdx.x;
  auto keep = [&](uint32_t v) { return __shfl_sync(~0u, v, lane); };
  auto BAR = [](int i) { return SB + OFF_BARS + 8 * i; };
  auto selector = [&](int c) { uint32_t v; asm volatile("ld.shared.u8 %0, [%1];" : "=r"(v) : "r"(sb + OFF_SEL + c) : "memory"); return v; };
  auto inbox = [&](int c, int k) { return gin + blk(c, k, selector(c)); };
  auto nearbox = [&](int c, int k) { return gin + blk(c, k, selector(cta) ^ flip((c ^ cta) & 15)); };
  const int g = lane >> 2, t = lane & 3;
  const int hI = cta >> 2, jI = cta & 3;
  const int bs = cta >> 1, hh = cta & 1;

  CLK_DECL;
  CLK(0);
  if (w == 8) {
    CLK(7);
    const uint32_t t_entry = gtime32();
    CLK(8);
    if (lane == 0) {
      if ((uint32_t)__cvta_generic_to_shared(smem_raw) != SB) __trap();
      mbar_init(BAR(BAR_WQ), 1); mbar_init(BAR(BAR_WQ + 1), 1); mbar_init(BAR(BAR_XC), 1); mbar_init(BAR(BAR_C), 1);
      asm volatile("fence.mbarrier_init.release.cluster;" ::: "memory");
      asm volatile("prefetch.tensormap [%0];" ::"l"(&P.wq) : "memory");
      mbar_expect(BAR(BAR_XC), 8192); mbar_expect(BAR(BAR_C), 8192); mbar_expect(BAR(BAR_WQ), 16384); mbar_expect(BAR(BAR_WQ + 1), 16384);
      CLK(9);
    }
    __syncwarp();
    asm volatile("barrier.cta.arrive.aligned 0, %0;" ::"n"(NTHREADS) : "memory");
    CLK(10);
    uint32_t tn = t_entry + T.PC_T0 + ((bs * 37) & 63) * T.PC_STAG / 64;
    const int h = hI, j = jI;
    if (lane == 0) {
      uint64_t pol; asm volatile("createpolicy.fractional.L2::evict_first.b64 %0, 1.0;" : "=l"(pol));
#pragma unroll
      for (int u = 0; u < 4; u++) {
        until_ns(tn + u * T.PC_P1);
        if (u == 0) CLK(11);
        tma2d(sb + OFF_WQ + u * 8192, &P.wq, 128 * h + 64 * (u >> 1), 128 * j + 64 * (u & 1), BAR(BAR_WQ + (u >> 1)), pol);
        if (u == 0) {
#pragma unroll
          for (int i = 0; i < 8; i++) { const int o = ((i + cta) & 3) * 2048; bulk_ld(sb + OFF_XS + (i >> 2) * 8192 + o, (i < 4 ? gx : gc) + o, 2048, BAR(i < 4 ? BAR_XC : BAR_C)); }
          CLK(1);
          asm volatile("prefetch.tensormap [%0];" ::"l"(&P.wuk) : "memory");
          asm volatile("prefetch.tensormap [%0];" ::"l"(&P.wm2) : "memory");
          asm volatile("prefetch.tensormap [%0];" ::"l"(&P.ckv2) : "memory");
        }
      }
    }
    __syncwarp();
    tn += 4 * T.PC_P1;
    bar_sync(5, 64);
    if (lane == 0) {
      uint64_t pol; asm volatile("createpolicy.fractional.L2::evict_first.b64 %0, 1.0;" : "=l"(pol));
#pragma unroll
      for (int u = 0; u < 4; u++) {
        if (u & 1) mbar_wait(BAR(BAR_WQ + (u >> 1)));
        slot(tn, T.PC_SL);
        tma5d(sb + OFF_WUK + u * 8192, &P.wuk, 128 * h + 64 * (u >> 1), 0, 0, 0, 8 * j + 4 * (u & 1), BAR(BAR_WUK + (u >> 1)), pol);
        tn += T.PC_P1;
      }
#pragma unroll
      for (int u = 0; u < 2; u++) {
        if (u) mbar_wait(BAR(BAR_WUK));
        slot(tn, T.PC_SL);
        if (j != 3) tma2d_nohint(sb + OFF_WM2 + u * 8192, &P.wm2, 1024 + 16 * (3 * h + j), 256 * u, BAR(BAR_WM2));
        tn += T.PC_PM;
      }
      const int row0 = (bs >> 3) * 4096 + (bs & 7) * 64;
      uint32_t dst = sb + OFF_RING;
#pragma unroll 1
      for (int n = 0; n < 31; n++) {
        if (n >= 4 && (n < 12 || (n & 3) == 0)) mbar_wait(BAR(n >= 12 ? BAR_EMPTY + (n >> 2) - 3 : (n == 7 && j != 3) ? BAR_P0BD : (n == 8 || n == 9) ? BAR_P2D : BAR_P1D));
        if (n < T.PC_NW) {
          if (n >= 4) mbar_wait(BAR(BAR_FULL + n - 4));
          else if (n & 1) mbar_wait(BAR((n < 2 || j == 3) ? BAR_WUK + 1 : BAR_WM2));
        }
        slot(tn, T.PC_SL);
        tma3d(dst, &P.ckv2, 0, row0 + (n >> 2) * 512, 2 * (n & 3), BAR(BAR_FULL + n), pol);
        dst = (n == 11 || n == 23) ? sb + OFF_RING : dst + 16384;
        tn += T.PC_P2;
        if (n == 4) CLK(2);
        if (n == 12) CLK(3);
        if (n == 20) CLK(4);
        if (n == 28) CLK(5);
        if (n == 24) {
          asm volatile("prefetch.tensormap [%0];" ::"l"(&P.ckv1) : "memory");
          asm volatile("prefetch.tensormap [%0];" ::"l"(&P.wuv) : "memory");
          asm volatile("prefetch.tensormap [%0];" ::"l"(&P.wo) : "memory");
          asm volatile("prefetch.tensormap [%0];" ::"l"(cta < NFF ? &P.w1 : &P.wm3) : "memory");
          asm volatile("prefetch.tensormap [%0];" ::"l"(&P.w2) : "memory");
        }
      }
      slot(tn, T.PC_SL);
      tma3d(dst, &P.ckv1, 0, row0 + 7 * 512, 6, BAR(BAR_LAST + 3), pol);
      tma3d(dst + 8192, &P.ckv1, 0, row0 + 7 * 512, 7, BAR(BAR_LAST + 4), pol);
      tn += T.PC_P2;
      CLK(6);
      auto unit = [&](int u) {
        if (u < 4) tma5d(sb + OFF_WUV + u * 8192, &P.wuv, 128 * h + 64 * (u >> 1), 0, 4 * (j >> 1), 0, 2 * (j & 1) + (u & 1), BAR(BAR_WUV + (u >> 1)), pol);
        else if (u < 8) tma2d(sb + OFF_WO + (u - 4) * 8192, &P.wo, 128 * j + 64 * ((u - 4) >> 1), 128 * h + 64 * (u & 1), BAR(BAR_WO + ((u - 4) >> 1)), pol);
        else if (u < 10) { if (cta < NFF) tma2d_nohint(sb + OFF_W1 + (u - 8) * 16384, &P.w1, 32 * bs, 256 * (u - 8), BAR(BAR_W1)); }
        else if (cta < NFF) tma3d(sb + OFF_W2 + (u - 10) * 8192, &P.w2, 0, 32 * bs, 4 * hh + 2 * (u - 10), BAR(BAR_W2), pol);
        else tma2d_nohint(sb + OFF_W1 + (u - 10) * 16384, &P.wm3, 2560 + 32 * (cta - NFF), 256 * (u - 10), BAR(BAR_W1));
      };
      mbar_wait(BAR(BAR_EMPTY + 5));
#pragma unroll
      for (int u = 0; u < 12; u++) {
        if (u == 8) mbar_wait(BAR(BAR_EMPTY + 6));
        until_ns(tn + (u < 4 ? T.T_UV + u * T.P_UV : u < 8 ? T.T_O + (u - 4) * T.P_O : u < 10 ? T.T_1 + (u - 8) * T.P_F : (cta < NFF ? T.T_2 : T.T_GB) + (u - 10) * T.P_F));
        unit(u);
        if (u == 3) {
#pragma unroll
          for (int q = 0; q < 4; q++)
            if (q < T.PF_N) {
              until_ns(tn + T.T_PF + q * T.P_PF);
              asm volatile("cp.async.bulk.prefetch.tensor.2d.L2.global.tile [%0, {%1,%2}];" ::"l"(&P.wo), "r"(128 * j + 64 * (q >> 1)), "r"(128 * h + 64 * (q & 1)) : "memory");
            }
        }
      }
      CLK_DUMP();
    }
    return;
  }

  if (w == 9) {
    if (lane == 0) {
#pragma unroll
      for (int i = 0; i < NBARS; i++) mbar_init(BAR(i), i >= BAR_P1D ? 8 : i >= BAR_EMPTY ? 4 : 1);
      asm volatile("fence.mbarrier_init.release.cluster;" ::: "memory");
    }
    __syncwarp();
    mbar_expect(BAR(lane), lane == BAR_LAST + 3 ? 8192 : 16384);
    if (lane < BAR_ALLCLR - 32) mbar_expect(BAR(32 + lane), lane == 0 ? 8192 : lane == BAR_W1 - 32 ? 32768 : 16384);
    CLK(9);
    asm volatile("barrier.cta.arrive.aligned 5, 64;" ::: "memory");
    asm volatile("barrier.cta.arrive.aligned 0, %0;" ::"n"(NTHREADS) : "memory");
  }
  const uint32_t epoch = ldg_rlx1(&gs->epoch);

  if (w == 9) {
    const int mo = g * 512 + 16 * hI + 2 * jI;
    const uint32_t xo0 = ldg_nc1(gx + mo * 2), xo1 = ldg_nc1(gx + mo * 2 + 16);
    const int par = epoch & 1;
    const uint32_t t0 = gtime32();
    const uint4 z = make_uint4(0, 0, 0, 0);
    uint32_t sel;
    {
      uint32_t* pa = gin + blk(cta, 5, 0) + 960;
      uint32_t* pb = gin + blk(cta, 5, 1) + 960;
      until_ns(t0 + T.PR_T0);
      if (lane < 4) stg4(reinterpret_cast<uint4*>(lane & 2 ? pa : pb) + (lane & 1), z);
      uint32_t ma = 0xffffffffu, mb = 0xffffffffu;
#pragma unroll 1
      for (int i = 0; i < 2 * T.PR_N; i++) {
        const uint32_t c0 = clk32();
        asm volatile("{\n.reg .pred q;\n.reg .b32 v;\nsetp.eq.u32 q, %1, 0;\nmov.u32 v, 0;\n@q atom.relaxed.gpu.global.add.u32 v, [%0], 1;\n"
                     "setp.eq.u32 q, v, 0xffffffff;\n@q trap;\n}" ::"l"(i & 1 ? pb : pa), "r"(lane) : "memory");
        const uint32_t d = clk32() - c0;
        if (i & 1) mb = min(mb, d); else ma = min(ma, d);
      }
      sel = __shfl_sync(~0u, (uint32_t)(mb < ma), 0);
      const uint32_t sw = 2 * (epoch + 1) + sel;
      if (lane < 2) stg4(reinterpret_cast<uint4*>(gin + blk(cta, 5, 1) + 896) + lane, make_uint4(sw, sw, sw, sw));
    }
    until_ns(t0 + T.CLR_T0);
    {
#pragma unroll 1
      for (int i0 = 0; i0 < 13; i0++) {
        uint4* q = reinterpret_cast<uint4*>(gin + (i0 < 12 ? blk(cta, i0 >> 1, sel) + (i0 & 1) * 512 : blk(cta, 4, sel ^ 1) + 512)) + lane;
#pragma unroll
        for (int i = 0; i < 4; i++) if (i0 != 11 || i < 3) stg4(q + i * 32, z);
        backoff(T.CLR_CLK);
      }
#pragma unroll
      for (int i = 0; i < 2; i++) {
        if (jI == 1) stg4(reinterpret_cast<uint4*>(gin + blk(cta, 6, i)) + lane, z);
        if (lane < 2) stg4(reinterpret_cast<uint4*>(gin + blk(cta, 5, i) + 928) + lane, z);
        stg4(reinterpret_cast<uint4*>(gin + blk(16 * g, 6 + (cta >> 6), i) + (cta & 63) * 16) + t, z);
      }
      CLK(1);
      {
        uint32_t sv = 0;
        uint32_t u[4];
        int it = 0;
        do {
#pragma unroll
          for (int i = 0; i < 4; i++) u[i] = ldg_rlx1(gin + blk(4 * lane + i, 5, 1) + 896) ^ (2 * (epoch + 1));
          if (++it > SPIN_LIMIT) __trap();
        } while (!__all_sync(~0u, (u[0] | u[1] | u[2] | u[3]) < 2));
#pragma unroll
        for (int i = 0; i < 4; i++) sv |= u[i] << (8 * i);
        sts1(sb + OFF_SEL + lane * 4, sv);
      }
      asm volatile("fence.acq_rel.gpu;" ::: "memory");
      CLK(2);
      __syncwarp();
      if (lane < NSYNC) asm volatile("red.relaxed.gpu.global.add.u32 [%0], 1;" ::"l"(&gs->sync[lane][0]) : "memory");
#pragma unroll
      for (int i = 0; i < 4; i++) stg4(reinterpret_cast<uint4*>(gs->QP[par ^ 1] + cta * 512) + i * 32 + lane, z);
      backoff(T.CLR_CLK);
#pragma unroll
      for (int i = 0; i < 4; i++) stg4(reinterpret_cast<uint4*>(gs->QX[par ^ 1] + cta * 512) + i * 32 + lane, z);
      stg4(reinterpret_cast<uint4*>(gs->MOD1[par ^ 1] + cta * 128) + lane, z);
      if (lane < 16) stg4(reinterpret_cast<uint4*>(gs->MOD2[par ^ 1] + cta * 64) + lane, z);
      const uint32_t target = (epoch + 1) * NCTA;
      uint32_t c; int it = 0;
      do {
        backoff(T.CLR_CLK);
        asm volatile("ld.acquire.gpu.global.u32 %0, [%1];" : "=r"(c) : "l"(&gs->sync[cta % NSYNC][0]) : "memory");
        if (++it > SPIN_LIMIT) __trap();
      } while (!__all_sync(~0u, (int)(c - target) >= 0));
      if (lane == 0) mbar_arrive(BAR(BAR_ALLCLR));
    }
    CLK(3);
    const uint32_t* const pg = gs->MOD2[par] + cta * 16 + g * 2;
    auto gate = [&](const uint32_t* q) { uint2 u; int it = 0; do { u = ldg_u64(q); if (++it > SPIN_LIMIT) __trap(); } while (!__all_sync(~0u, u.y != 0)); return u; };
    const uint2 gau = gate(pg);
    uint32_t anchor;
    {
      uint32_t* const po = gin + blk(16 * (lane & 7), 5, lane >> 3) + 928;
      const uint32_t* const pi = nearbox(cta & ~15, 5) + 928;
      mbar_wait(BAR(BAR_LAST + T.TS_P));
      unsigned long long now; asm volatile("mov.u64 %0, %%globaltimer;" : "=l"(now));
      if (lane < 16) asm volatile("red.relaxed.gpu.global.add.u64 [%0], %1;" ::"l"(po), "l"((now << 8) + 1) : "memory");
      backoff(T.D_TS);
      uint2 v; int it = 0;
      do { v = ldg_u64(pi); if (++it > SPIN_LIMIT) __trap(); } while (!__all_sync(~0u, (v.x & 255) == NCTA));
      const uint32_t mean = __funnelshift_r(v.x, v.y, 15);
      const int age = min(max((int)(gtime32() - mean), 0), 4000);
      anchor = clk32() - age * 7 / 4 + T.TS_O;
      if (lane == 0) { sts1(sb + OFF_TS, anchor); mbar_arrive(BAR(BAR_TS)); }
      CLK(10);
    }
    {
      const uint32_t* pm = pin(nearbox(4 * hI + 1, 6) + lane * 4);
      wait_clk(anchor, T.A_M);
      uint4 ml = ldg_2u64(pm);
      int it = 0;
      while (!__all_sync(~0u, ml.y != 0 && ml.w != 0)) { ml = ldg_2u64(pm); if (++it > SPIN_LIMIT) __trap(); }
      ITS(2, it);
      float M = fmaxf(__uint_as_float(ml.x), __uint_as_float(ml.z));
      M = fmaxf(M, __shfl_xor_sync(~0u, M, 1)); M = fmaxf(M, __shfl_xor_sync(~0u, M, 2));
      const float e0 = ex2(__uint_as_float(ml.x) - M), e1 = ex2(__uint_as_float(ml.z) - M);
      float l = e0 * __uint_as_float(ml.y) + e1 * __uint_as_float(ml.w);
      l += __shfl_xor_sync(~0u, l, 1); l += __shfl_xor_sync(~0u, l, 2);
      const float inv = __fdividef(1.f, l);
      sts2f(sb + OFF_WV + lane * 8, e0 * inv, e1 * inv);
      __syncwarp();
      if (lane == 0) mbar_arrive(BAR(BAR_WV));
      CLK(11);
    }
    uint32_t* x3o[4];
#pragma unroll
    for (int i = 0; i < 4; i++) x3o[i] = pin(gin + blk(32 * i + 16 * (t >> 1), 6 + (cta >> 6), t) + (cta & 63) * 16 + g * 2);
    uint32_t* const fo = pin(reinterpret_cast<uint32_t*>(gout) + mo / 2 + 4 * (t & 1));
    const uint32_t* const p3 = pin(gin + blk(cta, 4, sel) + t * 16 + g * 2);
    const uint32_t* const p4 = pin(gin + blk(cta, 5, sel) + t * 16 + g * 2);
    const uint32_t one = pin((g & 1) ? 0x3f800000u : 0x00003f80u);
    const float xf[4] = {pin(bf_lo(xo0)), pin(bf_hi(xo0)), pin(bf_lo(xo1)), pin(bf_hi(xo1))};
    const float ga[4] = {pin(bf_lo(gau.x)), pin(bf_hi(gau.x)), pin(bf_lo(gau.y)), pin(bf_hi(gau.y))};
    mbar_wait(BAR(BAR_P5D));
    backoff(T.D_X3A);
    wait_clk(anchor, T.A_X1 + T.R_X3A);
    CLK(4);
    float r[4];
    uint32_t x20, x21;
    int it = 0;
    bool ok;
    do {
      ok = sum_pieces<32>(p3, one, r);
      x20 = pack_bf16(xf[0] + ga[0] * r[0], xf[1] + ga[1] * r[1]); x21 = pack_bf16(xf[2] + ga[2] * r[2], xf[3] + ga[3] * r[3]);
#pragma unroll
      for (int i = 0; i < 4; i++) stg_u64_unless(!ok || (i == 3 && t >= 2), x3o[i], x20, x21);
    } while (!ok && ++it < SPIN_LIMIT);
    if (!ok) __trap();
    CLK(6);
    ITS(0, it);
    const uint32_t xw = (t & 1) ? x21 : x20;
    const float xa = pin(bf_lo(xw)), xb = pin(bf_hi(xw));
    if (cta < NFF) mbar_wait(BAR(BAR_P7D)); else wait_clk(anchor, T.A_X1 + T.R_X3A + T.R_X3B + T.R_FIN - T.D_FIN);
    uint2 gbu = ldg_u64(pg + 3 * 2048);
    backoff(T.D_FIN);
    CLK(7);
    do {
      ok = sum_pieces<NFG>(p4, one, r);
      ok = ok && __all_sync(~0u, gbu.y != 0);
      const uint32_t gw = (t & 1) ? gbu.y : gbu.x;
      const uint32_t o = pack_bf16(xa + bf_lo(gw) * ((t & 1) ? r[2] : r[0]), xb + bf_hi(gw) * ((t & 1) ? r[3] : r[1]));
      if (ok && t < 2) asm volatile("st.global.u32 [%0], %1;" ::"l"(fo), "r"(o) : "memory");
      reload_unit(gbu, pg + 3 * 2048);
    } while (!ok && ++it < SPIN_LIMIT);
    if (!ok) __trap();
    ITS(1, it);
    CLK(8);
    CLK_DUMP();
    if (cta == 0 && lane == 0) stg1(&gs->epoch, epoch + 1);
    return;
  }

  const int wg = w >> 2, wq = w & 3;
  uint32_t tstore;
  {
    const uint8_t* pw = gwmod + (size_t)(128 * jI + 16 * w + 4 * (g >> 1) + (g & 1)) * 6144 + 64 * hI + 16 * t;
    const uint4 w0 = ldg_nc4(pw), w1 = ldg_nc4(pw + 2 * 6144);
    const uint2 cc = ldg_nc2(gc + g * 1024 + 256 * jI + 32 * w + 8 * t);
    CLK(40);
    const uint32_t a[4] = {silu2(cc.x), 0u, silu2(cc.y), 0u};
    float d[4][4] = {{0.f, 0.f, 0.f, 0.f}, {0.f, 0.f, 0.f, 0.f}, {0.f, 0.f, 0.f, 0.f}, {0.f, 0.f, 0.f, 0.f}};
    mma16816(d[0], a, movm(w0.x), movm(w1.x)); mma16816(d[1], a, movm(w0.y), movm(w1.y));
    mma16816(d[2], a, movm(w0.z), movm(w1.z)); mma16816(d[3], a, movm(w0.w), movm(w1.w));
    CLK(1);
    sts4f(sb + OFF_P0S + w * 1088 + lane * 16, d[0][0], d[0][1], d[1][0], d[1][1]);
    sts4f(sb + OFF_P0S + w * 1088 + 544 + lane * 16, d[2][0], d[2][1], d[3][0], d[3][1]);
    bar_sync(0, NTHREADS);
    if (tid < 128) {
      const uint32_t src = sb + OFF_P0S + ((tid >> 2) & 1) * 544 + (((tid >> 3) & 7) * 4 + 2 * (tid >> 6) + (tid & 1)) * 16 + ((tid >> 1) & 1) * 8;
      float2 v[8];
#pragma unroll
      for (int i = 0; i < 8; i++) v[i] = ldsf2(src + i * 1088);
      const float ax = ((v[0].x + v[1].x) + (v[2].x + v[3].x)) + ((v[4].x + v[5].x) + (v[6].x + v[7].x));
      const float ay = ((v[0].y + v[1].y) + (v[2].y + v[3].y)) + ((v[4].y + v[5].y) + (v[6].y + v[7].y));
      stg1(gs->MOD1[epoch & 1] + jI * 4096 + hI * 128 + tid, nz(pack_bf16(ax, ay)));
    }
    tstore = clk32();
  }
  CLK(2);
  const int par = epoch & 1;
  uint32_t cf[4][4];
  mbar_wait(BAR(BAR_XC));
  {
    uint32_t u[2][4];
    lds4(u[0], sb + OFF_XS + w * 1024 + lane * 16); lds4(u[1], sb + OFF_XS + w * 1024 + 512 + lane * 16);
    float v[16];
#pragma unroll
    for (int i = 0; i < 8; i++) { v[2 * i] = bf_lo(u[i >> 2][i & 3]); v[2 * i + 1] = bf_hi(u[i >> 2][i & 3]); }
    float s = 0.f;
#pragma unroll
    for (int i = 0; i < 16; i++) s += v[i];
#pragma unroll
    for (int o = 16; o; o >>= 1) s += __shfl_xor_sync(~0u, s, o);
    const float mu = s * (1.f / 512.f);
    float q = 0.f;
#pragma unroll
    for (int i = 0; i < 16; i++) { v[i] -= mu; q += v[i] * v[i]; }
#pragma unroll
    for (int o = 16; o; o >>= 1) q += __shfl_xor_sync(~0u, q, o);
    const float rs = rsqrtf(q * (1.f / 512.f) + 1e-5f);
    const bool hi = jI & 2;
    uint32_t o[4];
#pragma unroll
    for (int i = 0; i < 4; i++) o[i] = pack_bf16((hi ? v[8 + 2 * i] : v[2 * i]) * rs, (hi ? v[9 + 2 * i] : v[2 * i + 1]) * rs);
    if ((lane >> 4) == (jI & 1)) sts4(sb + OFF_XN + w * 272 + (lane & 15) * 16, make_uint4(o[0], o[1], o[2], o[3]));
  }
  CLK(3);
  uint32_t aw[8][4];
  const uint32_t abase = keep(sb + a_t_offset(w, lane));
  {
    const uint32_t* pm = pin(gs->MOD1[par] + (8 * jI + w) * 64 + lane * 2);
    uint32_t* const qpo = pin(gs->QP[par] + (cta * 256 + tid) * 2);
    float d[4] = {0.f, 0.f, 0.f, 0.f};
    wait_clk(tstore, T.D_MOD);
    CLK(4);
    uint2 v[8];
    load_units<8, 2048>(v, pm);
    cbar();
    const uint32_t xn0 = lds1(sb + OFF_XN + g * 272 + w * 32 + t * 4), xn1 = lds1(sb + OFF_XN + g * 272 + w * 32 + 16 + t * 4);
    const bool early = __all_sync(~0u, mbar_test(BAR(BAR_WQ + wg)));
    if (early) load_a_t(aw, abase + OFF_WQ);
    int it = 0;
    while (true) {
      uint32_t mn = 0xffffffffu;
#pragma unroll
      for (int i = 0; i < 8; i++) mn = min(mn, min(v[i].x, v[i].y));
      if (__all_sync(~0u, mn != 0)) break;
#pragma unroll
      for (int i = 0; i < 8; i++) { if (v[i].x == 0) v[i].y = 0; reload_unit(v[i], pm + i * 2048); }
      if (++it > SPIN_LIMIT) __trap();
    }
    CLK(5);
    ITS(0, it);
    float sc[2][4];
#pragma unroll
    for (int i = 0; i < 2; i++) {
      sc[i][0] = (bf_lo(v[i].x) + bf_lo(v[2 + i].x)) + (bf_lo(v[4 + i].x) + bf_lo(v[6 + i].x));
      sc[i][1] = (bf_hi(v[i].x) + bf_hi(v[2 + i].x)) + (bf_hi(v[4 + i].x) + bf_hi(v[6 + i].x));
      sc[i][2] = (bf_lo(v[i].y) + bf_lo(v[2 + i].y)) + (bf_lo(v[4 + i].y) + bf_lo(v[6 + i].y));
      sc[i][3] = (bf_hi(v[i].y) + bf_hi(v[2 + i].y)) + (bf_hi(v[4 + i].y) + bf_hi(v[6 + i].y));
    }
    sts2(sb + OFF_BS1 + (w >> 1) * 512 + lane * 16 + (w & 1) * 8,
         pack_bf16(bf_lo(xn0) * (1.f + sc[1][0]) + sc[0][0], bf_hi(xn0) * (1.f + sc[1][1]) + sc[0][1]),
         pack_bf16(bf_lo(xn1) * (1.f + sc[1][2]) + sc[0][2], bf_hi(xn1) * (1.f + sc[1][3]) + sc[0][3]));
    if (!early) { mbar_wait(BAR(BAR_WQ + wg)); load_a_t(aw, abase + OFF_WQ); }
    CLK(6);
    cbar();
    uint32_t b[4][4];
#pragma unroll
    for (int kk = 0; kk < 4; kk++) lds4(b[kk], sb + OFF_BS1 + kk * 512 + lane * 16);
    mma128(d, aw, b);
    stg_u64(qpo, pack_bf16(d[0], d[1]), pack_bf16(d[2], d[3]));
    tstore = clk32();
    CLK(7);
    if (wg) {
      mbar_wait(BAR(BAR_C));
#pragma unroll
      for (int i = 0; i < 4; i++) lds4(cf[i], sb + OFF_CS + g * 1024 + wq * 256 + i * 64 + t * 16);
#pragma unroll
      for (int i = 0; i < 16; i++) cf[i >> 2][i & 3] = silu2(cf[i >> 2][i & 3]);
    }
    __syncwarp();
    if (lane == 0) mbar_arrive(BAR(BAR_P1D));
  }
  {
    const uint32_t* pq = pin(gs->QP[par] + (hI * 4 * 256 + tid) * 2);
    uint32_t* const qxo = pin(gs->QX[par] + (g * 32 + hI) * 256 + 64 * jI + 8 * w + 2 * t);
    uint2 v[4];
    float d[4] = {0.f, 0.f, 0.f, 0.f};
    wait_clk(tstore, T.D_QP);
    CLK(8);
    load_units<4, 512>(v, pq);
    const uint32_t kbase = sb + OFF_WUK + (16 * w + (lane & 15)) * 128;
    auto load_half = [&](int hf) {
#pragma unroll
      for (int ks = 0; ks < 4; ks++) ldsm4(aw[4 * hf + ks], kbase + hf * 16384 + (((2 * ks + (lane >> 4)) ^ (lane & 7)) << 4));
    };
    mbar_wait(BAR(BAR_WUK));
    load_half(0);
    const bool early = __all_sync(~0u, mbar_test(BAR(BAR_WUK + 1)));
    if (early) load_half(1);
    const int it = check_units<4, 512>(v, pq);
    CLK(9);
    ITS(1, it);
    sum4_to_smem(v, sb + OFF_BS2 + (16 * w + g) * 16 + t * 4);
    if (!early) { mbar_wait(BAR(BAR_WUK + 1)); load_half(1); }
    CLK(10);
    cbar();
    uint32_t b[4][4];
#pragma unroll
    for (int kk = 0; kk < 4; kk++) ldsm4t(b[kk], sb + OFF_BS2 + (32 * kk + lane) * 16);
    mma128(d, aw, b);
    const float sc = 0.08838834764831845f * 1.4426950408889634f;
    stg_u64(qxo, movm(pack_bf16(d[0] * sc, d[1] * sc)), movm(pack_bf16(d[2] * sc, d[3] * sc)));
    tstore = clk32();
    CLK(11);
    if (lane == 0) mbar_arrive(BAR(BAR_P2D));
  }
  if (wg && jI != 3) {
    const int mi = lane >> 3, r = lane & 7;
    const uint32_t a0 = sb + OFF_WM2 + (8 * (r >> 1) + (r & 1) + 2 * (mi >> 1)) * 32 + (mi & 1) * 16;
    mbar_wait(BAR(BAR_WM2));
#pragma unroll
    for (int s = 0; s < 8; s++) ldsm4t(aw[s], a0 + (128 * wq + 32 * (s >> 1) + 4 * (s & 1)) * 32);
    float d[4] = {0.f, 0.f, 0.f, 0.f};
    mma128(d, aw, cf);
    sts4f(sb + OFF_P0B + (tid - 128) * 16, d[0], d[1], d[2], d[3]);
    if (lane == 0) mbar_arrive(BAR(BAR_P0BD));
    bar_sync(3, 128);
    if (w == 4) {
      float4 v[4];
#pragma unroll
      for (int i = 0; i < 4; i++) v[i] = ldsf4(sb + OFF_P0B + (i * 32 + lane) * 16);
      stg_u64(gs->MOD2[par] + (3 * hI + jI) * 64 + t * 16 + g * 2, movm(pack_bf16((v[0].x + v[1].x) + (v[2].x + v[3].x), (v[0].y + v[1].y) + (v[2].y + v[3].y))),
              movm(pack_bf16((v[0].z + v[1].z) + (v[2].z + v[3].z), (v[0].w + v[1].w) + (v[2].w + v[3].w))));
    }
    CLK(15);
  }
  {
    const uint32_t* qx = pin(gs->QX[par] + ((bs >> 3) * 32 + 16 * hh) * 256 + tid * 4);
    const int ch = tid & 63, h0 = tid >> 6;
    const uint32_t dst = sb + OFF_Q + (ch >> 3) * 2048 + h0 * 128;
    wait_clk(tstore, T.D_QX);
    CLK(12);
    uint4 v[4];
#pragma unroll
    for (int i = 0; i < 4; i++) v[i] = ldg_2u64(qx + i * 1024);
    int it = 0;
    while (true) {
      uint32_t mn = 0xffffffffu;
#pragma unroll
      for (int i = 0; i < 4; i++) mn = min(mn, min(v[i].y, v[i].w));
      if (__all_sync(~0u, mn != 0)) break;
#pragma unroll
      for (int i = 0; i < 4; i++)
        asm volatile("{\n.reg .pred q;\nsetp.eq.u32 q, %5, 0;\n@q ld.relaxed.gpu.global.v4.b32 {%0, %1, %2, %3}, [%4];\n}"
                     : "+r"(v[i].x), "+r"(v[i].y), "+r"(v[i].z), "+r"(v[i].w) : "l"(qx + i * 1024), "r"(min(v[i].y, v[i].w)) : "memory");
      if (++it > SPIN_LIMIT) __trap();
    }
    CLK(13);
    ITS(2, it);
#pragma unroll
    for (int i = 0; i < 4; i++) sts4(dst + i * 512 + (((ch & 7) ^ ((4 * i + h0) & 7)) << 4), v[i]);
    asm volatile("fence.proxy.async.shared::cta;" ::: "memory");
    CLK(14);
    cbar();
  }

  uint2 cbf[4], sbf[4];
  const uint32_t* const pcb = gs->MOD2[par] + 2048 + (16 * w + t) * 16 + g * 2;
  auto load_frags = [&] {
    if (cta < NFF) { load_units<4, 64>(sbf, pcb); load_units<4, 64>(cbf, pcb + 2048); }
    else {
#pragma unroll
      for (int s = 0; s < 4; s++) { cbf[s].x = ldg_nc1(gc + g * 1024 + w * 128 + s * 32 + t * 4); cbf[s].y = ldg_nc1(gc + g * 1024 + w * 128 + s * 32 + 16 + t * 4); }
    }
  };
  uint32_t thand, anchor;
  const uint32_t opaque0 = w >> 4;
  if (wg == 0) {
    float mh[4];
    float L[8];
#pragma unroll
    for (int i = 0; i < 4; i++) { L[2 * i] = L[2 * i + 1] = 0.f; mh[i] = -INFINITY; }
    constexpr uint32_t dq = desc_lo(OFF_Q);
    const uint32_t ptw = sb + OFF_PT + (8 * (lane >> 4) + (lane & 7)) * 128 + (((2 * wq + ((lane >> 3) & 1)) ^ (lane & 7)) << 4);
    float S[8];
    auto softmax = [&](int tl) {
      auto write_p = [&](const float (&x)[8]) {
        float p[8];
#pragma unroll
        for (int i = 0; i < 8; i++) p[i] = ex2(x[i]);
        stsm4t(ptw + (tl & 1) * 2048, pack_bf16(p[0], p[1]), pack_bf16(p[2], p[3]), pack_bf16(p[4], p[5]), pack_bf16(p[6], p[7]));
        asm volatile("fence.proxy.async.shared::cta;" ::: "memory");
      };
      float x[8];
#pragma unroll
      for (int i = 0; i < 8; i++) x[i] = S[i] - mh[2 * (i >> 2) + (i & 1)];
      if (tl) write_p(x);
      const float ex = fmaxf(fmaxf(fmaxf(x[0], x[1]), fmaxf(x[2], x[3])), fmaxf(fmaxf(x[4], x[5]), fmaxf(x[6], x[7])));
      if (tl == 0 || bar_over(ex)) {
        float mx[4];
#pragma unroll
        for (int i = 0; i < 4; i++) mx[i] = fmaxf(S[4 * (i >> 1) + (i & 1)], S[4 * (i >> 1) + 2 + (i & 1)]);
        const float a = reduce_g(mx, lane, [](float u, float v) { return fmaxf(u, v); });
        stsf(sb + OFF_RED + wq * 64 + (8 * (lane >> 4) + 2 * t + ((lane >> 3) & 1)) * 4, a);
        bar_sync(2, 128);
#pragma unroll
        for (int jn = 0; jn < 2; jn++) {
          float m0 = mh[2 * jn], m1 = mh[2 * jn + 1];
#pragma unroll
          for (int i = 0; i < 4; i++) { const float2 v = ldsf2(sb + OFF_RED + i * 64 + (8 * jn + 2 * t) * 4); m0 = fmaxf(m0, v.x); m1 = fmaxf(m1, v.y); }
          const float a0 = ex2(mh[2 * jn] - m0), a1 = ex2(mh[2 * jn + 1] - m1);
          mh[2 * jn] = m0; mh[2 * jn + 1] = m1;
          L[4 * jn] *= a0; L[4 * jn + 1] *= a1; L[4 * jn + 2] *= a0; L[4 * jn + 3] *= a1;
          if (tid < 4) sts2f(sb + OFF_ALPHA + (8 * jn + 2 * t) * 4, a0, a1);
        }
        asm volatile("barrier.cta.arrive.aligned 1, 256;" ::: "memory");
#pragma unroll
        for (int i = 0; i < 8; i++) x[i] = S[i] - mh[2 * (i >> 2) + (i & 1)];
        write_p(x);
        bar_over(0.f);
      }
      const uint32_t dpt = __shfl_sync(~0u, desc_lo(OFF_PT) + (tl & 1) * 128, 0);
      wg_fence();
#pragma unroll
      for (int ks = 0; ks < 4; ks++) wgmma_n16_ones(L, ONE2, dpt + ks * 2);
      wg_commit();
    };
    uint32_t da = desc_lo(OFF_RING);
#pragma unroll 1
    for (int tl = 0; tl < 7; tl++) {
      if (tl == 5) { load_frags(); }
      uint32_t ok = 0;
#pragma unroll
      for (int u = 0; u < 4; u++) ok += mbar_test(BAR(BAR_FULL + 4 * tl + u));
      ok = __reduce_min_sync(~0u, ok);
      const uint32_t du = __shfl_sync(~0u, da, 0);
#pragma unroll
      for (int u = 0; u < 4; u++) {
        if (ok != 4) mbar_wait(BAR(BAR_FULL + 4 * tl + u));
        wg_fence();
#pragma unroll
        for (int k = 0; k < 8; k++) {
          const int i = 8 * u + k;
          if (i == 0) wgmma_n16<0, 0>(S, du, dq); else wgmma_n16<0, 1>(S, du + (i >> 2) * 512 + (i & 3) * 2, dq + (i >> 2) * 128 + (i & 3) * 2);
        }
        wg_commit();
      }
      wg_wait<0>();
      acc_fence(S); acc_fence(L);
      if (tl == 0) CLK(15);
      if (tl == 1) CLK(17);
      softmax(tl);
      if (tl == 0) CLK(16);
      if (tl == 1) CLK(18);
      if (tl == 3) CLK(19);
      if (tl == 6) CLK(20);
      da = (tl == 2 || tl == 5) ? da - 8192 : da + 4096;
    }
    mbar_wait(BAR(BAR_ALLCLR));
    uint32_t* const mlo = pin(gin + blk(4 * (16 * hh + 4 * (g & 2) + 2 * t + (g & 1)) + 1, 6, g >> 2) + bs * 2);
#pragma unroll
    for (int i = 0; i < 32; i++) {
      if (i == 0 || i == 8 || i == 16 || i == 24 || i == 28) {
        if (i) wg_commit();
        mbar_wait(BAR(BAR_LAST + (i == 28 ? 4 : i >> 3)));
        if (i == 28) CLK(21);
        wg_fence();
      }
      if (i == 0) wgmma_n16<0, 0>(S, desc_lo(65536), dq); else wgmma_n16<0, 1>(S, desc_lo(65536) + (i >> 2) * 512 + (i & 3) * 2, dq + (i >> 2) * 128 + (i & 3) * 2);
    }
    wg_commit();
    wg_wait<0>();
    acc_fence(S); acc_fence(L);
    CLK(22);
    softmax(7);
    CLK(23);
    thand = clk32();
    wg_wait<0>();
    acc_fence(L);
    if (tid < 32) red_u64(mlo, __float_as_uint(g & 2 ? (g & 1 ? mh[3] : mh[2]) : (g & 1 ? mh[1] : mh[0])), __float_as_uint(g & 2 ? (g & 1 ? L[5] : L[4]) : (g & 1 ? L[1] : L[0])));
    CLK(24);
  } else {
    float O[8][8];
#pragma unroll
    for (int i = 0; i < 8; i++)
#pragma unroll
      for (int k = 0; k < 8; k++) O[i][k] = 0.f;
    constexpr uint32_t dp = desc_lo(OFF_PT);
    auto handover = [&](int tl) {
      uint32_t over = opaque0 + (tl == 0);
#pragma unroll 1
      do {
        if (over) {
          cbar();
#pragma unroll
          for (int jn = 0; jn < 2; jn++) {
            const float2 a = ldsf2(sb + OFF_ALPHA + (8 * jn + 2 * t) * 4);
#pragma unroll
            for (int mb = 0; mb < 8; mb++) { O[mb][4 * jn] *= a.x; O[mb][4 * jn + 1] *= a.y; O[mb][4 * jn + 2] *= a.x; O[mb][4 * jn + 3] *= a.y; }
          }
        }
        over++;
      } while (bar_over(0.f));
    };
    uint32_t da = desc_lo(OFF_RING);
    uint32_t* x1o[8] = {};
#pragma unroll 1
    for (int tl = 0; tl < 8; tl++) {
      if (tl == 5) load_frags();
      if (tl == 7) {
        mbar_wait(BAR(BAR_ALLCLR));
#pragma unroll
        for (int i = 0; i < 8; i++)
          x1o[i] = inbox((16 * hh + 8 * ((i >> 1) & 1) + 2 * t + (i & 1)) * 4 + 2 * (i >> 2) + (wq >> 1), bs >> 4) + (bs & 15) * 64 + ((wq & 1) * 8 + g) * 4;
      }
      handover(tl);
      CLK(23);
      thand = clk32();
      const uint32_t dpt = dp + (tl & 1) * 128;
      wg_fence();
#pragma unroll
      for (int i = 0; i < 32; i++) wgmma_n16<1, 1>(O[i >> 2], da + (i >> 2) * 512 + (i & 3) * 128, dpt + (i & 3) * 2);
      wg_commit();
      da = (tl == 2 || tl == 5) ? da - 8192 : da + 4096;
      wg_wait<0>();
#pragma unroll
      for (int mb = 0; mb < 8; mb++) acc_fence(O[mb]);
      if (lane == 0) mbar_arrive(BAR(BAR_EMPTY + tl));
      if (tl == 0) CLK(16);
      if (tl == 1) CLK(18);
      if (tl == 3) CLK(19);
      if (tl == 6) CLK(20);
    }
    CLK(22);
#pragma unroll
    for (int i = 0; i < 8; i++) {
      const int J = i >> 2, k = 4 * ((i >> 1) & 1) + (i & 1);
      stg_cvt8(x1o[i], O[4 * J][k], O[4 * J][k + 2], O[4 * J + 1][k], O[4 * J + 1][k + 2], O[4 * J + 2][k], O[4 * J + 2][k + 2], O[4 * J + 3][k], O[4 * J + 3][k + 2]);
    }
    CLK(24);
  }

  uint32_t* const o = gin + keep((uint32_t)(inbox(4 * (8 * jI + w) + t, 4) - gin) + hI * 16 + g * 2);
  const uint32_t sdst5 = keep(sb + OFF_BS5 + (16 * w + g) * 16 + t * 4), lane16 = keep(sb + lane * 16);
  const uint32_t* x2i[4];
#pragma unroll
  for (int i = 0; i < 4; i++) x2i[i] = gin + keep((uint32_t)(nearbox(4 * hI + i, 4) - gin) + 512 + tid * 2);
  {
    const uint32_t* px = pin(inbox(cta, w >> 1) + (w & 1) * 512 + lane * 2);
    uint32_t* const x2o = pin(inbox(cta, 4) + 512 + tid * 2);
    uint32_t* const x2p = pin(gin + blk(cta, 4, selector(cta) ^ 1) + 512 + tid * 2);
    const uint32_t q4 = lds1(sb + OFF_SEL + 4 * hI) ^ 0x00010100u;
    const uint32_t same = pin((uint32_t)(q4 == 0 || q4 == 0x01010101u));
    mbar_wait(BAR(BAR_TS));
    anchor = lds1(sb + OFF_TS);
    const uint32_t sdst = keep(sb + OFF_BS4 + w * 272 + lane * 8), ssrc = keep(sb + OFF_BS4 + (lane & 7) * 272 + (lane >> 3) * 16);
    float d[4] = {0.f, 0.f, 0.f, 0.f};
    if (cta >= NFF) {
#pragma unroll
      for (int s = 0; s < 4; s++) { cbf[s].x = silu2(cbf[s].x); cbf[s].y = silu2(cbf[s].y); }
    } else {
      check_units<4, 64>(sbf, pcb);
      check_units<4, 64>(cbf, pcb + 2048);
#pragma unroll
      for (int s = 0; s < 4; s++) { cbf[s].x = hadd2(cbf[s].x, ONE2); cbf[s].y = hadd2(cbf[s].y, ONE2); }
    }
    wait_clk(thand, T.D_X1);
    wait_clk(anchor, T.A_X1 - T.R_X0);
    uint2 v[8];
    load_units<8, 64>(v, px);
    if (T.R_X0) {
      wait_clk(anchor, T.A_X1);
#pragma unroll
      for (int i = 0; i < 8; i++) reload_unit(v[i], px + i * 64);
    }
    CLK(25);
    const bool early = __all_sync(~0u, mbar_test(BAR(BAR_WUV + wg)));
    if (early) load_a_t(aw, abase + OFF_WUV);
    mbar_wait(BAR(BAR_WV));
    const float4 wa = ldsf4(sb + OFF_WV + w * 32), wb = ldsf4(sb + OFF_WV + w * 32 + 16);
    const float wv[8] = {wa.x, wa.y, wa.z, wa.w, wb.x, wb.y, wb.z, wb.w};
    CLK(27);
    uint32_t it = opaque0;
    bool ok;
#pragma unroll 1
    do {
      if (it) {
#pragma unroll
        for (int i = 0; i < 8; i++) reload_unit(v[i], px + i * 64);
        if (it > SPIN_LIMIT) __trap();
      }
      it++;
      float a0 = 0.f, a1 = 0.f, a2 = 0.f, a3 = 0.f;
#pragma unroll
      for (int i = 0; i < 8; i++) { a0 += wv[i] * bf_lo(v[i].x); a1 += wv[i] * bf_hi(v[i].x); a2 += wv[i] * bf_lo(v[i].y); a3 += wv[i] * bf_hi(v[i].y); }
      ok = __all_sync(~0u, min_flags(v) != 0);
      sts2(sdst, pack_bf16(a0, a1), pack_bf16(a2, a3));
    } while (!ok);
    CLK(29);
    cbar();
    uint32_t b[4][4];
#pragma unroll
    for (int kk = 0; kk < 4; kk++) ldsm4(b[kk], ssrc + kk * 64);
    if (__builtin_expect(!early, 0)) { mbar_wait(BAR(BAR_WUV + wg)); load_a_t(aw, abase + OFF_WUV); }
    mma128(d, aw, b);
    const uint32_t c0 = pack_bf16(d[0], d[1]), c1 = pack_bf16(d[2], d[3]);
    stg_u64(x2o, c0, c1);
    stg_u64_unless(same, x2p, c0, c1);
    ITS(4, it - 1);
    tstore = clk32();
    CLK(30);
  }
  {
    float d[4] = {0.f, 0.f, 0.f, 0.f};
    wait_clk(tstore, T.D_X2);
    uint2 v[4];
#pragma unroll
    for (int i = 0; i < 4; i++) v[i] = ldg_u64(x2i[i]);
    const bool early = __all_sync(~0u, mbar_test(BAR(BAR_WO + wg)));
    if (early) load_a_t(aw, abase + OFF_WO);
    CLK(31);
    uint32_t it = opaque0;
    bool ok;
#pragma unroll 1
    do {
      if (it) {
#pragma unroll
        for (int i = 0; i < 4; i++) reload_unit(v[i], x2i[i]);
        if (it > SPIN_LIMIT) __trap();
      }
      it++;
      ok = __all_sync(~0u, min_flags(v) != 0);
      sum4_to_smem(v, sdst5);
    } while (!ok);
    CLK(32);
    cbar();
    uint32_t b[4][4];
#pragma unroll
    for (int kk = 0; kk < 4; kk++) ldsm4t(b[kk], lane16 + OFF_BS5 + kk * 512);
    if (__builtin_expect(!early, 0)) { mbar_wait(BAR(BAR_WO + wg)); load_a_t(aw, abase + OFF_WO); }
    mma128(d, aw, b);
    stg_u64(o, movm(pack_bf16(d[0], d[1])), movm(pack_bf16(d[2], d[3])));
    ITS(5, it - 1);
    tstore = clk32();
    CLK(33);
    if (lane == 0) mbar_arrive(BAR(BAR_P5D));
  }
  if (cta < NFF) {
    const int mi = lane >> 3, r = lane & 7;
    uint32_t a1[2][4][4], a2[2][2][4];
    const int lp = (tid >> 2) & 31, kq = tid & 3;
    const int fo = 16 * wg + (lp >> 2) + 8 * (kq >> 1), bo = 2 * (lp & 3) + (kq & 1);
    const uint32_t* xb = gin + keep((uint32_t)(nearbox(cta & ~15, 6 + wg) - gin) + (16 * wq + t) * 16 + g * 2);
    uint32_t* const ox[2] = {gin + keep((uint32_t)(inbox(64 * hh + 8 * w + t, 5) - gin) + bs * 16 + g * 2), gin + keep((uint32_t)(inbox(64 * hh + 8 * w + 4 + t, 5) - gin) + bs * 16 + g * 2)};
    const uint32_t a1base = keep(sb + OFF_W1 + (64 * w + 8 * (mi >> 1) + r) * 64 + (((mi & 1) ^ (r >> 1)) << 4));
    const uint32_t a2base = keep(sb + OFF_W2 + (w >> 1) * 4096 + (8 * (mi >> 1) + r) * 128 + (((4 * (w & 1) + (mi & 1)) ^ r) << 4));
    const uint32_t s_g = keep(sb + OFF_REDG + w * 1024 + lane * 16), l_g = keep(sb + OFF_REDG + tid * 4);
    const uint32_t s_s = keep(sb + (t == (g >> 1) ? OFF_REDS + g * 80 + w * 8 : OFF_BS4 + tid * 8));
    const uint32_t l_s = keep(sb + OFF_REDS + bo * 80), s_h = keep(sb + OFF_H1 + fo * 16 + bo * 2);
    mbar_wait(BAR(BAR_W1));
#pragma unroll
    for (int i = 0; i < 8; i++) ldsm4t(a1[i & 1][i >> 1], (a1base ^ ((i & 1) << 5)) + (i >> 1) * 1024);
    {
      float u[2][2][4] = {};
#pragma unroll
      for (int s = 0; s < 4; s++)
#pragma unroll
        for (int mt = 0; mt < 2; mt++) { mma16816(u[0][mt], a1[mt][s], cbf[s].x, cbf[s].y); mma16816(u[1][mt], a1[mt][s], sbf[s].x, sbf[s].y); }
#pragma unroll
      for (int i = 0; i < 4; i++) sts4f(s_g + (OFF_REDU - OFF_REDG) + (i >> 1) * 8192 + (i & 1) * 512, u[i >> 1][i & 1][0], u[i >> 1][i & 1][1], u[i >> 1][i & 1][2], u[i >> 1][i & 1][3]);
    }
    CLK(34);
    wait_clk(tstore, T.D_X3B);
    wait_clk(anchor, T.A_X1 + T.R_X3A + T.R_X3B);
    uint2 x[4];
    load_units<4, 64>(x, xb);
    float U, V;
    {
      cbar();
      float u[8], v[8];
#pragma unroll
      for (int i = 0; i < 8; i++) { u[i] = ldsf(l_g + (OFF_REDU - OFF_REDG) + i * 1024); v[i] = ldsf(l_g + (OFF_REDV - OFF_REDG) + i * 1024); }
      U = pin(((u[0] + u[1]) + (u[2] + u[3])) + ((u[4] + u[5]) + (u[6] + u[7])));
      V = pin(((v[0] + v[1]) + (v[2] + v[3])) + ((v[4] + v[5]) + (v[6] + v[7])));
    }
    auto load_a2 = [&] {
#pragma unroll
      for (int i = 0; i < 4; i++) ldsm4t(a2[i >> 1][i & 1], (a2base ^ ((i >> 1) << 5)) + (i & 1) * 2048);
    };
    const bool early = __all_sync(~0u, mbar_test(BAR(BAR_W2)));
    if (early) load_a2();
    CLK(35);
    uint32_t it = opaque0;
    float G[2][2][4], S[2][4];
#pragma unroll 1
    do {
      if (it) {
#pragma unroll
        for (int i = 0; i < 4; i++) reload_unit(x[i], xb + i * 64);
        if (it > SPIN_LIMIT) __trap();
      }
      it++;
#pragma unroll
      for (int i = 0; i < 8; i++) { G[0][i >> 2][i & 3] = G[1][i >> 2][i & 3] = S[i >> 2][i & 3] = 0.f; }
      uint32_t y[4][2];
#pragma unroll
      for (int s = 0; s < 4; s++) { y[s][0] = hmul2(x[s].x, cbf[s].x); y[s][1] = hmul2(x[s].y, cbf[s].y); }
#pragma unroll
      for (int s2 = 0; s2 < 4; s2 += 2) {
#pragma unroll
        for (int s = s2; s < s2 + 2; s++) { mma16816(G[0][s & 1], a1[0][s], y[s][0], y[s][1]); mma16816(G[1][s & 1], a1[1][s], y[s][0], y[s][1]); }
#pragma unroll
        for (int s = s2; s < s2 + 2; s++) { const uint32_t sx[4] = {x[s].x, ONE2, x[s].y, ONE2}; mma16816(S[s & 1], sx, x[s].x, x[s].y); }
      }
    } while (!__all_sync(~0u, min_flags(x) != 0));
#pragma unroll
    for (int mt = 0; mt < 2; mt++)
      sts4f(s_g + mt * 512, G[mt][0][0] + G[mt][1][0], G[mt][0][1] + G[mt][1][1], G[mt][0][2] + G[mt][1][2], G[mt][0][3] + G[mt][1][3]);
    sts2f(s_s, (g & 1) ? S[0][3] + S[1][3] : S[0][2] + S[1][2], (g & 1) ? S[0][1] + S[1][1] : S[0][0] + S[1][0]);
    CLK(37);
    cbar();
    {
      float gv[8];
      float4 sv[4];
#pragma unroll
      for (int i = 0; i < 4; i++) sv[i] = ldsf4(l_s + i * 16);
#pragma unroll
      for (int i = 0; i < 8; i++) gv[i] = ldsf(l_g + i * 1024);
      const float s1 = ((sv[0].x + sv[0].z) + (sv[1].x + sv[1].z)) + ((sv[2].x + sv[2].z) + (sv[3].x + sv[3].z));
      const float s2 = ((sv[0].y + sv[0].w) + (sv[1].y + sv[1].w)) + ((sv[2].y + sv[2].w) + (sv[3].y + sv[3].w));
      const float gsum = ((gv[0] + gv[1]) + (gv[2] + gv[3])) + ((gv[4] + gv[5]) + (gv[6] + gv[7]));
      const float mu = s1 * (1.f / 512.f);
      float rs;
      asm("rsqrt.approx.ftz.f32 %0, %1;" : "=f"(rs) : "f"(fmaxf(s2 * (1.f / 512.f) - mu * mu, 0.f) + 1e-5f));
      const float hv = fmaxf(rs * (gsum - mu * U) + V, 0.f);
      asm volatile("st.shared.u16 [%0], %1;" ::"r"(s_h), "h"(__bfloat16_as_ushort(__float2bfloat16(hv))) : "memory");
    }
    ITS(6, it - 1);
    CLK(38);
    cbar();
    uint32_t b[4];
    ldsm4t(b, lane16 + OFF_H1);
    if (!early) { mbar_wait(BAR(BAR_W2)); load_a2(); }
    float o[2][2][4] = {};
#pragma unroll
    for (int i = 0; i < 4; i++) mma16816(o[i >> 1][i & 1], a2[i >> 1][i & 1], b[2 * (i & 1)], b[2 * (i & 1) + 1]);
#pragma unroll
    for (int mb = 0; mb < 2; mb++)
      stg_u64(ox[mb], movm(pack_bf16(o[mb][0][0] + o[mb][1][0], o[mb][0][1] + o[mb][1][1])), movm(pack_bf16(o[mb][0][2] + o[mb][1][2], o[mb][0][3] + o[mb][1][3])));
    CLK(39);
    if (lane == 0) mbar_arrive(BAR(BAR_P7D));
  } else {
    const int mi = lane >> 3, r = lane & 7;
    mbar_wait(BAR(BAR_W1));
#pragma unroll
    for (int mt = 0; mt < 2; mt++) {
      float u[4] = {0.f, 0.f, 0.f, 0.f};
#pragma unroll
      for (int ks = 0; ks < 4; ks++) ldsm4t(aw[4 * mt + ks], sb + OFF_W1 + (64 * w + 16 * ks + 8 * (mi >> 1) + r) * 64 + (((2 * mt + (mi & 1)) ^ (r >> 1)) << 4));
#pragma unroll
      for (int ks = 0; ks < 4; ks++) mma16816(u, aw[4 * mt + ks], cbf[ks].x, cbf[ks].y);
      sts4f(sb + OFF_REDU + w * 1024 + mt * 512 + lane * 16, u[0], u[1], u[2], u[3]);
    }
    cbar();
    if (w < 2) {
      float4 v[8];
#pragma unroll
      for (int i = 0; i < 8; i++) v[i] = ldsf4(sb + OFF_REDU + i * 1024 + tid * 16);
      stg_u64(gs->MOD2[par] + (96 + 2 * (cta - NFF) + w) * 64 + t * 16 + g * 2,
              movm(pack_bf16(((v[0].x + v[1].x) + (v[2].x + v[3].x)) + ((v[4].x + v[5].x) + (v[6].x + v[7].x)), ((v[0].y + v[1].y) + (v[2].y + v[3].y)) + ((v[4].y + v[5].y) + (v[6].y + v[7].y)))),
              movm(pack_bf16(((v[0].z + v[1].z) + (v[2].z + v[3].z)) + ((v[4].z + v[5].z) + (v[6].z + v[7].z)), ((v[0].w + v[1].w) + (v[2].w + v[3].w)) + ((v[4].w + v[5].w) + (v[6].w + v[7].w)))));
    }
    CLK(26);
  }
  CLK_DUMP();
}

typedef CUresult (*EncodeTiledFn)(CUtensorMap*, CUtensorMapDataType, cuuint32_t, void*, const cuuint64_t*, const cuuint64_t*,
                                  const cuuint32_t*, const cuuint32_t*, CUtensorMapInterleave, CUtensorMapSwizzle,
                                  CUtensorMapL2promotion, CUtensorMapFloatOOBfill);

struct Dim { uint64_t size, stride; uint32_t box; };
template <int R> void encode_map(EncodeTiledFn enc, CUtensorMap* m, const void* base, const Dim (&d)[R], CUtensorMapSwizzle sw, CUtensorMapL2promotion promo) {
  cuuint64_t dims[R], strides[R];
  cuuint32_t box[R], es[R];
  for (int i = 0; i < R; i++) { dims[i] = d[i].size; strides[i] = d[i].stride; box[i] = d[i].box; es[i] = 1; }
  enc(m, CU_TENSOR_MAP_DATA_TYPE_BFLOAT16, R, const_cast<void*>(base), dims, strides + 1, box, es, CU_TENSOR_MAP_INTERLEAVE_NONE, sw, promo,
      CU_TENSOR_MAP_FLOAT_OOB_FILL_NONE);
}

}

extern "C" void kernel_launch(void* const* d_in, const int* in_sizes, int n_in, void* d_out, int out_size) {
  (void)in_sizes; (void)n_in; (void)out_size;
  static EncodeTiledFn enc = nullptr;
  static Scratch* scratch = nullptr;
  static uint32_t* inbox = nullptr;
  if (!enc) {
    void* sp = nullptr;
    cudaGetSymbolAddress(&sp, g_s);
    scratch = (Scratch*)sp;
    cudaGetSymbolAddress(&sp, g_in);
    inbox = (uint32_t*)(((uintptr_t)sp + 0xfffff) & ~(uintptr_t)0xfffff);
    void* fn = nullptr;
    cudaDriverEntryPointQueryResult q;
    cudaGetDriverEntryPoint("cuTensorMapEncodeTiled", &fn, cudaEnableDefault, &q);
    enc = (EncodeTiledFn)fn;
    cudaFuncSetAttribute(fused_decode_kernel, cudaFuncAttributeMaxDynamicSharedMemorySize, SMEM_BYTES);
  }
  const CUtensorMapSwizzle S128 = CU_TENSOR_MAP_SWIZZLE_128B, S0 = CU_TENSOR_MAP_SWIZZLE_NONE;
  const CUtensorMapL2promotion L0 = CU_TENSOR_MAP_L2_PROMOTION_NONE, L128 = CU_TENSOR_MAP_L2_PROMOTION_L2_128B;
  Params P;
  encode_map<2>(enc, &P.wq, d_in[2], {{4096, 2, 64}, {512, 8192, 64}}, S128, L0);
  encode_map<5>(enc, &P.wuk, d_in[3], {{4096, 2, 64}, {2, 8192, 2}, {4, 4 * 8192, 4}, {2, 2 * 8192, 2}, {32, 16 * 8192, 4}}, S128, L0);
  encode_map<2>(enc, &P.wm2, d_in[10], {{3072, 2, 16}, {512, 6144, 256}}, S0, L128);
  encode_map<2>(enc, &P.wm3, d_in[10], {{3072, 2, 32}, {512, 6144, 256}}, CU_TENSOR_MAP_SWIZZLE_64B, L128);
  encode_map<3>(enc, &P.ckv2, d_in[1], {{64, 2, 64}, {8 * 4096, 1024, 64}, {8, 128, 2}}, S128, L0);
  encode_map<3>(enc, &P.ckv1, d_in[1], {{64, 2, 64}, {8 * 4096, 1024, 64}, {8, 128, 1}}, S128, L0);
  encode_map<5>(enc, &P.wuv, d_in[4], {{4096, 2, 64}, {2, 8 * 8192, 2}, {8, 64 * 8192, 4}, {8, 8192, 8}, {4, 16 * 8192, 1}}, S128, L0);
  encode_map<2>(enc, &P.wo, d_in[5], {{512, 2, 64}, {4096, 1024, 64}}, S128, L0);
  encode_map<2>(enc, &P.w1, d_in[7], {{1792, 2, 32}, {512, 3584, 256}}, CU_TENSOR_MAP_SWIZZLE_64B, L128);
  encode_map<3>(enc, &P.w2, d_in[8], {{64, 2, 64}, {1792, 1024, 32}, {8, 128, 2}}, S128, L0);
  fused_decode_kernel<<<NCTA, NTHREADS, SMEM_BYTES>>>((__nv_bfloat16*)d_out, scratch, (const uint8_t*)d_in[10], (const uint8_t*)d_in[0],
                     (const uint8_t*)d_in[9], inbox,
                     P);
}
```

```cpp
#include <cuda_runtime.h>
#include <cuda.h>
#include <cuda_bf16.h>
#include <stdint.h>
#define V4 1

namespace {

constexpr int NCTA = 128;
constexpr int NTHREADS = 320;
constexpr int NFG = 56;
constexpr int NFF = 2 * NFG;
constexpr int NSYNC = 4;

constexpr uint32_t OFF_RING = 0;
constexpr uint32_t OFF_WUK = 131072;
constexpr uint32_t OFF_WQ = 131072 + 32768;
constexpr uint32_t OFF_WM2 = 65536 + 49152;
constexpr uint32_t OFF_WUV = 131072;
constexpr uint32_t OFF_WO = 131072 + 32768;
constexpr uint32_t OFF_W1 = 0;
constexpr uint32_t OFF_W2 = 32768;
constexpr uint32_t OFF_Q = 196608;
constexpr uint32_t OFF_PT = 212992;
constexpr uint32_t OFF_SCR = 217088;
constexpr uint32_t OFF_XS = 65536;
constexpr uint32_t OFF_CS = 65536 + 8192;
constexpr uint32_t OFF_P0S = 65536 + 16384;
constexpr uint32_t OFF_BS1 = OFF_SCR + 2048;
constexpr uint32_t OFF_BS2 = OFF_SCR + 4096;
constexpr uint32_t OFF_P0B = OFF_SCR + 6144;
constexpr uint32_t OFF_XN = OFF_SCR + 8192;
constexpr uint32_t OFF_RED = OFF_SCR + 10496;
constexpr uint32_t OFF_ALPHA = OFF_SCR + 11072;
constexpr uint32_t OFF_WV = OFF_SCR + 6144;
constexpr uint32_t OFF_SEL = OFF_SCR + 10752;
constexpr uint32_t OFF_TS = OFF_SCR + 11136;
constexpr uint32_t OFF_BARS = OFF_SCR + 11264;
constexpr uint32_t SMEM_BYTES = OFF_BARS + 512;
constexpr uint32_t OFF_BS4 = OFF_Q;
constexpr uint32_t OFF_H1 = OFF_Q + 2304;
constexpr uint32_t OFF_REDS = OFF_Q + 2816;
constexpr uint32_t OFF_BS5 = OFF_Q + 4096;
constexpr uint32_t OFF_REDG = OFF_Q + 8192;
constexpr uint32_t OFF_REDU = 65536;
constexpr uint32_t OFF_REDV = 65536 + 8192;

constexpr int BAR_FULL = 0;
constexpr int BAR_LAST = 28;
constexpr int BAR_WUK = 33, BAR_WM2 = 35, BAR_WUV = 36, BAR_WO = 38, BAR_W1 = 40, BAR_W2 = 41;
constexpr int BAR_ALLCLR = 42, BAR_TS = 43, BAR_WV = 44;
constexpr int BAR_EMPTY = 45;
constexpr int BAR_P0BD = 53;
constexpr int BAR_P1D = 54, BAR_P2D = 55;
constexpr int BAR_P5D = 56, BAR_P7D = 57;
constexpr int NBARS = 58;
constexpr int BAR_XC = 58, BAR_WQ = 59;
constexpr int BAR_C = 61;
constexpr uint32_t SB = 1024;

#define TUNE_LIST(X) \
  X(PC_T0, 355) X(PC_P1, 320) X(PC_PM, 225) X(PC_P2, 320) X(PC_STAG, 390) X(PC_SL, 500) X(PC_NW, 6) \
  X(T_UV, 165) X(P_UV, 285) X(PF_N, 3) X(T_PF, 1060) X(P_PF, 230) X(T_O, 2180) X(P_O, 145) X(T_1, 2990) X(T_2, 3860) X(T_GB, 3370) X(P_F, 360) \
  X(PR_T0, 1000) X(PR_N, 4) X(CLR_T0, 3900) X(CLR_CLK, 190) \
  X(D_MOD, 1450) X(D_QP, 1200) X(D_QX, 950) X(TS_P, 1) X(TS_O, 1945) X(D_TS, 700) X(A_M, 1550) X(D_X1, 1350) X(A_X1, 2460) X(R_X0, 1550) \
  X(D_X2, 290) X(D_X3A, 60) X(R_X3A, 2835) X(D_X3B, 800) X(R_X3B, 915) X(D_FIN, 315) X(R_FIN, 1540)
struct Tune {
#define X(n, v) static constexpr int n = v;
  TUNE_LIST(X)
#undef X
};

struct Scratch {
  uint32_t MOD1[2][4 * 64 * 64];
  uint32_t MOD2[2][128 * 64];
  uint32_t QP[2][128 * 256 * 2];
  uint32_t QX[2][8 * 32 * 256];
  uint32_t epoch;
  uint32_t pad[31];
  uint32_t sync[NSYNC][32];
};
__device__ Scratch g_s;
__device__ uint32_t g_in[(128 + 16) * 16384];
__device__ __forceinline__ uint32_t blk(int c, int k, uint32_t sel) { return c * 16384 + k * 2048 + ((sel ^ k) & 1) * 1024; }
__device__ __forceinline__ uint32_t flip(int c) { return c ^ (c >> 1) ^ (c >> 3); }

#define CLK_DECL
#define CLK(i) do {} while (0)
#define CLK_DUMP() do {} while (0)
#define ITS(i, v) do {} while (0)

struct Params {
  CUtensorMap wq, wuk, wm2, wm3, ckv2, ckv1, wuv, wo, w1, w2;
};

__device__ __forceinline__ void mbar_init(uint32_t bar, int cnt) { asm volatile("mbarrier.init.shared::cta.b64 [%0], %1;" ::"r"(bar), "r"(cnt)); }
__device__ __forceinline__ void mbar_expect(uint32_t bar, uint32_t bytes) { asm volatile("mbarrier.arrive.expect_tx.shared::cta.b64 _, [%0], %1;" ::"r"(bar), "r"(bytes) : "memory"); }
__device__ __forceinline__ void mbar_arrive(uint32_t bar) { asm volatile("mbarrier.arrive.shared::cta.b64 _, [%0];" ::"r"(bar) : "memory"); }
__device__ __forceinline__ uint32_t clk32() { unsigned long long c; asm volatile("mov.u64 %0, %%clock64;" : "=l"(c) :: "memory"); return (uint32_t)c; }
__device__ __forceinline__ uint32_t gtime32() { uint32_t c; asm volatile("mov.u32 %0, %%globaltimer_lo;" : "=r"(c) :: "memory"); return c; }
__device__ __forceinline__ void wait_clk(uint32_t t0, int clocks) { while ((int)(clk32() - t0) < clocks) {} }
__device__ __forceinline__ void backoff(int clocks) { if (clocks > 0) wait_clk(clk32(), clocks); }
__device__ __forceinline__ void until_ns(uint32_t ns) { while ((int)(gtime32() - ns) < 0) {} }
__device__ __forceinline__ void slot(uint32_t& tn, int slack) {
  uint32_t now;
  do { now = gtime32(); } while ((int)(now - tn) < 0);
  if ((int)(now - tn) > slack) tn = now - slack;
}
template <typename T> __device__ __forceinline__ T* pin(T* p) { asm volatile("" : "+l"(p)); return p; }
__device__ __forceinline__ uint32_t pin(uint32_t v) { asm volatile("" : "+r"(v)); return v; }
__device__ __forceinline__ float pin(float v) { asm volatile("" : "+f"(v)); return v; }
constexpr int SPIN_LIMIT = 1 << 22;
__device__ __forceinline__ void mbar_wait(uint32_t bar) {
  asm volatile("{\n.reg .pred p;\n.reg .u32 c;\nmov.u32 c, 0;\n"
               "MW_LOOP:\nmbarrier.try_wait.parity.shared::cta.b64 p, [%0], 0;\n@p bra MW_DONE;\n"
               "add.u32 c, c, 1;\nsetp.lt.u32 p, c, 4194304;\n@p bra MW_LOOP;\ntrap;\nMW_DONE:\n}"
               ::"r"(bar) : "memory");
}
__device__ __forceinline__ bool mbar_test(uint32_t bar) {
  uint32_t ok;
  asm volatile("{\n.reg .pred p;\nmbarrier.test_wait.parity.shared::cta.b64 p, [%1], 0;\nselp.u32 %0,1,0,p;\n}" : "=r"(ok) : "r"(bar) : "memory");
  return ok;
}
__device__ __forceinline__ void tma2d(uint32_t dst, const CUtensorMap* m, int c0, int c1, uint32_t bar, uint64_t pol) {
  asm volatile("cp.async.bulk.tensor.2d.shared::cluster.global.mbarrier::complete_tx::bytes.L2::cache_hint [%0], [%1, {%3,%4}], [%2], %5;"
               ::"r"(dst), "l"(m), "r"(bar), "r"(c0), "r"(c1), "l"(pol) : "memory");
}
__device__ __forceinline__ void tma2d_nohint(uint32_t dst, const CUtensorMap* m, int c0, int c1, uint32_t bar) {
  asm volatile("cp.async.bulk.tensor.2d.shared::cluster.global.mbarrier::complete_tx::bytes [%0], [%1, {%3,%4}], [%2];"
               ::"r"(dst), "l"(m), "r"(bar), "r"(c0), "r"(c1) : "memory");
}
__device__ __forceinline__ void tma3d(uint32_t dst, const CUtensorMap* m, int c0, int c1, int c2, uint32_t bar, uint64_t pol) {
  asm volatile("cp.async.bulk.tensor.3d.shared::cluster.global.mbarrier::complete_tx::bytes.L2::cache_hint [%0], [%1, {%3,%4,%5}], [%2], %6;"
               ::"r"(dst), "l"(m), "r"(bar), "r"(c0), "r"(c1), "r"(c2), "l"(pol) : "memory");
}
__device__ __forceinline__ void tma5d(uint32_t dst, const CUtensorMap* m, int c0, int c1, int c2, int c3, int c4, uint32_t bar, uint64_t pol) {
  asm volatile("cp.async.bulk.tensor.5d.shared::cluster.global.mbarrier::complete_tx::bytes.L2::cache_hint [%0], [%1, {%3,%4,%5,%6,%7}], [%2], %8;"
               ::"r"(dst), "l"(m), "r"(bar), "r"(c0), "r"(c1), "r"(c2), "r"(c3), "r"(c4), "l"(pol) : "memory");
}
__device__ __forceinline__ void bulk_ld(uint32_t dst, const void* src, uint32_t bytes, uint32_t bar) {
  asm volatile("cp.async.bulk.shared::cluster.global.mbarrier::complete_tx::bytes [%0], [%1], %2, [%3];" ::"r"(dst), "l"(src), "r"(bytes), "r"(bar) : "memory");
}
__device__ __forceinline__ void bar_sync(int id, int n) { asm volatile("barrier.cta.sync.aligned %0, %1;" ::"r"(id), "r"(n) : "memory"); }
__device__ __forceinline__ void cbar() { asm volatile("barrier.cta.sync.aligned 1, 256;" ::: "memory"); }
__device__ __forceinline__ bool bar_over(float ex) {
  uint32_t over;
  asm volatile("{\n.reg .pred p, q;\nsetp.gtu.f32 p, %1, 0f42700000;\nbarrier.cta.red.or.aligned.pred q, 4, 256, p;\nselp.u32 %0, 1, 0, q;\n}"
               : "=r"(over) : "f"(ex) : "memory");
  return over;
}

__device__ __forceinline__ uint32_t ldg_nc1(const void* p) { uint32_t v; asm volatile("ld.global.nc.L1::no_allocate.u32 %0, [%1];" : "=r"(v) : "l"(p)); return v; }
__device__ __forceinline__ uint2 ldg_nc2(const void* p) { uint2 v; asm volatile("ld.global.nc.v2.u32 {%0,%1}, [%2];" : "=r"(v.x), "=r"(v.y) : "l"(p)); return v; }
__device__ __forceinline__ uint4 ldg_nc4(const void* p) { uint4 v; asm volatile("ld.global.nc.L1::no_allocate.v4.u32 {%0,%1,%2,%3}, [%4];" : "=r"(v.x), "=r"(v.y), "=r"(v.z), "=r"(v.w) : "l"(p)); return v; }
__device__ __forceinline__ uint32_t ldg_rlx1(const void* p) { uint32_t v; asm volatile("ld.relaxed.gpu.global.u32 %0, [%1];" : "=r"(v) : "l"(p) : "memory"); return v; }
__device__ __forceinline__ void stg4(void* p, uint4 v) { asm volatile("st.relaxed.gpu.global.v4.u32 [%0], {%1,%2,%3,%4};" ::"l"(p), "r"(v.x), "r"(v.y), "r"(v.z), "r"(v.w) : "memory"); }
__device__ __forceinline__ void stg1(void* p, uint32_t a) { asm volatile("st.relaxed.gpu.global.u32 [%0], %1;" ::"l"(p), "r"(a) : "memory"); }
__device__ __forceinline__ uint32_t nz(uint32_t w) { return max(w, 1u); }
__device__ __forceinline__ uint2 ldg_u64(const void* p) {
  uint2 v; asm volatile("{\n.reg .b64 a;\nld.relaxed.gpu.global.b64 a, [%2];\nmov.b64 {%0,%1}, a;\n}" : "=r"(v.x), "=r"(v.y) : "l"(p) : "memory"); return v;
}
__device__ __forceinline__ uint4 ldg_2u64(const void* p) {
  uint4 v; asm volatile("{\n.reg .b64 a, b;\nld.relaxed.gpu.global.v2.b64 {a, b}, [%4];\nmov.b64 {%0,%1}, a;\nmov.b64 {%2,%3}, b;\n}" : "=r"(v.x), "=r"(v.y), "=r"(v.z), "=r"(v.w) : "l"(p) : "memory"); return v;
}
__device__ __forceinline__ void stg_u64(void* p, uint32_t x, uint32_t y) {
  asm volatile("{\n.reg .b32 y;\nmax.u32 y, %2, 1;\nst.relaxed.gpu.global.v2.b32 [%0], {%1, y};\n}" ::"l"(p), "r"(x), "r"(y) : "memory");
}
__device__ __forceinline__ void red_u64(void* p, uint32_t x, uint32_t y) {
  asm volatile("{\n.reg .b32 y;\n.reg .b64 a;\nmax.u32 y, %2, 1;\nmov.b64 a, {%1, y};\nred.relaxed.gpu.global.or.b64 [%0], a;\n}" ::"l"(p), "r"(x), "r"(y) : "memory");
}
__device__ __forceinline__ void stg_u64_unless(uint32_t bad, void* p, uint32_t x, uint32_t y) {
  asm volatile("{\n.reg .b32 y;\n.reg .pred q;\nsetp.eq.u32 q, %3, 0;\nmax.u32 y, %2, 1;\n@q st.relaxed.gpu.global.v2.b32 [%0], {%1, y};\n}" ::"l"(p), "r"(x), "r"(y), "r"(bad) : "memory");
}

__device__ __forceinline__ void stg_cvt8(void* p, float a0, float a1, float b0, float b1, float c0, float c1, float d0, float d1) {
  asm volatile("{\n.reg .b32 x, y, z, w;\ncvt.rn.bf16x2.f32 x, %2, %1;\ncvt.rn.bf16x2.f32 y, %4, %3;\ncvt.rn.bf16x2.f32 z, %6, %5;\ncvt.rn.bf16x2.f32 w, %8, %7;\n"
               "max.u32 y, y, 1;\nmax.u32 w, w, 1;\nst.relaxed.gpu.global.v4.b32 [%0], {x, y, z, w};\n}"
               ::"l"(p), "f"(a0), "f"(a1), "f"(b0), "f"(b1), "f"(c0), "f"(c1), "f"(d0), "f"(d1) : "memory");
}
__device__ __forceinline__ uint32_t pack_bf16(float lo, float hi) { uint32_t r; asm("cvt.rn.bf16x2.f32 %0, %1, %2;" : "=r"(r) : "f"(hi), "f"(lo)); return r; }
__device__ __forceinline__ float bf_lo(uint32_t w) { return __uint_as_float(w << 16); }
__device__ __forceinline__ float bf_hi(uint32_t w) { return __uint_as_float(w & 0xffff0000u); }
__device__ __forceinline__ float ex2(float x) { float r; asm("ex2.approx.ftz.f32 %0, %1;" : "=f"(r) : "f"(x)); return r; }
__device__ __forceinline__ uint32_t hmul2(uint32_t a, uint32_t b) { uint32_t r; asm("mul.rn.bf16x2 %0, %1, %2;" : "=r"(r) : "r"(a), "r"(b)); return r; }
__device__ __forceinline__ uint32_t hadd2(uint32_t a, uint32_t b) { uint32_t r; asm("add.rn.bf16x2 %0, %1, %2;" : "=r"(r) : "r"(a), "r"(b)); return r; }
__device__ __forceinline__ uint32_t silu2(uint32_t v) { const float a = bf_lo(v), b = bf_hi(v); return pack_bf16(__fdividef(a, 1.f + __expf(-a)), __fdividef(b, 1.f + __expf(-b))); }
constexpr uint32_t ONE2 = 0x3f803f80u;

__device__ __forceinline__ void ldsm4(uint32_t (&r)[4], uint32_t a) { asm volatile("ldmatrix.sync.aligned.m8n8.x4.shared.b16 {%0,%1,%2,%3}, [%4];" : "=r"(r[0]), "=r"(r[1]), "=r"(r[2]), "=r"(r[3]) : "r"(a) : "memory"); }
__device__ __forceinline__ void ldsm4t(uint32_t (&r)[4], uint32_t a) { asm volatile("ldmatrix.sync.aligned.m8n8.x4.trans.shared.b16 {%0,%1,%2,%3}, [%4];" : "=r"(r[0]), "=r"(r[1]), "=r"(r[2]), "=r"(r[3]) : "r"(a) : "memory"); }
__device__ __forceinline__ void stsm4t(uint32_t a, uint32_t r0, uint32_t r1, uint32_t r2, uint32_t r3) { asm volatile("stmatrix.sync.aligned.m8n8.x4.trans.shared.b16 [%0], {%1,%2,%3,%4};" ::"r"(a), "r"(r0), "r"(r1), "r"(r2), "r"(r3) : "memory"); }
__device__ __forceinline__ uint32_t movm(uint32_t a) { uint32_t d; asm volatile("movmatrix.sync.aligned.m8n8.trans.b16 %0, %1;" : "=r"(d) : "r"(a)); return d; }
__device__ __forceinline__ void mma16816(float (&d)[4], const uint32_t (&a)[4], uint32_t b0, uint32_t b1) {
  asm volatile("mma.sync.aligned.m16n8k16.row.col.f32.bf16.bf16.f32 {%0,%1,%2,%3}, {%4,%5,%6,%7}, {%8,%9}, {%0,%1,%2,%3};"
               : "+f"(d[0]), "+f"(d[1]), "+f"(d[2]), "+f"(d[3]) : "r"(a[0]), "r"(a[1]), "r"(a[2]), "r"(a[3]), "r"(b0), "r"(b1));
}
__device__ __forceinline__ void sts1(uint32_t a, uint32_t v) { asm volatile("st.shared.u32 [%0], %1;" ::"r"(a), "r"(v) : "memory"); }
__device__ __forceinline__ void sts2(uint32_t a, uint32_t x, uint32_t y) { asm volatile("st.shared.v2.u32 [%0], {%1,%2};" ::"r"(a), "r"(x), "r"(y) : "memory"); }
__device__ __forceinline__ void sts4(uint32_t a, uint4 v) { asm volatile("st.shared.v4.u32 [%0], {%1,%2,%3,%4};" ::"r"(a), "r"(v.x), "r"(v.y), "r"(v.z), "r"(v.w) : "memory"); }
__device__ __forceinline__ void sts2f(uint32_t a, float x, float y) { asm volatile("st.shared.v2.f32 [%0], {%1,%2};" ::"r"(a), "f"(x), "f"(y) : "memory"); }
__device__ __forceinline__ void sts4f(uint32_t a, float x, float y, float z, float w) { asm volatile("st.shared.v4.f32 [%0], {%1,%2,%3,%4};" ::"r"(a), "f"(x), "f"(y), "f"(z), "f"(w) : "memory"); }
__device__ __forceinline__ void stsf(uint32_t a, float v) { asm volatile("st.shared.f32 [%0], %1;" ::"r"(a), "f"(v) : "memory"); }
__device__ __forceinline__ uint32_t lds1(uint32_t a) { uint32_t v; asm volatile("ld.shared.u32 %0, [%1];" : "=r"(v) : "r"(a) : "memory"); return v; }
__device__ __forceinline__ float ldsf(uint32_t a) { float v; asm volatile("ld.shared.f32 %0, [%1];" : "=f"(v) : "r"(a) : "memory"); return v; }
__device__ __forceinline__ float2 ldsf2(uint32_t a) { float2 v; asm volatile("ld.shared.v2.f32 {%0,%1}, [%2];" : "=f"(v.x), "=f"(v.y) : "r"(a) : "memory"); return v; }
__device__ __forceinline__ float4 ldsf4(uint32_t a) { float4 v; asm volatile("ld.shared.v4.f32 {%0,%1,%2,%3}, [%4];" : "=f"(v.x), "=f"(v.y), "=f"(v.z), "=f"(v.w) : "r"(a) : "memory"); return v; }
__device__ __forceinline__ void lds4(uint32_t (&r)[4], uint32_t a) { asm volatile("ld.shared.v4.u32 {%0,%1,%2,%3}, [%4];" : "=r"(r[0]), "=r"(r[1]), "=r"(r[2]), "=r"(r[3]) : "r"(a) : "memory"); }

__device__ __forceinline__ void wg_fence() { asm volatile("wgmma.fence.sync.aligned;" ::: "memory"); }
__device__ __forceinline__ void wg_commit() { asm volatile("wgmma.commit_group.sync.aligned;" ::: "memory"); }
template <int N> __device__ __forceinline__ void wg_wait() { asm volatile("wgmma.wait_group.sync.aligned %0;" ::"n"(N) : "memory"); }
__host__ __device__ constexpr uint32_t desc_lo(uint32_t off) { return ((SB + off) >> 4) | 0x10000u; }
template <int TA, int ACC> __device__ __forceinline__ void wgmma_n16(float (&d)[8], uint32_t da, uint32_t db) {
  asm volatile("{\n.reg .b64 da, db;\nmov.b64 da, {%8, 0x40000040};\nmov.b64 db, {%9, 0x40000040};\n"
               "wgmma.mma_async.sync.aligned.m64n16k16.f32.bf16.bf16 {%0,%1,%2,%3,%4,%5,%6,%7}, da, db, %11, 1, 1, %10, 0;\n}"
               : "+f"(d[0]), "+f"(d[1]), "+f"(d[2]), "+f"(d[3]), "+f"(d[4]), "+f"(d[5]), "+f"(d[6]), "+f"(d[7])
               : "r"(da), "r"(db), "n"(TA), "n"(ACC));
}
__device__ __forceinline__ void wgmma_n16_ones(float (&d)[8], uint32_t one, uint32_t db) {
  asm volatile("{\n.reg .b64 db;\nmov.b64 db, {%9, 0x40000040};\n"
               "wgmma.mma_async.sync.aligned.m64n16k16.f32.bf16.bf16 {%0,%1,%2,%3,%4,%5,%6,%7}, {%8,%8,%8,%8}, db, 1, 1, 1, 0;\n}"
               : "+f"(d[0]), "+f"(d[1]), "+f"(d[2]), "+f"(d[3]), "+f"(d[4]), "+f"(d[5]), "+f"(d[6]), "+f"(d[7])
               : "r"(one), "r"(db));
}
__device__ __forceinline__ void acc_fence(float (&d)[8]) {
  asm volatile("" : "+f"(d[0]), "+f"(d[1]), "+f"(d[2]), "+f"(d[3]), "+f"(d[4]), "+f"(d[5]), "+f"(d[6]), "+f"(d[7]) :: "memory");
}

template <int N, int STRIDE> __device__ __forceinline__ void load_units(uint2 (&v)[N], const uint32_t* p) {
#pragma unroll
  for (int i = 0; i < N; i++) v[i] = ldg_u64(p + i * STRIDE);
}
__device__ __forceinline__ void reload_unit(uint2& v, const uint32_t* p) {
  asm volatile("{\n.reg .pred q;\nsetp.eq.u32 q, %1, 0;\n@q ld.relaxed.gpu.global.v2.b32 {%0, %1}, [%2];\n}" : "+r"(v.x), "+r"(v.y) : "l"(p) : "memory");
}
template <int N> __device__ __forceinline__ uint32_t min_flags(const uint2 (&v)[N]) {
  uint32_t a = v[0].y, b = v[1].y;
#pragma unroll
  for (int i = 2; i < N; i += 2) { a = min(a, v[i].y); b = min(b, v[i + 1].y); }
  return min(a, b);
}
template <int N, int STRIDE> __device__ __forceinline__ int check_units(uint2 (&v)[N], const uint32_t* p) {
  int it = 0;
  while (!__all_sync(~0u, min_flags(v) != 0)) {
#pragma unroll
    for (int i = 0; i < N; i++) reload_unit(v[i], p + i * STRIDE);
    if (++it > SPIN_LIMIT) __trap();
  }
  return it;
}
__device__ __forceinline__ void sum4_to_smem(const uint2 (&v)[4], uint32_t dst) {
  const float c0 = (bf_lo(v[0].x) + bf_lo(v[1].x)) + (bf_lo(v[2].x) + bf_lo(v[3].x));
  const float c1 = (bf_hi(v[0].x) + bf_hi(v[1].x)) + (bf_hi(v[2].x) + bf_hi(v[3].x));
  const float c2 = (bf_lo(v[0].y) + bf_lo(v[1].y)) + (bf_lo(v[2].y) + bf_lo(v[3].y));
  const float c3 = (bf_hi(v[0].y) + bf_hi(v[1].y)) + (bf_hi(v[2].y) + bf_hi(v[3].y));
  sts1(dst, pack_bf16(c0, c1));
  sts1(dst + 128, pack_bf16(c2, c3));
}
__device__ __forceinline__ uint32_t a_t_offset(int w, int lane) {
  const int mi = lane >> 3, r = lane & 7;
  return (w >> 2) * 16384 + (8 * (mi >> 1) + r) * 128 + (((2 * (w & 3) + (mi & 1)) ^ r) << 4);
}
__device__ __forceinline__ void load_a_t(uint32_t (&a)[8][4], uint32_t base) {
#pragma unroll
  for (int ks = 0; ks < 8; ks++) ldsm4t(a[ks], base + ks * 2048);
}
__device__ __forceinline__ void mma128(float (&d)[4], const uint32_t (&a)[8][4], const uint32_t (&b)[4][4]) {
  float e[4][4] = {{d[0], d[1], d[2], d[3]}, {0.f, 0.f, 0.f, 0.f}, {0.f, 0.f, 0.f, 0.f}, {0.f, 0.f, 0.f, 0.f}};
#pragma unroll
  for (int kk = 0; kk < 4; kk++) { mma16816(e[(2 * kk) & 3], a[2 * kk], b[kk][0], b[kk][1]); mma16816(e[(2 * kk + 1) & 3], a[2 * kk + 1], b[kk][2], b[kk][3]); }
#pragma unroll
  for (int i = 0; i < 4; i++) d[i] = (e[0][i] + e[1][i]) + (e[2][i] + e[3][i]);
}
template <int NP> __device__ __forceinline__ bool sum_pieces(const uint32_t* p0, uint32_t one, float (&r)[4]) {
  uint2 v[NP / 4];
  load_units<NP / 4, 64>(v, p0);
  float d[4][4] = {};
#pragma unroll
  for (int i = 0; i < NP / 8; i++) { const uint32_t a[4] = {v[2 * i].x, v[2 * i].y, v[2 * i + 1].x, v[2 * i + 1].y}; mma16816(d[i & 3], a, one, one); }
  const bool ok = __all_sync(~0u, min_flags(v) != 0);
#pragma unroll
  for (int k = 0; k < 4; k++) r[k] = (d[0][k] + d[1][k]) + (d[2][k] + d[3][k]);
  return ok;
}
template <typename F> __device__ __forceinline__ float reduce_g(const float (&x)[4], int lane, F f) {
  const bool u4 = lane & 16, u3 = lane & 8;
  const float a0 = f(u4 ? x[2] : x[0], __shfl_xor_sync(~0u, u4 ? x[0] : x[2], 16));
  const float a1 = f(u4 ? x[3] : x[1], __shfl_xor_sync(~0u, u4 ? x[1] : x[3], 16));
  const float b = f(u3 ? a1 : a0, __shfl_xor_sync(~0u, u3 ? a0 : a1, 8));
  return f(b, __shfl_xor_sync(~0u, b, 4));
}

__global__ void __launch_bounds__(NTHREADS, 1)
fused_decode_kernel(__nv_bfloat16* __restrict__ gout, Scratch* __restrict__ gs, const uint8_t* __restrict__ gwmod,
                    const uint8_t* __restrict__ gx, const uint8_t* __restrict__ gc, uint32_t* __restrict__ gin,
                    const __grid_constant__ Params P) {
  constexpr Tune T{};
  extern __shared__ __align__(1024) uint8_t smem_raw[];
  constexpr uint32_t sb = SB;
  const int tid = __shfl_xor_sync(0xffffffffu, threadIdx.x ^ 1, 1), lane = tid & 31;
  const int w = __shfl_sync(0xffffffffu, threadIdx.x >> 5, 0);
  const int cta = blockIdx.x;
  auto keep = [&](uint32_t v) { return __shfl_sync(~0u, v, lane); };
  auto BAR = [](int i) { return SB + OFF_BARS + 8 * i; };
  auto selector = [&](int c) { uint32_t v; asm volatile("ld.shared.u8 %0, [%1];" : "=r"(v) : "r"(sb + OFF_SEL + c) : "memory"); return v; };
  auto inbox = [&](int c, int k) { return gin + blk(c, k, selector(c)); };
  auto nearbox = [&](int c, int k) { return gin + blk(c, k, selector(cta) ^ flip((c ^ cta) & 15)); };
  const int g = lane >> 2, t = lane & 3;
  const int hI = cta >> 2, jI = cta & 3;
  const int bs = cta >> 1, hh = cta & 1;

  CLK_DECL;
  CLK(0);
  if (w == 8) {
    CLK(7);
    const uint32_t t_entry = gtime32();
    CLK(8);
    if (lane == 0) {
      if ((uint32_t)__cvta_generic_to_shared(smem_raw) != SB) __trap();
      mbar_init(BAR(BAR_WQ), 1); mbar_init(BAR(BAR_WQ + 1), 1); mbar_init(BAR(BAR_XC), 1); mbar_init(BAR(BAR_C), 1);
      asm volatile("fence.mbarrier_init.release.cluster;" ::: "memory");
      asm volatile("prefetch.tensormap [%0];" ::"l"(&P.wq) : "memory");
      mbar_expect(BAR(BAR_XC), 8192); mbar_expect(BAR(BAR_C), 8192); mbar_expect(BAR(BAR_WQ), 16384); mbar_expect(BAR(BAR_WQ + 1), 16384);
      CLK(9);
    }
    __syncwarp();
    asm volatile("barrier.cta.arrive.aligned 0, %0;" ::"n"(NTHREADS) : "memory");
    CLK(10);
    uint32_t tn = t_entry + T.PC_T0 + ((bs * 37) & 63) * T.PC_STAG / 64;
    const int h = hI, j = jI;
    if (lane == 0) {
      uint64_t pol; asm volatile("createpolicy.fractional.L2::evict_first.b64 %0, 1.0;" : "=l"(pol));
#pragma unroll
      for (int u = 0; u < 4; u++) {
        until_ns(tn + u * T.PC_P1);
        if (u == 0) CLK(11);
        tma2d(sb + OFF_WQ + u * 8192, &P.wq, 128 * h + 64 * (u >> 1), 128 * j + 64 * (u & 1), BAR(BAR_WQ + (u >> 1)), pol);
        if (u == 0) {
#pragma unroll
          for (int i = 0; i < 8; i++) { const int o = ((i + cta) & 3) * 2048; bulk_ld(sb + OFF_XS + (i >> 2) * 8192 + o, (i < 4 ? gx : gc) + o, 2048, BAR(i < 4 ? BAR_XC : BAR_C)); }
          CLK(1);
          asm volatile("prefetch.tensormap [%0];" ::"l"(&P.wuk) : "memory");
          asm volatile("prefetch.tensormap [%0];" ::"l"(&P.wm2) : "memory");
          asm volatile("prefetch.tensormap [%0];" ::"l"(&P.ckv2) : "memory");
        }
      }
    }
    __syncwarp();
    tn += 4 * T.PC_P1;
    bar_sync(5, 64);
    if (lane == 0) {
      uint64_t pol; asm volatile("createpolicy.fractional.L2::evict_first.b64 %0, 1.0;" : "=l"(pol));
#pragma unroll
      for (int u = 0; u < 4; u++) {
        if (u & 1) mbar_wait(BAR(BAR_WQ + (u >> 1)));
        slot(tn, T.PC_SL);
        tma5d(sb + OFF_WUK + u * 8192, &P.wuk, 128 * h + 64 * (u >> 1), 0, 0, 0, 8 * j + 4 * (u & 1), BAR(BAR_WUK + (u >> 1)), pol);
        tn += T.PC_P1;
      }
#pragma unroll
      for (int u = 0; u < 2; u++) {
        if (u) mbar_wait(BAR(BAR_WUK));
        slot(tn, T.PC_SL);
        if (j != 3) tma2d_nohint(sb + OFF_WM2 + u * 8192, &P.wm2, 1024 + 16 * (3 * h + j), 256 * u, BAR(BAR_WM2));
        tn += T.PC_PM;
      }
      const int row0 = (bs >> 3) * 4096 + (bs & 7) * 64;
      uint32_t dst = sb + OFF_RING;
#pragma unroll 1
      for (int n = 0; n < 31; n++) {
        if (n >= 4 && (n < 12 || (n & 3) == 0)) mbar_wait(BAR(n >= 12 ? BAR_EMPTY + (n >> 2) - 3 : (n == 7 && j != 3) ? BAR_P0BD : (n == 8 || n == 9) ? BAR_P2D : BAR_P1D));
        if (n < T.PC_NW) {
          if (n >= 4) mbar_wait(BAR(BAR_FULL + n - 4));
          else if (n & 1) mbar_wait(BAR((n < 2 || j == 3) ? BAR_WUK + 1 : BAR_WM2));
        }
        slot(tn, T.PC_SL);
        tma3d(dst, &P.ckv2, 0, row0 + (n >> 2) * 512, 2 * (n & 3), BAR(BAR_FULL + n), pol);
        dst = (n == 11 || n == 23) ? sb + OFF_RING : dst + 16384;
        tn += T.PC_P2;
        if (n == 4) CLK(2);
        if (n == 12) CLK(3);
        if (n == 20) CLK(4);
        if (n == 28) CLK(5);
        if (n == 24) {
          asm volatile("prefetch.tensormap [%0];" ::"l"(&P.ckv1) : "memory");
          asm volatile("prefetch.tensormap [%0];" ::"l"(&P.wuv) : "memory");
          asm volatile("prefetch.tensormap [%0];" ::"l"(&P.wo) : "memory");
          asm volatile("prefetch.tensormap [%0];" ::"l"(cta < NFF ? &P.w1 : &P.wm3) : "memory");
          asm volatile("prefetch.tensormap [%0];" ::"l"(&P.w2) : "memory");
        }
      }
      slot(tn, T.PC_SL);
      tma3d(dst, &P.ckv1, 0, row0 + 7 * 512, 6, BAR(BAR_LAST + 3), pol);
      tma3d(dst + 8192, &P.ckv1, 0, row0 + 7 * 512, 7, BAR(BAR_LAST + 4), pol);
      tn += T.PC_P2;
      CLK(6);
      auto unit = [&](int u) {
        if (u < 4) tma5d(sb + OFF_WUV + u * 8192, &P.wuv, 128 * h + 64 * (u >> 1), 0, 4 * (j >> 1), 0, 2 * (j & 1) + (u & 1), BAR(BAR_WUV + (u >> 1)), pol);
        else if (u < 8) tma2d(sb + OFF_WO + (u - 4) * 8192, &P.wo, 128 * j + 64 * ((u - 4) >> 1), 128 * h + 64 * (u & 1), BAR(BAR_WO + ((u - 4) >> 1)), pol);
        else if (u < 10) { if (cta < NFF) tma2d_nohint(sb + OFF_W1 + (u - 8) * 16384, &P.w1, 32 * bs, 256 * (u - 8), BAR(BAR_W1)); }
        else if (cta < NFF) tma3d(sb + OFF_W2 + (u - 10) * 8192, &P.w2, 0, 32 * bs, 4 * hh + 2 * (u - 10), BAR(BAR_W2), pol);
        else tma2d_nohint(sb + OFF_W1 + (u - 10) * 16384, &P.wm3, 2560 + 32 * (cta - NFF), 256 * (u - 10), BAR(BAR_W1));
      };
      mbar_wait(BAR(BAR_EMPTY + 5));
#pragma unroll
      for (int u = 0; u < 12; u++) {
        if (u == 8) mbar_wait(BAR(BAR_EMPTY + 6));
        until_ns(tn + (u < 4 ? T.T_UV + u * T.P_UV : u < 8 ? T.T_O + (u - 4) * T.P_O : u < 10 ? T.T_1 + (u - 8) * T.P_F : (cta < NFF ? T.T_2 : T.T_GB) + (u - 10) * T.P_F));
        unit(u);
        if (u == 3) {
#pragma unroll
          for (int q = 0; q < 4; q++)
            if (q < T.PF_N) {
              until_ns(tn + T.T_PF + q * T.P_PF);
              asm volatile("cp.async.bulk.prefetch.tensor.2d.L2.global.tile [%0, {%1,%2}];" ::"l"(&P.wo), "r"(128 * j + 64 * (q >> 1)), "r"(128 * h + 64 * (q & 1)) : "memory");
            }
        }
      }
      CLK_DUMP();
    }
    return;
  }

  if (w == 9) {
    if (lane == 0) {
#pragma unroll
      for (int i = 0; i < NBARS; i++) mbar_init(BAR(i), i >= BAR_P1D ? 8 : i >= BAR_EMPTY ? 4 : 1);
      asm volatile("fence.mbarrier_init.release.cluster;" ::: "memory");
    }
    __syncwarp();
    mbar_expect(BAR(lane), lane == BAR_LAST + 3 ? 8192 : 16384);
    if (lane < BAR_ALLCLR - 32) mbar_expect(BAR(32 + lane), lane == 0 ? 8192 : lane == BAR_W1 - 32 ? 32768 : 16384);
    CLK(9);
    asm volatile("barrier.cta.arrive.aligned 5, 64;" ::: "memory");
    asm volatile("barrier.cta.arrive.aligned 0, %0;" ::"n"(NTHREADS) : "memory");
  }
  const uint32_t epoch = ldg_rlx1(&gs->epoch);

  if (w == 9) {
    const int mo = g * 512 + 16 * hI + 2 * jI;
    const uint32_t xo0 = ldg_nc1(gx + mo * 2), xo1 = ldg_nc1(gx + mo * 2 + 16);
    const int par = epoch & 1;
    const uint32_t t0 = gtime32();
    const uint4 z = make_uint4(0, 0, 0, 0);
    uint32_t sel;
    {
      uint32_t* pa = gin + blk(cta, 5, 0) + 960;
      uint32_t* pb = gin + blk(cta, 5, 1) + 960;
      until_ns(t0 + T.PR_T0);
      if (lane < 4) stg4(reinterpret_cast<uint4*>(lane & 2 ? pa : pb) + (lane & 1), z);
      uint32_t ma = 0xffffffffu, mb = 0xffffffffu;
#pragma unroll 1
      for (int i = 0; i < 2 * T.PR_N; i++) {
        const uint32_t c0 = clk32();
        asm volatile("{\n.reg .pred q;\n.reg .b32 v;\nsetp.eq.u32 q, %1, 0;\nmov.u32 v, 0;\n@q atom.relaxed.gpu.global.add.u32 v, [%0], 1;\n"
                     "setp.eq.u32 q, v, 0xffffffff;\n@q trap;\n}" ::"l"(i & 1 ? pb : pa), "r"(lane) : "memory");
        const uint32_t d = clk32() - c0;
        if (i & 1) mb = min(mb, d); else ma = min(ma, d);
      }
      sel = __shfl_sync(~0u, (uint32_t)(mb < ma), 0);
      const uint32_t sw = 2 * (epoch + 1) + sel;
      if (lane < 2) stg4(reinterpret_cast<uint4*>(gin + blk(cta, 5, 1) + 896) + lane, make_uint4(sw, sw, sw, sw));
    }
    until_ns(t0 + T.CLR_T0);
    {
#pragma unroll 1
      for (int i0 = 0; i0 < 13; i0++) {
        uint4* q = reinterpret_cast<uint4*>(gin + (i0 < 12 ? blk(cta, i0 >> 1, sel) + (i0 & 1) * 512 : blk(cta, 4, sel ^ 1) + 512)) + lane;
#pragma unroll
        for (int i = 0; i < 4; i++) if (i0 != 11 || i < 3) stg4(q + i * 32, z);
        backoff(T.CLR_CLK);
      }
#pragma unroll
      for (int i = 0; i < 2; i++) {
        if (jI == 1) stg4(reinterpret_cast<uint4*>(gin + blk(cta, 6, i)) + lane, z);
        if (lane < 2) stg4(reinterpret_cast<uint4*>(gin + blk(cta, 5, i) + 928) + lane, z);
        stg4(reinterpret_cast<uint4*>(gin + blk(16 * g, 6 + (cta >> 6), i) + (cta & 63) * 16) + t, z);
      }
      CLK(1);
      {
        uint32_t sv = 0;
        uint32_t u[4];
        int it = 0;
        do {
#pragma unroll
          for (int i = 0; i < 4; i++) u[i] = ldg_rlx1(gin + blk(4 * lane + i, 5, 1) + 896) ^ (2 * (epoch + 1));
          if (++it > SPIN_LIMIT) __trap();
        } while (!__all_sync(~0u, (u[0] | u[1] | u[2] | u[3]) < 2));
#pragma unroll
        for (int i = 0; i < 4; i++) sv |= u[i] << (8 * i);
        sts1(sb + OFF_SEL + lane * 4, sv);
      }
      asm volatile("fence.acq_rel.gpu;" ::: "memory");
      CLK(2);
      __syncwarp();
      if (lane < NSYNC) asm volatile("red.relaxed.gpu.global.add.u32 [%0], 1;" ::"l"(&gs->sync[lane][0]) : "memory");
#pragma unroll
      for (int i = 0; i < 4; i++) stg4(reinterpret_cast<uint4*>(gs->QP[par ^ 1] + cta * 512) + i * 32 + lane, z);
      backoff(T.CLR_CLK);
#pragma unroll
      for (int i = 0; i < 4; i++) stg4(reinterpret_cast<uint4*>(gs->QX[par ^ 1] + cta * 512) + i * 32 + lane, z);
      stg4(reinterpret_cast<uint4*>(gs->MOD1[par ^ 1] + cta * 128) + lane, z);
      if (lane < 16) stg4(reinterpret_cast<uint4*>(gs->MOD2[par ^ 1] + cta * 64) + lane, z);
      const uint32_t target = (epoch + 1) * NCTA;
      uint32_t c; int it = 0;
      do {
        backoff(T.CLR_CLK);
        asm volatile("ld.acquire.gpu.global.u32 %0, [%1];" : "=r"(c) : "l"(&gs->sync[cta % NSYNC][0]) : "memory");
        if (++it > SPIN_LIMIT) __trap();
      } while (!__all_sync(~0u, (int)(c - target) >= 0));
      if (lane == 0) mbar_arrive(BAR(BAR_ALLCLR));
    }
    CLK(3);
    const uint32_t* const pg = gs->MOD2[par] + cta * 16 + g * 2;
    auto gate = [&](const uint32_t* q) { uint2 u; int it = 0; do { u = ldg_u64(q); if (++it > SPIN_LIMIT) __trap(); } while (!__all_sync(~0u, u.y != 0)); return u; };
    const uint2 gau = gate(pg);
    uint32_t anchor;
    {
      uint32_t* const po = gin + blk(16 * (lane & 7), 5, lane >> 3) + 928;
      const uint32_t* const pi = nearbox(cta & ~15, 5) + 928;
      mbar_wait(BAR(BAR_LAST + T.TS_P));
      unsigned long long now; asm volatile("mov.u64 %0, %%globaltimer;" : "=l"(now));
      if (lane < 16) asm volatile("red.relaxed.gpu.global.add.u64 [%0], %1;" ::"l"(po), "l"((now << 8) + 1) : "memory");
      backoff(T.D_TS);
      uint2 v; int it = 0;
      do { v = ldg_u64(pi); if (++it > SPIN_LIMIT) __trap(); } while (!__all_sync(~0u, (v.x & 255) == NCTA));
      const uint32_t mean = __funnelshift_r(v.x, v.y, 15);
      const int age = min(max((int)(gtime32() - mean), 0), 4000);
      anchor = clk32() - age * 7 / 4 + T.TS_O;
      if (lane == 0) { sts1(sb + OFF_TS, anchor); mbar_arrive(BAR(BAR_TS)); }
      CLK(10);
    }
    {
      const uint32_t* pm = pin(nearbox(4 * hI + 1, 6) + lane * 4);
      wait_clk(anchor, T.A_M);
      uint4 ml = ldg_2u64(pm);
      int it = 0;
      while (!__all_sync(~0u, ml.y != 0 && ml.w != 0)) { ml = ldg_2u64(pm); if (++it > SPIN_LIMIT) __trap(); }
      ITS(2, it);
      float M = fmaxf(__uint_as_float(ml.x), __uint_as_float(ml.z));
      M = fmaxf(M, __shfl_xor_sync(~0u, M, 1)); M = fmaxf(M, __shfl_xor_sync(~0u, M, 2));
      const float e0 = ex2(__uint_as_float(ml.x) - M), e1 = ex2(__uint_as_float(ml.z) - M);
      float l = e0 * __uint_as_float(ml.y) + e1 * __uint_as_float(ml.w);
      l += __shfl_xor_sync(~0u, l, 1); l += __shfl_xor_sync(~0u, l, 2);
      const float inv = __fdividef(1.f, l);
      sts2f(sb + OFF_WV + lane * 8, e0 * inv, e1 * inv);
      __syncwarp();
      if (lane == 0) mbar_arrive(BAR(BAR_WV));
      CLK(11);
    }
    uint32_t* x3o[4];
#pragma unroll
    for (int i = 0; i < 4; i++) x3o[i] = pin(gin + blk(32 * i + 16 * (t >> 1), 6 + (cta >> 6), t) + (cta & 63) * 16 + g * 2);
    uint32_t* const fo = pin(reinterpret_cast<uint32_t*>(gout) + mo / 2 + 4 * (t & 1));
    const uint32_t* const p3 = pin(gin + blk(cta, 4, sel) + t * 16 + g * 2);
    const uint32_t* const p4 = pin(gin + blk(cta, 5, sel) + t * 16 + g * 2);
    const uint32_t one = pin((g & 1) ? 0x3f800000u : 0x00003f80u);
    const float xf[4] = {pin(bf_lo(xo0)), pin(bf_hi(xo0)), pin(bf_lo(xo1)), pin(bf_hi(xo1))};
    const float ga[4] = {pin(bf_lo(gau.x)), pin(bf_hi(gau.x)), pin(bf_lo(gau.y)), pin(bf_hi(gau.y))};
    mbar_wait(BAR(BAR_P5D));
    backoff(T.D_X3A);
    wait_clk(anchor, T.A_X1 + T.R_X3A);
    CLK(4);
    float r[4];
    uint32_t x20, x21;
    int it = 0;
    bool ok;
    do {
      ok = sum_pieces<32>(p3, one, r);
      x20 = pack_bf16(xf[0] + ga[0] * r[0], xf[1] + ga[1] * r[1]); x21 = pack_bf16(xf[2] + ga[2] * r[2], xf[3] + ga[3] * r[3]);
#pragma unroll
      for (int i = 0; i < 4; i++) stg_u64_unless(!ok || (i == 3 && t >= 2), x3o[i], x20, x21);
    } while (!ok && ++it < SPIN_LIMIT);
    if (!ok) __trap();
    CLK(6);
    ITS(0, it);
    const uint32_t xw = (t & 1) ? x21 : x20;
    const float xa = pin(bf_lo(xw)), xb = pin(bf_hi(xw));
    if (cta < NFF) mbar_wait(BAR(BAR_P7D)); else wait_clk(anchor, T.A_X1 + T.R_X3A + T.R_X3B + T.R_FIN - T.D_FIN);
    uint2 gbu = ldg_u64(pg + 3 * 2048);
    backoff(T.D_FIN);
    CLK(7);
    do {
      ok = sum_pieces<NFG>(p4, one, r);
      ok = ok && __all_sync(~0u, gbu.y != 0);
      const uint32_t gw = (t & 1) ? gbu.y : gbu.x;
      const uint32_t o = pack_bf16(xa + bf_lo(gw) * ((t & 1) ? r[2] : r[0]), xb + bf_hi(gw) * ((t & 1) ? r[3] : r[1]));
      if (ok && t < 2) asm volatile("st.global.u32 [%0], %1;" ::"l"(fo), "r"(o) : "memory");
      reload_unit(gbu, pg + 3 * 2048);
    } while (!ok && ++it < SPIN_LIMIT);
    if (!ok) __trap();
    ITS(1, it);
    CLK(8);
    CLK_DUMP();
    if (cta == 0 && lane == 0) stg1(&gs->epoch, epoch + 1);
    return;
  }

  const int wg = w >> 2, wq = w & 3;
  uint32_t tstore;
  {
    const uint8_t* pw = gwmod + (size_t)(128 * jI + 16 * w + 4 * (g >> 1) + (g & 1)) * 6144 + 64 * hI + 16 * t;
    const uint4 w0 = ldg_nc4(pw), w1 = ldg_nc4(pw + 2 * 6144);
    const uint2 cc = ldg_nc2(gc + g * 1024 + 256 * jI + 32 * w + 8 * t);
    CLK(40);
    const uint32_t a[4] = {silu2(cc.x), 0u, silu2(cc.y), 0u};
    float d[4][4] = {{0.f, 0.f, 0.f, 0.f}, {0.f, 0.f, 0.f, 0.f}, {0.f, 0.f, 0.f, 0.f}, {0.f, 0.f, 0.f, 0.f}};
    mma16816(d[0], a, movm(w0.x), movm(w1.x)); mma16816(d[1], a, movm(w0.y), movm(w1.y));
    mma16816(d[2], a, movm(w0.z), movm(w1.z)); mma16816(d[3], a, movm(w0.w), movm(w1.w));
    CLK(1);
    sts4f(sb + OFF_P0S + w * 1088 + lane * 16, d[0][0], d[0][1], d[1][0], d[1][1]);
    sts4f(sb + OFF_P0S + w * 1088 + 544 + lane * 16, d[2][0], d[2][1], d[3][0], d[3][1]);
    bar_sync(0, NTHREADS);
    if (tid < 128) {
      const uint32_t src = sb + OFF_P0S + ((tid >> 2) & 1) * 544 + (((tid >> 3) & 7) * 4 + 2 * (tid >> 6) + (tid & 1)) * 16 + ((tid >> 1) & 1) * 8;
      float2 v[8];
#pragma unroll
      for (int i = 0; i < 8; i++) v[i] = ldsf2(src + i * 1088);
      const float ax = ((v[0].x + v[1].x) + (v[2].x + v[3].x)) + ((v[4].x + v[5].x) + (v[6].x + v[7].x));
      const float ay = ((v[0].y + v[1].y) + (v[2].y + v[3].y)) + ((v[4].y + v[5].y) + (v[6].y + v[7].y));
      stg1(gs->MOD1[epoch & 1] + jI * 4096 + hI * 128 + tid, nz(pack_bf16(ax, ay)));
    }
    tstore = clk32();
  }
  CLK(2);
  const int par = epoch & 1;
  uint32_t cf[4][4];
  mbar_wait(BAR(BAR_XC));
  {
    uint32_t u[2][4];
    lds4(u[0], sb + OFF_XS + w * 1024 + lane * 16); lds4(u[1], sb + OFF_XS + w * 1024 + 512 + lane * 16);
    float v[16];
#pragma unroll
    for (int i = 0; i < 8; i++) { v[2 * i] = bf_lo(u[i >> 2][i & 3]); v[2 * i + 1] = bf_hi(u[i >> 2][i & 3]); }
    float s = 0.f;
#pragma unroll
    for (int i = 0; i < 16; i++) s += v[i];
#pragma unroll
    for (int o = 16; o; o >>= 1) s += __shfl_xor_sync(~0u, s, o);
    const float mu = s * (1.f / 512.f);
    float q = 0.f;
#pragma unroll
    for (int i = 0; i < 16; i++) { v[i] -= mu; q += v[i] * v[i]; }
#pragma unroll
    for (int o = 16; o; o >>= 1) q += __shfl_xor_sync(~0u, q, o);
    const float rs = rsqrtf(q * (1.f / 512.f) + 1e-5f);
    const bool hi = jI & 2;
    uint32_t o[4];
#pragma unroll
    for (int i = 0; i < 4; i++) o[i] = pack_bf16((hi ? v[8 + 2 * i] : v[2 * i]) * rs, (hi ? v[9 + 2 * i] : v[2 * i + 1]) * rs);
    if ((lane >> 4) == (jI & 1)) sts4(sb + OFF_XN + w * 272 + (lane & 15) * 16, make_uint4(o[0], o[1], o[2], o[3]));
  }
  CLK(3);
  uint32_t aw[8][4];
  const uint32_t abase = keep(sb + a_t_offset(w, lane));
  {
    const uint32_t* pm = pin(gs->MOD1[par] + (8 * jI + w) * 64 + lane * 2);
    uint32_t* const qpo = pin(gs->QP[par] + (cta * 256 + tid) * 2);
    float d[4] = {0.f, 0.f, 0.f, 0.f};
    wait_clk(tstore, T.D_MOD);
    CLK(4);
    uint2 v[8];
    load_units<8, 2048>(v, pm);
    cbar();
    const uint32_t xn0 = lds1(sb + OFF_XN + g * 272 + w * 32 + t * 4), xn1 = lds1(sb + OFF_XN + g * 272 + w * 32 + 16 + t * 4);
    const bool early = __all_sync(~0u, mbar_test(BAR(BAR_WQ + wg)));
    if (early) load_a_t(aw, abase + OFF_WQ);
    int it = 0;
    while (true) {
      uint32_t mn = 0xffffffffu;
#pragma unroll
      for (int i = 0; i < 8; i++) mn = min(mn, min(v[i].x, v[i].y));
      if (__all_sync(~0u, mn != 0)) break;
#pragma unroll
      for (int i = 0; i < 8; i++) { if (v[i].x == 0) v[i].y = 0; reload_unit(v[i], pm + i * 2048); }
      if (++it > SPIN_LIMIT) __trap();
    }
    CLK(5);
    ITS(0, it);
    float sc[2][4];
#pragma unroll
    for (int i = 0; i < 2; i++) {
      sc[i][0] = (bf_lo(v[i].x) + bf_lo(v[2 + i].x)) + (bf_lo(v[4 + i].x) + bf_lo(v[6 + i].x));
      sc[i][1] = (bf_hi(v[i].x) + bf_hi(v[2 + i].x)) + (bf_hi(v[4 + i].x) + bf_hi(v[6 + i].x));
      sc[i][2] = (bf_lo(v[i].y) + bf_lo(v[2 + i].y)) + (bf_lo(v[4 + i].y) + bf_lo(v[6 + i].y));
      sc[i][3] = (bf_hi(v[i].y) + bf_hi(v[2 + i].y)) + (bf_hi(v[4 + i].y) + bf_hi(v[6 + i].y));
    }
    sts2(sb + OFF_BS1 + (w >> 1) * 512 + lane * 16 + (w & 1) * 8,
         pack_bf16(bf_lo(xn0) * (1.f + sc[1][0]) + sc[0][0], bf_hi(xn0) * (1.f + sc[1][1]) + sc[0][1]),
         pack_bf16(bf_lo(xn1) * (1.f + sc[1][2]) + sc[0][2], bf_hi(xn1) * (1.f + sc[1][3]) + sc[0][3]));
    if (!early) { mbar_wait(BAR(BAR_WQ + wg)); load_a_t(aw, abase + OFF_WQ); }
    CLK(6);
    cbar();
    uint32_t b[4][4];
#pragma unroll
    for (int kk = 0; kk < 4; kk++) lds4(b[kk], sb + OFF_BS1 + kk * 512 + lane * 16);
    mma128(d, aw, b);
    stg_u64(qpo, pack_bf16(d[0], d[1]), pack_bf16(d[2], d[3]));
    tstore = clk32();
    CLK(7);
    if (wg) {
      mbar_wait(BAR(BAR_C));
#pragma unroll
      for (int i = 0; i < 4; i++) lds4(cf[i], sb + OFF_CS + g * 1024 + wq * 256 + i * 64 + t * 16);
#pragma unroll
      for (int i = 0; i < 16; i++) cf[i >> 2][i & 3] = silu2(cf[i >> 2][i & 3]);
    }
    __syncwarp();
    if (lane == 0) mbar_arrive(BAR(BAR_P1D));
  }
  {
    const uint32_t* pq = pin(gs->QP[par] + (hI * 4 * 256 + tid) * 2);
    uint32_t* const qxo = pin(gs->QX[par] + (g * 32 + hI) * 256 + 64 * jI + 8 * w + 2 * t);
    uint2 v[4];
    float d[4] = {0.f, 0.f, 0.f, 0.f};
    wait_clk(tstore, T.D_QP);
    CLK(8);
    load_units<4, 512>(v, pq);
    const uint32_t kbase = sb + OFF_WUK + (16 * w + (lane & 15)) * 128;
    auto load_half = [&](int hf) {
#pragma unroll
      for (int ks = 0; ks < 4; ks++) ldsm4(aw[4 * hf + ks], kbase + hf * 16384 + (((2 * ks + (lane >> 4)) ^ (lane & 7)) << 4));
    };
    mbar_wait(BAR(BAR_WUK));
    load_half(0);
    const bool early = __all_sync(~0u, mbar_test(BAR(BAR_WUK + 1)));
    if (early) load_half(1);
    const int it = check_units<4, 512>(v, pq);
    CLK(9);
    ITS(1, it);
    sum4_to_smem(v, sb + OFF_BS2 + (16 * w + g) * 16 + t * 4);
    if (!early) { mbar_wait(BAR(BAR_WUK + 1)); load_half(1); }
    CLK(10);
    cbar();
    uint32_t b[4][4];
#pragma unroll
    for (int kk = 0; kk < 4; kk++) ldsm4t(b[kk], sb + OFF_BS2 + (32 * kk + lane) * 16);
    mma128(d, aw, b);
    const float sc = 0.08838834764831845f * 1.4426950408889634f;
    stg_u64(qxo, movm(pack_bf16(d[0] * sc, d[1] * sc)), movm(pack_bf16(d[2] * sc, d[3] * sc)));
    tstore = clk32();
    CLK(11);
    if (lane == 0) mbar_arrive(BAR(BAR_P2D));
  }
  if (wg && jI != 3) {
    const int mi = lane >> 3, r = lane & 7;
    const uint32_t a0 = sb + OFF_WM2 + (8 * (r >> 1) + (r & 1) + 2 * (mi >> 1)) * 32 + (mi & 1) * 16;
    mbar_wait(BAR(BAR_WM2));
#pragma unroll
    for (int s = 0; s < 8; s++) ldsm4t(aw[s], a0 + (128 * wq + 32 * (s >> 1) + 4 * (s & 1)) * 32);
    float d[4] = {0.f, 0.f, 0.f, 0.f};
    mma128(d, aw, cf);
    sts4f(sb + OFF_P0B + (tid - 128) * 16, d[0], d[1], d[2], d[3]);
    if (lane == 0) mbar_arrive(BAR(BAR_P0BD));
    bar_sync(3, 128);
    if (w == 4) {
      float4 v[4];
#pragma unroll
      for (int i = 0; i < 4; i++) v[i] = ldsf4(sb + OFF_P0B + (i * 32 + lane) * 16);
      stg_u64(gs->MOD2[par] + (3 * hI + jI) * 64 + t * 16 + g * 2, movm(pack_bf16((v[0].x + v[1].x) + (v[2].x + v[3].x), (v[0].y + v[1].y) + (v[2].y + v[3].y))),
              movm(pack_bf16((v[0].z + v[1].z) + (v[2].z + v[3].z), (v[0].w + v[1].w) + (v[2].w + v[3].w))));
    }
    CLK(15);
  }
  {
    const uint32_t* qx = pin(gs->QX[par] + ((bs >> 3) * 32 + 16 * hh) * 256 + tid * 4);
    const int ch = tid & 63, h0 = tid >> 6;
    const uint32_t dst = sb + OFF_Q + (ch >> 3) * 2048 + h0 * 128;
    wait_clk(tstore, T.D_QX);
    CLK(12);
    uint4 v[4];
#pragma unroll
    for (int i = 0; i < 4; i++) v[i] = ldg_2u64(qx + i * 1024);
    int it = 0;
    while (true) {
      uint32_t mn = 0xffffffffu;
#pragma unroll
      for (int i = 0; i < 4; i++) mn = min(mn, min(v[i].y, v[i].w));
      if (__all_sync(~0u, mn != 0)) break;
#pragma unroll
      for (int i = 0; i < 4; i++)
        asm volatile("{\n.reg .pred q;\nsetp.eq.u32 q, %5, 0;\n@q ld.relaxed.gpu.global.v4.b32 {%0, %1, %2, %3}, [%4];\n}"
                     : "+r"(v[i].x), "+r"(v[i].y), "+r"(v[i].z), "+r"(v[i].w) : "l"(qx + i * 1024), "r"(min(v[i].y, v[i].w)) : "memory");
      if (++it > SPIN_LIMIT) __trap();
    }
    CLK(13);
    ITS(2, it);
#pragma unroll
    for (int i = 0; i < 4; i++) sts4(dst + i * 512 + (((ch & 7) ^ ((4 * i + h0) & 7)) << 4), v[i]);
    asm volatile("fence.proxy.async.shared::cta;" ::: "memory");
    CLK(14);
    cbar();
  }

  uint2 cbf[4], sbf[4];
  const uint32_t* const pcb = gs->MOD2[par] + 2048 + (16 * w + t) * 16 + g * 2;
  auto load_frags = [&] {
    if (cta < NFF) { load_units<4, 64>(sbf, pcb); load_units<4, 64>(cbf, pcb + 2048); }
    else {
#pragma unroll
      for (int s = 0; s < 4; s++) { cbf[s].x = ldg_nc1(gc + g * 1024 + w * 128 + s * 32 + t * 4); cbf[s].y = ldg_nc1(gc + g * 1024 + w * 128 + s * 32 + 16 + t * 4); }
    }
  };
  uint32_t thand, anchor;
  const uint32_t opaque0 = w >> 4;
  if (wg == 0) {
    float mh[4];
    float L[8];
#pragma unroll
    for (int i = 0; i < 4; i++) { L[2 * i] = L[2 * i + 1] = 0.f; mh[i] = -INFINITY; }
    constexpr uint32_t dq = desc_lo(OFF_Q);
    const uint32_t ptw = sb + OFF_PT + (8 * (lane >> 4) + (lane & 7)) * 128 + (((2 * wq + ((lane >> 3) & 1)) ^ (lane & 7)) << 4);
    float S[8];
    auto softmax = [&](int tl) {
      auto write_p = [&](const float (&x)[8]) {
        float p[8];
#pragma unroll
        for (int i = 0; i < 8; i++) p[i] = ex2(x[i]);
        stsm4t(ptw + (tl & 1) * 2048, pack_bf16(p[0], p[1]), pack_bf16(p[2], p[3]), pack_bf16(p[4], p[5]), pack_bf16(p[6], p[7]));
        asm volatile("fence.proxy.async.shared::cta;" ::: "memory");
      };
      float x[8];
#pragma unroll
      for (int i = 0; i < 8; i++) x[i] = S[i] - mh[2 * (i >> 2) + (i & 1)];
      if (tl) write_p(x);
      const float ex = fmaxf(fmaxf(fmaxf(x[0], x[1]), fmaxf(x[2], x[3])), fmaxf(fmaxf(x[4], x[5]), fmaxf(x[6], x[7])));
      if (tl == 0 || bar_over(ex)) {
        float mx[4];
#pragma unroll
        for (int i = 0; i < 4; i++) mx[i] = fmaxf(S[4 * (i >> 1) + (i & 1)], S[4 * (i >> 1) + 2 + (i & 1)]);
        const float a = reduce_g(mx, lane, [](float u, float v) { return fmaxf(u, v); });
        stsf(sb + OFF_RED + wq * 64 + (8 * (lane >> 4) + 2 * t + ((lane >> 3) & 1)) * 4, a);
        bar_sync(2, 128);
#pragma unroll
        for (int jn = 0; jn < 2; jn++) {
          float m0 = mh[2 * jn], m1 = mh[2 * jn + 1];
#pragma unroll
          for (int i = 0; i < 4; i++) { const float2 v = ldsf2(sb + OFF_RED + i * 64 + (8 * jn + 2 * t) * 4); m0 = fmaxf(m0, v.x); m1 = fmaxf(m1, v.y); }
          const float a0 = ex2(mh[2 * jn] - m0), a1 = ex2(mh[2 * jn + 1] - m1);
          mh[2 * jn] = m0; mh[2 * jn + 1] = m1;
          L[4 * jn] *= a0; L[4 * jn + 1] *= a1; L[4 * jn + 2] *= a0; L[4 * jn + 3] *= a1;
          if (tid < 4) sts2f(sb + OFF_ALPHA + (8 * jn + 2 * t) * 4, a0, a1);
        }
        asm volatile("barrier.cta.arrive.aligned 1, 256;" ::: "memory");
#pragma unroll
        for (int i = 0; i < 8; i++) x[i] = S[i] - mh[2 * (i >> 2) + (i & 1)];
        write_p(x);
        bar_over(0.f);
      }
      const uint32_t dpt = __shfl_sync(~0u, desc_lo(OFF_PT) + (tl & 1) * 128, 0);
      wg_fence();
#pragma unroll
      for (int ks = 0; ks < 4; ks++) wgmma_n16_ones(L, ONE2, dpt + ks * 2);
      wg_commit();
    };
    uint32_t da = desc_lo(OFF_RING);
#pragma unroll 1
    for (int tl = 0; tl < 7; tl++) {
      if (tl == 5) { load_frags(); }
      uint32_t ok = 0;
#pragma unroll
      for (int u = 0; u < 4; u++) ok += mbar_test(BAR(BAR_FULL + 4 * tl + u));
      ok = __reduce_min_sync(~0u, ok);
      const uint32_t du = __shfl_sync(~0u, da, 0);
#pragma unroll
      for (int u = 0; u < 4; u++) {
        if (ok != 4) mbar_wait(BAR(BAR_FULL + 4 * tl + u));
        wg_fence();
#pragma unroll
        for (int k = 0; k < 8; k++) {
          const int i = 8 * u + k;
          if (i == 0) wgmma_n16<0, 0>(S, du, dq); else wgmma_n16<0, 1>(S, du + (i >> 2) * 512 + (i & 3) * 2, dq + (i >> 2) * 128 + (i & 3) * 2);
        }
        wg_commit();
      }
      wg_wait<0>();
      acc_fence(S); acc_fence(L);
      if (tl == 0) CLK(15);
      if (tl == 1) CLK(17);
      softmax(tl);
      if (tl == 0) CLK(16);
      if (tl == 1) CLK(18);
      if (tl == 3) CLK(19);
      if (tl == 6) CLK(20);
      da = (tl == 2 || tl == 5) ? da - 8192 : da + 4096;
    }
    mbar_wait(BAR(BAR_ALLCLR));
    uint32_t* const mlo = pin(gin + blk(4 * (16 * hh + 4 * (g & 2) + 2 * t + (g & 1)) + 1, 6, g >> 2) + bs * 2);
#pragma unroll
    for (int i = 0; i < 32; i++) {
      if (i == 0 || i == 8 || i == 16 || i == 24 || i == 28) {
        if (i) wg_commit();
        mbar_wait(BAR(BAR_LAST + (i == 28 ? 4 : i >> 3)));
        if (i == 28) CLK(21);
        wg_fence();
      }
      if (i == 0) wgmma_n16<0, 0>(S, desc_lo(65536), dq); else wgmma_n16<0, 1>(S, desc_lo(65536) + (i >> 2) * 512 + (i & 3) * 2, dq + (i >> 2) * 128 + (i & 3) * 2);
    }
    wg_commit();
    wg_wait<0>();
    acc_fence(S); acc_fence(L);
    CLK(22);
    softmax(7);
    CLK(23);
    thand = clk32();
    wg_wait<0>();
    acc_fence(L);
    if (tid < 32) red_u64(mlo, __float_as_uint(g & 2 ? (g & 1 ? mh[3] : mh[2]) : (g & 1 ? mh[1] : mh[0])), __float_as_uint(g & 2 ? (g & 1 ? L[5] : L[4]) : (g & 1 ? L[1] : L[0])));
    CLK(24);
  } else {
    float O[8][8];
#pragma unroll
    for (int i = 0; i < 8; i++)
#pragma unroll
      for (int k = 0; k < 8; k++) O[i][k] = 0.f;
    constexpr uint32_t dp = desc_lo(OFF_PT);
    auto handover = [&](int tl) {
      uint32_t over = opaque0 + (tl == 0);
#pragma unroll 1
      do {
        if (over) {
          cbar();
#pragma unroll
          for (int jn = 0; jn < 2; jn++) {
            const float2 a = ldsf2(sb + OFF_ALPHA + (8 * jn + 2 * t) * 4);
#pragma unroll
            for (int mb = 0; mb < 8; mb++) { O[mb][4 * jn] *= a.x; O[mb][4 * jn + 1] *= a.y; O[mb][4 * jn + 2] *= a.x; O[mb][4 * jn + 3] *= a.y; }
          }
        }
        over++;
      } while (bar_over(0.f));
    };
    uint32_t da = desc_lo(OFF_RING);
    uint32_t* x1o[8] = {};
#pragma unroll 1
    for (int tl = 0; tl < 8; tl++) {
      if (tl == 5) load_frags();
      if (tl == 7) {
        mbar_wait(BAR(BAR_ALLCLR));
#pragma unroll
        for (int i = 0; i < 8; i++)
          x1o[i] = inbox((16 * hh + 8 * ((i >> 1) & 1) + 2 * t + (i & 1)) * 4 + 2 * (i >> 2) + (wq >> 1), bs >> 4) + (bs & 15) * 64 + ((wq & 1) * 8 + g) * 4;
      }
      handover(tl);
      CLK(23);
      thand = clk32();
      const uint32_t dpt = dp + (tl & 1) * 128;
      wg_fence();
#pragma unroll
      for (int i = 0; i < 32; i++) wgmma_n16<1, 1>(O[i >> 2], da + (i >> 2) * 512 + (i & 3) * 128, dpt + (i & 3) * 2);
      wg_commit();
      da = (tl == 2 || tl == 5) ? da - 8192 : da + 4096;
      wg_wait<0>();
#pragma unroll
      for (int mb = 0; mb < 8; mb++) acc_fence(O[mb]);
      if (lane == 0) mbar_arrive(BAR(BAR_EMPTY + tl));
      if (tl == 0) CLK(16);
      if (tl == 1) CLK(18);
      if (tl == 3) CLK(19);
      if (tl == 6) CLK(20);
    }
    CLK(22);
#pragma unroll
    for (int i = 0; i < 8; i++) {
      const int J = i >> 2, k = 4 * ((i >> 1) & 1) + (i & 1);
      stg_cvt8(x1o[i], O[4 * J][k], O[4 * J][k + 2], O[4 * J + 1][k], O[4 * J + 1][k + 2], O[4 * J + 2][k], O[4 * J + 2][k + 2], O[4 * J + 3][k], O[4 * J + 3][k + 2]);
    }
    CLK(24);
  }

  uint32_t* const o = gin + keep((uint32_t)(inbox(4 * (8 * jI + w) + t, 4) - gin) + hI * 16 + g * 2);
  const uint32_t sdst5 = keep(sb + OFF_BS5 + (16 * w + g) * 16 + t * 4), lane16 = keep(sb + lane * 16);
  const uint32_t* x2i[4];
#pragma unroll
  for (int i = 0; i < 4; i++) x2i[i] = gin + keep((uint32_t)(nearbox(4 * hI + i, 4) - gin) + 512 + tid * 2);
  {
    const uint32_t* px = pin(inbox(cta, w >> 1) + (w & 1) * 512 + lane * 2);
    uint32_t* const x2o = pin(inbox(cta, 4) + 512 + tid * 2);
    uint32_t* const x2p = pin(gin + blk(cta, 4, selector(cta) ^ 1) + 512 + tid * 2);
    const uint32_t q4 = lds1(sb + OFF_SEL + 4 * hI) ^ 0x00010100u;
    const uint32_t same = pin((uint32_t)(q4 == 0 || q4 == 0x01010101u));
    mbar_wait(BAR(BAR_TS));
    anchor = lds1(sb + OFF_TS);
    const uint32_t sdst = keep(sb + OFF_BS4 + w * 272 + lane * 8), ssrc = keep(sb + OFF_BS4 + (lane & 7) * 272 + (lane >> 3) * 16);
    float d[4] = {0.f, 0.f, 0.f, 0.f};
    if (cta >= NFF) {
#pragma unroll
      for (int s = 0; s < 4; s++) { cbf[s].x = silu2(cbf[s].x); cbf[s].y = silu2(cbf[s].y); }
    } else {
      check_units<4, 64>(sbf, pcb);
      check_units<4, 64>(cbf, pcb + 2048);
#pragma unroll
      for (int s = 0; s < 4; s++) { cbf[s].x = hadd2(cbf[s].x, ONE2); cbf[s].y = hadd2(cbf[s].y, ONE2); }
    }
    wait_clk(thand, T.D_X1);
    wait_clk(anchor, T.A_X1 - T.R_X0);
    uint2 v[8];
    load_units<8, 64>(v, px);
    if (T.R_X0) {
      wait_clk(anchor, T.A_X1);
#pragma unroll
      for (int i = 0; i < 8; i++) reload_unit(v[i], px + i * 64);
    }
    CLK(25);
    const bool early = __all_sync(~0u, mbar_test(BAR(BAR_WUV + wg)));
    if (early) load_a_t(aw, abase + OFF_WUV);
    mbar_wait(BAR(BAR_WV));
    const float4 wa = ldsf4(sb + OFF_WV + w * 32), wb = ldsf4(sb + OFF_WV + w * 32 + 16);
    const float wv[8] = {wa.x, wa.y, wa.z, wa.w, wb.x, wb.y, wb.z, wb.w};
    CLK(27);
    uint32_t it = opaque0;
    bool ok;
#pragma unroll 1
    do {
      if (it) {
#pragma unroll
        for (int i = 0; i < 8; i++) reload_unit(v[i], px + i * 64);
        if (it > SPIN_LIMIT) __trap();
      }
      it++;
      float a0 = 0.f, a1 = 0.f, a2 = 0.f, a3 = 0.f;
#pragma unroll
      for (int i = 0; i < 8; i++) { a0 += wv[i] * bf_lo(v[i].x); a1 += wv[i] * bf_hi(v[i].x); a2 += wv[i] * bf_lo(v[i].y); a3 += wv[i] * bf_hi(v[i].y); }
      ok = __all_sync(~0u, min_flags(v) != 0);
      sts2(sdst, pack_bf16(a0, a1), pack_bf16(a2, a3));
    } while (!ok);
    CLK(29);
    cbar();
    uint32_t b[4][4];
#pragma unroll
    for (int kk = 0; kk < 4; kk++) ldsm4(b[kk], ssrc + kk * 64);
    if (__builtin_expect(!early, 0)) { mbar_wait(BAR(BAR_WUV + wg)); load_a_t(aw, abase + OFF_WUV); }
    mma128(d, aw, b);
    const uint32_t c0 = pack_bf16(d[0], d[1]), c1 = pack_bf16(d[2], d[3]);
    stg_u64(x2o, c0, c1);
    stg_u64_unless(same, x2p, c0, c1);
    ITS(4, it - 1);
    tstore = clk32();
    CLK(30);
  }
  {
    float d[4] = {0.f, 0.f, 0.f, 0.f};
    wait_clk(tstore, T.D_X2);
    uint2 v[4];
#pragma unroll
    for (int i = 0; i < 4; i++) v[i] = ldg_u64(x2i[i]);
    const bool early = __all_sync(~0u, mbar_test(BAR(BAR_WO + wg)));
    if (early) load_a_t(aw, abase + OFF_WO);
    CLK(31);
    uint32_t it = opaque0;
    bool ok;
#pragma unroll 1
    do {
      if (it) {
#pragma unroll
        for (int i = 0; i < 4; i++) reload_unit(v[i], x2i[i]);
        if (it > SPIN_LIMIT) __trap();
      }
      it++;
      ok = __all_sync(~0u, min_flags(v) != 0);
      sum4_to_smem(v, sdst5);
    } while (!ok);
    CLK(32);
    cbar();
    uint32_t b[4][4];
#pragma unroll
    for (int kk = 0; kk < 4; kk++) ldsm4t(b[kk], lane16 + OFF_BS5 + kk * 512);
    if (__builtin_expect(!early, 0)) { mbar_wait(BAR(BAR_WO + wg)); load_a_t(aw, abase + OFF_WO); }
    mma128(d, aw, b);
    stg_u64(o, movm(pack_bf16(d[0], d[1])), movm(pack_bf16(d[2], d[3])));
    ITS(5, it - 1);
    tstore = clk32();
    CLK(33);
    if (lane == 0) mbar_arrive(BAR(BAR_P5D));
  }
  if (cta < NFF) {
    const int mi = lane >> 3, r = lane & 7;
    uint32_t a1[2][4][4], a2[2][2][4];
    const int lp = (tid >> 2) & 31, kq = tid & 3;
    const int fo = 16 * wg + (lp >> 2) + 8 * (kq >> 1), bo = 2 * (lp & 3) + (kq & 1);
    const uint32_t* xb = gin + keep((uint32_t)(nearbox(cta & ~15, 6 + wg) - gin) + (16 * wq + t) * 16 + g * 2);
    uint32_t* const ox[2] = {gin + keep((uint32_t)(inbox(64 * hh + 8 * w + t, 5) - gin) + bs * 16 + g * 2), gin + keep((uint32_t)(inbox(64 * hh + 8 * w + 4 + t, 5) - gin) + bs * 16 + g * 2)};
    const uint32_t a1base = keep(sb + OFF_W1 + (64 * w + 8 * (mi >> 1) + r) * 64 + (((mi & 1) ^ (r >> 1)) << 4));
    const uint32_t a2base = keep(sb + OFF_W2 + (w >> 1) * 4096 + (8 * (mi >> 1) + r) * 128 + (((4 * (w & 1) + (mi & 1)) ^ r) << 4));
    const uint32_t s_g = keep(sb + OFF_REDG + w * 1024 + lane * 16), l_g = keep(sb + OFF_REDG + tid * 4);
    const uint32_t s_s = keep(sb + (t == (g >> 1) ? OFF_REDS + g * 80 + w * 8 : OFF_BS4 + tid * 8));
    const uint32_t l_s = keep(sb + OFF_REDS + bo * 80), s_h = keep(sb + OFF_H1 + fo * 16 + bo * 2);
    mbar_wait(BAR(BAR_W1));
#pragma unroll
    for (int i = 0; i < 8; i++) ldsm4t(a1[i & 1][i >> 1], (a1base ^ ((i & 1) << 5)) + (i >> 1) * 1024);
    {
      float u[2][2][4] = {};
#pragma unroll
      for (int s = 0; s < 4; s++)
#pragma unroll
        for (int mt = 0; mt < 2; mt++) { mma16816(u[0][mt], a1[mt][s], cbf[s].x, cbf[s].y); mma16816(u[1][mt], a1[mt][s], sbf[s].x, sbf[s].y); }
#pragma unroll
      for (int i = 0; i < 4; i++) sts4f(s_g + (OFF_REDU - OFF_REDG) + (i >> 1) * 8192 + (i & 1) * 512, u[i >> 1][i & 1][0], u[i >> 1][i & 1][1], u[i >> 1][i & 1][2], u[i >> 1][i & 1][3]);
    }
    CLK(34);
    wait_clk(tstore, T.D_X3B);
    wait_clk(anchor, T.A_X1 + T.R_X3A + T.R_X3B);
    uint2 x[4];
    load_units<4, 64>(x, xb);
    float U, V;
    {
      cbar();
      float u[8], v[8];
#pragma unroll
      for (int i = 0; i < 8; i++) { u[i] = ldsf(l_g + (OFF_REDU - OFF_REDG) + i * 1024); v[i] = ldsf(l_g + (OFF_REDV - OFF_REDG) + i * 1024); }
      U = pin(((u[0] + u[1]) + (u[2] + u[3])) + ((u[4] + u[5]) + (u[6] + u[7])));
      V = pin(((v[0] + v[1]) + (v[2] + v[3])) + ((v[4] + v[5]) + (v[6] + v[7])));
    }
    auto load_a2 = [&] {
#pragma unroll
      for (int i = 0; i < 4; i++) ldsm4t(a2[i >> 1][i & 1], (a2base ^ ((i >> 1) << 5)) + (i & 1) * 2048);
    };
    const bool early = __all_sync(~0u, mbar_test(BAR(BAR_W2)));
    if (early) load_a2();
    CLK(35);
    uint32_t it = opaque0;
    float G[2][2][4], S[2][4];
#pragma unroll 1
    do {
      if (it) {
#pragma unroll
        for (int i = 0; i < 4; i++) reload_unit(x[i], xb + i * 64);
        if (it > SPIN_LIMIT) __trap();
      }
      it++;
#pragma unroll
      for (int i = 0; i < 8; i++) { G[0][i >> 2][i & 3] = G[1][i >> 2][i & 3] = S[i >> 2][i & 3] = 0.f; }
      uint32_t y[4][2];
#pragma unroll
      for (int s = 0; s < 4; s++) { y[s][0] = hmul2(x[s].x, cbf[s].x); y[s][1] = hmul2(x[s].y, cbf[s].y); }
#pragma unroll
      for (int s2 = 0; s2 < 4; s2 += 2) {
#pragma unroll
        for (int s = s2; s < s2 + 2; s++) { mma16816(G[0][s & 1], a1[0][s], y[s][0], y[s][1]); mma16816(G[1][s & 1], a1[1][s], y[s][0], y[s][1]); }
#pragma unroll
        for (int s = s2; s < s2 + 2; s++) { const uint32_t sx[4] = {x[s].x, ONE2, x[s].y, ONE2}; mma16816(S[s & 1], sx, x[s].x, x[s].y); }
      }
    } while (!__all_sync(~0u, min_flags(x) != 0));
#pragma unroll
    for (int mt = 0; mt < 2; mt++)
      sts4f(s_g + mt * 512, G[mt][0][0] + G[mt][1][0], G[mt][0][1] + G[mt][1][1], G[mt][0][2] + G[mt][1][2], G[mt][0][3] + G[mt][1][3]);
    sts2f(s_s, (g & 1) ? S[0][3] + S[1][3] : S[0][2] + S[1][2], (g & 1) ? S[0][1] + S[1][1] : S[0][0] + S[1][0]);
    CLK(37);
    cbar();
    {
      float gv[8];
      float4 sv[4];
#pragma unroll
      for (int i = 0; i < 4; i++) sv[i] = ldsf4(l_s + i * 16);
#pragma unroll
      for (int i = 0; i < 8; i++) gv[i] = ldsf(l_g + i * 1024);
      const float s1 = ((sv[0].x + sv[0].z) + (sv[1].x + sv[1].z)) + ((sv[2].x + sv[2].z) + (sv[3].x + sv[3].z));
      const float s2 = ((sv[0].y + sv[0].w) + (sv[1].y + sv[1].w)) + ((sv[2].y + sv[2].w) + (sv[3].y + sv[3].w));
      const float gsum = ((gv[0] + gv[1]) + (gv[2] + gv[3])) + ((gv[4] + gv[5]) + (gv[6] + gv[7]));
      const float mu = s1 * (1.f / 512.f);
      float rs;
      asm("rsqrt.approx.ftz.f32 %0, %1;" : "=f"(rs) : "f"(fmaxf(s2 * (1.f / 512.f) - mu * mu, 0.f) + 1e-5f));
      const float hv = fmaxf(rs * (gsum - mu * U) + V, 0.f);
      asm volatile("st.shared.u16 [%0], %1;" ::"r"(s_h), "h"(__bfloat16_as_ushort(__float2bfloat16(hv))) : "memory");
    }
    ITS(6, it - 1);
    CLK(38);
    cbar();
    uint32_t b[4];
    ldsm4t(b, lane16 + OFF_H1);
    if (!early) { mbar_wait(BAR(BAR_W2)); load_a2(); }
    float o[2][2][4] = {};
#pragma unroll
    for (int i = 0; i < 4; i++) mma16816(o[i >> 1][i & 1], a2[i >> 1][i & 1], b[2 * (i & 1)], b[2 * (i & 1) + 1]);
#pragma unroll
    for (int mb = 0; mb < 2; mb++)
      stg_u64(ox[mb], movm(pack_bf16(o[mb][0][0] + o[mb][1][0], o[mb][0][1] + o[mb][1][1])), movm(pack_bf16(o[mb][0][2] + o[mb][1][2], o[mb][0][3] + o[mb][1][3])));
    CLK(39);
    if (lane == 0) mbar_arrive(BAR(BAR_P7D));
  } else {
    const int mi = lane >> 3, r = lane & 7;
    mbar_wait(BAR(BAR_W1));
#pragma unroll
    for (int mt = 0; mt < 2; mt++) {
      float u[4] = {0.f, 0.f, 0.f, 0.f};
#pragma unroll
      for (int ks = 0; ks < 4; ks++) ldsm4t(aw[4 * mt + ks], sb + OFF_W1 + (64 * w + 16 * ks + 8 * (mi >> 1) + r) * 64 + (((2 * mt + (mi & 1)) ^ (r >> 1)) << 4));
#pragma unroll
      for (int ks = 0; ks < 4; ks++) mma16816(u, aw[4 * mt + ks], cbf[ks].x, cbf[ks].y);
      sts4f(sb + OFF_REDU + w * 1024 + mt * 512 + lane * 16, u[0], u[1], u[2], u[3]);
    }
    cbar();
    if (w < 2) {
      float4 v[8];
#pragma unroll
      for (int i = 0; i < 8; i++) v[i] = ldsf4(sb + OFF_REDU + i * 1024 + tid * 16);
      stg_u64(gs->MOD2[par] + (96 + 2 * (cta - NFF) + w) * 64 + t * 16 + g * 2,
              movm(pack_bf16(((v[0].x + v[1].x) + (v[2].x + v[3].x)) + ((v[4].x + v[5].x) + (v[6].x + v[7].x)), ((v[0].y + v[1].y) + (v[2].y + v[3].y)) + ((v[4].y + v[5].y) + (v[6].y + v[7].y)))),
              movm(pack_bf16(((v[0].z + v[1].z) + (v[2].z + v[3].z)) + ((v[4].z + v[5].z) + (v[6].z + v[7].z)), ((v[0].w + v[1].w) + (v[2].w + v[3].w)) + ((v[4].w + v[5].w) + (v[6].w + v[7].w)))));
    }
    CLK(26);
  }
  CLK_DUMP();
}

typedef CUresult (*EncodeTiledFn)(CUtensorMap*, CUtensorMapDataType, cuuint32_t, void*, const cuuint64_t*, const cuuint64_t*,
                                  const cuuint32_t*, const cuuint32_t*, CUtensorMapInterleave, CUtensorMapSwizzle,
                                  CUtensorMapL2promotion, CUtensorMapFloatOOBfill);

struct Dim { uint64_t size, stride; uint32_t box; };
template <int R> void encode_map(EncodeTiledFn enc, CUtensorMap* m, const void* base, const Dim (&d)[R], CUtensorMapSwizzle sw, CUtensorMapL2promotion promo) {
  cuuint64_t dims[R], strides[R];
  cuuint32_t box[R], es[R];
  for (int i = 0; i < R; i++) { dims[i] = d[i].size; strides[i] = d[i].stride; box[i] = d[i].box; es[i] = 1; }
  enc(m, CU_TENSOR_MAP_DATA_TYPE_BFLOAT16, R, const_cast<void*>(base), dims, strides + 1, box, es, CU_TENSOR_MAP_INTERLEAVE_NONE, sw, promo,
      CU_TENSOR_MAP_FLOAT_OOB_FILL_NONE);
}

}

extern "C" void kernel_launch(void* const* d_in, const int* in_sizes, int n_in, void* d_out, int out_size) {
  (void)in_sizes; (void)n_in; (void)out_size;
  static EncodeTiledFn enc = nullptr;
  static Scratch* scratch = nullptr;
  static uint32_t* inbox = nullptr;
  if (!enc) {
    void* sp = nullptr;
    cudaGetSymbolAddress(&sp, g_s);
    scratch = (Scratch*)sp;
    cudaGetSymbolAddress(&sp, g_in);
    inbox = (uint32_t*)(((uintptr_t)sp + 0xfffff) & ~(uintptr_t)0xfffff);
    void* fn = nullptr;
    cudaDriverEntryPointQueryResult q;
    cudaGetDriverEntryPoint("cuTensorMapEncodeTiled", &fn, cudaEnableDefault, &q);
    enc = (EncodeTiledFn)fn;
    cudaFuncSetAttribute(fused_decode_kernel, cudaFuncAttributeMaxDynamicSharedMemorySize, SMEM_BYTES);
  }
  const CUtensorMapSwizzle S128 = CU_TENSOR_MAP_SWIZZLE_128B, S0 = CU_TENSOR_MAP_SWIZZLE_NONE;
  const CUtensorMapL2promotion L0 = CU_TENSOR_MAP_L2_PROMOTION_NONE, L128 = CU_TENSOR_MAP_L2_PROMOTION_L2_128B;
  Params P;
  encode_map<2>(enc, &P.wq, d_in[2], {{4096, 2, 64}, {512, 8192, 64}}, S128, L0);
  encode_map<5>(enc, &P.wuk, d_in[3], {{4096, 2, 64}, {2, 8192, 2}, {4, 4 * 8192, 4}, {2, 2 * 8192, 2}, {32, 16 * 8192, 4}}, S128, L0);
  encode_map<2>(enc, &P.wm2, d_in[10], {{3072, 2, 16}, {512, 6144, 256}}, S0, L128);
  encode_map<2>(enc, &P.wm3, d_in[10], {{3072, 2, 32}, {512, 6144, 256}}, CU_TENSOR_MAP_SWIZZLE_64B, L128);
  encode_map<3>(enc, &P.ckv2, d_in[1], {{64, 2, 64}, {8 * 4096, 1024, 64}, {8, 128, 2}}, S128, L0);
  encode_map<3>(enc, &P.ckv1, d_in[1], {{64, 2, 64}, {8 * 4096, 1024, 64}, {8, 128, 1}}, S128, L0);
  encode_map<5>(enc, &P.wuv, d_in[4], {{4096, 2, 64}, {2, 8 * 8192, 2}, {8, 64 * 8192, 4}, {8, 8192, 8}, {4, 16 * 8192, 1}}, S128, L0);
  encode_map<2>(enc, &P.wo, d_in[5], {{512, 2, 64}, {4096, 1024, 64}}, S128, L0);
  encode_map<2>(enc, &P.w1, d_in[7], {{1792, 2, 32}, {512, 3584, 256}}, CU_TENSOR_MAP_SWIZZLE_64B, L128);
  encode_map<3>(enc, &P.w2, d_in[8], {{64, 2, 64}, {1792, 1024, 32}, {8, 128, 2}}, S128, L0);
  fused_decode_kernel<<<NCTA, NTHREADS, SMEM_BYTES>>>((__nv_bfloat16*)d_out, scratch, (const uint8_t*)d_in[10], (const uint8_t*)d_in[0],
                     (const uint8_t*)d_in[9], inbox,
                     P);
}
```

```cpp
#include <cuda_runtime.h>
#include <cuda.h>
#include <cuda_bf16.h>
#include <stdint.h>
#define V4 1

namespace {

constexpr int NCTA = 128;
constexpr int NTHREADS = 320;
constexpr int NFG = 56;
constexpr int NFF = 2 * NFG;
constexpr int NSYNC = 4;

constexpr uint32_t OFF_RING = 0;
constexpr uint32_t OFF_WUK = 131072;
constexpr uint32_t OFF_WQ = 131072 + 32768;
constexpr uint32_t OFF_WM2 = 65536 + 49152;
constexpr uint32_t OFF_WUV = 131072;
constexpr uint32_t OFF_WO = 131072 + 32768;
constexpr uint32_t OFF_W1 = 0;
constexpr uint32_t OFF_W2 = 32768;
constexpr uint32_t OFF_Q = 196608;
constexpr uint32_t OFF_PT = 212992;
constexpr uint32_t OFF_SCR = 217088;
constexpr uint32_t OFF_XS = 65536;
constexpr uint32_t OFF_CS = 65536 + 8192;
constexpr uint32_t OFF_P0S = 65536 + 16384;
constexpr uint32_t OFF_BS1 = OFF_SCR + 2048;
constexpr uint32_t OFF_BS2 = OFF_SCR + 4096;
constexpr uint32_t OFF_P0B = OFF_SCR + 6144;
constexpr uint32_t OFF_XN = OFF_SCR + 8192;
constexpr uint32_t OFF_RED = OFF_SCR + 10496;
constexpr uint32_t OFF_ALPHA = OFF_SCR + 11072;
constexpr uint32_t OFF_WV = OFF_SCR + 6144;
constexpr uint32_t OFF_SEL = OFF_SCR + 10752;
constexpr uint32_t OFF_TS = OFF_SCR + 11136;
constexpr uint32_t OFF_BARS = OFF_SCR + 11264;
constexpr uint32_t SMEM_BYTES = OFF_BARS + 512;
constexpr uint32_t OFF_BS4 = OFF_Q;
constexpr uint32_t OFF_H1 = OFF_Q + 2304;
constexpr uint32_t OFF_REDS = OFF_Q + 2816;
constexpr uint32_t OFF_BS5 = OFF_Q + 4096;
constexpr uint32_t OFF_REDG = OFF_Q + 8192;
constexpr uint32_t OFF_REDU = 65536;
constexpr uint32_t OFF_REDV = 65536 + 8192;

constexpr int BAR_FULL = 0;
constexpr int BAR_LAST = 28;
constexpr int BAR_WUK = 33, BAR_WM2 = 35, BAR_WUV = 36, BAR_WO = 38, BAR_W1 = 40, BAR_W2 = 41;
constexpr int BAR_ALLCLR = 42, BAR_TS = 43, BAR_WV = 44;
constexpr int BAR_EMPTY = 45;
constexpr int BAR_P0BD = 53;
constexpr int BAR_P1D = 54, BAR_P2D = 55;
constexpr int BAR_P5D = 56, BAR_P7D = 57;
constexpr int NBARS = 58;
constexpr int BAR_XC = 58, BAR_WQ = 59;
constexpr int BAR_C = 61;
constexpr uint32_t SB = 1024;

#define TUNE_LIST(X) \
  X(PC_T0, -30) X(PC_P1, 322) X(PC_PM, 225) X(PC_P2, 320) X(PC_STAG, 360) X(PC_SL, 500) X(PC_NW, 8) \
  X(T_UV, 165) X(P_UV, 285) X(PF_N, 3) X(T_PF, 1020) X(P_PF, 230) X(T_O, 2180) X(P_O, 145) X(T_1, 2990) X(T_2, 3700) X(T_GB, 3370) X(P_F, 360) \
  X(PR_T0, 700) X(PR_N, 4) X(CLR_T0, 3300) X(CLR_CLK, 190) \
  X(D_MOD, 1280) X(D_QP, 1200) X(D_QX, 850) X(TS_P, 1) X(TS_O, 1900) X(D_TS, 700) X(A_M, 1550) X(D_X1, 1350) X(A_X1, 2460) X(R_X0, 1550) \
  X(D_X2, 290) X(D_X3A, 60) X(R_X3A, 2835) X(D_X3B, 800) X(R_X3B, 915) X(D_FIN, 315) X(R_FIN, 1540)
struct Tune {
#define X(n, v) static constexpr int n = v;
  TUNE_LIST(X)
#undef X
};

struct Scratch {
  uint32_t MOD1[2][4 * 64 * 64];
  uint32_t MOD2[2][128 * 64];
  uint32_t QP[2][128 * 256 * 2];
  uint32_t QX[2][8 * 32 * 256];
  uint32_t epoch;
  uint32_t pad[31];
  uint32_t sync[NSYNC][32];
};
__device__ Scratch g_s;
__device__ uint32_t g_in[(128 + 16) * 16384];
__device__ __forceinline__ uint32_t blk(int c, int k, uint32_t sel) { return c * 16384 + k * 2048 + ((sel ^ k) & 1) * 1024; }
__device__ __forceinline__ uint32_t flip(int c) { return c ^ (c >> 1) ^ (c >> 3); }

#define CLK_DECL
#define CLK(i) do {} while (0)
#define CLK_DUMP() do {} while (0)
#define ITS(i, v) do {} while (0)

struct Params {
  CUtensorMap wq, wuk, wm2, wm3, ckv2, ckv1, wuv, wo, w1, w2;
};

__device__ __forceinline__ void mbar_init(uint32_t bar, int cnt) { asm volatile("mbarrier.init.shared::cta.b64 [%0], %1;" ::"r"(bar), "r"(cnt)); }
__device__ __forceinline__ void mbar_expect(uint32_t bar, uint32_t bytes) { asm volatile("mbarrier.arrive.expect_tx.shared::cta.b64 _, [%0], %1;" ::"r"(bar), "r"(bytes) : "memory"); }
__device__ __forceinline__ void mbar_arrive(uint32_t bar) { asm volatile("mbarrier.arrive.shared::cta.b64 _, [%0];" ::"r"(bar) : "memory"); }
__device__ __forceinline__ uint32_t clk32() { unsigned long long c; asm volatile("mov.u64 %0, %%clock64;" : "=l"(c) :: "memory"); return (uint32_t)c; }
__device__ __forceinline__ uint32_t gtime32() { uint32_t c; asm volatile("mov.u32 %0, %%globaltimer_lo;" : "=r"(c) :: "memory"); return c; }
__device__ __forceinline__ void wait_clk(uint32_t t0, int clocks) { while ((int)(clk32() - t0) < clocks) {} }
__device__ __forceinline__ void backoff(int clocks) { if (clocks > 0) wait_clk(clk32(), clocks); }
__device__ __forceinline__ void until_ns(uint32_t ns) { while ((int)(gtime32() - ns) < 0) {} }
__device__ __forceinline__ void slot(uint32_t& tn, int slack) {
  uint32_t now;
  do { now = gtime32(); } while ((int)(now - tn) < 0);
  if ((int)(now - tn) > slack) tn = now - slack;
}
template <typename T> __device__ __forceinline__ T* pin(T* p) { asm volatile("" : "+l"(p)); return p; }
__device__ __forceinline__ uint32_t pin(uint32_t v) { asm volatile("" : "+r"(v)); return v; }
__device__ __forceinline__ float pin(float v) { asm volatile("" : "+f"(v)); return v; }
constexpr int SPIN_LIMIT = 1 << 22;
__device__ __forceinline__ void mbar_wait(uint32_t bar) {
  asm volatile("{\n.reg .pred p;\n.reg .u32 c;\nmov.u32 c, 0;\n"
               "MW_LOOP:\nmbarrier.try_wait.parity.shared::cta.b64 p, [%0], 0;\n@p bra MW_DONE;\n"
               "add.u32 c, c, 1;\nsetp.lt.u32 p, c, 4194304;\n@p bra MW_LOOP;\ntrap;\nMW_DONE:\n}"
               ::"r"(bar) : "memory");
}
__device__ __forceinline__ bool mbar_test(uint32_t bar) {
  uint32_t ok;
  asm volatile("{\n.reg .pred p;\nmbarrier.test_wait.parity.shared::cta.b64 p, [%1], 0;\nselp.u32 %0,1,0,p;\n}" : "=r"(ok) : "r"(bar) : "memory");
  return ok;
}
__device__ __forceinline__ void tma2d(uint32_t dst, const CUtensorMap* m, int c0, int c1, uint32_t bar, uint64_t pol) {
  asm volatile("cp.async.bulk.tensor.2d.shared::cluster.global.mbarrier::complete_tx::bytes.L2::cache_hint [%0], [%1, {%3,%4}], [%2], %5;"
               ::"r"(dst), "l"(m), "r"(bar), "r"(c0), "r"(c1), "l"(pol) : "memory");
}
__device__ __forceinline__ void tma2d_nohint(uint32_t dst, const CUtensorMap* m, int c0, int c1, uint32_t bar) {
  asm volatile("cp.async.bulk.tensor.2d.shared::cluster.global.mbarrier::complete_tx::bytes [%0], [%1, {%3,%4}], [%2];"
               ::"r"(dst), "l"(m), "r"(bar), "r"(c0), "r"(c1) : "memory");
}
__device__ __forceinline__ void tma3d(uint32_t dst, const CUtensorMap* m, int c0, int c1, int c2, uint32_t bar, uint64_t pol) {
  asm volatile("cp.async.bulk.tensor.3d.shared::cluster.global.mbarrier::complete_tx::bytes.L2::cache_hint [%0], [%1, {%3,%4,%5}], [%2], %6;"
               ::"r"(dst), "l"(m), "r"(bar), "r"(c0), "r"(c1), "r"(c2), "l"(pol) : "memory");
}
__device__ __forceinline__ void tma5d(uint32_t dst, const CUtensorMap* m, int c0, int c1, int c2, int c3, int c4, uint32_t bar, uint64_t pol) {
  asm volatile("cp.async.bulk.tensor.5d.shared::cluster.global.mbarrier::complete_tx::bytes.L2::cache_hint [%0], [%1, {%3,%4,%5,%6,%7}], [%2], %8;"
               ::"r"(dst), "l"(m), "r"(bar), "r"(c0), "r"(c1), "r"(c2), "r"(c3), "r"(c4), "l"(pol) : "memory");
}
__device__ __forceinline__ void bulk_ld(uint32_t dst, const void* src, uint32_t bytes, uint32_t bar) {
  asm volatile("cp.async.bulk.shared::cluster.global.mbarrier::complete_tx::bytes [%0], [%1], %2, [%3];" ::"r"(dst), "l"(src), "r"(bytes), "r"(bar) : "memory");
}
__device__ __forceinline__ void bar_sync(int id, int n) { asm volatile("barrier.cta.sync.aligned %0, %1;" ::"r"(id), "r"(n) : "memory"); }
__device__ __forceinline__ void cbar() { asm volatile("barrier.cta.sync.aligned 1, 256;" ::: "memory"); }
__device__ __forceinline__ bool bar_over(float ex) {
  uint32_t over;
  asm volatile("{\n.reg .pred p, q;\nsetp.gtu.f32 p, %1, 0f42700000;\nbarrier.cta.red.or.aligned.pred q, 4, 256, p;\nselp.u32 %0, 1, 0, q;\n}"
               : "=r"(over) : "f"(ex) : "memory");
  return over;
}

__device__ __forceinline__ uint32_t ldg_nc1(const void* p) { uint32_t v; asm volatile("ld.global.nc.L1::no_allocate.u32 %0, [%1];" : "=r"(v) : "l"(p)); return v; }
__device__ __forceinline__ uint32_t ldg_rlx1(const void* p) { uint32_t v; asm volatile("ld.relaxed.gpu.global.u32 %0, [%1];" : "=r"(v) : "l"(p) : "memory"); return v; }
__device__ __forceinline__ void stg4(void* p, uint4 v) { asm volatile("st.relaxed.gpu.global.v4.u32 [%0], {%1,%2,%3,%4};" ::"l"(p), "r"(v.x), "r"(v.y), "r"(v.z), "r"(v.w) : "memory"); }
__device__ __forceinline__ void stg1(void* p, uint32_t a) { asm volatile("st.relaxed.gpu.global.u32 [%0], %1;" ::"l"(p), "r"(a) : "memory"); }
__device__ __forceinline__ uint32_t nz(uint32_t w) { return max(w, 1u); }
__device__ __forceinline__ uint2 ldg_u64(const void* p) {
  uint2 v; asm volatile("{\n.reg .b64 a;\nld.relaxed.gpu.global.b64 a, [%2];\nmov.b64 {%0,%1}, a;\n}" : "=r"(v.x), "=r"(v.y) : "l"(p) : "memory"); return v;
}
__device__ __forceinline__ uint4 ldg_2u64(const void* p) {
  uint4 v; asm volatile("{\n.reg .b64 a, b;\nld.relaxed.gpu.global.v2.b64 {a, b}, [%4];\nmov.b64 {%0,%1}, a;\nmov.b64 {%2,%3}, b;\n}" : "=r"(v.x), "=r"(v.y), "=r"(v.z), "=r"(v.w) : "l"(p) : "memory"); return v;
}
__device__ __forceinline__ void stg_u64(void* p, uint32_t x, uint32_t y) {
  asm volatile("{\n.reg .b32 y;\nmax.u32 y, %2, 1;\nst.relaxed.gpu.global.v2.b32 [%0], {%1, y};\n}" ::"l"(p), "r"(x), "r"(y) : "memory");
}
__device__ __forceinline__ void red_u64(void* p, uint32_t x, uint32_t y) {
  asm volatile("{\n.reg .b32 y;\n.reg .b64 a;\nmax.u32 y, %2, 1;\nmov.b64 a, {%1, y};\nred.relaxed.gpu.global.or.b64 [%0], a;\n}" ::"l"(p), "r"(x), "r"(y) : "memory");
}
__device__ __forceinline__ void stg_u64_unless(uint32_t bad, void* p, uint32_t x, uint32_t y) {
  asm volatile("{\n.reg .b32 y;\n.reg .pred q;\nsetp.eq.u32 q, %3, 0;\nmax.u32 y, %2, 1;\n@q st.relaxed.gpu.global.v2.b32 [%0], {%1, y};\n}" ::"l"(p), "r"(x), "r"(y), "r"(bad) : "memory");
}

__device__ __forceinline__ void stg_cvt8(void* p, float a0, float a1, float b0, float b1, float c0, float c1, float d0, float d1) {
  asm volatile("{\n.reg .b32 x, y, z, w;\ncvt.rn.bf16x2.f32 x, %2, %1;\ncvt.rn.bf16x2.f32 y, %4, %3;\ncvt.rn.bf16x2.f32 z, %6, %5;\ncvt.rn.bf16x2.f32 w, %8, %7;\n"
               "max.u32 y, y, 1;\nmax.u32 w, w, 1;\nst.relaxed.gpu.global.v4.b32 [%0], {x, y, z, w};\n}"
               ::"l"(p), "f"(a0), "f"(a1), "f"(b0), "f"(b1), "f"(c0), "f"(c1), "f"(d0), "f"(d1) : "memory");
}
__device__ __forceinline__ uint32_t pack_bf16(float lo, float hi) { uint32_t r; asm("cvt.rn.bf16x2.f32 %0, %1, %2;" : "=r"(r) : "f"(hi), "f"(lo)); return r; }
__device__ __forceinline__ float bf_lo(uint32_t w) { return __uint_as_float(w << 16); }
__device__ __forceinline__ float bf_hi(uint32_t w) { return __uint_as_float(w & 0xffff0000u); }
__device__ __forceinline__ float ex2(float x) { float r; asm("ex2.approx.ftz.f32 %0, %1;" : "=f"(r) : "f"(x)); return r; }
__device__ __forceinline__ uint32_t hmul2(uint32_t a, uint32_t b) { uint32_t r; asm("mul.rn.bf16x2 %0, %1, %2;" : "=r"(r) : "r"(a), "r"(b)); return r; }
__device__ __forceinline__ uint32_t hadd2(uint32_t a, uint32_t b) { uint32_t r; asm("add.rn.bf16x2 %0, %1, %2;" : "=r"(r) : "r"(a), "r"(b)); return r; }
__device__ __forceinline__ uint32_t silu2(uint32_t v) { const float a = bf_lo(v), b = bf_hi(v); return pack_bf16(__fdividef(a, 1.f + __expf(-a)), __fdividef(b, 1.f + __expf(-b))); }
constexpr uint32_t ONE2 = 0x3f803f80u;

__device__ __forceinline__ void ldsm4(uint32_t (&r)[4], uint32_t a) { asm volatile("ldmatrix.sync.aligned.m8n8.x4.shared.b16 {%0,%1,%2,%3}, [%4];" : "=r"(r[0]), "=r"(r[1]), "=r"(r[2]), "=r"(r[3]) : "r"(a) : "memory"); }
__device__ __forceinline__ void ldsm4t(uint32_t (&r)[4], uint32_t a) { asm volatile("ldmatrix.sync.aligned.m8n8.x4.trans.shared.b16 {%0,%1,%2,%3}, [%4];" : "=r"(r[0]), "=r"(r[1]), "=r"(r[2]), "=r"(r[3]) : "r"(a) : "memory"); }
__device__ __forceinline__ void stsm4t(uint32_t a, uint32_t r0, uint32_t r1, uint32_t r2, uint32_t r3) { asm volatile("stmatrix.sync.aligned.m8n8.x4.trans.shared.b16 [%0], {%1,%2,%3,%4};" ::"r"(a), "r"(r0), "r"(r1), "r"(r2), "r"(r3) : "memory"); }
__device__ __forceinline__ uint32_t movm(uint32_t a) { uint32_t d; asm volatile("movmatrix.sync.aligned.m8n8.trans.b16 %0, %1;" : "=r"(d) : "r"(a)); return d; }
__device__ __forceinline__ void mma16816(float (&d)[4], const uint32_t (&a)[4], uint32_t b0, uint32_t b1) {
  asm volatile("mma.sync.aligned.m16n8k16.row.col.f32.bf16.bf16.f32 {%0,%1,%2,%3}, {%4,%5,%6,%7}, {%8,%9}, {%0,%1,%2,%3};"
               : "+f"(d[0]), "+f"(d[1]), "+f"(d[2]), "+f"(d[3]) : "r"(a[0]), "r"(a[1]), "r"(a[2]), "r"(a[3]), "r"(b0), "r"(b1));
}
__device__ __forceinline__ void sts1(uint32_t a, uint32_t v) { asm volatile("st.shared.u32 [%0], %1;" ::"r"(a), "r"(v) : "memory"); }
__device__ __forceinline__ void sts2(uint32_t a, uint32_t x, uint32_t y) { asm volatile("st.shared.v2.u32 [%0], {%1,%2};" ::"r"(a), "r"(x), "r"(y) : "memory"); }
__device__ __forceinline__ void sts4(uint32_t a, uint4 v) { asm volatile("st.shared.v4.u32 [%0], {%1,%2,%3,%4};" ::"r"(a), "r"(v.x), "r"(v.y), "r"(v.z), "r"(v.w) : "memory"); }
__device__ __forceinline__ void sts2f(uint32_t a, float x, float y) { asm volatile("st.shared.v2.f32 [%0], {%1,%2};" ::"r"(a), "f"(x), "f"(y) : "memory"); }
__device__ __forceinline__ void sts4f(uint32_t a, float x, float y, float z, float w) { asm volatile("st.shared.v4.f32 [%0], {%1,%2,%3,%4};" ::"r"(a), "f"(x), "f"(y), "f"(z), "f"(w) : "memory"); }
__device__ __forceinline__ void stsf(uint32_t a, float v) { asm volatile("st.shared.f32 [%0], %1;" ::"r"(a), "f"(v) : "memory"); }
__device__ __forceinline__ uint32_t lds1(uint32_t a) { uint32_t v; asm volatile("ld.shared.u32 %0, [%1];" : "=r"(v) : "r"(a) : "memory"); return v; }
__device__ __forceinline__ float ldsf(uint32_t a) { float v; asm volatile("ld.shared.f32 %0, [%1];" : "=f"(v) : "r"(a) : "memory"); return v; }
__device__ __forceinline__ float2 ldsf2(uint32_t a) { float2 v; asm volatile("ld.shared.v2.f32 {%0,%1}, [%2];" : "=f"(v.x), "=f"(v.y) : "r"(a) : "memory"); return v; }
__device__ __forceinline__ float4 ldsf4(uint32_t a) { float4 v; asm volatile("ld.shared.v4.f32 {%0,%1,%2,%3}, [%4];" : "=f"(v.x), "=f"(v.y), "=f"(v.z), "=f"(v.w) : "r"(a) : "memory"); return v; }
__device__ __forceinline__ void lds4(uint32_t (&r)[4], uint32_t a) { asm volatile("ld.shared.v4.u32 {%0,%1,%2,%3}, [%4];" : "=r"(r[0]), "=r"(r[1]), "=r"(r[2]), "=r"(r[3]) : "r"(a) : "memory"); }

__device__ __forceinline__ void wg_fence() { asm volatile("wgmma.fence.sync.aligned;" ::: "memory"); }
__device__ __forceinline__ void wg_commit() { asm volatile("wgmma.commit_group.sync.aligned;" ::: "memory"); }
template <int N> __device__ __forceinline__ void wg_wait() { asm volatile("wgmma.wait_group.sync.aligned %0;" ::"n"(N) : "memory"); }
__host__ __device__ constexpr uint32_t desc_lo(uint32_t off) { return ((SB + off) >> 4) | 0x10000u; }
template <int TA, int ACC> __device__ __forceinline__ void wgmma_n16(float (&d)[8], uint32_t da, uint32_t db) {
  asm volatile("{\n.reg .b64 da, db;\nmov.b64 da, {%8, 0x40000040};\nmov.b64 db, {%9, 0x40000040};\n"
               "wgmma.mma_async.sync.aligned.m64n16k16.f32.bf16.bf16 {%0,%1,%2,%3,%4,%5,%6,%7}, da, db, %11, 1, 1, %10, 0;\n}"
               : "+f"(d[0]), "+f"(d[1]), "+f"(d[2]), "+f"(d[3]), "+f"(d[4]), "+f"(d[5]), "+f"(d[6]), "+f"(d[7])
               : "r"(da), "r"(db), "n"(TA), "n"(ACC));
}
__device__ __forceinline__ void wgmma_n16_ones(float (&d)[8], uint32_t one, uint32_t db) {
  asm volatile("{\n.reg .b64 db;\nmov.b64 db, {%9, 0x40000040};\n"
               "wgmma.mma_async.sync.aligned.m64n16k16.f32.bf16.bf16 {%0,%1,%2,%3,%4,%5,%6,%7}, {%8,%8,%8,%8}, db, 1, 1, 1, 0;\n}"
               : "+f"(d[0]), "+f"(d[1]), "+f"(d[2]), "+f"(d[3]), "+f"(d[4]), "+f"(d[5]), "+f"(d[6]), "+f"(d[7])
               : "r"(one), "r"(db));
}
__device__ __forceinline__ void acc_fence(float (&d)[8]) {
  asm volatile("" : "+f"(d[0]), "+f"(d[1]), "+f"(d[2]), "+f"(d[3]), "+f"(d[4]), "+f"(d[5]), "+f"(d[6]), "+f"(d[7]) :: "memory");
}

template <int N, int STRIDE> __device__ __forceinline__ void load_units(uint2 (&v)[N], const uint32_t* p) {
#pragma unroll
  for (int i = 0; i < N; i++) v[i] = ldg_u64(p + i * STRIDE);
}
__device__ __forceinline__ void reload_unit(uint2& v, const uint32_t* p) {
  asm volatile("{\n.reg .pred q;\nsetp.eq.u32 q, %1, 0;\n@q ld.relaxed.gpu.global.v2.b32 {%0, %1}, [%2];\n}" : "+r"(v.x), "+r"(v.y) : "l"(p) : "memory");
}
template <int N> __device__ __forceinline__ uint32_t min_flags(const uint2 (&v)[N]) {
  uint32_t a = v[0].y, b = v[1].y;
#pragma unroll
  for (int i = 2; i < N; i += 2) { a = min(a, v[i].y); b = min(b, v[i + 1].y); }
  return min(a, b);
}
template <int N, int STRIDE> __device__ __forceinline__ int check_units(uint2 (&v)[N], const uint32_t* p) {
  int it = 0;
  while (!__all_sync(~0u, min_flags(v) != 0)) {
#pragma unroll
    for (int i = 0; i < N; i++) reload_unit(v[i], p + i * STRIDE);
    if (++it > SPIN_LIMIT) __trap();
  }
  return it;
}
__device__ __forceinline__ void sum4_to_smem(const uint2 (&v)[4], uint32_t dst) {
  const float c0 = (bf_lo(v[0].x) + bf_lo(v[1].x)) + (bf_lo(v[2].x) + bf_lo(v[3].x));
  const float c1 = (bf_hi(v[0].x) + bf_hi(v[1].x)) + (bf_hi(v[2].x) + bf_hi(v[3].x));
  const float c2 = (bf_lo(v[0].y) + bf_lo(v[1].y)) + (bf_lo(v[2].y) + bf_lo(v[3].y));
  const float c3 = (bf_hi(v[0].y) + bf_hi(v[1].y)) + (bf_hi(v[2].y) + bf_hi(v[3].y));
  sts1(dst, pack_bf16(c0, c1));
  sts1(dst + 128, pack_bf16(c2, c3));
}
__device__ __forceinline__ uint32_t a_t_offset(int w, int lane) {
  const int mi = lane >> 3, r = lane & 7;
  return (w >> 2) * 16384 + (8 * (mi >> 1) + r) * 128 + (((2 * (w & 3) + (mi & 1)) ^ r) << 4);
}
__device__ __forceinline__ void load_a_t(uint32_t (&a)[8][4], uint32_t base) {
#pragma unroll
  for (int ks = 0; ks < 8; ks++) ldsm4t(a[ks], base + ks * 2048);
}
__device__ __forceinline__ void mma128(float (&d)[4], const uint32_t (&a)[8][4], const uint32_t (&b)[4][4]) {
  float e[4][4] = {{d[0], d[1], d[2], d[3]}, {0.f, 0.f, 0.f, 0.f}, {0.f, 0.f, 0.f, 0.f}, {0.f, 0.f, 0.f, 0.f}};
#pragma unroll
  for (int kk = 0; kk < 4; kk++) { mma16816(e[(2 * kk) & 3], a[2 * kk], b[kk][0], b[kk][1]); mma16816(e[(2 * kk + 1) & 3], a[2 * kk + 1], b[kk][2], b[kk][3]); }
#pragma unroll
  for (int i = 0; i < 4; i++) d[i] = (e[0][i] + e[1][i]) + (e[2][i] + e[3][i]);
}
template <int NP> __device__ __forceinline__ bool sum_pieces(const uint32_t* p0, uint32_t one, float (&r)[4]) {
  uint2 v[NP / 4];
  load_units<NP / 4, 64>(v, p0);
  float d[4][4] = {};
#pragma unroll
  for (int i = 0; i < NP / 8; i++) { const uint32_t a[4] = {v[2 * i].x, v[2 * i].y, v[2 * i + 1].x, v[2 * i + 1].y}; mma16816(d[i & 3], a, one, one); }
  const bool ok = __all_sync(~0u, min_flags(v) != 0);
#pragma unroll
  for (int k = 0; k < 4; k++) r[k] = (d[0][k] + d[1][k]) + (d[2][k] + d[3][k]);
  return ok;
}
template <typename F> __device__ __forceinline__ float reduce_g(const float (&x)[4], int lane, F f) {
  const bool u4 = lane & 16, u3 = lane & 8;
  const float a0 = f(u4 ? x[2] : x[0], __shfl_xor_sync(~0u, u4 ? x[0] : x[2], 16));
  const float a1 = f(u4 ? x[3] : x[1], __shfl_xor_sync(~0u, u4 ? x[1] : x[3], 16));
  const float b = f(u3 ? a1 : a0, __shfl_xor_sync(~0u, u3 ? a0 : a1, 8));
  return f(b, __shfl_xor_sync(~0u, b, 4));
}

__global__ void __launch_bounds__(NTHREADS, 1)
fused_decode_kernel(__nv_bfloat16* __restrict__ gout, Scratch* __restrict__ gs, const uint8_t* __restrict__ gwmod,
                    const uint8_t* __restrict__ gx, const uint8_t* __restrict__ gc, uint32_t* __restrict__ gin,
                    const __grid_constant__ Params P) {
  constexpr Tune T{};
  extern __shared__ __align__(1024) uint8_t smem_raw[];
  constexpr uint32_t sb = SB;
  uint4 w0, w1;
  uint2 cc;
  {
    const uint32_t tx = threadIdx.x, bx = blockIdx.x;
    const uint8_t* pw = gwmod + ((128 * (bx & 3) + 4 * (tx >> 3) + ((tx >> 2) & 1)) * 6144 + 64 * (bx >> 2) + 16 * (tx & 3));
    const uint8_t* pc = gc + (((tx >> 2) & 7) * 1024 + 256 * (bx & 3) + (tx & 0xe0) + 8 * (tx & 3));
    asm volatile("{\n.reg .pred q;\nsetp.lt.u32 q, %12, 256;\n@q ld.global.nc.L1::no_allocate.v4.u32 {%0,%1,%2,%3}, [%10];\n"
                 "@q ld.global.nc.L1::no_allocate.v4.u32 {%4,%5,%6,%7}, [%10+12288];\n@q ld.global.nc.v2.u32 {%8,%9}, [%11];\n}"
                 : "=r"(w0.x), "=r"(w0.y), "=r"(w0.z), "=r"(w0.w), "=r"(w1.x), "=r"(w1.y), "=r"(w1.z), "=r"(w1.w), "=r"(cc.x), "=r"(cc.y)
                 : "l"(pw), "l"(pc), "r"(tx));
  }
  const int tid = __shfl_xor_sync(0xffffffffu, threadIdx.x ^ 1, 1), lane = tid & 31;
  const int w = __shfl_sync(0xffffffffu, threadIdx.x >> 5, 0);
  const int cta = blockIdx.x;
  auto keep = [&](uint32_t v) { return __shfl_sync(~0u, v, lane); };
  auto BAR = [](int i) { return SB + OFF_BARS + 8 * i; };
  auto selector = [&](int c) { uint32_t v; asm volatile("ld.shared.u8 %0, [%1];" : "=r"(v) : "r"(sb + OFF_SEL + c) : "memory"); return v; };
  auto inbox = [&](int c, int k) { return gin + blk(c, k, selector(c)); };
  auto nearbox = [&](int c, int k) { return gin + blk(c, k, selector(cta) ^ flip((c ^ cta) & 15)); };
  const int g = lane >> 2, t = lane & 3;
  const int hI = cta >> 2, jI = cta & 3;
  const int bs = cta >> 1, hh = cta & 1;

  CLK_DECL;
  CLK(0);
  if (w == 8) {
    CLK(7);
    const uint32_t t_entry = gtime32();
    CLK(8);
    if (lane == 0) {
      if ((uint32_t)__cvta_generic_to_shared(smem_raw) != SB) __trap();
      mbar_init(BAR(BAR_WQ), 1); mbar_init(BAR(BAR_WQ + 1), 1); mbar_init(BAR(BAR_XC), 1); mbar_init(BAR(BAR_C), 1);
      asm volatile("fence.mbarrier_init.release.cluster;" ::: "memory");
      asm volatile("prefetch.tensormap [%0];" ::"l"(&P.wq) : "memory");
      mbar_expect(BAR(BAR_XC), 8192); mbar_expect(BAR(BAR_C), 8192); mbar_expect(BAR(BAR_WQ), 16384); mbar_expect(BAR(BAR_WQ + 1), 16384);
      CLK(9);
    }
    __syncwarp();
    asm volatile("barrier.cta.arrive.aligned 0, %0;" ::"n"(NTHREADS) : "memory");
    CLK(10);
    uint32_t tn = t_entry + (uint32_t)(T.PC_T0 + ((bs * 37) & 63) * T.PC_STAG / 64);
    const int h = hI, j = jI;
    if (lane == 0) {
      uint64_t pol; asm volatile("createpolicy.fractional.L2::evict_first.b64 %0, 1.0;" : "=l"(pol));
#pragma unroll
      for (int u = 0; u < 4; u++) {
        until_ns(tn + u * T.PC_P1);
        if (u == 0) CLK(11);
        tma2d(sb + OFF_WQ + u * 8192, &P.wq, 128 * h + 64 * (u >> 1), 128 * j + 64 * (u & 1), BAR(BAR_WQ + (u >> 1)), pol);
        if (u == 0) {
#pragma unroll
          for (int i = 0; i < 8; i++) { const int o = ((i + cta) & 3) * 2048; bulk_ld(sb + OFF_XS + (i >> 2) * 8192 + o, (i < 4 ? gx : gc) + o, 2048, BAR(i < 4 ? BAR_XC : BAR_C)); }
          CLK(1);
          asm volatile("prefetch.tensormap [%0];" ::"l"(&P.wuk) : "memory");
          asm volatile("prefetch.tensormap [%0];" ::"l"(&P.wm2) : "memory");
          asm volatile("prefetch.tensormap [%0];" ::"l"(&P.ckv2) : "memory");
        }
      }
    }
    __syncwarp();
    tn += 4 * T.PC_P1;
    bar_sync(5, 64);
    if (lane == 0) {
      uint64_t pol; asm volatile("createpolicy.fractional.L2::evict_first.b64 %0, 1.0;" : "=l"(pol));
#pragma unroll
      for (int u = 0; u < 4; u++) {
        if (u & 1) mbar_wait(BAR(BAR_WQ + (u >> 1)));
        slot(tn, T.PC_SL);
        tma5d(sb + OFF_WUK + u * 8192, &P.wuk, 128 * h + 64 * (u >> 1), 0, 0, 0, 8 * j + 4 * (u & 1), BAR(BAR_WUK + (u >> 1)), pol);
        tn += T.PC_P1;
      }
#pragma unroll
      for (int u = 0; u < 2; u++) {
        if (u) mbar_wait(BAR(BAR_WUK));
        slot(tn, T.PC_SL);
        if (j != 3) tma2d_nohint(sb + OFF_WM2 + u * 8192, &P.wm2, 1024 + 16 * (3 * h + j), 256 * u, BAR(BAR_WM2));
        tn += T.PC_PM;
      }
      const int row0 = (bs >> 3) * 4096 + (bs & 7) * 64;
      uint32_t dst = sb + OFF_RING;
#pragma unroll 1
      for (int n = 0; n < 31; n++) {
        if (n >= 4 && (n < 12 || (n & 3) == 0)) mbar_wait(BAR(n >= 12 ? BAR_EMPTY + (n >> 2) - 3 : (n == 7 && j != 3) ? BAR_P0BD : (n == 8 || n == 9) ? BAR_P2D : BAR_P1D));
        if (n < T.PC_NW) {
          if (n >= 4) mbar_wait(BAR(BAR_FULL + n - 4));
          else if (n & 1) mbar_wait(BAR((n < 2 || j == 3) ? BAR_WUK + 1 : BAR_WM2));
        }
        slot(tn, T.PC_SL);
        tma3d(dst, &P.ckv2, 0, row0 + (n >> 2) * 512, 2 * (n & 3), BAR(BAR_FULL + n), pol);
        dst = (n == 11 || n == 23) ? sb + OFF_RING : dst + 16384;
        tn += T.PC_P2;
        if (n == 4) CLK(2);
        if (n == 12) CLK(3);
        if (n == 20) CLK(4);
        if (n == 28) CLK(5);
        if (n == 24) {
          asm volatile("prefetch.tensormap [%0];" ::"l"(&P.ckv1) : "memory");
          asm volatile("prefetch.tensormap [%0];" ::"l"(&P.wuv) : "memory");
          asm volatile("prefetch.tensormap [%0];" ::"l"(&P.wo) : "memory");
          asm volatile("prefetch.tensormap [%0];" ::"l"(cta < NFF ? &P.w1 : &P.wm3) : "memory");
          asm volatile("prefetch.tensormap [%0];" ::"l"(&P.w2) : "memory");
        }
      }
      slot(tn, T.PC_SL);
      tma3d(dst, &P.ckv1, 0, row0 + 7 * 512, 6, BAR(BAR_LAST + 3), pol);
      tma3d(dst + 8192, &P.ckv1, 0, row0 + 7 * 512, 7, BAR(BAR_LAST + 4), pol);
      tn += T.PC_P2;
      CLK(6);
      auto unit = [&](int u) {
        if (u < 4) tma5d(sb + OFF_WUV + u * 8192, &P.wuv, 128 * h + 64 * (u >> 1), 0, 4 * (j >> 1), 0, 2 * (j & 1) + (u & 1), BAR(BAR_WUV + (u >> 1)), pol);
        else if (u < 8) tma2d(sb + OFF_WO + (u - 4) * 8192, &P.wo, 128 * j + 64 * ((u - 4) >> 1), 128 * h + 64 * (u & 1), BAR(BAR_WO + ((u - 4) >> 1)), pol);
        else if (u < 10) { if (cta < NFF) tma2d_nohint(sb + OFF_W1 + (u - 8) * 16384, &P.w1, 32 * bs, 256 * (u - 8), BAR(BAR_W1)); }
        else if (cta < NFF) tma3d(sb + OFF_W2 + (u - 10) * 8192, &P.w2, 0, 32 * bs, 4 * hh + 2 * (u - 10), BAR(BAR_W2), pol);
        else tma2d_nohint(sb + OFF_W1 + (u - 10) * 16384, &P.wm3, 2560 + 32 * (cta - NFF), 256 * (u - 10), BAR(BAR_W1));
      };
      mbar_wait(BAR(BAR_EMPTY + 5));
#pragma unroll
      for (int u = 0; u < 12; u++) {
        if (u == 8) mbar_wait(BAR(BAR_EMPTY + 6));
        until_ns(tn + (u < 4 ? T.T_UV + u * T.P_UV : u < 8 ? T.T_O + (u - 4) * T.P_O : u < 10 ? T.T_1 + (u - 8) * T.P_F : (cta < NFF ? T.T_2 : T.T_GB) + (u - 10) * T.P_F));
        unit(u);
        if (u == 3) {
#pragma unroll
          for (int q = 0; q < 4; q++)
            if (q < T.PF_N) {
              until_ns(tn + T.T_PF + q * T.P_PF);
              asm volatile("cp.async.bulk.prefetch.tensor.2d.L2.global.tile [%0, {%1,%2}];" ::"l"(&P.wo), "r"(128 * j + 64 * (q >> 1)), "r"(128 * h + 64 * (q & 1)) : "memory");
            }
        }
      }
      CLK_DUMP();
    }
    return;
  }

  if (w == 9) {
    if (lane == 0) {
#pragma unroll
      for (int i = 0; i < NBARS; i++) mbar_init(BAR(i), i >= BAR_P1D ? 8 : i >= BAR_EMPTY ? 4 : 1);
      asm volatile("fence.mbarrier_init.release.cluster;" ::: "memory");
    }
    __syncwarp();
    mbar_expect(BAR(lane), lane == BAR_LAST + 3 ? 8192 : 16384);
    if (lane < BAR_ALLCLR - 32) mbar_expect(BAR(32 + lane), lane == 0 ? 8192 : lane == BAR_W1 - 32 ? 32768 : 16384);
    CLK(9);
    asm volatile("barrier.cta.arrive.aligned 5, 64;" ::: "memory");
    asm volatile("barrier.cta.arrive.aligned 0, %0;" ::"n"(NTHREADS) : "memory");
  }
  const uint32_t epoch = ldg_rlx1(&gs->epoch);

  if (w == 9) {
    const int mo = g * 512 + 16 * hI + 2 * jI;
    const uint32_t xo0 = ldg_nc1(gx + mo * 2), xo1 = ldg_nc1(gx + mo * 2 + 16);
    const int par = epoch & 1;
    const uint32_t t0 = gtime32();
    const uint4 z = make_uint4(0, 0, 0, 0);
    uint32_t sel;
    {
      uint32_t* pa = gin + blk(cta, 5, 0) + 960;
      uint32_t* pb = gin + blk(cta, 5, 1) + 960;
      until_ns(t0 + T.PR_T0);
      if (lane < 4) stg4(reinterpret_cast<uint4*>(lane & 2 ? pa : pb) + (lane & 1), z);
      uint32_t ma = 0xffffffffu, mb = 0xffffffffu;
#pragma unroll 1
      for (int i = 0; i < 2 * T.PR_N; i++) {
        const uint32_t c0 = clk32();
        asm volatile("{\n.reg .pred q;\n.reg .b32 v;\nsetp.eq.u32 q, %1, 0;\nmov.u32 v, 0;\n@q atom.relaxed.gpu.global.add.u32 v, [%0], 1;\n"
                     "setp.eq.u32 q, v, 0xffffffff;\n@q trap;\n}" ::"l"(i & 1 ? pb : pa), "r"(lane) : "memory");
        const uint32_t d = clk32() - c0;
        if (i & 1) mb = min(mb, d); else ma = min(ma, d);
      }
      sel = __shfl_sync(~0u, (uint32_t)(mb < ma), 0);
      const uint32_t sw = 2 * (epoch + 1) + sel;
      if (lane < 2) stg4(reinterpret_cast<uint4*>(gin + blk(cta, 5, 1) + 896) + lane, make_uint4(sw, sw, sw, sw));
    }
    until_ns(t0 + T.CLR_T0);
    {
#pragma unroll 1
      for (int i0 = 0; i0 < 13; i0++) {
        uint4* q = reinterpret_cast<uint4*>(gin + (i0 < 12 ? blk(cta, i0 >> 1, sel) + (i0 & 1) * 512 : blk(cta, 4, sel ^ 1) + 512)) + lane;
#pragma unroll
        for (int i = 0; i < 4; i++) if (i0 != 11 || i < 3) stg4(q + i * 32, z);
        backoff(T.CLR_CLK);
      }
#pragma unroll
      for (int i = 0; i < 2; i++) {
        if (jI == 1) stg4(reinterpret_cast<uint4*>(gin + blk(cta, 6, i)) + lane, z);
        if (lane < 2) stg4(reinterpret_cast<uint4*>(gin + blk(cta, 5, i) + 928) + lane, z);
        stg4(reinterpret_cast<uint4*>(gin + blk(16 * g, 6 + (cta >> 6), i) + (cta & 63) * 16) + t, z);
      }
      CLK(1);
      {
        uint32_t sv = 0;
        uint32_t u[4];
        int it = 0;
        do {
#pragma unroll
          for (int i = 0; i < 4; i++) u[i] = ldg_rlx1(gin + blk(4 * lane + i, 5, 1) + 896) ^ (2 * (epoch + 1));
          if (++it > SPIN_LIMIT) __trap();
        } while (!__all_sync(~0u, (u[0] | u[1] | u[2] | u[3]) < 2));
#pragma unroll
        for (int i = 0; i < 4; i++) sv |= u[i] << (8 * i);
        sts1(sb + OFF_SEL + lane * 4, sv);
      }
      asm volatile("fence.acq_rel.gpu;" ::: "memory");
      CLK(2);
      __syncwarp();
      if (lane < NSYNC) asm volatile("red.relaxed.gpu.global.add.u32 [%0], 1;" ::"l"(&gs->sync[lane][0]) : "memory");
#pragma unroll
      for (int i = 0; i < 4; i++) stg4(reinterpret_cast<uint4*>(gs->QP[par ^ 1] + cta * 512) + i * 32 + lane, z);
      backoff(T.CLR_CLK);
#pragma unroll
      for (int i = 0; i < 4; i++) stg4(reinterpret_cast<uint4*>(gs->QX[par ^ 1] + cta * 512) + i * 32 + lane, z);
      stg4(reinterpret_cast<uint4*>(gs->MOD1[par ^ 1] + cta * 128) + lane, z);
      if (lane < 16) stg4(reinterpret_cast<uint4*>(gs->MOD2[par ^ 1] + cta * 64) + lane, z);
      const uint32_t target = (epoch + 1) * NCTA;
      uint32_t c; int it = 0;
      do {
        backoff(T.CLR_CLK);
        asm volatile("ld.acquire.gpu.global.u32 %0, [%1];" : "=r"(c) : "l"(&gs->sync[cta % NSYNC][0]) : "memory");
        if (++it > SPIN_LIMIT) __trap();
      } while (!__all_sync(~0u, (int)(c - target) >= 0));
      if (lane == 0) mbar_arrive(BAR(BAR_ALLCLR));
    }
    CLK(3);
    const uint32_t* const pg = gs->MOD2[par] + cta * 16 + g * 2;
    auto gate = [&](const uint32_t* q) { uint2 u; int it = 0; do { u = ldg_u64(q); if (++it > SPIN_LIMIT) __trap(); } while (!__all_sync(~0u, u.y != 0)); return u; };
    const uint2 gau = gate(pg);
    uint32_t anchor;
    {
      uint32_t* const po = gin + blk(16 * (lane & 7), 5, lane >> 3) + 928;
      const uint32_t* const pi = nearbox(cta & ~15, 5) + 928;
      mbar_wait(BAR(BAR_LAST + T.TS_P));
      unsigned long long now; asm volatile("mov.u64 %0, %%globaltimer;" : "=l"(now));
      if (lane < 16) asm volatile("red.relaxed.gpu.global.add.u64 [%0], %1;" ::"l"(po), "l"((now << 8) + 1) : "memory");
      backoff(T.D_TS);
      uint2 v; int it = 0;
      do { v = ldg_u64(pi); if (++it > SPIN_LIMIT) __trap(); } while (!__all_sync(~0u, (v.x & 255) == NCTA));
      const uint32_t mean = __funnelshift_r(v.x, v.y, 15);
      const int age = min(max((int)(gtime32() - mean), 0), 4000);
      anchor = clk32() - age * 7 / 4 + T.TS_O;
      if (lane == 0) { sts1(sb + OFF_TS, anchor); mbar_arrive(BAR(BAR_TS)); }
      CLK(10);
    }
    {
      const uint32_t* pm = pin(nearbox(4 * hI + 1, 6) + lane * 4);
      wait_clk(anchor, T.A_M);
      uint4 ml = ldg_2u64(pm);
      int it = 0;
      while (!__all_sync(~0u, ml.y != 0 && ml.w != 0)) { ml = ldg_2u64(pm); if (++it > SPIN_LIMIT) __trap(); }
      ITS(2, it);
      float M = fmaxf(__uint_as_float(ml.x), __uint_as_float(ml.z));
      M = fmaxf(M, __shfl_xor_sync(~0u, M, 1)); M = fmaxf(M, __shfl_xor_sync(~0u, M, 2));
      const float e0 = ex2(__uint_as_float(ml.x) - M), e1 = ex2(__uint_as_float(ml.z) - M);
      float l = e0 * __uint_as_float(ml.y) + e1 * __uint_as_float(ml.w);
      l += __shfl_xor_sync(~0u, l, 1); l += __shfl_xor_sync(~0u, l, 2);
      const float inv = __fdividef(1.f, l);
      sts2f(sb + OFF_WV + lane * 8, e0 * inv, e1 * inv);
      __syncwarp();
      if (lane == 0) mbar_arrive(BAR(BAR_WV));
      CLK(11);
    }
    uint32_t* x3o[4];
#pragma unroll
    for (int i = 0; i < 4; i++) x3o[i] = pin(gin + blk(32 * i + 16 * (t >> 1), 6 + (cta >> 6), t) + (cta & 63) * 16 + g * 2);
    uint32_t* const fo = pin(reinterpret_cast<uint32_t*>(gout) + mo / 2 + 4 * (t & 1));
    const uint32_t* const p3 = pin(gin + blk(cta, 4, sel) + t * 16 + g * 2);
    const uint32_t* const p4 = pin(gin + blk(cta, 5, sel) + t * 16 + g * 2);
    const uint32_t one = pin((g & 1) ? 0x3f800000u : 0x00003f80u);
    const float xf[4] = {pin(bf_lo(xo0)), pin(bf_hi(xo0)), pin(bf_lo(xo1)), pin(bf_hi(xo1))};
    const float ga[4] = {pin(bf_lo(gau.x)), pin(bf_hi(gau.x)), pin(bf_lo(gau.y)), pin(bf_hi(gau.y))};
    mbar_wait(BAR(BAR_P5D));
    backoff(T.D_X3A);
    wait_clk(anchor, T.A_X1 + T.R_X3A);
    CLK(4);
    float r[4];
    uint32_t x20, x21;
    int it = 0;
    bool ok;
    do {
      ok = sum_pieces<32>(p3, one, r);
      x20 = pack_bf16(xf[0] + ga[0] * r[0], xf[1] + ga[1] * r[1]); x21 = pack_bf16(xf[2] + ga[2] * r[2], xf[3] + ga[3] * r[3]);
#pragma unroll
      for (int i = 0; i < 4; i++) stg_u64_unless(!ok || (i == 3 && t >= 2), x3o[i], x20, x21);
    } while (!ok && ++it < SPIN_LIMIT);
    if (!ok) __trap();
    CLK(6);
    ITS(0, it);
    const uint32_t xw = (t & 1) ? x21 : x20;
    const float xa = pin(bf_lo(xw)), xb = pin(bf_hi(xw));
    if (cta < NFF) mbar_wait(BAR(BAR_P7D)); else wait_clk(anchor, T.A_X1 + T.R_X3A + T.R_X3B + T.R_FIN - T.D_FIN);
    uint2 gbu = ldg_u64(pg + 3 * 2048);
    backoff(T.D_FIN);
    CLK(7);
    do {
      ok = sum_pieces<NFG>(p4, one, r);
      ok = ok && __all_sync(~0u, gbu.y != 0);
      const uint32_t gw = (t & 1) ? gbu.y : gbu.x;
      const uint32_t o = pack_bf16(xa + bf_lo(gw) * ((t & 1) ? r[2] : r[0]), xb + bf_hi(gw) * ((t & 1) ? r[3] : r[1]));
      if (ok && t < 2) asm volatile("st.global.u32 [%0], %1;" ::"l"(fo), "r"(o) : "memory");
      reload_unit(gbu, pg + 3 * 2048);
    } while (!ok && ++it < SPIN_LIMIT);
    if (!ok) __trap();
    ITS(1, it);
    CLK(8);
    CLK_DUMP();
    if (cta == 0 && lane == 0) stg1(&gs->epoch, epoch + 1);
    return;
  }

  const int wg = w >> 2, wq = w & 3;
  uint32_t tstore;
  {
    CLK(40);
    const uint32_t a[4] = {silu2(cc.x), 0u, silu2(cc.y), 0u};
    float d[4][4] = {{0.f, 0.f, 0.f, 0.f}, {0.f, 0.f, 0.f, 0.f}, {0.f, 0.f, 0.f, 0.f}, {0.f, 0.f, 0.f, 0.f}};
    mma16816(d[0], a, movm(w0.x), movm(w1.x)); mma16816(d[1], a, movm(w0.y), movm(w1.y));
    mma16816(d[2], a, movm(w0.z), movm(w1.z)); mma16816(d[3], a, movm(w0.w), movm(w1.w));
    CLK(1);
    sts4f(sb + OFF_P0S + w * 1088 + lane * 16, d[0][0], d[0][1], d[1][0], d[1][1]);
    sts4f(sb + OFF_P0S + w * 1088 + 544 + lane * 16, d[2][0], d[2][1], d[3][0], d[3][1]);
    bar_sync(0, NTHREADS);
    if (tid < 128) {
      const uint32_t src = sb + OFF_P0S + ((tid >> 2) & 1) * 544 + (((tid >> 3) & 7) * 4 + 2 * (tid >> 6) + (tid & 1)) * 16 + ((tid >> 1) & 1) * 8;
      float2 v[8];
#pragma unroll
      for (int i = 0; i < 8; i++) v[i] = ldsf2(src + i * 1088);
      const float ax = ((v[0].x + v[1].x) + (v[2].x + v[3].x)) + ((v[4].x + v[5].x) + (v[6].x + v[7].x));
      const float ay = ((v[0].y + v[1].y) + (v[2].y + v[3].y)) + ((v[4].y + v[5].y) + (v[6].y + v[7].y));
      stg1(gs->MOD1[epoch & 1] + jI * 4096 + hI * 128 + tid, nz(pack_bf16(ax, ay)));
    }
    tstore = clk32();
  }
  CLK(2);
  const int par = epoch & 1;
  uint32_t cf[4][4];
  mbar_wait(BAR(BAR_XC));
  {
    uint32_t u[2][4];
    lds4(u[0], sb + OFF_XS + w * 1024 + lane * 16); lds4(u[1], sb + OFF_XS + w * 1024 + 512 + lane * 16);
    float v[16];
#pragma unroll
    for (int i = 0; i < 8; i++) { v[2 * i] = bf_lo(u[i >> 2][i & 3]); v[2 * i + 1] = bf_hi(u[i >> 2][i & 3]); }
    float s = 0.f;
#pragma unroll
    for (int i = 0; i < 16; i++) s += v[i];
#pragma unroll
    for (int o = 16; o; o >>= 1) s += __shfl_xor_sync(~0u, s, o);
    const float mu = s * (1.f / 512.f);
    float q = 0.f;
#pragma unroll
    for (int i = 0; i < 16; i++) { v[i] -= mu; q += v[i] * v[i]; }
#pragma unroll
    for (int o = 16; o; o >>= 1) q += __shfl_xor_sync(~0u, q, o);
    const float rs = rsqrtf(q * (1.f / 512.f) + 1e-5f);
    const bool hi = jI & 2;
    uint32_t o[4];
#pragma unroll
    for (int i = 0; i < 4; i++) o[i] = pack_bf16((hi ? v[8 + 2 * i] : v[2 * i]) * rs, (hi ? v[9 + 2 * i] : v[2 * i + 1]) * rs);
    if ((lane >> 4) == (jI & 1)) sts4(sb + OFF_XN + w * 272 + (lane & 15) * 16, make_uint4(o[0], o[1], o[2], o[3]));
  }
  CLK(3);
  uint32_t aw[8][4];
  const uint32_t abase = keep(sb + a_t_offset(w, lane));
  {
    const uint32_t* pm = pin(gs->MOD1[par] + (8 * jI + w) * 64 + lane * 2);
    uint32_t* const qpo = pin(gs->QP[par] + (cta * 256 + tid) * 2);
    float d[4] = {0.f, 0.f, 0.f, 0.f};
    wait_clk(tstore, T.D_MOD);
    CLK(4);
    uint2 v[8];
    load_units<8, 2048>(v, pm);
    cbar();
    const uint32_t xn0 = lds1(sb + OFF_XN + g * 272 + w * 32 + t * 4), xn1 = lds1(sb + OFF_XN + g * 272 + w * 32 + 16 + t * 4);
    const bool early = __all_sync(~0u, mbar_test(BAR(BAR_WQ + wg)));
    if (early) load_a_t(aw, abase + OFF_WQ);
    int it = 0;
    while (true) {
      uint32_t mn = 0xffffffffu;
#pragma unroll
      for (int i = 0; i < 8; i++) mn = min(mn, min(v[i].x, v[i].y));
      if (__all_sync(~0u, mn != 0)) break;
#pragma unroll
      for (int i = 0; i < 8; i++) { if (v[i].x == 0) v[i].y = 0; reload_unit(v[i], pm + i * 2048); }
      if (++it > SPIN_LIMIT) __trap();
    }
    CLK(5);
    ITS(0, it);
    float sc[2][4];
#pragma unroll
    for (int i = 0; i < 2; i++) {
      sc[i][0] = (bf_lo(v[i].x) + bf_lo(v[2 + i].x)) + (bf_lo(v[4 + i].x) + bf_lo(v[6 + i].x));
      sc[i][1] = (bf_hi(v[i].x) + bf_hi(v[2 + i].x)) + (bf_hi(v[4 + i].x) + bf_hi(v[6 + i].x));
      sc[i][2] = (bf_lo(v[i].y) + bf_lo(v[2 + i].y)) + (bf_lo(v[4 + i].y) + bf_lo(v[6 + i].y));
      sc[i][3] = (bf_hi(v[i].y) + bf_hi(v[2 + i].y)) + (bf_hi(v[4 + i].y) + bf_hi(v[6 + i].y));
    }
    sts2(sb + OFF_BS1 + (w >> 1) * 512 + lane * 16 + (w & 1) * 8,
         pack_bf16(bf_lo(xn0) * (1.f + sc[1][0]) + sc[0][0], bf_hi(xn0) * (1.f + sc[1][1]) + sc[0][1]),
         pack_bf16(bf_lo(xn1) * (1.f + sc[1][2]) + sc[0][2], bf_hi(xn1) * (1.f + sc[1][3]) + sc[0][3]));
    if (!early) { mbar_wait(BAR(BAR_WQ + wg)); load_a_t(aw, abase + OFF_WQ); }
    CLK(6);
    cbar();
    uint32_t b[4][4];
#pragma unroll
    for (int kk = 0; kk < 4; kk++) lds4(b[kk], sb + OFF_BS1 + kk * 512 + lane * 16);
    mma128(d, aw, b);
    stg_u64(qpo, pack_bf16(d[0], d[1]), pack_bf16(d[2], d[3]));
    tstore = clk32();
    CLK(7);
    if (wg) {
      mbar_wait(BAR(BAR_C));
#pragma unroll
      for (int i = 0; i < 4; i++) lds4(cf[i], sb + OFF_CS + g * 1024 + wq * 256 + i * 64 + t * 16);
#pragma unroll
      for (int i = 0; i < 16; i++) cf[i >> 2][i & 3] = silu2(cf[i >> 2][i & 3]);
    }
    __syncwarp();
    if (lane == 0) mbar_arrive(BAR(BAR_P1D));
  }
  {
    const uint32_t* pq = pin(gs->QP[par] + (hI * 4 * 256 + tid) * 2);
    uint32_t* const qxo = pin(gs->QX[par] + (g * 32 + hI) * 256 + 64 * jI + 8 * w + 2 * t);
    uint2 v[4];
    float d[4] = {0.f, 0.f, 0.f, 0.f};
    wait_clk(tstore, T.D_QP);
    CLK(8);
    load_units<4, 512>(v, pq);
    const uint32_t kbase = sb + OFF_WUK + (16 * w + (lane & 15)) * 128;
    auto load_half = [&](int hf) {
#pragma unroll
      for (int ks = 0; ks < 4; ks++) ldsm4(aw[4 * hf + ks], kbase + hf * 16384 + (((2 * ks + (lane >> 4)) ^ (lane & 7)) << 4));
    };
    mbar_wait(BAR(BAR_WUK));
    load_half(0);
    const bool early = __all_sync(~0u, mbar_test(BAR(BAR_WUK + 1)));
    if (early) load_half(1);
    const int it = check_units<4, 512>(v, pq);
    CLK(9);
    ITS(1, it);
    sum4_to_smem(v, sb + OFF_BS2 + (16 * w + g) * 16 + t * 4);
    if (!early) { mbar_wait(BAR(BAR_WUK + 1)); load_half(1); }
    CLK(10);
    cbar();
    uint32_t b[4][4];
#pragma unroll
    for (int kk = 0; kk < 4; kk++) ldsm4t(b[kk], sb + OFF_BS2 + (32 * kk + lane) * 16);
    mma128(d, aw, b);
    const float sc = 0.08838834764831845f * 1.4426950408889634f;
    stg_u64(qxo, movm(pack_bf16(d[0] * sc, d[1] * sc)), movm(pack_bf16(d[2] * sc, d[3] * sc)));
    tstore = clk32();
    CLK(11);
    if (lane == 0) mbar_arrive(BAR(BAR_P2D));
  }
  if (wg && jI != 3) {
    const int mi = lane >> 3, r = lane & 7;
    const uint32_t a0 = sb + OFF_WM2 + (8 * (r >> 1) + (r & 1) + 2 * (mi >> 1)) * 32 + (mi & 1) * 16;
    mbar_wait(BAR(BAR_WM2));
#pragma unroll
    for (int s = 0; s < 8; s++) ldsm4t(aw[s], a0 + (128 * wq + 32 * (s >> 1) + 4 * (s & 1)) * 32);
    float d[4] = {0.f, 0.f, 0.f, 0.f};
    mma128(d, aw, cf);
    sts4f(sb + OFF_P0B + (tid - 128) * 16, d[0], d[1], d[2], d[3]);
    if (lane == 0) mbar_arrive(BAR(BAR_P0BD));
    bar_sync(3, 128);
    if (w == 4) {
      float4 v[4];
#pragma unroll
      for (int i = 0; i < 4; i++) v[i] = ldsf4(sb + OFF_P0B + (i * 32 + lane) * 16);
      stg_u64(gs->MOD2[par] + (3 * hI + jI) * 64 + t * 16 + g * 2, movm(pack_bf16((v[0].x + v[1].x) + (v[2].x + v[3].x), (v[0].y + v[1].y) + (v[2].y + v[3].y))),
              movm(pack_bf16((v[0].z + v[1].z) + (v[2].z + v[3].z), (v[0].w + v[1].w) + (v[2].w + v[3].w))));
    }
    CLK(15);
  }
  {
    const uint32_t* qx = pin(gs->QX[par] + ((bs >> 3) * 32 + 16 * hh) * 256 + tid * 4);
    const int ch = tid & 63, h0 = tid >> 6;
    const uint32_t dst = sb + OFF_Q + (ch >> 3) * 2048 + h0 * 128;
    wait_clk(tstore, T.D_QX);
    CLK(12);
    uint4 v[4];
#pragma unroll
    for (int i = 0; i < 4; i++) v[i] = ldg_2u64(qx + i * 1024);
    int it = 0;
    while (true) {
      uint32_t mn = 0xffffffffu;
#pragma unroll
      for (int i = 0; i < 4; i++) mn = min(mn, min(v[i].y, v[i].w));
      if (__all_sync(~0u, mn != 0)) break;
#pragma unroll
      for (int i = 0; i < 4; i++)
        asm volatile("{\n.reg .pred q;\nsetp.eq.u32 q, %5, 0;\n@q ld.relaxed.gpu.global.v4.b32 {%0, %1, %2, %3}, [%4];\n}"
                     : "+r"(v[i].x), "+r"(v[i].y), "+r"(v[i].z), "+r"(v[i].w) : "l"(qx + i * 1024), "r"(min(v[i].y, v[i].w)) : "memory");
      if (++it > SPIN_LIMIT) __trap();
    }
    CLK(13);
    ITS(2, it);
#pragma unroll
    for (int i = 0; i < 4; i++) sts4(dst + i * 512 + (((ch & 7) ^ ((4 * i + h0) & 7)) << 4), v[i]);
    asm volatile("fence.proxy.async.shared::cta;" ::: "memory");
    CLK(14);
    cbar();
  }

  uint2 cbf[4], sbf[4];
  const uint32_t* const pcb = gs->MOD2[par] + 2048 + (16 * w + t) * 16 + g * 2;
  auto load_frags = [&] {
    if (cta < NFF) { load_units<4, 64>(sbf, pcb); load_units<4, 64>(cbf, pcb + 2048); }
    else {
#pragma unroll
      for (int s = 0; s < 4; s++) { cbf[s].x = ldg_nc1(gc + g * 1024 + w * 128 + s * 32 + t * 4); cbf[s].y = ldg_nc1(gc + g * 1024 + w * 128 + s * 32 + 16 + t * 4); }
    }
  };
  uint32_t thand, anchor;
  const uint32_t opaque0 = w >> 4;
  if (wg == 0) {
    float mh[4];
    float L[8];
#pragma unroll
    for (int i = 0; i < 4; i++) { L[2 * i] = L[2 * i + 1] = 0.f; mh[i] = -INFINITY; }
    constexpr uint32_t dq = desc_lo(OFF_Q);
    const uint32_t ptw = sb + OFF_PT + (8 * (lane >> 4) + (lane & 7)) * 128 + (((2 * wq + ((lane >> 3) & 1)) ^ (lane & 7)) << 4);
    float S[8];
    auto softmax = [&](int tl) {
      auto write_p = [&](const float (&x)[8]) {
        float p[8];
#pragma unroll
        for (int i = 0; i < 8; i++) p[i] = ex2(x[i]);
        stsm4t(ptw + (tl & 1) * 2048, pack_bf16(p[0], p[1]), pack_bf16(p[2], p[3]), pack_bf16(p[4], p[5]), pack_bf16(p[6], p[7]));
        asm volatile("fence.proxy.async.shared::cta;" ::: "memory");
      };
      float x[8];
#pragma unroll
      for (int i = 0; i < 8; i++) x[i] = S[i] - mh[2 * (i >> 2) + (i & 1)];
      if (tl) write_p(x);
      const float ex = fmaxf(fmaxf(fmaxf(x[0], x[1]), fmaxf(x[2], x[3])), fmaxf(fmaxf(x[4], x[5]), fmaxf(x[6], x[7])));
      if (tl == 0 || bar_over(ex)) {
        float mx[4];
#pragma unroll
        for (int i = 0; i < 4; i++) mx[i] = fmaxf(S[4 * (i >> 1) + (i & 1)], S[4 * (i >> 1) + 2 + (i & 1)]);
        const float a = reduce_g(mx, lane, [](float u, float v) { return fmaxf(u, v); });
        stsf(sb + OFF_RED + wq * 64 + (8 * (lane >> 4) + 2 * t + ((lane >> 3) & 1)) * 4, a);
        bar_sync(2, 128);
#pragma unroll
        for (int jn = 0; jn < 2; jn++) {
          float m0 = mh[2 * jn], m1 = mh[2 * jn + 1];
#pragma unroll
          for (int i = 0; i < 4; i++) { const float2 v = ldsf2(sb + OFF_RED + i * 64 + (8 * jn + 2 * t) * 4); m0 = fmaxf(m0, v.x); m1 = fmaxf(m1, v.y); }
          const float a0 = ex2(mh[2 * jn] - m0), a1 = ex2(mh[2 * jn + 1] - m1);
          mh[2 * jn] = m0; mh[2 * jn + 1] = m1;
          L[4 * jn] *= a0; L[4 * jn + 1] *= a1; L[4 * jn + 2] *= a0; L[4 * jn + 3] *= a1;
          if (tid < 4) sts2f(sb + OFF_ALPHA + (8 * jn + 2 * t) * 4, a0, a1);
        }
        asm volatile("barrier.cta.arrive.aligned 1, 256;" ::: "memory");
#pragma unroll
        for (int i = 0; i < 8; i++) x[i] = S[i] - mh[2 * (i >> 2) + (i & 1)];
        write_p(x);
        bar_over(0.f);
      }
      const uint32_t dpt = __shfl_sync(~0u, desc_lo(OFF_PT) + (tl & 1) * 128, 0);
      wg_fence();
#pragma unroll
      for (int ks = 0; ks < 4; ks++) wgmma_n16_ones(L, ONE2, dpt + ks * 2);
      wg_commit();
    };
    uint32_t da = desc_lo(OFF_RING);
#pragma unroll 1
    for (int tl = 0; tl < 7; tl++) {
      if (tl == 1) mbar_wait(BAR(BAR_EMPTY));
      if (tl == 5) { load_frags(); }
      uint32_t ok = 0;
#pragma unroll
      for (int u = 0; u < 4; u++) ok += mbar_test(BAR(BAR_FULL + 4 * tl + u));
      ok = __reduce_min_sync(~0u, ok);
      const uint32_t du = __shfl_sync(~0u, da, 0);
#pragma unroll
      for (int u = 0; u < 4; u++) {
        if (ok != 4) mbar_wait(BAR(BAR_FULL + 4 * tl + u));
        wg_fence();
#pragma unroll
        for (int k = 0; k < 8; k++) {
          const int i = 8 * u + k;
          if (i == 0) wgmma_n16<0, 0>(S, du, dq); else wgmma_n16<0, 1>(S, du + (i >> 2) * 512 + (i & 3) * 2, dq + (i >> 2) * 128 + (i & 3) * 2);
        }
        wg_commit();
      }
      wg_wait<0>();
      acc_fence(S); acc_fence(L);
      if (tl == 0) CLK(15);
      if (tl == 1) CLK(17);
      softmax(tl);
      if (tl == 0) CLK(16);
      if (tl == 1) CLK(18);
      if (tl == 3) CLK(19);
      if (tl == 6) CLK(20);
      da = (tl == 2 || tl == 5) ? da - 8192 : da + 4096;
    }
    mbar_wait(BAR(BAR_ALLCLR));
    uint32_t* const mlo = pin(gin + blk(4 * (16 * hh + 4 * (g & 2) + 2 * t + (g & 1)) + 1, 6, g >> 2) + bs * 2);
#pragma unroll
    for (int i = 0; i < 32; i++) {
      if (i == 0 || i == 8 || i == 16 || i == 24 || i == 28) {
        if (i) wg_commit();
        mbar_wait(BAR(BAR_LAST + (i == 28 ? 4 : i >> 3)));
        if (i == 28) CLK(21);
        wg_fence();
      }
      if (i == 0) wgmma_n16<0, 0>(S, desc_lo(65536), dq); else wgmma_n16<0, 1>(S, desc_lo(65536) + (i >> 2) * 512 + (i & 3) * 2, dq + (i >> 2) * 128 + (i & 3) * 2);
    }
    wg_commit();
    wg_wait<0>();
    acc_fence(S); acc_fence(L);
    CLK(22);
    softmax(7);
    CLK(23);
    thand = clk32();
    wg_wait<0>();
    acc_fence(L);
    if (tid < 32) red_u64(mlo, __float_as_uint(g & 2 ? (g & 1 ? mh[3] : mh[2]) : (g & 1 ? mh[1] : mh[0])), __float_as_uint(g & 2 ? (g & 1 ? L[5] : L[4]) : (g & 1 ? L[1] : L[0])));
    CLK(24);
  } else {
    float O[8][8];
#pragma unroll
    for (int i = 0; i < 8; i++)
#pragma unroll
      for (int k = 0; k < 8; k++) O[i][k] = 0.f;
    constexpr uint32_t dp = desc_lo(OFF_PT);
    auto handover = [&](int tl) {
      uint32_t over = opaque0 + (tl == 0);
#pragma unroll 1
      do {
        if (over) {
          cbar();
#pragma unroll
          for (int jn = 0; jn < 2; jn++) {
            const float2 a = ldsf2(sb + OFF_ALPHA + (8 * jn + 2 * t) * 4);
#pragma unroll
            for (int mb = 0; mb < 8; mb++) { O[mb][4 * jn] *= a.x; O[mb][4 * jn + 1] *= a.y; O[mb][4 * jn + 2] *= a.x; O[mb][4 * jn + 3] *= a.y; }
          }
        }
        over++;
      } while (bar_over(0.f));
    };
    uint32_t da = desc_lo(OFF_RING);
    uint32_t* x1o[8] = {};
#pragma unroll 1
    for (int tl = 0; tl < 8; tl++) {
      if (tl == 5) load_frags();
      if (tl == 7) {
        mbar_wait(BAR(BAR_ALLCLR));
#pragma unroll
        for (int i = 0; i < 8; i++)
          x1o[i] = inbox((16 * hh + 8 * ((i >> 1) & 1) + 2 * t + (i & 1)) * 4 + 2 * (i >> 2) + (wq >> 1), bs >> 4) + (bs & 15) * 64 + ((wq & 1) * 8 + g) * 4;
      }
      handover(tl);
      CLK(23);
      thand = clk32();
      const uint32_t dpt = dp + (tl & 1) * 128;
      wg_fence();
#pragma unroll
      for (int i = 0; i < 32; i++) wgmma_n16<1, 1>(O[i >> 2], da + (i >> 2) * 512 + (i & 3) * 128, dpt + (i & 3) * 2);
      wg_commit();
      da = (tl == 2 || tl == 5) ? da - 8192 : da + 4096;
      wg_wait<0>();
#pragma unroll
      for (int mb = 0; mb < 8; mb++) acc_fence(O[mb]);
      if (lane == 0) mbar_arrive(BAR(BAR_EMPTY + tl));
      if (tl == 0) CLK(16);
      if (tl == 1) CLK(18);
      if (tl == 3) CLK(19);
      if (tl == 6) CLK(20);
    }
    CLK(22);
#pragma unroll
    for (int i = 0; i < 8; i++) {
      const int J = i >> 2, k = 4 * ((i >> 1) & 1) + (i & 1);
      stg_cvt8(x1o[i], O[4 * J][k], O[4 * J][k + 2], O[4 * J + 1][k], O[4 * J + 1][k + 2], O[4 * J + 2][k], O[4 * J + 2][k + 2], O[4 * J + 3][k], O[4 * J + 3][k + 2]);
    }
    CLK(24);
  }

  uint32_t* const o = gin + keep((uint32_t)(inbox(4 * (8 * jI + w) + t, 4) - gin) + hI * 16 + g * 2);
  const uint32_t sdst5 = keep(sb + OFF_BS5 + (16 * w + g) * 16 + t * 4), lane16 = keep(sb + lane * 16);
  const uint32_t* x2i[4];
#pragma unroll
  for (int i = 0; i < 4; i++) x2i[i] = gin + keep((uint32_t)(nearbox(4 * hI + i, 4) - gin) + 512 + tid * 2);
  {
    const uint32_t* px = pin(inbox(cta, w >> 1) + (w & 1) * 512 + lane * 2);
    uint32_t* const x2o = pin(inbox(cta, 4) + 512 + tid * 2);
    uint32_t* const x2p = pin(gin + blk(cta, 4, selector(cta) ^ 1) + 512 + tid * 2);
    const uint32_t q4 = lds1(sb + OFF_SEL + 4 * hI) ^ 0x00010100u;
    const uint32_t same = pin((uint32_t)(q4 == 0 || q4 == 0x01010101u));
    mbar_wait(BAR(BAR_TS));
    anchor = lds1(sb + OFF_TS);
    const uint32_t sdst = keep(sb + OFF_BS4 + w * 272 + lane * 8), ssrc = keep(sb + OFF_BS4 + (lane & 7) * 272 + (lane >> 3) * 16);
    float d[4] = {0.f, 0.f, 0.f, 0.f};
    if (cta >= NFF) {
#pragma unroll
      for (int s = 0; s < 4; s++) { cbf[s].x = silu2(cbf[s].x); cbf[s].y = silu2(cbf[s].y); }
    } else {
      check_units<4, 64>(sbf, pcb);
      check_units<4, 64>(cbf, pcb + 2048);
#pragma unroll
      for (int s = 0; s < 4; s++) { cbf[s].x = hadd2(cbf[s].x, ONE2); cbf[s].y = hadd2(cbf[s].y, ONE2); }
    }
    wait_clk(thand, T.D_X1);
    wait_clk(anchor, T.A_X1 - T.R_X0);
    uint2 v[8];
    load_units<8, 64>(v, px);
    if (T.R_X0) {
      wait_clk(anchor, T.A_X1);
#pragma unroll
      for (int i = 0; i < 8; i++) reload_unit(v[i], px + i * 64);
    }
    CLK(25);
    const bool early = __all_sync(~0u, mbar_test(BAR(BAR_WUV + wg)));
    if (early) load_a_t(aw, abase + OFF_WUV);
    mbar_wait(BAR(BAR_WV));
    const float4 wa = ldsf4(sb + OFF_WV + w * 32), wb = ldsf4(sb + OFF_WV + w * 32 + 16);
    const float wv[8] = {wa.x, wa.y, wa.z, wa.w, wb.x, wb.y, wb.z, wb.w};
    CLK(27);
    uint32_t it = opaque0;
    bool ok;
#pragma unroll 1
    do {
      if (it) {
#pragma unroll
        for (int i = 0; i < 8; i++) reload_unit(v[i], px + i * 64);
        if (it > SPIN_LIMIT) __trap();
      }
      it++;
      float a0 = 0.f, a1 = 0.f, a2 = 0.f, a3 = 0.f;
#pragma unroll
      for (int i = 0; i < 8; i++) { a0 += wv[i] * bf_lo(v[i].x); a1 += wv[i] * bf_hi(v[i].x); a2 += wv[i] * bf_lo(v[i].y); a3 += wv[i] * bf_hi(v[i].y); }
      ok = __all_sync(~0u, min_flags(v) != 0);
      sts2(sdst, pack_bf16(a0, a1), pack_bf16(a2, a3));
    } while (!ok);
    CLK(29);
    cbar();
    uint32_t b[4][4];
#pragma unroll
    for (int kk = 0; kk < 4; kk++) ldsm4(b[kk], ssrc + kk * 64);
    if (__builtin_expect(!early, 0)) { mbar_wait(BAR(BAR_WUV + wg)); load_a_t(aw, abase + OFF_WUV); }
    mma128(d, aw, b);
    const uint32_t c0 = pack_bf16(d[0], d[1]), c1 = pack_bf16(d[2], d[3]);
    stg_u64(x2o, c0, c1);
    stg_u64_unless(same, x2p, c0, c1);
    ITS(4, it - 1);
    tstore = clk32();
    CLK(30);
  }
  {
    float d[4] = {0.f, 0.f, 0.f, 0.f};
    wait_clk(tstore, T.D_X2);
    uint2 v[4];
#pragma unroll
    for (int i = 0; i < 4; i++) v[i] = ldg_u64(x2i[i]);
    const bool early = __all_sync(~0u, mbar_test(BAR(BAR_WO + wg)));
    if (early) load_a_t(aw, abase + OFF_WO);
    CLK(31);
    uint32_t it = opaque0;
    bool ok;
#pragma unroll 1
    do {
      if (it) {
#pragma unroll
        for (int i = 0; i < 4; i++) reload_unit(v[i], x2i[i]);
        if (it > SPIN_LIMIT) __trap();
      }
      it++;
      ok = __all_sync(~0u, min_flags(v) != 0);
      sum4_to_smem(v, sdst5);
    } while (!ok);
    CLK(32);
    cbar();
    uint32_t b[4][4];
#pragma unroll
    for (int kk = 0; kk < 4; kk++) ldsm4t(b[kk], lane16 + OFF_BS5 + kk * 512);
    if (__builtin_expect(!early, 0)) { mbar_wait(BAR(BAR_WO + wg)); load_a_t(aw, abase + OFF_WO); }
    mma128(d, aw, b);
    stg_u64(o, movm(pack_bf16(d[0], d[1])), movm(pack_bf16(d[2], d[3])));
    ITS(5, it - 1);
    tstore = clk32();
    CLK(33);
    if (lane == 0) mbar_arrive(BAR(BAR_P5D));
  }
  if (cta < NFF) {
    const int mi = lane >> 3, r = lane & 7;
    uint32_t a1[2][4][4], a2[2][2][4];
    const int lp = (tid >> 2) & 31, kq = tid & 3;
    const int fo = 16 * wg + (lp >> 2) + 8 * (kq >> 1), bo = 2 * (lp & 3) + (kq & 1);
    const uint32_t* xb = gin + keep((uint32_t)(nearbox(cta & ~15, 6 + wg) - gin) + (16 * wq + t) * 16 + g * 2);
    uint32_t* const ox[2] = {gin + keep((uint32_t)(inbox(64 * hh + 8 * w + t, 5) - gin) + bs * 16 + g * 2), gin + keep((uint32_t)(inbox(64 * hh + 8 * w + 4 + t, 5) - gin) + bs * 16 + g * 2)};
    const uint32_t a1base = keep(sb + OFF_W1 + (64 * w + 8 * (mi >> 1) + r) * 64 + (((mi & 1) ^ (r >> 1)) << 4));
    const uint32_t a2base = keep(sb + OFF_W2 + (w >> 1) * 4096 + (8 * (mi >> 1) + r) * 128 + (((4 * (w & 1) + (mi & 1)) ^ r) << 4));
    const uint32_t s_g = keep(sb + OFF_REDG + w * 1024 + lane * 16), l_g = keep(sb + OFF_REDG + tid * 4);
    const uint32_t s_s = keep(sb + (t == (g >> 1) ? OFF_REDS + g * 80 + w * 8 : OFF_BS4 + tid * 8));
    const uint32_t l_s = keep(sb + OFF_REDS + bo * 80), s_h = keep(sb + OFF_H1 + fo * 16 + bo * 2);
    mbar_wait(BAR(BAR_W1));
#pragma unroll
    for (int i = 0; i < 8; i++) ldsm4t(a1[i & 1][i >> 1], (a1base ^ ((i & 1) << 5)) + (i >> 1) * 1024);
    {
      float u[2][2][4] = {};
#pragma unroll
      for (int s = 0; s < 4; s++)
#pragma unroll
        for (int mt = 0; mt < 2; mt++) { mma16816(u[0][mt], a1[mt][s], cbf[s].x, cbf[s].y); mma16816(u[1][mt], a1[mt][s], sbf[s].x, sbf[s].y); }
#pragma unroll
      for (int i = 0; i < 4; i++) sts4f(s_g + (OFF_REDU - OFF_REDG) + (i >> 1) * 8192 + (i & 1) * 512, u[i >> 1][i & 1][0], u[i >> 1][i & 1][1], u[i >> 1][i & 1][2], u[i >> 1][i & 1][3]);
    }
    CLK(34);
    wait_clk(tstore, T.D_X3B);
    wait_clk(anchor, T.A_X1 + T.R_X3A + T.R_X3B);
    uint2 x[4];
    load_units<4, 64>(x, xb);
    float U, V;
    {
      cbar();
      float u[8], v[8];
#pragma unroll
      for (int i = 0; i < 8; i++) { u[i] = ldsf(l_g + (OFF_REDU - OFF_REDG) + i * 1024); v[i] = ldsf(l_g + (OFF_REDV - OFF_REDG) + i * 1024); }
      U = pin(((u[0] + u[1]) + (u[2] + u[3])) + ((u[4] + u[5]) + (u[6] + u[7])));
      V = pin(((v[0] + v[1]) + (v[2] + v[3])) + ((v[4] + v[5]) + (v[6] + v[7])));
    }
    auto load_a2 = [&] {
#pragma unroll
      for (int i = 0; i < 4; i++) ldsm4t(a2[i >> 1][i & 1], (a2base ^ ((i >> 1) << 5)) + (i & 1) * 2048);
    };
    const bool early = __all_sync(~0u, mbar_test(BAR(BAR_W2)));
    if (early) load_a2();
    CLK(35);
    uint32_t it = opaque0;
    float G[2][2][4], S[2][4];
#pragma unroll 1
    do {
      if (it) {
#pragma unroll
        for (int i = 0; i < 4; i++) reload_unit(x[i], xb + i * 64);
        if (it > SPIN_LIMIT) __trap();
      }
      it++;
#pragma unroll
      for (int i = 0; i < 8; i++) { G[0][i >> 2][i & 3] = G[1][i >> 2][i & 3] = S[i >> 2][i & 3] = 0.f; }
      uint32_t y[4][2];
#pragma unroll
      for (int s = 0; s < 4; s++) { y[s][0] = hmul2(x[s].x, cbf[s].x); y[s][1] = hmul2(x[s].y, cbf[s].y); }
#pragma unroll
      for (int s2 = 0; s2 < 4; s2 += 2) {
#pragma unroll
        for (int s = s2; s < s2 + 2; s++) { mma16816(G[0][s & 1], a1[0][s], y[s][0], y[s][1]); mma16816(G[1][s & 1], a1[1][s], y[s][0], y[s][1]); }
#pragma unroll
        for (int s = s2; s < s2 + 2; s++) { const uint32_t sx[4] = {x[s].x, ONE2, x[s].y, ONE2}; mma16816(S[s & 1], sx, x[s].x, x[s].y); }
      }
    } while (!__all_sync(~0u, min_flags(x) != 0));
#pragma unroll
    for (int mt = 0; mt < 2; mt++)
      sts4f(s_g + mt * 512, G[mt][0][0] + G[mt][1][0], G[mt][0][1] + G[mt][1][1], G[mt][0][2] + G[mt][1][2], G[mt][0][3] + G[mt][1][3]);
    sts2f(s_s, (g & 1) ? S[0][3] + S[1][3] : S[0][2] + S[1][2], (g & 1) ? S[0][1] + S[1][1] : S[0][0] + S[1][0]);
    CLK(37);
    cbar();
    {
      float gv[8];
      float4 sv[4];
#pragma unroll
      for (int i = 0; i < 4; i++) sv[i] = ldsf4(l_s + i * 16);
#pragma unroll
      for (int i = 0; i < 8; i++) gv[i] = ldsf(l_g + i * 1024);
      const float s1 = ((sv[0].x + sv[0].z) + (sv[1].x + sv[1].z)) + ((sv[2].x + sv[2].z) + (sv[3].x + sv[3].z));
      const float s2 = ((sv[0].y + sv[0].w) + (sv[1].y + sv[1].w)) + ((sv[2].y + sv[2].w) + (sv[3].y + sv[3].w));
      const float gsum = ((gv[0] + gv[1]) + (gv[2] + gv[3])) + ((gv[4] + gv[5]) + (gv[6] + gv[7]));
      const float mu = s1 * (1.f / 512.f);
      float rs;
      asm("rsqrt.approx.ftz.f32 %0, %1;" : "=f"(rs) : "f"(fmaxf(s2 * (1.f / 512.f) - mu * mu, 0.f) + 1e-5f));
      const float hv = fmaxf(rs * (gsum - mu * U) + V, 0.f);
      asm volatile("st.shared.u16 [%0], %1;" ::"r"(s_h), "h"(__bfloat16_as_ushort(__float2bfloat16(hv))) : "memory");
    }
    ITS(6, it - 1);
    CLK(38);
    cbar();
    uint32_t b[4];
    ldsm4t(b, lane16 + OFF_H1);
    if (!early) { mbar_wait(BAR(BAR_W2)); load_a2(); }
    float o[2][2][4] = {};
#pragma unroll
    for (int i = 0; i < 4; i++) mma16816(o[i >> 1][i & 1], a2[i >> 1][i & 1], b[2 * (i & 1)], b[2 * (i & 1) + 1]);
#pragma unroll
    for (int mb = 0; mb < 2; mb++)
      stg_u64(ox[mb], movm(pack_bf16(o[mb][0][0] + o[mb][1][0], o[mb][0][1] + o[mb][1][1])), movm(pack_bf16(o[mb][0][2] + o[mb][1][2], o[mb][0][3] + o[mb][1][3])));
    CLK(39);
    if (lane == 0) mbar_arrive(BAR(BAR_P7D));
  } else {
    const int mi = lane >> 3, r = lane & 7;
    mbar_wait(BAR(BAR_W1));
#pragma unroll
    for (int mt = 0; mt < 2; mt++) {
      float u[4] = {0.f, 0.f, 0.f, 0.f};
#pragma unroll
      for (int ks = 0; ks < 4; ks++) ldsm4t(aw[4 * mt + ks], sb + OFF_W1 + (64 * w + 16 * ks + 8 * (mi >> 1) + r) * 64 + (((2 * mt + (mi & 1)) ^ (r >> 1)) << 4));
#pragma unroll
      for (int ks = 0; ks < 4; ks++) mma16816(u, aw[4 * mt + ks], cbf[ks].x, cbf[ks].y);
      sts4f(sb + OFF_REDU + w * 1024 + mt * 512 + lane * 16, u[0], u[1], u[2], u[3]);
    }
    cbar();
    if (w < 2) {
      float4 v[8];
#pragma unroll
      for (int i = 0; i < 8; i++) v[i] = ldsf4(sb + OFF_REDU + i * 1024 + tid * 16);
      stg_u64(gs->MOD2[par] + (96 + 2 * (cta - NFF) + w) * 64 + t * 16 + g * 2,
              movm(pack_bf16(((v[0].x + v[1].x) + (v[2].x + v[3].x)) + ((v[4].x + v[5].x) + (v[6].x + v[7].x)), ((v[0].y + v[1].y) + (v[2].y + v[3].y)) + ((v[4].y + v[5].y) + (v[6].y + v[7].y)))),
              movm(pack_bf16(((v[0].z + v[1].z) + (v[2].z + v[3].z)) + ((v[4].z + v[5].z) + (v[6].z + v[7].z)), ((v[0].w + v[1].w) + (v[2].w + v[3].w)) + ((v[4].w + v[5].w) + (v[6].w + v[7].w)))));
    }
    CLK(26);
  }
  CLK_DUMP();
}

typedef CUresult (*EncodeTiledFn)(CUtensorMap*, CUtensorMapDataType, cuuint32_t, void*, const cuuint64_t*, const cuuint64_t*,
                                  const cuuint32_t*, const cuuint32_t*, CUtensorMapInterleave, CUtensorMapSwizzle,
                                  CUtensorMapL2promotion, CUtensorMapFloatOOBfill);

struct Dim { uint64_t size, stride; uint32_t box; };
template <int R> void encode_map(EncodeTiledFn enc, CUtensorMap* m, const void* base, const Dim (&d)[R], CUtensorMapSwizzle sw, CUtensorMapL2promotion promo) {
  cuuint64_t dims[R], strides[R];
  cuuint32_t box[R], es[R];
  for (int i = 0; i < R; i++) { dims[i] = d[i].size; strides[i] = d[i].stride; box[i] = d[i].box; es[i] = 1; }
  enc(m, CU_TENSOR_MAP_DATA_TYPE_BFLOAT16, R, const_cast<void*>(base), dims, strides + 1, box, es, CU_TENSOR_MAP_INTERLEAVE_NONE, sw, promo,
      CU_TENSOR_MAP_FLOAT_OOB_FILL_NONE);
}

}

extern "C" void kernel_launch(void* const* d_in, const int* in_sizes, int n_in, void* d_out, int out_size) {
  (void)in_sizes; (void)n_in; (void)out_size;
  static EncodeTiledFn enc = nullptr;
  static Scratch* scratch = nullptr;
  static uint32_t* inbox = nullptr;
  if (!enc) {
    void* sp = nullptr;
    cudaGetSymbolAddress(&sp, g_s);
    scratch = (Scratch*)sp;
    cudaGetSymbolAddress(&sp, g_in);
    inbox = (uint32_t*)(((uintptr_t)sp + 0xfffff) & ~(uintptr_t)0xfffff);
    void* fn = nullptr;
    cudaDriverEntryPointQueryResult q;
    cudaGetDriverEntryPoint("cuTensorMapEncodeTiled", &fn, cudaEnableDefault, &q);
    enc = (EncodeTiledFn)fn;
    cudaFuncSetAttribute(fused_decode_kernel, cudaFuncAttributeMaxDynamicSharedMemorySize, SMEM_BYTES);
  }
  const CUtensorMapSwizzle S128 = CU_TENSOR_MAP_SWIZZLE_128B, S0 = CU_TENSOR_MAP_SWIZZLE_NONE;
  const CUtensorMapL2promotion L0 = CU_TENSOR_MAP_L2_PROMOTION_NONE, L128 = CU_TENSOR_MAP_L2_PROMOTION_L2_128B;
  Params P;
  encode_map<2>(enc, &P.wq, d_in[2], {{4096, 2, 64}, {512, 8192, 64}}, S128, L0);
  encode_map<5>(enc, &P.wuk, d_in[3], {{4096, 2, 64}, {2, 8192, 2}, {4, 4 * 8192, 4}, {2, 2 * 8192, 2}, {32, 16 * 8192, 4}}, S128, L0);
  encode_map<2>(enc, &P.wm2, d_in[10], {{3072, 2, 16}, {512, 6144, 256}}, S0, L128);
  encode_map<2>(enc, &P.wm3, d_in[10], {{3072, 2, 32}, {512, 6144, 256}}, CU_TENSOR_MAP_SWIZZLE_64B, L128);
  encode_map<3>(enc, &P.ckv2, d_in[1], {{64, 2, 64}, {8 * 4096, 1024, 64}, {8, 128, 2}}, S128, L0);
  encode_map<3>(enc, &P.ckv1, d_in[1], {{64, 2, 64}, {8 * 4096, 1024, 64}, {8, 128, 1}}, S128, L0);
  encode_map<5>(enc, &P.wuv, d_in[4], {{4096, 2, 64}, {2, 8 * 8192, 2}, {8, 64 * 8192, 4}, {8, 8192, 8}, {4, 16 * 8192, 1}}, S128, L0);
  encode_map<2>(enc, &P.wo, d_in[5], {{512, 2, 64}, {4096, 1024, 64}}, S128, L0);
  encode_map<2>(enc, &P.w1, d_in[7], {{1792, 2, 32}, {512, 3584, 256}}, CU_TENSOR_MAP_SWIZZLE_64B, L128);
  encode_map<3>(enc, &P.w2, d_in[8], {{64, 2, 64}, {1792, 1024, 32}, {8, 128, 2}}, S128, L0);
  fused_decode_kernel<<<NCTA, NTHREADS, SMEM_BYTES>>>((__nv_bfloat16*)d_out, scratch, (const uint8_t*)d_in[10], (const uint8_t*)d_in[0],
                     (const uint8_t*)d_in[9], inbox,
                     P);
}
```

```cpp
#include <cuda_runtime.h>
#include <cuda.h>
#include <cuda_bf16.h>
#include <stdint.h>

namespace {

constexpr int NCTA = 128;
constexpr int NTHREADS = 320;
constexpr int NFG = 56;
constexpr int NFF = 2 * NFG;
constexpr int NSYNC = 4;

constexpr uint32_t OFF_RING = 0;
constexpr uint32_t OFF_WUK = 131072;
constexpr uint32_t OFF_WQ = 131072 + 32768;
constexpr uint32_t OFF_WM2 = 65536 + 49152;
constexpr uint32_t OFF_WUV = 131072;
constexpr uint32_t OFF_WO = 131072 + 32768;
constexpr uint32_t OFF_W1 = 0;
constexpr uint32_t OFF_W2 = 32768;
constexpr uint32_t OFF_Q = 196608;
constexpr uint32_t OFF_PT = 212992;
constexpr uint32_t OFF_SCR = 217088;
constexpr uint32_t OFF_XS = 65536;
constexpr uint32_t OFF_CS = 65536 + 8192;
constexpr uint32_t OFF_P0S = 65536 + 16384;
constexpr uint32_t OFF_BS1 = OFF_SCR + 2048;
constexpr uint32_t OFF_BS2 = OFF_SCR + 4096;
constexpr uint32_t OFF_P0B = OFF_SCR + 6144;
constexpr uint32_t OFF_XN = OFF_SCR + 8192;
constexpr uint32_t OFF_RED = OFF_SCR + 10496;
constexpr uint32_t OFF_ALPHA = OFF_SCR + 11072;
constexpr uint32_t OFF_WV = OFF_SCR + 6144;
constexpr uint32_t OFF_SEL = OFF_SCR + 10752;
constexpr uint32_t OFF_TS = OFF_SCR + 11136;
constexpr uint32_t OFF_BARS = OFF_SCR + 11264;
constexpr uint32_t SMEM_BYTES = OFF_BARS + 512;
constexpr uint32_t OFF_BS4 = OFF_Q;
constexpr uint32_t OFF_H1 = OFF_Q + 2304;
constexpr uint32_t OFF_REDS = OFF_Q + 2816;
constexpr uint32_t OFF_BS5 = OFF_Q + 4096;
constexpr uint32_t OFF_REDG = OFF_Q + 8192;
constexpr uint32_t OFF_REDU = 65536;
constexpr uint32_t OFF_REDV = 65536 + 8192;

constexpr int BAR_FULL = 0;
constexpr int BAR_LAST = 28;
constexpr int BAR_WUK = 33, BAR_WM2 = 35, BAR_WUV = 36, BAR_WO = 38, BAR_W1 = 40, BAR_W2 = 41;
constexpr int BAR_ALLCLR = 42, BAR_TS = 43, BAR_WV = 44;
constexpr int BAR_EMPTY = 45;
constexpr int BAR_P0BD = 53;
constexpr int BAR_P1D = 54, BAR_P2D = 55;
constexpr int BAR_P5D = 56, BAR_P7D = 57;
constexpr int NBARS = 58;
constexpr int BAR_XC = 58, BAR_WQ = 59;
constexpr int BAR_C = 61;
constexpr uint32_t SB = 1024;

#define TUNE_LIST(X) \
  X(PC_T0, -30) X(PC_P1, 322) X(PC_PM, 225) X(PC_P2, 320) X(PC_STAG, 360) X(PC_SL, 500) X(PC_NW, 8) \
  X(T_UV, 165) X(P_UV, 285) X(PF_N, 3) X(T_PF, 1020) X(P_PF, 230) X(T_O, 2180) X(P_O, 145) X(T_1, 2990) X(T_2, 3700) X(T_GB, 3370) X(P_F, 360) \
  X(PR_T0, 700) X(PR_N, 4) X(CLR_T0, 3300) X(CLR_CLK, 190) \
  X(D_MOD, 1280) X(D_QP, 1200) X(D_QX, 850) X(TS_P, 1) X(TS_O, 1900) X(D_TS, 700) X(A_M, 1550) X(D_X1, 1350) X(A_X1, 2460) X(R_X0, 1550) \
  X(D_X2, 290) X(D_X3A, 60) X(R_X3A, 2835) X(D_X3B, 800) X(R_X3B, 915) X(D_FIN, 315) X(R_FIN, 1540)
struct Tune {
#define X(n, v) static constexpr int n = v;
  TUNE_LIST(X)
#undef X
};

struct Scratch {
  uint32_t MOD1[2][4 * 64 * 64];
  uint32_t MOD2[2][128 * 64];
  uint32_t QP[2][128 * 256 * 2];
  uint32_t QX[2][8 * 32 * 256];
  uint32_t epoch;
  uint32_t pad[31];
  uint32_t sync[NSYNC][32];
};
__device__ Scratch g_s;
__device__ uint32_t g_in[(128 + 16) * 16384];
__device__ __forceinline__ uint32_t blk(int c, int k, uint32_t sel) { return c * 16384 + k * 2048 + ((sel ^ k) & 1) * 1024; }
__device__ __forceinline__ uint32_t flip(int c) { return c ^ (c >> 1) ^ (c >> 3); }

struct Params {
  CUtensorMap wq, wuk, wm2, wm3, ckv2, ckv1, wuv, wo, w1, w2;
};

__device__ __forceinline__ void mbar_init(uint32_t bar, int cnt) { asm volatile("mbarrier.init.shared::cta.b64 [%0], %1;" ::"r"(bar), "r"(cnt)); }
__device__ __forceinline__ void mbar_expect(uint32_t bar, uint32_t bytes) { asm volatile("mbarrier.arrive.expect_tx.shared::cta.b64 _, [%0], %1;" ::"r"(bar), "r"(bytes) : "memory"); }
__device__ __forceinline__ void mbar_arrive(uint32_t bar) { asm volatile("mbarrier.arrive.shared::cta.b64 _, [%0];" ::"r"(bar) : "memory"); }
__device__ __forceinline__ uint32_t clk32() { unsigned long long c; asm volatile("mov.u64 %0, %%clock64;" : "=l"(c) :: "memory"); return (uint32_t)c; }
__device__ __forceinline__ uint32_t gtime32() { uint32_t c; asm volatile("mov.u32 %0, %%globaltimer_lo;" : "=r"(c) :: "memory"); return c; }
__device__ __forceinline__ void wait_clk(uint32_t t0, int clocks) { while ((int)(clk32() - t0) < clocks) {} }
__device__ __forceinline__ void backoff(int clocks) { if (clocks > 0) wait_clk(clk32(), clocks); }
__device__ __forceinline__ void until_ns(uint32_t ns) { while ((int)(gtime32() - ns) < 0) {} }
__device__ __forceinline__ void slot(uint32_t& tn, int slack) {
  uint32_t now;
  do { now = gtime32(); } while ((int)(now - tn) < 0);
  if ((int)(now - tn) > slack) tn = now - slack;
}
template <typename T> __device__ __forceinline__ T* pin(T* p) { asm volatile("" : "+l"(p)); return p; }
__device__ __forceinline__ uint32_t pin(uint32_t v) { asm volatile("" : "+r"(v)); return v; }
__device__ __forceinline__ float pin(float v) { asm volatile("" : "+f"(v)); return v; }
constexpr int SPIN_LIMIT = 1 << 22;
__device__ __forceinline__ void mbar_wait(uint32_t bar) {
  asm volatile("{\n.reg .pred p;\n.reg .u32 c;\nmov.u32 c, 0;\n"
               "MW_LOOP:\nmbarrier.try_wait.parity.shared::cta.b64 p, [%0], 0;\n@p bra MW_DONE;\n"
               "add.u32 c, c, 1;\nsetp.lt.u32 p, c, 4194304;\n@p bra MW_LOOP;\ntrap;\nMW_DONE:\n}"
               ::"r"(bar) : "memory");
}
__device__ __forceinline__ bool mbar_test(uint32_t bar) {
  uint32_t ok;
  asm volatile("{\n.reg .pred p;\nmbarrier.test_wait.parity.shared::cta.b64 p, [%1], 0;\nselp.u32 %0,1,0,p;\n}" : "=r"(ok) : "r"(bar) : "memory");
  return ok;
}
__device__ __forceinline__ void tma2d(uint32_t dst, const CUtensorMap* m, int c0, int c1, uint32_t bar, uint64_t pol) {
  asm volatile("cp.async.bulk.tensor.2d.shared::cluster.global.mbarrier::complete_tx::bytes.L2::cache_hint [%0], [%1, {%3,%4}], [%2], %5;"
               ::"r"(dst), "l"(m), "r"(bar), "r"(c0), "r"(c1), "l"(pol) : "memory");
}
__device__ __forceinline__ void tma2d_nohint(uint32_t dst, const CUtensorMap* m, int c0, int c1, uint32_t bar) {
  asm volatile("cp.async.bulk.tensor.2d.shared::cluster.global.mbarrier::complete_tx::bytes [%0], [%1, {%3,%4}], [%2];"
               ::"r"(dst), "l"(m), "r"(bar), "r"(c0), "r"(c1) : "memory");
}
__device__ __forceinline__ void tma3d(uint32_t dst, const CUtensorMap* m, int c0, int c1, int c2, uint32_t bar, uint64_t pol) {
  asm volatile("cp.async.bulk.tensor.3d.shared::cluster.global.mbarrier::complete_tx::bytes.L2::cache_hint [%0], [%1, {%3,%4,%5}], [%2], %6;"
               ::"r"(dst), "l"(m), "r"(bar), "r"(c0), "r"(c1), "r"(c2), "l"(pol) : "memory");
}
__device__ __forceinline__ void tma5d(uint32_t dst, const CUtensorMap* m, int c0, int c1, int c2, int c3, int c4, uint32_t bar, uint64_t pol) {
  asm volatile("cp.async.bulk.tensor.5d.shared::cluster.global.mbarrier::complete_tx::bytes.L2::cache_hint [%0], [%1, {%3,%4,%5,%6,%7}], [%2], %8;"
               ::"r"(dst), "l"(m), "r"(bar), "r"(c0), "r"(c1), "r"(c2), "r"(c3), "r"(c4), "l"(pol) : "memory");
}
__device__ __forceinline__ void bulk_ld(uint32_t dst, const void* src, uint32_t bytes, uint32_t bar) {
  asm volatile("cp.async.bulk.shared::cluster.global.mbarrier::complete_tx::bytes [%0], [%1], %2, [%3];" ::"r"(dst), "l"(src), "r"(bytes), "r"(bar) : "memory");
}
__device__ __forceinline__ void bar_sync(int id, int n) { asm volatile("barrier.cta.sync.aligned %0, %1;" ::"r"(id), "r"(n) : "memory"); }
__device__ __forceinline__ void cbar() { asm volatile("barrier.cta.sync.aligned 1, 256;" ::: "memory"); }
__device__ __forceinline__ bool bar_over(float ex) {
  uint32_t over;
  asm volatile("{\n.reg .pred p, q;\nsetp.gtu.f32 p, %1, 0f42700000;\nbarrier.cta.red.or.aligned.pred q, 4, 256, p;\nselp.u32 %0, 1, 0, q;\n}"
               : "=r"(over) : "f"(ex) : "memory");
  return over;
}

__device__ __forceinline__ uint32_t ldg_nc1(const void* p) { uint32_t v; asm volatile("ld.global.nc.L1::no_allocate.u32 %0, [%1];" : "=r"(v) : "l"(p)); return v; }
__device__ __forceinline__ uint32_t ldg_rlx1(const void* p) { uint32_t v; asm volatile("ld.relaxed.gpu.global.u32 %0, [%1];" : "=r"(v) : "l"(p) : "memory"); return v; }
__device__ __forceinline__ void stg4(void* p, uint4 v) { asm volatile("st.relaxed.gpu.global.v4.u32 [%0], {%1,%2,%3,%4};" ::"l"(p), "r"(v.x), "r"(v.y), "r"(v.z), "r"(v.w) : "memory"); }
__device__ __forceinline__ void stg1(void* p, uint32_t a) { asm volatile("st.relaxed.gpu.global.u32 [%0], %1;" ::"l"(p), "r"(a) : "memory"); }
__device__ __forceinline__ uint32_t nz(uint32_t w) { return max(w, 1u); }
__device__ __forceinline__ uint2 ldg_u64(const void* p) {
  uint2 v; asm volatile("{\n.reg .b64 a;\nld.relaxed.gpu.global.b64 a, [%2];\nmov.b64 {%0,%1}, a;\n}" : "=r"(v.x), "=r"(v.y) : "l"(p) : "memory"); return v;
}
__device__ __forceinline__ uint4 ldg_2u64(const void* p) {
  uint4 v; asm volatile("{\n.reg .b64 a, b;\nld.relaxed.gpu.global.v2.b64 {a, b}, [%4];\nmov.b64 {%0,%1}, a;\nmov.b64 {%2,%3}, b;\n}" : "=r"(v.x), "=r"(v.y), "=r"(v.z), "=r"(v.w) : "l"(p) : "memory"); return v;
}
__device__ __forceinline__ void stg_u64(void* p, uint32_t x, uint32_t y) {
  asm volatile("{\n.reg .b32 y;\nmax.u32 y, %2, 1;\nst.relaxed.gpu.global.v2.b32 [%0], {%1, y};\n}" ::"l"(p), "r"(x), "r"(y) : "memory");
}
__device__ __forceinline__ void red_u64(void* p, uint32_t x, uint32_t y) {
  asm volatile("{\n.reg .b32 y;\n.reg .b64 a;\nmax.u32 y, %2, 1;\nmov.b64 a, {%1, y};\nred.relaxed.gpu.global.or.b64 [%0], a;\n}" ::"l"(p), "r"(x), "r"(y) : "memory");
}
__device__ __forceinline__ void stg_u64_unless(uint32_t bad, void* p, uint32_t x, uint32_t y) {
  asm volatile("{\n.reg .b32 y;\n.reg .pred q;\nsetp.eq.u32 q, %3, 0;\nmax.u32 y, %2, 1;\n@q st.relaxed.gpu.global.v2.b32 [%0], {%1, y};\n}" ::"l"(p), "r"(x), "r"(y), "r"(bad) : "memory");
}

__device__ __forceinline__ void stg_cvt8(void* p, float a0, float a1, float b0, float b1, float c0, float c1, float d0, float d1) {
  asm volatile("{\n.reg .b32 x, y, z, w;\ncvt.rn.bf16x2.f32 x, %2, %1;\ncvt.rn.bf16x2.f32 y, %4, %3;\ncvt.rn.bf16x2.f32 z, %6, %5;\ncvt.rn.bf16x2.f32 w, %8, %7;\n"
               "max.u32 y, y, 1;\nmax.u32 w, w, 1;\nst.relaxed.gpu.global.v4.b32 [%0], {x, y, z, w};\n}"
               ::"l"(p), "f"(a0), "f"(a1), "f"(b0), "f"(b1), "f"(c0), "f"(c1), "f"(d0), "f"(d1) : "memory");
}
__device__ __forceinline__ uint32_t pack_bf16(float lo, float hi) { uint32_t r; asm("cvt.rn.bf16x2.f32 %0, %1, %2;" : "=r"(r) : "f"(hi), "f"(lo)); return r; }
__device__ __forceinline__ float bf_lo(uint32_t w) { return __uint_as_float(w << 16); }
__device__ __forceinline__ float bf_hi(uint32_t w) { return __uint_as_float(w & 0xffff0000u); }
__device__ __forceinline__ float ex2(float x) { float r; asm("ex2.approx.ftz.f32 %0, %1;" : "=f"(r) : "f"(x)); return r; }
__device__ __forceinline__ uint32_t hmul2(uint32_t a, uint32_t b) { uint32_t r; asm("mul.rn.bf16x2 %0, %1, %2;" : "=r"(r) : "r"(a), "r"(b)); return r; }
__device__ __forceinline__ uint32_t hadd2(uint32_t a, uint32_t b) { uint32_t r; asm("add.rn.bf16x2 %0, %1, %2;" : "=r"(r) : "r"(a), "r"(b)); return r; }
__device__ __forceinline__ uint32_t silu2(uint32_t v) { const float a = bf_lo(v), b = bf_hi(v); return pack_bf16(__fdividef(a, 1.f + __expf(-a)), __fdividef(b, 1.f + __expf(-b))); }
constexpr uint32_t ONE2 = 0x3f803f80u;

__device__ __forceinline__ void ldsm4(uint32_t (&r)[4], uint32_t a) { asm volatile("ldmatrix.sync.aligned.m8n8.x4.shared.b16 {%0,%1,%2,%3}, [%4];" : "=r"(r[0]), "=r"(r[1]), "=r"(r[2]), "=r"(r[3]) : "r"(a) : "memory"); }
__device__ __forceinline__ void ldsm4t(uint32_t (&r)[4], uint32_t a) { asm volatile("ldmatrix.sync.aligned.m8n8.x4.trans.shared.b16 {%0,%1,%2,%3}, [%4];" : "=r"(r[0]), "=r"(r[1]), "=r"(r[2]), "=r"(r[3]) : "r"(a) : "memory"); }
__device__ __forceinline__ void stsm4t(uint32_t a, uint32_t r0, uint32_t r1, uint32_t r2, uint32_t r3) { asm volatile("stmatrix.sync.aligned.m8n8.x4.trans.shared.b16 [%0], {%1,%2,%3,%4};" ::"r"(a), "r"(r0), "r"(r1), "r"(r2), "r"(r3) : "memory"); }
__device__ __forceinline__ uint32_t movm(uint32_t a) { uint32_t d; asm volatile("movmatrix.sync.aligned.m8n8.trans.b16 %0, %1;" : "=r"(d) : "r"(a)); return d; }
__device__ __forceinline__ void mma16816(float (&d)[4], const uint32_t (&a)[4], uint32_t b0, uint32_t b1) {
  asm volatile("mma.sync.aligned.m16n8k16.row.col.f32.bf16.bf16.f32 {%0,%1,%2,%3}, {%4,%5,%6,%7}, {%8,%9}, {%0,%1,%2,%3};"
               : "+f"(d[0]), "+f"(d[1]), "+f"(d[2]), "+f"(d[3]) : "r"(a[0]), "r"(a[1]), "r"(a[2]), "r"(a[3]), "r"(b0), "r"(b1));
}
__device__ __forceinline__ void sts1(uint32_t a, uint32_t v) { asm volatile("st.shared.u32 [%0], %1;" ::"r"(a), "r"(v) : "memory"); }
__device__ __forceinline__ void sts2(uint32_t a, uint32_t x, uint32_t y) { asm volatile("st.shared.v2.u32 [%0], {%1,%2};" ::"r"(a), "r"(x), "r"(y) : "memory"); }
__device__ __forceinline__ void sts4(uint32_t a, uint4 v) { asm volatile("st.shared.v4.u32 [%0], {%1,%2,%3,%4};" ::"r"(a), "r"(v.x), "r"(v.y), "r"(v.z), "r"(v.w) : "memory"); }
__device__ __forceinline__ void sts2f(uint32_t a, float x, float y) { asm volatile("st.shared.v2.f32 [%0], {%1,%2};" ::"r"(a), "f"(x), "f"(y) : "memory"); }
__device__ __forceinline__ void sts4f(uint32_t a, float x, float y, float z, float w) { asm volatile("st.shared.v4.f32 [%0], {%1,%2,%3,%4};" ::"r"(a), "f"(x), "f"(y), "f"(z), "f"(w) : "memory"); }
__device__ __forceinline__ void stsf(uint32_t a, float v) { asm volatile("st.shared.f32 [%0], %1;" ::"r"(a), "f"(v) : "memory"); }
__device__ __forceinline__ uint32_t lds1(uint32_t a) { uint32_t v; asm volatile("ld.shared.u32 %0, [%1];" : "=r"(v) : "r"(a) : "memory"); return v; }
__device__ __forceinline__ float ldsf(uint32_t a) { float v; asm volatile("ld.shared.f32 %0, [%1];" : "=f"(v) : "r"(a) : "memory"); return v; }
__device__ __forceinline__ float2 ldsf2(uint32_t a) { float2 v; asm volatile("ld.shared.v2.f32 {%0,%1}, [%2];" : "=f"(v.x), "=f"(v.y) : "r"(a) : "memory"); return v; }
__device__ __forceinline__ float4 ldsf4(uint32_t a) { float4 v; asm volatile("ld.shared.v4.f32 {%0,%1,%2,%3}, [%4];" : "=f"(v.x), "=f"(v.y), "=f"(v.z), "=f"(v.w) : "r"(a) : "memory"); return v; }
__device__ __forceinline__ void lds4(uint32_t (&r)[4], uint32_t a) { asm volatile("ld.shared.v4.u32 {%0,%1,%2,%3}, [%4];" : "=r"(r[0]), "=r"(r[1]), "=r"(r[2]), "=r"(r[3]) : "r"(a) : "memory"); }

__device__ __forceinline__ void wg_fence() { asm volatile("wgmma.fence.sync.aligned;" ::: "memory"); }
__device__ __forceinline__ void wg_commit() { asm volatile("wgmma.commit_group.sync.aligned;" ::: "memory"); }
template <int N> __device__ __forceinline__ void wg_wait() { asm volatile("wgmma.wait_group.sync.aligned %0;" ::"n"(N) : "memory"); }
__host__ __device__ constexpr uint32_t desc_lo(uint32_t off) { return ((SB + off) >> 4) | 0x10000u; }
template <int TA, int ACC> __device__ __forceinline__ void wgmma_n16(float (&d)[8], uint32_t da, uint32_t db) {
  asm volatile("{\n.reg .b64 da, db;\nmov.b64 da, {%8, 0x40000040};\nmov.b64 db, {%9, 0x40000040};\n"
               "wgmma.mma_async.sync.aligned.m64n16k16.f32.bf16.bf16 {%0,%1,%2,%3,%4,%5,%6,%7}, da, db, %11, 1, 1, %10, 0;\n}"
               : "+f"(d[0]), "+f"(d[1]), "+f"(d[2]), "+f"(d[3]), "+f"(d[4]), "+f"(d[5]), "+f"(d[6]), "+f"(d[7])
               : "r"(da), "r"(db), "n"(TA), "n"(ACC));
}
__device__ __forceinline__ void wgmma_n16_ones(float (&d)[8], uint32_t one, uint32_t db) {
  asm volatile("{\n.reg .b64 db;\nmov.b64 db, {%9, 0x40000040};\n"
               "wgmma.mma_async.sync.aligned.m64n16k16.f32.bf16.bf16 {%0,%1,%2,%3,%4,%5,%6,%7}, {%8,%8,%8,%8}, db, 1, 1, 1, 0;\n}"
               : "+f"(d[0]), "+f"(d[1]), "+f"(d[2]), "+f"(d[3]), "+f"(d[4]), "+f"(d[5]), "+f"(d[6]), "+f"(d[7])
               : "r"(one), "r"(db));
}
__device__ __forceinline__ void acc_fence(float (&d)[8]) {
  asm volatile("" : "+f"(d[0]), "+f"(d[1]), "+f"(d[2]), "+f"(d[3]), "+f"(d[4]), "+f"(d[5]), "+f"(d[6]), "+f"(d[7]) :: "memory");
}

template <int N, int STRIDE> __device__ __forceinline__ void load_units(uint2 (&v)[N], const uint32_t* p) {
#pragma unroll
  for (int i = 0; i < N; i++) v[i] = ldg_u64(p + i * STRIDE);
}
__device__ __forceinline__ void reload_unit(uint2& v, const uint32_t* p) {
  asm volatile("{\n.reg .pred q;\nsetp.eq.u32 q, %1, 0;\n@q ld.relaxed.gpu.global.v2.b32 {%0, %1}, [%2];\n}" : "+r"(v.x), "+r"(v.y) : "l"(p) : "memory");
}
template <int N> __device__ __forceinline__ uint32_t min_flags(const uint2 (&v)[N]) {
  uint32_t a = v[0].y, b = v[1].y;
#pragma unroll
  for (int i = 2; i < N; i += 2) { a = min(a, v[i].y); b = min(b, v[i + 1].y); }
  return min(a, b);
}
template <int N, int STRIDE> __device__ __forceinline__ int check_units(uint2 (&v)[N], const uint32_t* p) {
  int it = 0;
  while (!__all_sync(~0u, min_flags(v) != 0)) {
#pragma unroll
    for (int i = 0; i < N; i++) reload_unit(v[i], p + i * STRIDE);
    if (++it > SPIN_LIMIT) __trap();
  }
  return it;
}
__device__ __forceinline__ void sum4_to_smem(const uint2 (&v)[4], uint32_t dst) {
  const float c0 = (bf_lo(v[0].x) + bf_lo(v[1].x)) + (bf_lo(v[2].x) + bf_lo(v[3].x));
  const float c1 = (bf_hi(v[0].x) + bf_hi(v[1].x)) + (bf_hi(v[2].x) + bf_hi(v[3].x));
  const float c2 = (bf_lo(v[0].y) + bf_lo(v[1].y)) + (bf_lo(v[2].y) + bf_lo(v[3].y));
  const float c3 = (bf_hi(v[0].y) + bf_hi(v[1].y)) + (bf_hi(v[2].y) + bf_hi(v[3].y));
  sts1(dst, pack_bf16(c0, c1));
  sts1(dst + 128, pack_bf16(c2, c3));
}
__device__ __forceinline__ uint32_t a_t_offset(int w, int lane) {
  const int mi = lane >> 3, r = lane & 7;
  return (w >> 2) * 16384 + (8 * (mi >> 1) + r) * 128 + (((2 * (w & 3) + (mi & 1)) ^ r) << 4);
}
__device__ __forceinline__ void load_a_t(uint32_t (&a)[8][4], uint32_t base) {
#pragma unroll
  for (int ks = 0; ks < 8; ks++) ldsm4t(a[ks], base + ks * 2048);
}
__device__ __forceinline__ void mma128(float (&d)[4], const uint32_t (&a)[8][4], const uint32_t (&b)[4][4]) {
  float e[4][4] = {{d[0], d[1], d[2], d[3]}, {0.f, 0.f, 0.f, 0.f}, {0.f, 0.f, 0.f, 0.f}, {0.f, 0.f, 0.f, 0.f}};
#pragma unroll
  for (int kk = 0; kk < 4; kk++) { mma16816(e[(2 * kk) & 3], a[2 * kk], b[kk][0], b[kk][1]); mma16816(e[(2 * kk + 1) & 3], a[2 * kk + 1], b[kk][2], b[kk][3]); }
#pragma unroll
  for (int i = 0; i < 4; i++) d[i] = (e[0][i] + e[1][i]) + (e[2][i] + e[3][i]);
}
template <int NP> __device__ __forceinline__ bool sum_pieces(const uint32_t* p0, uint32_t one, float (&r)[4]) {
  uint2 v[NP / 4];
  load_units<NP / 4, 64>(v, p0);
  float d[4][4] = {};
#pragma unroll
  for (int i = 0; i < NP / 8; i++) { const uint32_t a[4] = {v[2 * i].x, v[2 * i].y, v[2 * i + 1].x, v[2 * i + 1].y}; mma16816(d[i & 3], a, one, one); }
  const bool ok = __all_sync(~0u, min_flags(v) != 0);
#pragma unroll
  for (int k = 0; k < 4; k++) r[k] = (d[0][k] + d[1][k]) + (d[2][k] + d[3][k]);
  return ok;
}
template <typename F> __device__ __forceinline__ float reduce_g(const float (&x)[4], int lane, F f) {
  const bool u4 = lane & 16, u3 = lane & 8;
  const float a0 = f(u4 ? x[2] : x[0], __shfl_xor_sync(~0u, u4 ? x[0] : x[2], 16));
  const float a1 = f(u4 ? x[3] : x[1], __shfl_xor_sync(~0u, u4 ? x[1] : x[3], 16));
  const float b = f(u3 ? a1 : a0, __shfl_xor_sync(~0u, u3 ? a0 : a1, 8));
  return f(b, __shfl_xor_sync(~0u, b, 4));
}

__global__ void __launch_bounds__(NTHREADS, 1)
fused_decode_kernel(__nv_bfloat16* __restrict__ gout, Scratch* __restrict__ gs, const uint8_t* __restrict__ gwmod,
                    const uint8_t* __restrict__ gx, const uint8_t* __restrict__ gc, uint32_t* __restrict__ gin,
                    const __grid_constant__ Params P) {
  constexpr Tune T{};
  extern __shared__ __align__(1024) uint8_t smem_raw[];
  constexpr uint32_t sb = SB;
  uint4 w0, w1;
  uint2 cc;
  {
    const uint32_t tx = threadIdx.x, bx = blockIdx.x;
    const uint8_t* pw = gwmod + ((128 * (bx & 3) + 4 * (tx >> 3) + ((tx >> 2) & 1)) * 6144 + 64 * (bx >> 2) + 16 * (tx & 3));
    const uint8_t* pc = gc + (((tx >> 2) & 7) * 1024 + 256 * (bx & 3) + (tx & 0xe0) + 8 * (tx & 3));
    asm volatile("{\n.reg .pred q;\nsetp.lt.u32 q, %12, 256;\n@q ld.global.nc.L1::no_allocate.v4.u32 {%0,%1,%2,%3}, [%10];\n"
                 "@q ld.global.nc.L1::no_allocate.v4.u32 {%4,%5,%6,%7}, [%10+12288];\n@q ld.global.nc.v2.u32 {%8,%9}, [%11];\n}"
                 : "=r"(w0.x), "=r"(w0.y), "=r"(w0.z), "=r"(w0.w), "=r"(w1.x), "=r"(w1.y), "=r"(w1.z), "=r"(w1.w), "=r"(cc.x), "=r"(cc.y)
                 : "l"(pw), "l"(pc), "r"(tx));
  }
  const int tid = __shfl_xor_sync(0xffffffffu, threadIdx.x ^ 1, 1), lane = tid & 31;
  const int w = __shfl_sync(0xffffffffu, threadIdx.x >> 5, 0);
  const int cta = blockIdx.x;
  auto keep = [&](uint32_t v) { return __shfl_sync(~0u, v, lane); };
  auto BAR = [](int i) { return SB + OFF_BARS + 8 * i; };
  auto selector = [&](int c) { uint32_t v; asm volatile("ld.shared.u8 %0, [%1];" : "=r"(v) : "r"(sb + OFF_SEL + c) : "memory"); return v; };
  auto inbox = [&](int c, int k) { return gin + blk(c, k, selector(c)); };
  auto nearbox = [&](int c, int k) { return gin + blk(c, k, selector(cta) ^ flip((c ^ cta) & 15)); };
  const int g = lane >> 2, t = lane & 3;
  const int hI = cta >> 2, jI = cta & 3;
  const int bs = cta >> 1, hh = cta & 1;

  if (w == 8) {
    const uint32_t t_entry = gtime32();
    if (lane == 0) {
      if ((uint32_t)__cvta_generic_to_shared(smem_raw) != SB) __trap();
      mbar_init(BAR(BAR_WQ), 1); mbar_init(BAR(BAR_WQ + 1), 1); mbar_init(BAR(BAR_XC), 1); mbar_init(BAR(BAR_C), 1);
      asm volatile("fence.mbarrier_init.release.cluster;" ::: "memory");
      asm volatile("prefetch.tensormap [%0];" ::"l"(&P.wq) : "memory");
      mbar_expect(BAR(BAR_XC), 8192); mbar_expect(BAR(BAR_C), 8192); mbar_expect(BAR(BAR_WQ), 16384); mbar_expect(BAR(BAR_WQ + 1), 16384);
    }
    __syncwarp();
    asm volatile("barrier.cta.arrive.aligned 0, %0;" ::"n"(NTHREADS) : "memory");
    uint32_t tn = t_entry + (uint32_t)(T.PC_T0 + ((bs * 37) & 63) * T.PC_STAG / 64);
    const int h = hI, j = jI;
    if (lane == 0) {
      uint64_t pol; asm volatile("createpolicy.fractional.L2::evict_first.b64 %0, 1.0;" : "=l"(pol));
#pragma unroll
      for (int u = 0; u < 4; u++) {
        until_ns(tn + u * T.PC_P1);
        tma2d(sb + OFF_WQ + u * 8192, &P.wq, 128 * h + 64 * (u >> 1), 128 * j + 64 * (u & 1), BAR(BAR_WQ + (u >> 1)), pol);
        if (u == 0) {
#pragma unroll
          for (int i = 0; i < 8; i++) { const int o = ((i + cta) & 3) * 2048; bulk_ld(sb + OFF_XS + (i >> 2) * 8192 + o, (i < 4 ? gx : gc) + o, 2048, BAR(i < 4 ? BAR_XC : BAR_C)); }
          asm volatile("prefetch.tensormap [%0];" ::"l"(&P.wuk) : "memory");
          asm volatile("prefetch.tensormap [%0];" ::"l"(&P.wm2) : "memory");
          asm volatile("prefetch.tensormap [%0];" ::"l"(&P.ckv2) : "memory");
        }
      }
    }
    __syncwarp();
    tn += 4 * T.PC_P1;
    bar_sync(5, 64);
    if (lane == 0) {
      uint64_t pol; asm volatile("createpolicy.fractional.L2::evict_first.b64 %0, 1.0;" : "=l"(pol));
#pragma unroll
      for (int u = 0; u < 4; u++) {
        if (u & 1) mbar_wait(BAR(BAR_WQ + (u >> 1)));
        slot(tn, T.PC_SL);
        tma5d(sb + OFF_WUK + u * 8192, &P.wuk, 128 * h + 64 * (u >> 1), 0, 0, 0, 8 * j + 4 * (u & 1), BAR(BAR_WUK + (u >> 1)), pol);
        tn += T.PC_P1;
      }
#pragma unroll
      for (int u = 0; u < 2; u++) {
        if (u) mbar_wait(BAR(BAR_WUK));
        slot(tn, T.PC_SL);
        if (j != 3) tma2d_nohint(sb + OFF_WM2 + u * 8192, &P.wm2, 1024 + 16 * (3 * h + j), 256 * u, BAR(BAR_WM2));
        tn += T.PC_PM;
      }
      const int row0 = (bs >> 3) * 4096 + (bs & 7) * 64;
      uint32_t dst = sb + OFF_RING;
#pragma unroll 1
      for (int n = 0; n < 31; n++) {
        if (n >= 4 && (n < 12 || (n & 3) == 0)) mbar_wait(BAR(n >= 12 ? BAR_EMPTY + (n >> 2) - 3 : (n == 7 && j != 3) ? BAR_P0BD : (n == 8 || n == 9) ? BAR_P2D : BAR_P1D));
        if (n < T.PC_NW) {
          if (n >= 4) mbar_wait(BAR(BAR_FULL + n - 4));
          else if (n & 1) mbar_wait(BAR((n < 2 || j == 3) ? BAR_WUK + 1 : BAR_WM2));
        }
        slot(tn, T.PC_SL);
        tma3d(dst, &P.ckv2, 0, row0 + (n >> 2) * 512, 2 * (n & 3), BAR(BAR_FULL + n), pol);
        dst = (n == 11 || n == 23) ? sb + OFF_RING : dst + 16384;
        tn += T.PC_P2;
        if (n == 24) {
          asm volatile("prefetch.tensormap [%0];" ::"l"(&P.ckv1) : "memory");
          asm volatile("prefetch.tensormap [%0];" ::"l"(&P.wuv) : "memory");
          asm volatile("prefetch.tensormap [%0];" ::"l"(&P.wo) : "memory");
          asm volatile("prefetch.tensormap [%0];" ::"l"(cta < NFF ? &P.w1 : &P.wm3) : "memory");
          asm volatile("prefetch.tensormap [%0];" ::"l"(&P.w2) : "memory");
        }
      }
      slot(tn, T.PC_SL);
      tma3d(dst, &P.ckv1, 0, row0 + 7 * 512, 6, BAR(BAR_LAST + 3), pol);
      tma3d(dst + 8192, &P.ckv1, 0, row0 + 7 * 512, 7, BAR(BAR_LAST + 4), pol);
      tn += T.PC_P2;
      auto unit = [&](int u) {
        if (u < 4) tma5d(sb + OFF_WUV + u * 8192, &P.wuv, 128 * h + 64 * (u >> 1), 0, 4 * (j >> 1), 0, 2 * (j & 1) + (u & 1), BAR(BAR_WUV + (u >> 1)), pol);
        else if (u < 8) tma2d(sb + OFF_WO + (u - 4) * 8192, &P.wo, 128 * j + 64 * ((u - 4) >> 1), 128 * h + 64 * (u & 1), BAR(BAR_WO + ((u - 4) >> 1)), pol);
        else if (u < 10) { if (cta < NFF) tma2d_nohint(sb + OFF_W1 + (u - 8) * 16384, &P.w1, 32 * bs, 256 * (u - 8), BAR(BAR_W1)); }
        else if (cta < NFF) tma3d(sb + OFF_W2 + (u - 10) * 8192, &P.w2, 0, 32 * bs, 4 * hh + 2 * (u - 10), BAR(BAR_W2), pol);
        else tma2d_nohint(sb + OFF_W1 + (u - 10) * 16384, &P.wm3, 2560 + 32 * (cta - NFF), 256 * (u - 10), BAR(BAR_W1));
      };
      mbar_wait(BAR(BAR_EMPTY + 5));
#pragma unroll
      for (int u = 0; u < 12; u++) {
        if (u == 8) mbar_wait(BAR(BAR_EMPTY + 6));
        until_ns(tn + (u < 4 ? T.T_UV + u * T.P_UV : u < 8 ? T.T_O + (u - 4) * T.P_O : u < 10 ? T.T_1 + (u - 8) * T.P_F : (cta < NFF ? T.T_2 : T.T_GB) + (u - 10) * T.P_F));
        unit(u);
        if (u == 3) {
#pragma unroll
          for (int q = 0; q < 4; q++)
            if (q < T.PF_N) {
              until_ns(tn + T.T_PF + q * T.P_PF);
              asm volatile("cp.async.bulk.prefetch.tensor.2d.L2.global.tile [%0, {%1,%2}];" ::"l"(&P.wo), "r"(128 * j + 64 * (q >> 1)), "r"(128 * h + 64 * (q & 1)) : "memory");
            }
        }
      }
    }
    return;
  }

  if (w == 9) {
    if (lane == 0) {
#pragma unroll
      for (int i = 0; i < NBARS; i++) mbar_init(BAR(i), i >= BAR_P1D ? 8 : i >= BAR_EMPTY ? 4 : 1);
      asm volatile("fence.mbarrier_init.release.cluster;" ::: "memory");
    }
    __syncwarp();
    mbar_expect(BAR(lane), lane == BAR_LAST + 3 ? 8192 : 16384);
    if (lane < BAR_ALLCLR - 32) mbar_expect(BAR(32 + lane), lane == 0 ? 8192 : lane == BAR_W1 - 32 ? 32768 : 16384);
    asm volatile("barrier.cta.arrive.aligned 5, 64;" ::: "memory");
    asm volatile("barrier.cta.arrive.aligned 0, %0;" ::"n"(NTHREADS) : "memory");
  }
  const uint32_t epoch = ldg_rlx1(&gs->epoch);

  if (w == 9) {
    const int mo = g * 512 + 16 * hI + 2 * jI;
    const uint32_t xo0 = ldg_nc1(gx + mo * 2), xo1 = ldg_nc1(gx + mo * 2 + 16);
    const int par = epoch & 1;
    const uint32_t t0 = gtime32();
    const uint4 z = make_uint4(0, 0, 0, 0);
    uint32_t sel;
    {
      uint32_t* pa = gin + blk(cta, 5, 0) + 960;
      uint32_t* pb = gin + blk(cta, 5, 1) + 960;
      until_ns(t0 + T.PR_T0);
      if (lane < 4) stg4(reinterpret_cast<uint4*>(lane & 2 ? pa : pb) + (lane & 1), z);
      uint32_t ma = 0xffffffffu, mb = 0xffffffffu;
#pragma unroll 1
      for (int i = 0; i < 2 * T.PR_N; i++) {
        const uint32_t c0 = clk32();
        asm volatile("{\n.reg .pred q;\n.reg .b32 v;\nsetp.eq.u32 q, %1, 0;\nmov.u32 v, 0;\n@q atom.relaxed.gpu.global.add.u32 v, [%0], 1;\n"
                     "setp.eq.u32 q, v, 0xffffffff;\n@q trap;\n}" ::"l"(i & 1 ? pb : pa), "r"(lane) : "memory");
        const uint32_t d = clk32() - c0;
        if (i & 1) mb = min(mb, d); else ma = min(ma, d);
      }
      sel = __shfl_sync(~0u, (uint32_t)(mb < ma), 0);
      const uint32_t sw = 2 * (epoch + 1) + sel;
      if (lane < 2) stg4(reinterpret_cast<uint4*>(gin + blk(cta, 5, 1) + 896) + lane, make_uint4(sw, sw, sw, sw));
    }
    until_ns(t0 + T.CLR_T0);
    {
#pragma unroll 1
      for (int i0 = 0; i0 < 13; i0++) {
        uint4* q = reinterpret_cast<uint4*>(gin + (i0 < 12 ? blk(cta, i0 >> 1, sel) + (i0 & 1) * 512 : blk(cta, 4, sel ^ 1) + 512)) + lane;
#pragma unroll
        for (int i = 0; i < 4; i++) if (i0 != 11 || i < 3) stg4(q + i * 32, z);
        backoff(T.CLR_CLK);
      }
#pragma unroll
      for (int i = 0; i < 2; i++) {
        if (jI == 1) stg4(reinterpret_cast<uint4*>(gin + blk(cta, 6, i)) + lane, z);
        if (lane < 2) stg4(reinterpret_cast<uint4*>(gin + blk(cta, 5, i) + 928) + lane, z);
        stg4(reinterpret_cast<uint4*>(gin + blk(16 * g, 6 + (cta >> 6), i) + (cta & 63) * 16) + t, z);
      }
      {
        uint32_t sv = 0;
        uint32_t u[4];
        int it = 0;
        do {
#pragma unroll
          for (int i = 0; i < 4; i++) u[i] = ldg_rlx1(gin + blk(4 * lane + i, 5, 1) + 896) ^ (2 * (epoch + 1));
          if (++it > SPIN_LIMIT) __trap();
        } while (!__all_sync(~0u, (u[0] | u[1] | u[2] | u[3]) < 2));
#pragma unroll
        for (int i = 0; i < 4; i++) sv |= u[i] << (8 * i);
        sts1(sb + OFF_SEL + lane * 4, sv);
      }
      asm volatile("fence.acq_rel.gpu;" ::: "memory");
      __syncwarp();
      if (lane < NSYNC) asm volatile("red.relaxed.gpu.global.add.u32 [%0], 1;" ::"l"(&gs->sync[lane][0]) : "memory");
#pragma unroll
      for (int i = 0; i < 4; i++) stg4(reinterpret_cast<uint4*>(gs->QP[par ^ 1] + cta * 512) + i * 32 + lane, z);
      backoff(T.CLR_CLK);
#pragma unroll
      for (int i = 0; i < 4; i++) stg4(reinterpret_cast<uint4*>(gs->QX[par ^ 1] + cta * 512) + i * 32 + lane, z);
      stg4(reinterpret_cast<uint4*>(gs->MOD1[par ^ 1] + cta * 128) + lane, z);
      if (lane < 16) stg4(reinterpret_cast<uint4*>(gs->MOD2[par ^ 1] + cta * 64) + lane, z);
      const uint32_t target = (epoch + 1) * NCTA;
      uint32_t c; int it = 0;
      do {
        backoff(T.CLR_CLK);
        asm volatile("ld.acquire.gpu.global.u32 %0, [%1];" : "=r"(c) : "l"(&gs->sync[cta % NSYNC][0]) : "memory");
        if (++it > SPIN_LIMIT) __trap();
      } while (!__all_sync(~0u, (int)(c - target) >= 0));
      if (lane == 0) mbar_arrive(BAR(BAR_ALLCLR));
    }
    const uint32_t* const pg = gs->MOD2[par] + cta * 16 + g * 2;
    auto gate = [&](const uint32_t* q) { uint2 u; int it = 0; do { u = ldg_u64(q); if (++it > SPIN_LIMIT) __trap(); } while (!__all_sync(~0u, u.y != 0)); return u; };
    const uint2 gau = gate(pg);
    uint32_t anchor;
    {
      uint32_t* const po = gin + blk(16 * (lane & 7), 5, lane >> 3) + 928;
      const uint32_t* const pi = nearbox(cta & ~15, 5) + 928;
      mbar_wait(BAR(BAR_LAST + T.TS_P));
      unsigned long long now; asm volatile("mov.u64 %0, %%globaltimer;" : "=l"(now));
      if (lane < 16) asm volatile("red.relaxed.gpu.global.add.u64 [%0], %1;" ::"l"(po), "l"((now << 8) + 1) : "memory");
      backoff(T.D_TS);
      uint2 v; int it = 0;
      do { v = ldg_u64(pi); if (++it > SPIN_LIMIT) __trap(); } while (!__all_sync(~0u, (v.x & 255) == NCTA));
      const uint32_t mean = __funnelshift_r(v.x, v.y, 15);
      const int age = min(max((int)(gtime32() - mean), 0), 4000);
      anchor = clk32() - age * 7 / 4 + T.TS_O;
      if (lane == 0) { sts1(sb + OFF_TS, anchor); mbar_arrive(BAR(BAR_TS)); }
      if (cta == 0 && lane == 0) stg1(&gs->epoch, epoch + 1);
    }
    {
      const uint32_t* pm = pin(nearbox(4 * hI + 1, 6) + lane * 4);
      wait_clk(anchor, T.A_M);
      uint4 ml = ldg_2u64(pm);
      int it = 0;
      while (!__all_sync(~0u, ml.y != 0 && ml.w != 0)) { ml = ldg_2u64(pm); if (++it > SPIN_LIMIT) __trap(); }
      float M = fmaxf(__uint_as_float(ml.x), __uint_as_float(ml.z));
      M = fmaxf(M, __shfl_xor_sync(~0u, M, 1)); M = fmaxf(M, __shfl_xor_sync(~0u, M, 2));
      const float e0 = ex2(__uint_as_float(ml.x) - M), e1 = ex2(__uint_as_float(ml.z) - M);
      float l = e0 * __uint_as_float(ml.y) + e1 * __uint_as_float(ml.w);
      l += __shfl_xor_sync(~0u, l, 1); l += __shfl_xor_sync(~0u, l, 2);
      const float inv = __fdividef(1.f, l);
      sts2f(sb + OFF_WV + lane * 8, e0 * inv, e1 * inv);
      __syncwarp();
      if (lane == 0) mbar_arrive(BAR(BAR_WV));
    }
    uint32_t* x3o[4];
#pragma unroll
    for (int i = 0; i < 4; i++) x3o[i] = pin(gin + blk(32 * i + 16 * (t >> 1), 6 + (cta >> 6), t) + (cta & 63) * 16 + g * 2);
    uint32_t* const fo = pin(reinterpret_cast<uint32_t*>(gout) + mo / 2 + 4 * (t & 1));
    const uint32_t* const p3 = pin(gin + blk(cta, 4, sel) + t * 16 + g * 2);
    const uint32_t* const p4 = pin(gin + blk(cta, 5, sel) + t * 16 + g * 2);
    const uint32_t one = pin((g & 1) ? 0x3f800000u : 0x00003f80u);
    const float xf[4] = {pin(bf_lo(xo0)), pin(bf_hi(xo0)), pin(bf_lo(xo1)), pin(bf_hi(xo1))};
    const float ga[4] = {pin(bf_lo(gau.x)), pin(bf_hi(gau.x)), pin(bf_lo(gau.y)), pin(bf_hi(gau.y))};
    mbar_wait(BAR(BAR_P5D));
    backoff(T.D_X3A);
    wait_clk(anchor, T.A_X1 + T.R_X3A);
    float r[4];
    uint32_t x20, x21;
    int it = 0;
    bool ok;
    do {
      ok = sum_pieces<32>(p3, one, r);
      x20 = pack_bf16(xf[0] + ga[0] * r[0], xf[1] + ga[1] * r[1]); x21 = pack_bf16(xf[2] + ga[2] * r[2], xf[3] + ga[3] * r[3]);
#pragma unroll
      for (int i = 0; i < 4; i++) stg_u64_unless(!ok || (i == 3 && t >= 2), x3o[i], x20, x21);
    } while (!ok && ++it < SPIN_LIMIT);
    if (!ok) __trap();
    const uint32_t xw = (t & 1) ? x21 : x20;
    const float xa = pin(bf_lo(xw)), xb = pin(bf_hi(xw));
    if (cta < NFF) mbar_wait(BAR(BAR_P7D)); else wait_clk(anchor, T.A_X1 + T.R_X3A + T.R_X3B + T.R_FIN - T.D_FIN);
    uint2 gbu = ldg_u64(pg + 3 * 2048);
    backoff(T.D_FIN);
    do {
      ok = sum_pieces<NFG>(p4, one, r);
      ok = ok && __all_sync(~0u, gbu.y != 0);
      const uint32_t gw = (t & 1) ? gbu.y : gbu.x;
      const uint32_t o = pack_bf16(xa + bf_lo(gw) * ((t & 1) ? r[2] : r[0]), xb + bf_hi(gw) * ((t & 1) ? r[3] : r[1]));
      if (ok && t < 2) asm volatile("st.global.u32 [%0], %1;" ::"l"(fo), "r"(o) : "memory");
      reload_unit(gbu, pg + 3 * 2048);
    } while (!ok && ++it < SPIN_LIMIT);
    if (!ok) __trap();
    return;
  }

  const int wg = w >> 2, wq = w & 3;
  uint32_t tstore;
  {
    const uint32_t a[4] = {silu2(cc.x), 0u, silu2(cc.y), 0u};
    float d[4][4] = {{0.f, 0.f, 0.f, 0.f}, {0.f, 0.f, 0.f, 0.f}, {0.f, 0.f, 0.f, 0.f}, {0.f, 0.f, 0.f, 0.f}};
    mma16816(d[0], a, movm(w0.x), movm(w1.x)); mma16816(d[1], a, movm(w0.y), movm(w1.y));
    mma16816(d[2], a, movm(w0.z), movm(w1.z)); mma16816(d[3], a, movm(w0.w), movm(w1.w));
    sts4f(sb + OFF_P0S + w * 1088 + lane * 16, d[0][0], d[0][1], d[1][0], d[1][1]);
    sts4f(sb + OFF_P0S + w * 1088 + 544 + lane * 16, d[2][0], d[2][1], d[3][0], d[3][1]);
    bar_sync(0, NTHREADS);
    if (tid < 128) {
      const uint32_t src = sb + OFF_P0S + ((tid >> 2) & 1) * 544 + (((tid >> 3) & 7) * 4 + 2 * (tid >> 6) + (tid & 1)) * 16 + ((tid >> 1) & 1) * 8;
      float2 v[8];
#pragma unroll
      for (int i = 0; i < 8; i++) v[i] = ldsf2(src + i * 1088);
      const float ax = ((v[0].x + v[1].x) + (v[2].x + v[3].x)) + ((v[4].x + v[5].x) + (v[6].x + v[7].x));
      const float ay = ((v[0].y + v[1].y) + (v[2].y + v[3].y)) + ((v[4].y + v[5].y) + (v[6].y + v[7].y));
      stg1(gs->MOD1[epoch & 1] + jI * 4096 + hI * 128 + tid, nz(pack_bf16(ax, ay)));
    }
    tstore = clk32();
  }
  const int par = epoch & 1;
  uint32_t cf[4][4];
  mbar_wait(BAR(BAR_XC));
  {
    uint32_t u[2][4];
    lds4(u[0], sb + OFF_XS + w * 1024 + lane * 16); lds4(u[1], sb + OFF_XS + w * 1024 + 512 + lane * 16);
    float v[16];
#pragma unroll
    for (int i = 0; i < 8; i++) { v[2 * i] = bf_lo(u[i >> 2][i & 3]); v[2 * i + 1] = bf_hi(u[i >> 2][i & 3]); }
    float s = 0.f;
#pragma unroll
    for (int i = 0; i < 16; i++) s += v[i];
#pragma unroll
    for (int o = 16; o; o >>= 1) s += __shfl_xor_sync(~0u, s, o);
    const float mu = s * (1.f / 512.f);
    float q = 0.f;
#pragma unroll
    for (int i = 0; i < 16; i++) { v[i] -= mu; q += v[i] * v[i]; }
#pragma unroll
    for (int o = 16; o; o >>= 1) q += __shfl_xor_sync(~0u, q, o);
    const float rs = rsqrtf(q * (1.f / 512.f) + 1e-5f);
    const bool hi = jI & 2;
    uint32_t o[4];
#pragma unroll
    for (int i = 0; i < 4; i++) o[i] = pack_bf16((hi ? v[8 + 2 * i] : v[2 * i]) * rs, (hi ? v[9 + 2 * i] : v[2 * i + 1]) * rs);
    if ((lane >> 4) == (jI & 1)) sts4(sb + OFF_XN + w * 272 + (lane & 15) * 16, make_uint4(o[0], o[1], o[2], o[3]));
  }
  uint32_t aw[8][4];
  const uint32_t abase = keep(sb + a_t_offset(w, lane));
  {
    const uint32_t* pm = pin(gs->MOD1[par] + (8 * jI + w) * 64 + lane * 2);
    uint32_t* const qpo = pin(gs->QP[par] + (cta * 256 + tid) * 2);
    float d[4] = {0.f, 0.f, 0.f, 0.f};
    wait_clk(tstore, T.D_MOD);
    uint2 v[8];
    load_units<8, 2048>(v, pm);
    cbar();
    const uint32_t xn0 = lds1(sb + OFF_XN + g * 272 + w * 32 + t * 4), xn1 = lds1(sb + OFF_XN + g * 272 + w * 32 + 16 + t * 4);
    const bool early = __all_sync(~0u, mbar_test(BAR(BAR_WQ + wg)));
    if (early) load_a_t(aw, abase + OFF_WQ);
    int it = 0;
    while (true) {
      uint32_t mn = 0xffffffffu;
#pragma unroll
      for (int i = 0; i < 8; i++) mn = min(mn, min(v[i].x, v[i].y));
      if (__all_sync(~0u, mn != 0)) break;
#pragma unroll
      for (int i = 0; i < 8; i++) { if (v[i].x == 0) v[i].y = 0; reload_unit(v[i], pm + i * 2048); }
      if (++it > SPIN_LIMIT) __trap();
    }
    float sc[2][4];
#pragma unroll
    for (int i = 0; i < 2; i++) {
      sc[i][0] = (bf_lo(v[i].x) + bf_lo(v[2 + i].x)) + (bf_lo(v[4 + i].x) + bf_lo(v[6 + i].x));
      sc[i][1] = (bf_hi(v[i].x) + bf_hi(v[2 + i].x)) + (bf_hi(v[4 + i].x) + bf_hi(v[6 + i].x));
      sc[i][2] = (bf_lo(v[i].y) + bf_lo(v[2 + i].y)) + (bf_lo(v[4 + i].y) + bf_lo(v[6 + i].y));
      sc[i][3] = (bf_hi(v[i].y) + bf_hi(v[2 + i].y)) + (bf_hi(v[4 + i].y) + bf_hi(v[6 + i].y));
    }
    sts2(sb + OFF_BS1 + (w >> 1) * 512 + lane * 16 + (w & 1) * 8,
         pack_bf16(bf_lo(xn0) * (1.f + sc[1][0]) + sc[0][0], bf_hi(xn0) * (1.f + sc[1][1]) + sc[0][1]),
         pack_bf16(bf_lo(xn1) * (1.f + sc[1][2]) + sc[0][2], bf_hi(xn1) * (1.f + sc[1][3]) + sc[0][3]));
    if (!early) { mbar_wait(BAR(BAR_WQ + wg)); load_a_t(aw, abase + OFF_WQ); }
    cbar();
    uint32_t b[4][4];
#pragma unroll
    for (int kk = 0; kk < 4; kk++) lds4(b[kk], sb + OFF_BS1 + kk * 512 + lane * 16);
    mma128(d, aw, b);
    stg_u64(qpo, pack_bf16(d[0], d[1]), pack_bf16(d[2], d[3]));
    tstore = clk32();
    if (wg) {
      mbar_wait(BAR(BAR_C));
#pragma unroll
      for (int i = 0; i < 4; i++) lds4(cf[i], sb + OFF_CS + g * 1024 + wq * 256 + i * 64 + t * 16);
#pragma unroll
      for (int i = 0; i < 16; i++) cf[i >> 2][i & 3] = silu2(cf[i >> 2][i & 3]);
    }
    __syncwarp();
    if (lane == 0) mbar_arrive(BAR(BAR_P1D));
  }
  {
    const uint32_t* pq = pin(gs->QP[par] + (hI * 4 * 256 + tid) * 2);
    uint32_t* const qxo = pin(gs->QX[par] + (g * 32 + hI) * 256 + 64 * jI + 8 * w + 2 * t);
    uint2 v[4];
    float d[4] = {0.f, 0.f, 0.f, 0.f};
    wait_clk(tstore, T.D_QP);
    load_units<4, 512>(v, pq);
    const uint32_t kbase = sb + OFF_WUK + (16 * w + (lane & 15)) * 128;
    auto load_half = [&](int hf) {
#pragma unroll
      for (int ks = 0; ks < 4; ks++) ldsm4(aw[4 * hf + ks], kbase + hf * 16384 + (((2 * ks + (lane >> 4)) ^ (lane & 7)) << 4));
    };
    mbar_wait(BAR(BAR_WUK));
    load_half(0);
    const bool early = __all_sync(~0u, mbar_test(BAR(BAR_WUK + 1)));
    if (early) load_half(1);
    check_units<4, 512>(v, pq);
    sum4_to_smem(v, sb + OFF_BS2 + (16 * w + g) * 16 + t * 4);
    if (!early) { mbar_wait(BAR(BAR_WUK + 1)); load_half(1); }
    cbar();
    uint32_t b[4][4];
#pragma unroll
    for (int kk = 0; kk < 4; kk++) ldsm4t(b[kk], sb + OFF_BS2 + (32 * kk + lane) * 16);
    mma128(d, aw, b);
    const float sc = 0.08838834764831845f * 1.4426950408889634f;
    stg_u64(qxo, movm(pack_bf16(d[0] * sc, d[1] * sc)), movm(pack_bf16(d[2] * sc, d[3] * sc)));
    tstore = clk32();
    if (lane == 0) mbar_arrive(BAR(BAR_P2D));
  }
  if (wg && jI != 3) {
    const int mi = lane >> 3, r = lane & 7;
    const uint32_t a0 = sb + OFF_WM2 + (8 * (r >> 1) + (r & 1) + 2 * (mi >> 1)) * 32 + (mi & 1) * 16;
    mbar_wait(BAR(BAR_WM2));
#pragma unroll
    for (int s = 0; s < 8; s++) ldsm4t(aw[s], a0 + (128 * wq + 32 * (s >> 1) + 4 * (s & 1)) * 32);
    float d[4] = {0.f, 0.f, 0.f, 0.f};
    mma128(d, aw, cf);
    sts4f(sb + OFF_P0B + (tid - 128) * 16, d[0], d[1], d[2], d[3]);
    if (lane == 0) mbar_arrive(BAR(BAR_P0BD));
    bar_sync(3, 128);
    if (w == 4) {
      float4 v[4];
#pragma unroll
      for (int i = 0; i < 4; i++) v[i] = ldsf4(sb + OFF_P0B + (i * 32 + lane) * 16);
      stg_u64(gs->MOD2[par] + (3 * hI + jI) * 64 + t * 16 + g * 2, movm(pack_bf16((v[0].x + v[1].x) + (v[2].x + v[3].x), (v[0].y + v[1].y) + (v[2].y + v[3].y))),
              movm(pack_bf16((v[0].z + v[1].z) + (v[2].z + v[3].z), (v[0].w + v[1].w) + (v[2].w + v[3].w))));
    }
  }
  {
    const uint32_t* qx = pin(gs->QX[par] + ((bs >> 3) * 32 + 16 * hh) * 256 + tid * 4);
    const int ch = tid & 63, h0 = tid >> 6;
    const uint32_t dst = sb + OFF_Q + (ch >> 3) * 2048 + h0 * 128;
    wait_clk(tstore, T.D_QX);
    uint4 v[4];
#pragma unroll
    for (int i = 0; i < 4; i++) v[i] = ldg_2u64(qx + i * 1024);
    int it = 0;
    while (true) {
      uint32_t mn = 0xffffffffu;
#pragma unroll
      for (int i = 0; i < 4; i++) mn = min(mn, min(v[i].y, v[i].w));
      if (__all_sync(~0u, mn != 0)) break;
#pragma unroll
      for (int i = 0; i < 4; i++)
        asm volatile("{\n.reg .pred q;\nsetp.eq.u32 q, %5, 0;\n@q ld.relaxed.gpu.global.v4.b32 {%0, %1, %2, %3}, [%4];\n}"
                     : "+r"(v[i].x), "+r"(v[i].y), "+r"(v[i].z), "+r"(v[i].w) : "l"(qx + i * 1024), "r"(min(v[i].y, v[i].w)) : "memory");
      if (++it > SPIN_LIMIT) __trap();
    }
#pragma unroll
    for (int i = 0; i < 4; i++) sts4(dst + i * 512 + (((ch & 7) ^ ((4 * i + h0) & 7)) << 4), v[i]);
    asm volatile("fence.proxy.async.shared::cta;" ::: "memory");
    cbar();
  }

  uint2 cbf[4], sbf[4];
  const uint32_t* const pcb = gs->MOD2[par] + 2048 + (16 * w + t) * 16 + g * 2;
  auto load_frags = [&] {
    if (cta < NFF) { load_units<4, 64>(sbf, pcb); load_units<4, 64>(cbf, pcb + 2048); }
    else {
#pragma unroll
      for (int s = 0; s < 4; s++) { cbf[s].x = ldg_nc1(gc + g * 1024 + w * 128 + s * 32 + t * 4); cbf[s].y = ldg_nc1(gc + g * 1024 + w * 128 + s * 32 + 16 + t * 4); }
    }
  };
  uint32_t thand, anchor;
  const uint32_t opaque0 = w >> 4;
  if (wg == 0) {
    float mh[4];
    float L[8];
#pragma unroll
    for (int i = 0; i < 4; i++) { L[2 * i] = L[2 * i + 1] = 0.f; mh[i] = -INFINITY; }
    constexpr uint32_t dq = desc_lo(OFF_Q);
    const uint32_t ptw = sb + OFF_PT + (8 * (lane >> 4) + (lane & 7)) * 128 + (((2 * wq + ((lane >> 3) & 1)) ^ (lane & 7)) << 4);
    float S[8];
    auto softmax = [&](int tl) {
      auto write_p = [&](const float (&x)[8]) {
        float p[8];
#pragma unroll
        for (int i = 0; i < 8; i++) p[i] = ex2(x[i]);
        stsm4t(ptw + (tl & 1) * 2048, pack_bf16(p[0], p[1]), pack_bf16(p[2], p[3]), pack_bf16(p[4], p[5]), pack_bf16(p[6], p[7]));
        asm volatile("fence.proxy.async.shared::cta;" ::: "memory");
      };
      float x[8];
#pragma unroll
      for (int i = 0; i < 8; i++) x[i] = S[i] - mh[2 * (i >> 2) + (i & 1)];
      if (tl) write_p(x);
      const float ex = fmaxf(fmaxf(fmaxf(x[0], x[1]), fmaxf(x[2], x[3])), fmaxf(fmaxf(x[4], x[5]), fmaxf(x[6], x[7])));
      if (tl == 0 || bar_over(ex)) {
        float mx[4];
#pragma unroll
        for (int i = 0; i < 4; i++) mx[i] = fmaxf(S[4 * (i >> 1) + (i & 1)], S[4 * (i >> 1) + 2 + (i & 1)]);
        const float a = reduce_g(mx, lane, [](float u, float v) { return fmaxf(u, v); });
        stsf(sb + OFF_RED + wq * 64 + (8 * (lane >> 4) + 2 * t + ((lane >> 3) & 1)) * 4, a);
        bar_sync(2, 128);
#pragma unroll
        for (int jn = 0; jn < 2; jn++) {
          float m0 = mh[2 * jn], m1 = mh[2 * jn + 1];
#pragma unroll
          for (int i = 0; i < 4; i++) { const float2 v = ldsf2(sb + OFF_RED + i * 64 + (8 * jn + 2 * t) * 4); m0 = fmaxf(m0, v.x); m1 = fmaxf(m1, v.y); }
          const float a0 = ex2(mh[2 * jn] - m0), a1 = ex2(mh[2 * jn + 1] - m1);
          mh[2 * jn] = m0; mh[2 * jn + 1] = m1;
          L[4 * jn] *= a0; L[4 * jn + 1] *= a1; L[4 * jn + 2] *= a0; L[4 * jn + 3] *= a1;
          if (tid < 4) sts2f(sb + OFF_ALPHA + (8 * jn + 2 * t) * 4, a0, a1);
        }
        asm volatile("barrier.cta.arrive.aligned 1, 256;" ::: "memory");
#pragma unroll
        for (int i = 0; i < 8; i++) x[i] = S[i] - mh[2 * (i >> 2) + (i & 1)];
        write_p(x);
        bar_over(0.f);
      }
      const uint32_t dpt = __shfl_sync(~0u, desc_lo(OFF_PT) + (tl & 1) * 128, 0);
      wg_fence();
#pragma unroll
      for (int ks = 0; ks < 4; ks++) wgmma_n16_ones(L, ONE2, dpt + ks * 2);
      wg_commit();
    };
    uint32_t da = desc_lo(OFF_RING);
#pragma unroll 1
    for (int tl = 0; tl < 7; tl++) {
      if (tl == 1) mbar_wait(BAR(BAR_EMPTY));
      if (tl == 5) { load_frags(); }
      uint32_t ok = 0;
#pragma unroll
      for (int u = 0; u < 4; u++) ok += mbar_test(BAR(BAR_FULL + 4 * tl + u));
      ok = __reduce_min_sync(~0u, ok);
      const uint32_t du = __shfl_sync(~0u, da, 0);
#pragma unroll
      for (int u = 0; u < 4; u++) {
        if (ok != 4) mbar_wait(BAR(BAR_FULL + 4 * tl + u));
        wg_fence();
#pragma unroll
        for (int k = 0; k < 8; k++) {
          const int i = 8 * u + k;
          if (i == 0) wgmma_n16<0, 0>(S, du, dq); else wgmma_n16<0, 1>(S, du + (i >> 2) * 512 + (i & 3) * 2, dq + (i >> 2) * 128 + (i & 3) * 2);
        }
        wg_commit();
      }
      wg_wait<0>();
      acc_fence(S); acc_fence(L);
      softmax(tl);
      da = (tl == 2 || tl == 5) ? da - 8192 : da + 4096;
    }
    mbar_wait(BAR(BAR_ALLCLR));
    uint32_t* const mlo = pin(gin + blk(4 * (16 * hh + 4 * (g & 2) + 2 * t + (g & 1)) + 1, 6, g >> 2) + bs * 2);
#pragma unroll
    for (int i = 0; i < 32; i++) {
      if (i == 0 || i == 8 || i == 16 || i == 24 || i == 28) {
        if (i) wg_commit();
        mbar_wait(BAR(BAR_LAST + (i == 28 ? 4 : i >> 3)));
        wg_fence();
      }
      if (i == 0) wgmma_n16<0, 0>(S, desc_lo(65536), dq); else wgmma_n16<0, 1>(S, desc_lo(65536) + (i >> 2) * 512 + (i & 3) * 2, dq + (i >> 2) * 128 + (i & 3) * 2);
    }
    wg_commit();
    wg_wait<0>();
    acc_fence(S); acc_fence(L);
    softmax(7);
    thand = clk32();
    wg_wait<0>();
    acc_fence(L);
    if (tid < 32) red_u64(mlo, __float_as_uint(g & 2 ? (g & 1 ? mh[3] : mh[2]) : (g & 1 ? mh[1] : mh[0])), __float_as_uint(g & 2 ? (g & 1 ? L[5] : L[4]) : (g & 1 ? L[1] : L[0])));
  } else {
    float O[8][8];
#pragma unroll
    for (int i = 0; i < 8; i++)
#pragma unroll
      for (int k = 0; k < 8; k++) O[i][k] = 0.f;
    constexpr uint32_t dp = desc_lo(OFF_PT);
    auto handover = [&](int tl) {
      uint32_t over = opaque0 + (tl == 0);
#pragma unroll 1
      do {
        if (over) {
          cbar();
#pragma unroll
          for (int jn = 0; jn < 2; jn++) {
            const float2 a = ldsf2(sb + OFF_ALPHA + (8 * jn + 2 * t) * 4);
#pragma unroll
            for (int mb = 0; mb < 8; mb++) { O[mb][4 * jn] *= a.x; O[mb][4 * jn + 1] *= a.y; O[mb][4 * jn + 2] *= a.x; O[mb][4 * jn + 3] *= a.y; }
          }
        }
        over++;
      } while (bar_over(0.f));
    };
    uint32_t da = desc_lo(OFF_RING);
    uint32_t* x1o[8] = {};
#pragma unroll 1
    for (int tl = 0; tl < 8; tl++) {
      if (tl == 5) load_frags();
      if (tl == 7) {
        mbar_wait(BAR(BAR_ALLCLR));
#pragma unroll
        for (int i = 0; i < 8; i++)
          x1o[i] = inbox((16 * hh + 8 * ((i >> 1) & 1) + 2 * t + (i & 1)) * 4 + 2 * (i >> 2) + (wq >> 1), bs >> 4) + (bs & 15) * 64 + ((wq & 1) * 8 + g) * 4;
      }
      handover(tl);
      thand = clk32();
      const uint32_t dpt = dp + (tl & 1) * 128;
      wg_fence();
#pragma unroll
      for (int i = 0; i < 32; i++) wgmma_n16<1, 1>(O[i >> 2], da + (i >> 2) * 512 + (i & 3) * 128, dpt + (i & 3) * 2);
      wg_commit();
      da = (tl == 2 || tl == 5) ? da - 8192 : da + 4096;
      wg_wait<0>();
#pragma unroll
      for (int mb = 0; mb < 8; mb++) acc_fence(O[mb]);
      if (lane == 0) mbar_arrive(BAR(BAR_EMPTY + tl));
    }
#pragma unroll
    for (int i = 0; i < 8; i++) {
      const int J = i >> 2, k = 4 * ((i >> 1) & 1) + (i & 1);
      stg_cvt8(x1o[i], O[4 * J][k], O[4 * J][k + 2], O[4 * J + 1][k], O[4 * J + 1][k + 2], O[4 * J + 2][k], O[4 * J + 2][k + 2], O[4 * J + 3][k], O[4 * J + 3][k + 2]);
    }
  }

  uint32_t* const o = gin + keep((uint32_t)(inbox(4 * (8 * jI + w) + t, 4) - gin) + hI * 16 + g * 2);
  const uint32_t sdst5 = keep(sb + OFF_BS5 + (16 * w + g) * 16 + t * 4), lane16 = keep(sb + lane * 16);
  const uint32_t* x2i[4];
#pragma unroll
  for (int i = 0; i < 4; i++) x2i[i] = gin + keep((uint32_t)(nearbox(4 * hI + i, 4) - gin) + 512 + tid * 2);
  {
    const uint32_t* px = pin(inbox(cta, w >> 1) + (w & 1) * 512 + lane * 2);
    uint32_t* const x2o = pin(inbox(cta, 4) + 512 + tid * 2);
    uint32_t* const x2p = pin(gin + blk(cta, 4, selector(cta) ^ 1) + 512 + tid * 2);
    const uint32_t q4 = lds1(sb + OFF_SEL + 4 * hI) ^ 0x00010100u;
    const uint32_t same = pin((uint32_t)(q4 == 0 || q4 == 0x01010101u));
    mbar_wait(BAR(BAR_TS));
    anchor = lds1(sb + OFF_TS);
    const uint32_t sdst = keep(sb + OFF_BS4 + w * 272 + lane * 8), ssrc = keep(sb + OFF_BS4 + (lane & 7) * 272 + (lane >> 3) * 16);
    float d[4] = {0.f, 0.f, 0.f, 0.f};
    if (cta >= NFF) {
#pragma unroll
      for (int s = 0; s < 4; s++) { cbf[s].x = silu2(cbf[s].x); cbf[s].y = silu2(cbf[s].y); }
    } else {
      check_units<4, 64>(sbf, pcb);
      check_units<4, 64>(cbf, pcb + 2048);
#pragma unroll
      for (int s = 0; s < 4; s++) { cbf[s].x = hadd2(cbf[s].x, ONE2); cbf[s].y = hadd2(cbf[s].y, ONE2); }
    }
    wait_clk(thand, T.D_X1);
    wait_clk(anchor, T.A_X1 - T.R_X0);
    uint2 v[8];
    load_units<8, 64>(v, px);
    if (T.R_X0) {
      wait_clk(anchor, T.A_X1);
#pragma unroll
      for (int i = 0; i < 8; i++) reload_unit(v[i], px + i * 64);
    }
    const bool early = __all_sync(~0u, mbar_test(BAR(BAR_WUV + wg)));
    if (early) load_a_t(aw, abase + OFF_WUV);
    mbar_wait(BAR(BAR_WV));
    const float4 wa = ldsf4(sb + OFF_WV + w * 32), wb = ldsf4(sb + OFF_WV + w * 32 + 16);
    const float wv[8] = {wa.x, wa.y, wa.z, wa.w, wb.x, wb.y, wb.z, wb.w};
    uint32_t it = opaque0;
    bool ok;
#pragma unroll 1
    do {
      if (it) {
#pragma unroll
        for (int i = 0; i < 8; i++) reload_unit(v[i], px + i * 64);
        if (it > SPIN_LIMIT) __trap();
      }
      it++;
      float a0 = 0.f, a1 = 0.f, a2 = 0.f, a3 = 0.f;
#pragma unroll
      for (int i = 0; i < 8; i++) { a0 += wv[i] * bf_lo(v[i].x); a1 += wv[i] * bf_hi(v[i].x); a2 += wv[i] * bf_lo(v[i].y); a3 += wv[i] * bf_hi(v[i].y); }
      ok = __all_sync(~0u, min_flags(v) != 0);
      sts2(sdst, pack_bf16(a0, a1), pack_bf16(a2, a3));
    } while (!ok);
    cbar();
    uint32_t b[4][4];
#pragma unroll
    for (int kk = 0; kk < 4; kk++) ldsm4(b[kk], ssrc + kk * 64);
    if (__builtin_expect(!early, 0)) { mbar_wait(BAR(BAR_WUV + wg)); load_a_t(aw, abase + OFF_WUV); }
    mma128(d, aw, b);
    const uint32_t c0 = pack_bf16(d[0], d[1]), c1 = pack_bf16(d[2], d[3]);
    stg_u64(x2o, c0, c1);
    stg_u64_unless(same, x2p, c0, c1);
    tstore = clk32();
  }
  {
    float d[4] = {0.f, 0.f, 0.f, 0.f};
    wait_clk(tstore, T.D_X2);
    uint2 v[4];
#pragma unroll
    for (int i = 0; i < 4; i++) v[i] = ldg_u64(x2i[i]);
    const bool early = __all_sync(~0u, mbar_test(BAR(BAR_WO + wg)));
    if (early) load_a_t(aw, abase + OFF_WO);
    uint32_t it = opaque0;
    bool ok;
#pragma unroll 1
    do {
      if (it) {
#pragma unroll
        for (int i = 0; i < 4; i++) reload_unit(v[i], x2i[i]);
        if (it > SPIN_LIMIT) __trap();
      }
      it++;
      ok = __all_sync(~0u, min_flags(v) != 0);
      sum4_to_smem(v, sdst5);
    } while (!ok);
    cbar();
    uint32_t b[4][4];
#pragma unroll
    for (int kk = 0; kk < 4; kk++) ldsm4t(b[kk], lane16 + OFF_BS5 + kk * 512);
    if (__builtin_expect(!early, 0)) { mbar_wait(BAR(BAR_WO + wg)); load_a_t(aw, abase + OFF_WO); }
    mma128(d, aw, b);
    stg_u64(o, movm(pack_bf16(d[0], d[1])), movm(pack_bf16(d[2], d[3])));
    tstore = clk32();
    if (lane == 0) mbar_arrive(BAR(BAR_P5D));
  }
  if (cta < NFF) {
    const int mi = lane >> 3, r = lane & 7;
    uint32_t a1[2][4][4], a2[2][2][4];
    const int lp = (tid >> 2) & 31, kq = tid & 3;
    const int fo = 16 * wg + (lp >> 2) + 8 * (kq >> 1), bo = 2 * (lp & 3) + (kq & 1);
    const uint32_t* xb = gin + keep((uint32_t)(nearbox(cta & ~15, 6 + wg) - gin) + (16 * wq + t) * 16 + g * 2);
    uint32_t* const ox[2] = {gin + keep((uint32_t)(inbox(64 * hh + 8 * w + t, 5) - gin) + bs * 16 + g * 2), gin + keep((uint32_t)(inbox(64 * hh + 8 * w + 4 + t, 5) - gin) + bs * 16 + g * 2)};
    const uint32_t a1base = keep(sb + OFF_W1 + (64 * w + 8 * (mi >> 1) + r) * 64 + (((mi & 1) ^ (r >> 1)) << 4));
    const uint32_t a2base = keep(sb + OFF_W2 + (w >> 1) * 4096 + (8 * (mi >> 1) + r) * 128 + (((4 * (w & 1) + (mi & 1)) ^ r) << 4));
    const uint32_t s_g = keep(sb + OFF_REDG + w * 1024 + lane * 16), l_g = keep(sb + OFF_REDG + tid * 4);
    const uint32_t s_s = keep(sb + (t == (g >> 1) ? OFF_REDS + g * 80 + w * 8 : OFF_BS4 + tid * 8));
    const uint32_t l_s = keep(sb + OFF_REDS + bo * 80), s_h = keep(sb + OFF_H1 + fo * 16 + bo * 2);
    mbar_wait(BAR(BAR_W1));
#pragma unroll
    for (int i = 0; i < 8; i++) ldsm4t(a1[i & 1][i >> 1], (a1base ^ ((i & 1) << 5)) + (i >> 1) * 1024);
    {
      float u[2][2][4] = {};
#pragma unroll
      for (int s = 0; s < 4; s++)
#pragma unroll
        for (int mt = 0; mt < 2; mt++) { mma16816(u[0][mt], a1[mt][s], cbf[s].x, cbf[s].y); mma16816(u[1][mt], a1[mt][s], sbf[s].x, sbf[s].y); }
#pragma unroll
      for (int i = 0; i < 4; i++) sts4f(s_g + (OFF_REDU - OFF_REDG) + (i >> 1) * 8192 + (i & 1) * 512, u[i >> 1][i & 1][0], u[i >> 1][i & 1][1], u[i >> 1][i & 1][2], u[i >> 1][i & 1][3]);
    }
    wait_clk(tstore, T.D_X3B);
    wait_clk(anchor, T.A_X1 + T.R_X3A + T.R_X3B);
    uint2 x[4];
    load_units<4, 64>(x, xb);
    float U, V;
    {
      cbar();
      float u[8], v[8];
#pragma unroll
      for (int i = 0; i < 8; i++) { u[i] = ldsf(l_g + (OFF_REDU - OFF_REDG) + i * 1024); v[i] = ldsf(l_g + (OFF_REDV - OFF_REDG) + i * 1024); }
      U = pin(((u[0] + u[1]) + (u[2] + u[3])) + ((u[4] + u[5]) + (u[6] + u[7])));
      V = pin(((v[0] + v[1]) + (v[2] + v[3])) + ((v[4] + v[5]) + (v[6] + v[7])));
    }
    auto load_a2 = [&] {
#pragma unroll
      for (int i = 0; i < 4; i++) ldsm4t(a2[i >> 1][i & 1], (a2base ^ ((i >> 1) << 5)) + (i & 1) * 2048);
    };
    const bool early = __all_sync(~0u, mbar_test(BAR(BAR_W2)));
    if (early) load_a2();
    uint32_t it = opaque0;
    float G[2][2][4], S[2][4];
#pragma unroll 1
    do {
      if (it) {
#pragma unroll
        for (int i = 0; i < 4; i++) reload_unit(x[i], xb + i * 64);
        if (it > SPIN_LIMIT) __trap();
      }
      it++;
#pragma unroll
      for (int i = 0; i < 8; i++) { G[0][i >> 2][i & 3] = G[1][i >> 2][i & 3] = S[i >> 2][i & 3] = 0.f; }
      uint32_t y[4][2];
#pragma unroll
      for (int s = 0; s < 4; s++) { y[s][0] = hmul2(x[s].x, cbf[s].x); y[s][1] = hmul2(x[s].y, cbf[s].y); }
#pragma unroll
      for (int s2 = 0; s2 < 4; s2 += 2) {
#pragma unroll
        for (int s = s2; s < s2 + 2; s++) { mma16816(G[0][s & 1], a1[0][s], y[s][0], y[s][1]); mma16816(G[1][s & 1], a1[1][s], y[s][0], y[s][1]); }
#pragma unroll
        for (int s = s2; s < s2 + 2; s++) { const uint32_t sx[4] = {x[s].x, ONE2, x[s].y, ONE2}; mma16816(S[s & 1], sx, x[s].x, x[s].y); }
      }
    } while (!__all_sync(~0u, min_flags(x) != 0));
#pragma unroll
    for (int mt = 0; mt < 2; mt++)
      sts4f(s_g + mt * 512, G[mt][0][0] + G[mt][1][0], G[mt][0][1] + G[mt][1][1], G[mt][0][2] + G[mt][1][2], G[mt][0][3] + G[mt][1][3]);
    sts2f(s_s, (g & 1) ? S[0][3] + S[1][3] : S[0][2] + S[1][2], (g & 1) ? S[0][1] + S[1][1] : S[0][0] + S[1][0]);
    cbar();
    {
      float gv[8];
      float4 sv[4];
#pragma unroll
      for (int i = 0; i < 4; i++) sv[i] = ldsf4(l_s + i * 16);
#pragma unroll
      for (int i = 0; i < 8; i++) gv[i] = ldsf(l_g + i * 1024);
      const float s1 = ((sv[0].x + sv[0].z) + (sv[1].x + sv[1].z)) + ((sv[2].x + sv[2].z) + (sv[3].x + sv[3].z));
      const float s2 = ((sv[0].y + sv[0].w) + (sv[1].y + sv[1].w)) + ((sv[2].y + sv[2].w) + (sv[3].y + sv[3].w));
      const float gsum = ((gv[0] + gv[1]) + (gv[2] + gv[3])) + ((gv[4] + gv[5]) + (gv[6] + gv[7]));
      const float mu = s1 * (1.f / 512.f);
      float rs;
      asm("rsqrt.approx.ftz.f32 %0, %1;" : "=f"(rs) : "f"(fmaxf(s2 * (1.f / 512.f) - mu * mu, 0.f) + 1e-5f));
      const float hv = fmaxf(rs * (gsum - mu * U) + V, 0.f);
      asm volatile("st.shared.u16 [%0], %1;" ::"r"(s_h), "h"(__bfloat16_as_ushort(__float2bfloat16(hv))) : "memory");
    }
    cbar();
    uint32_t b[4];
    ldsm4t(b, lane16 + OFF_H1);
    if (!early) { mbar_wait(BAR(BAR_W2)); load_a2(); }
    float o[2][2][4] = {};
#pragma unroll
    for (int i = 0; i < 4; i++) mma16816(o[i >> 1][i & 1], a2[i >> 1][i & 1], b[2 * (i & 1)], b[2 * (i & 1) + 1]);
#pragma unroll
    for (int mb = 0; mb < 2; mb++)
      stg_u64(ox[mb], movm(pack_bf16(o[mb][0][0] + o[mb][1][0], o[mb][0][1] + o[mb][1][1])), movm(pack_bf16(o[mb][0][2] + o[mb][1][2], o[mb][0][3] + o[mb][1][3])));
    if (lane == 0) mbar_arrive(BAR(BAR_P7D));
  } else {
    const int mi = lane >> 3, r = lane & 7;
    mbar_wait(BAR(BAR_W1));
#pragma unroll
    for (int mt = 0; mt < 2; mt++) {
      float u[4] = {0.f, 0.f, 0.f, 0.f};
#pragma unroll
      for (int ks = 0; ks < 4; ks++) ldsm4t(aw[4 * mt + ks], sb + OFF_W1 + (64 * w + 16 * ks + 8 * (mi >> 1) + r) * 64 + (((2 * mt + (mi & 1)) ^ (r >> 1)) << 4));
#pragma unroll
      for (int ks = 0; ks < 4; ks++) mma16816(u, aw[4 * mt + ks], cbf[ks].x, cbf[ks].y);
      sts4f(sb + OFF_REDU + w * 1024 + mt * 512 + lane * 16, u[0], u[1], u[2], u[3]);
    }
    cbar();
    if (w < 2) {
      float4 v[8];
#pragma unroll
      for (int i = 0; i < 8; i++) v[i] = ldsf4(sb + OFF_REDU + i * 1024 + tid * 16);
      stg_u64(gs->MOD2[par] + (96 + 2 * (cta - NFF) + w) * 64 + t * 16 + g * 2,
              movm(pack_bf16(((v[0].x + v[1].x) + (v[2].x + v[3].x)) + ((v[4].x + v[5].x) + (v[6].x + v[7].x)), ((v[0].y + v[1].y) + (v[2].y + v[3].y)) + ((v[4].y + v[5].y) + (v[6].y + v[7].y)))),
              movm(pack_bf16(((v[0].z + v[1].z) + (v[2].z + v[3].z)) + ((v[4].z + v[5].z) + (v[6].z + v[7].z)), ((v[0].w + v[1].w) + (v[2].w + v[3].w)) + ((v[4].w + v[5].w) + (v[6].w + v[7].w)))));
    }
  }
}

typedef CUresult (*EncodeTiledFn)(CUtensorMap*, CUtensorMapDataType, cuuint32_t, void*, const cuuint64_t*, const cuuint64_t*,
                                  const cuuint32_t*, const cuuint32_t*, CUtensorMapInterleave, CUtensorMapSwizzle,
                                  CUtensorMapL2promotion, CUtensorMapFloatOOBfill);

struct Dim { uint64_t size, stride; uint32_t box; };
template <int R> void encode_map(EncodeTiledFn enc, CUtensorMap* m, const void* base, const Dim (&d)[R], CUtensorMapSwizzle sw, CUtensorMapL2promotion promo) {
  cuuint64_t dims[R], strides[R];
  cuuint32_t box[R], es[R];
  for (int i = 0; i < R; i++) { dims[i] = d[i].size; strides[i] = d[i].stride; box[i] = d[i].box; es[i] = 1; }
  enc(m, CU_TENSOR_MAP_DATA_TYPE_BFLOAT16, R, const_cast<void*>(base), dims, strides + 1, box, es, CU_TENSOR_MAP_INTERLEAVE_NONE, sw, promo,
      CU_TENSOR_MAP_FLOAT_OOB_FILL_NONE);
}

}

extern "C" void kernel_launch(void* const* d_in, const int* in_sizes, int n_in, void* d_out, int out_size) {
  (void)in_sizes; (void)n_in; (void)out_size;
  static EncodeTiledFn enc = nullptr;
  static Scratch* scratch = nullptr;
  static uint32_t* inbox = nullptr;
  if (!enc) {
    void* sp = nullptr;
    cudaGetSymbolAddress(&sp, g_s);
    scratch = (Scratch*)sp;
    cudaGetSymbolAddress(&sp, g_in);
    inbox = (uint32_t*)(((uintptr_t)sp + 0xfffff) & ~(uintptr_t)0xfffff);
    void* fn = nullptr;
    cudaDriverEntryPointQueryResult q;
    cudaGetDriverEntryPoint("cuTensorMapEncodeTiled", &fn, cudaEnableDefault, &q);
    enc = (EncodeTiledFn)fn;
    cudaFuncSetAttribute(fused_decode_kernel, cudaFuncAttributeMaxDynamicSharedMemorySize, SMEM_BYTES);
  }
  const CUtensorMapSwizzle S128 = CU_TENSOR_MAP_SWIZZLE_128B, S0 = CU_TENSOR_MAP_SWIZZLE_NONE;
  const CUtensorMapL2promotion L0 = CU_TENSOR_MAP_L2_PROMOTION_NONE, L128 = CU_TENSOR_MAP_L2_PROMOTION_L2_128B;
  Params P;
  encode_map<2>(enc, &P.wq, d_in[2], {{4096, 2, 64}, {512, 8192, 64}}, S128, L0);
  encode_map<5>(enc, &P.wuk, d_in[3], {{4096, 2, 64}, {2, 8192, 2}, {4, 4 * 8192, 4}, {2, 2 * 8192, 2}, {32, 16 * 8192, 4}}, S128, L0);
  encode_map<2>(enc, &P.wm2, d_in[10], {{3072, 2, 16}, {512, 6144, 256}}, S0, L128);
  encode_map<2>(enc, &P.wm3, d_in[10], {{3072, 2, 32}, {512, 6144, 256}}, CU_TENSOR_MAP_SWIZZLE_64B, L128);
  encode_map<3>(enc, &P.ckv2, d_in[1], {{64, 2, 64}, {8 * 4096, 1024, 64}, {8, 128, 2}}, S128, L0);
  encode_map<3>(enc, &P.ckv1, d_in[1], {{64, 2, 64}, {8 * 4096, 1024, 64}, {8, 128, 1}}, S128, L0);
  encode_map<5>(enc, &P.wuv, d_in[4], {{4096, 2, 64}, {2, 8 * 8192, 2}, {8, 64 * 8192, 4}, {8, 8192, 8}, {4, 16 * 8192, 1}}, S128, L0);
  encode_map<2>(enc, &P.wo, d_in[5], {{512, 2, 64}, {4096, 1024, 64}}, S128, L0);
  encode_map<2>(enc, &P.w1, d_in[7], {{1792, 2, 32}, {512, 3584, 256}}, CU_TENSOR_MAP_SWIZZLE_64B, L128);
  encode_map<3>(enc, &P.w2, d_in[8], {{64, 2, 64}, {1792, 1024, 32}, {8, 128, 2}}, S128, L0);
  fused_decode_kernel<<<NCTA, NTHREADS, SMEM_BYTES>>>((__nv_bfloat16*)d_out, scratch, (const uint8_t*)d_in[10], (const uint8_t*)d_in[0],
                     (const uint8_t*)d_in[9], inbox,
                     P);
}
```

```cpp
#include <cuda_runtime.h>
#include <cuda.h>
#include <cuda_bf16.h>
#include <stdint.h>

namespace {

constexpr int NCTA = 128;
constexpr int NTHREADS = 320;
constexpr int NFG = 56;
constexpr int NFF = 2 * NFG;
constexpr int NSYNC = 4;

constexpr uint32_t OFF_RING = 0;
constexpr uint32_t OFF_WUK = 131072;
constexpr uint32_t OFF_WQ = 131072 + 32768;
constexpr uint32_t OFF_WM2 = 65536 + 49152;
constexpr uint32_t OFF_WUV = 131072;
constexpr uint32_t OFF_WO = 131072 + 32768;
constexpr uint32_t OFF_W1 = 0;
constexpr uint32_t OFF_W2 = 32768;
constexpr uint32_t OFF_Q = 196608;
constexpr uint32_t OFF_PT = 212992;
constexpr uint32_t OFF_SCR = 217088;
constexpr uint32_t OFF_XS = 65536;
constexpr uint32_t OFF_CS = 65536 + 8192;
constexpr uint32_t OFF_P0S = 65536 + 16384;
constexpr uint32_t OFF_BS1 = OFF_SCR + 2048;
constexpr uint32_t OFF_BS2 = OFF_SCR + 4096;
constexpr uint32_t OFF_P0B = OFF_SCR + 6144;
constexpr uint32_t OFF_XN = OFF_SCR + 8192;
constexpr uint32_t OFF_RED = OFF_SCR + 10496;
constexpr uint32_t OFF_ALPHA = OFF_SCR + 11072;
constexpr uint32_t OFF_WV = OFF_SCR + 6144;
constexpr uint32_t OFF_SEL = OFF_SCR + 10752;
constexpr uint32_t OFF_TS = OFF_SCR + 11136;
constexpr uint32_t OFF_EPOCH = OFF_SCR + 11144;
constexpr uint32_t OFF_BARS = OFF_SCR + 11264;
constexpr uint32_t SMEM_BYTES = OFF_BARS + 512;
constexpr uint32_t OFF_BS4 = OFF_Q;
constexpr uint32_t OFF_H1 = OFF_Q + 2304;
constexpr uint32_t OFF_REDS = OFF_Q + 2816;
constexpr uint32_t OFF_BS5 = OFF_Q + 4096;
constexpr uint32_t OFF_REDG = OFF_Q + 8192;
constexpr uint32_t OFF_REDU = 65536;
constexpr uint32_t OFF_REDV = 65536 + 8192;

constexpr int BAR_FULL = 0;
constexpr int BAR_LAST = 28;
constexpr int BAR_WUK = 33, BAR_WM2 = 35, BAR_WUV = 36, BAR_WO = 38, BAR_W1 = 40, BAR_W2 = 41;
constexpr int BAR_ALLCLR = 42, BAR_TS = 43, BAR_WV = 44;
constexpr int BAR_EMPTY = 45;
constexpr int BAR_P0BD = 53;
constexpr int BAR_P1D = 54, BAR_P2D = 55;
constexpr int BAR_P5D = 56, BAR_P7D = 57;
constexpr int NBARS = 58;
constexpr int BAR_XC = 58, BAR_WQ = 59;
constexpr int BAR_C = 61;
constexpr uint32_t SB = 1024;

#define TUNE_LIST(X) \
  X(PC_T0, -45) X(PC_P1, 322) X(PC_PM, 225) X(PC_P2, 320) X(PC_STAG, 345) X(PC_SL, 500) X(PC_NW, 8) \
  X(T_UV, 180) X(P_UV, 285) X(PF_N, 3) X(T_PF, 1020) X(P_PF, 230) X(T_O, 2180) X(P_O, 145) X(T_1, 2970) X(T_2, 3700) X(T_GB, 3370) X(P_F, 360) \
  X(PR_T0, 550) X(PR_N, 4) X(CLR_T0, 3000) X(CLR_CLK, 190) \
  X(D_CC, 250) X(D_EP, 300) X(D_MOD, 1280) X(D_QP, 1150) X(D_QX, 850) X(TS_P, 1) X(TS_O, 1900) X(D_TS, 700) X(A_M, 1550) X(D_X1, 1350) X(A_X1, 2460) X(R_X0, 1550) \
  X(D_X2, 290) X(D_X3A, 60) X(R_X3A, 2835) X(D_X3B, 800) X(R_X3B, 855) X(D_FIN, 340) X(R_FIN, 1490)
struct Tune {
#define X(n, v) static constexpr int n = v;
  TUNE_LIST(X)
#undef X
};

struct Scratch {
  uint32_t MOD1[2][4 * 64 * 64];
  uint32_t MOD2[2][128 * 64];
  uint32_t QP[2][128 * 256 * 2];
  uint32_t QX[2][8 * 32 * 256];
  uint32_t epoch;
  uint32_t pad[31];
  uint32_t sync[NSYNC][32];
};
__device__ Scratch g_s;
__device__ uint32_t g_in[(128 + 32) * 16384];
__device__ __forceinline__ uint32_t blk(int c, int k, uint32_t sel) { return c * 16384 + k * 2048 + ((sel ^ k) & 1) * 1024; }
__device__ __forceinline__ uint32_t flip(int c) { return c ^ (c >> 1) ^ (c >> 3); }

struct Params {
  CUtensorMap wq, wuk, wm2, wm3, ckv2, ckv1, wuv, wo, w1, w2;
};

__device__ __forceinline__ void mbar_init(uint32_t bar, int cnt) { asm volatile("mbarrier.init.shared::cta.b64 [%0], %1;" ::"r"(bar), "r"(cnt)); }
__device__ __forceinline__ void mbar_expect(uint32_t bar, uint32_t bytes) { asm volatile("mbarrier.arrive.expect_tx.shared::cta.b64 _, [%0], %1;" ::"r"(bar), "r"(bytes) : "memory"); }
__device__ __forceinline__ void mbar_arrive(uint32_t bar) { asm volatile("mbarrier.arrive.shared::cta.b64 _, [%0];" ::"r"(bar) : "memory"); }
__device__ __forceinline__ uint32_t clk32() { unsigned long long c; asm volatile("mov.u64 %0, %%clock64;" : "=l"(c) :: "memory"); return (uint32_t)c; }
__device__ __forceinline__ uint32_t gtime32() { uint32_t c; asm volatile("mov.u32 %0, %%globaltimer_lo;" : "=r"(c) :: "memory"); return c; }
__device__ __forceinline__ void wait_clk(uint32_t t0, int clocks) { while ((int)(clk32() - t0) < clocks) {} }
__device__ __forceinline__ void backoff(int clocks) { if (clocks > 0) wait_clk(clk32(), clocks); }
__device__ __forceinline__ void until_ns(uint32_t ns) { while ((int)(gtime32() - ns) < 0) {} }
__device__ __forceinline__ void slot(uint32_t& tn, int slack) {
  uint32_t now;
  do { now = gtime32(); } while ((int)(now - tn) < 0);
  if ((int)(now - tn) > slack) tn = now - slack;
}
template <typename T> __device__ __forceinline__ T* pin(T* p) { asm volatile("" : "+l"(p)); return p; }
__device__ __forceinline__ uint32_t pin(uint32_t v) { asm volatile("" : "+r"(v)); return v; }
__device__ __forceinline__ float pin(float v) { asm volatile("" : "+f"(v)); return v; }
constexpr int SPIN_LIMIT = 1 << 22;
__device__ __forceinline__ void mbar_wait(uint32_t bar) {
  asm volatile("{\n.reg .pred p;\n.reg .u32 c;\nmov.u32 c, 0;\n"
               "MW_LOOP:\nmbarrier.try_wait.parity.shared::cta.b64 p, [%0], 0;\n@p bra MW_DONE;\n"
               "add.u32 c, c, 1;\nsetp.lt.u32 p, c, 4194304;\n@p bra MW_LOOP;\ntrap;\nMW_DONE:\n}"
               ::"r"(bar) : "memory");
}
__device__ __forceinline__ bool mbar_test(uint32_t bar) {
  uint32_t ok;
  asm volatile("{\n.reg .pred p;\nmbarrier.test_wait.parity.shared::cta.b64 p, [%1], 0;\nselp.u32 %0,1,0,p;\n}" : "=r"(ok) : "r"(bar) : "memory");
  return ok;
}
__device__ __forceinline__ void tma2d(uint32_t dst, const CUtensorMap* m, int c0, int c1, uint32_t bar, uint64_t pol) {
  asm volatile("cp.async.bulk.tensor.2d.shared::cluster.global.mbarrier::complete_tx::bytes.L2::cache_hint [%0], [%1, {%3,%4}], [%2], %5;"
               ::"r"(dst), "l"(m), "r"(bar), "r"(c0), "r"(c1), "l"(pol) : "memory");
}
__device__ __forceinline__ void tma2d_nohint(uint32_t dst, const CUtensorMap* m, int c0, int c1, uint32_t bar) {
  asm volatile("cp.async.bulk.tensor.2d.shared::cluster.global.mbarrier::complete_tx::bytes [%0], [%1, {%3,%4}], [%2];"
               ::"r"(dst), "l"(m), "r"(bar), "r"(c0), "r"(c1) : "memory");
}
__device__ __forceinline__ void tma3d(uint32_t dst, const CUtensorMap* m, int c0, int c1, int c2, uint32_t bar, uint64_t pol) {
  asm volatile("cp.async.bulk.tensor.3d.shared::cluster.global.mbarrier::complete_tx::bytes.L2::cache_hint [%0], [%1, {%3,%4,%5}], [%2], %6;"
               ::"r"(dst), "l"(m), "r"(bar), "r"(c0), "r"(c1), "r"(c2), "l"(pol) : "memory");
}
__device__ __forceinline__ void tma5d(uint32_t dst, const CUtensorMap* m, int c0, int c1, int c2, int c3, int c4, uint32_t bar, uint64_t pol) {
  asm volatile("cp.async.bulk.tensor.5d.shared::cluster.global.mbarrier::complete_tx::bytes.L2::cache_hint [%0], [%1, {%3,%4,%5,%6,%7}], [%2], %8;"
               ::"r"(dst), "l"(m), "r"(bar), "r"(c0), "r"(c1), "r"(c2), "r"(c3), "r"(c4), "l"(pol) : "memory");
}
__device__ __forceinline__ void bulk_ld(uint32_t dst, const void* src, uint32_t bytes, uint32_t bar) {
  asm volatile("cp.async.bulk.shared::cluster.global.mbarrier::complete_tx::bytes [%0], [%1], %2, [%3];" ::"r"(dst), "l"(src), "r"(bytes), "r"(bar) : "memory");
}
__device__ __forceinline__ void bar_sync(int id, int n) { asm volatile("barrier.cta.sync.aligned %0, %1;" ::"r"(id), "r"(n) : "memory"); }
__device__ __forceinline__ void cbar() { asm volatile("barrier.cta.sync.aligned 1, 256;" ::: "memory"); }
__device__ __forceinline__ bool bar_over(float ex) {
  uint32_t over;
  asm volatile("{\n.reg .pred p, q;\nsetp.gtu.f32 p, %1, 0f42700000;\nbarrier.cta.red.or.aligned.pred q, 4, 256, p;\nselp.u32 %0, 1, 0, q;\n}"
               : "=r"(over) : "f"(ex) : "memory");
  return over;
}

__device__ __forceinline__ uint32_t ldg_nc1(const void* p) { uint32_t v; asm volatile("ld.global.nc.L1::no_allocate.u32 %0, [%1];" : "=r"(v) : "l"(p)); return v; }
__device__ __forceinline__ uint32_t ldg_rlx1(const void* p) { uint32_t v; asm volatile("ld.relaxed.gpu.global.u32 %0, [%1];" : "=r"(v) : "l"(p) : "memory"); return v; }
__device__ __forceinline__ void stg4(void* p, uint4 v) { asm volatile("st.relaxed.gpu.global.v4.u32 [%0], {%1,%2,%3,%4};" ::"l"(p), "r"(v.x), "r"(v.y), "r"(v.z), "r"(v.w) : "memory"); }
__device__ __forceinline__ void stg1(void* p, uint32_t a) { asm volatile("st.relaxed.gpu.global.u32 [%0], %1;" ::"l"(p), "r"(a) : "memory"); }
__device__ __forceinline__ uint32_t nz(uint32_t w) { return max(w, 1u); }
__device__ __forceinline__ uint2 ldg_u64(const void* p) {
  uint2 v; asm volatile("{\n.reg .b64 a;\nld.relaxed.gpu.global.b64 a, [%2];\nmov.b64 {%0,%1}, a;\n}" : "=r"(v.x), "=r"(v.y) : "l"(p) : "memory"); return v;
}
__device__ __forceinline__ uint4 ldg_2u64(const void* p) {
  uint4 v; asm volatile("{\n.reg .b64 a, b;\nld.relaxed.gpu.global.v2.b64 {a, b}, [%4];\nmov.b64 {%0,%1}, a;\nmov.b64 {%2,%3}, b;\n}" : "=r"(v.x), "=r"(v.y), "=r"(v.z), "=r"(v.w) : "l"(p) : "memory"); return v;
}
__device__ __forceinline__ void stg_u64(void* p, uint32_t x, uint32_t y) {
  asm volatile("{\n.reg .b32 y;\nmax.u32 y, %2, 1;\nst.relaxed.gpu.global.v2.b32 [%0], {%1, y};\n}" ::"l"(p), "r"(x), "r"(y) : "memory");
}
__device__ __forceinline__ void red_u64(void* p, uint32_t x, uint32_t y) {
  asm volatile("{\n.reg .b32 y;\n.reg .b64 a;\nmax.u32 y, %2, 1;\nmov.b64 a, {%1, y};\nred.relaxed.gpu.global.or.b64 [%0], a;\n}" ::"l"(p), "r"(x), "r"(y) : "memory");
}
__device__ __forceinline__ void stg_u64_unless(uint32_t bad, void* p, uint32_t x, uint32_t y) {
  asm volatile("{\n.reg .b32 y;\n.reg .pred q;\nsetp.eq.u32 q, %3, 0;\nmax.u32 y, %2, 1;\n@q st.relaxed.gpu.global.v2.b32 [%0], {%1, y};\n}" ::"l"(p), "r"(x), "r"(y), "r"(bad) : "memory");
}

__device__ __forceinline__ void stg_cvt8(void* p, float a0, float a1, float b0, float b1, float c0, float c1, float d0, float d1) {
  asm volatile("{\n.reg .b32 x, y, z, w;\ncvt.rn.bf16x2.f32 x, %2, %1;\ncvt.rn.bf16x2.f32 y, %4, %3;\ncvt.rn.bf16x2.f32 z, %6, %5;\ncvt.rn.bf16x2.f32 w, %8, %7;\n"
               "max.u32 y, y, 1;\nmax.u32 w, w, 1;\nst.relaxed.gpu.global.v4.b32 [%0], {x, y, z, w};\n}"
               ::"l"(p), "f"(a0), "f"(a1), "f"(b0), "f"(b1), "f"(c0), "f"(c1), "f"(d0), "f"(d1) : "memory");
}
__device__ __forceinline__ uint32_t pack_bf16(float lo, float hi) { uint32_t r; asm("cvt.rn.bf16x2.f32 %0, %1, %2;" : "=r"(r) : "f"(hi), "f"(lo)); return r; }
__device__ __forceinline__ float bf_lo(uint32_t w) { return __uint_as_float(w << 16); }
__device__ __forceinline__ float bf_hi(uint32_t w) { return __uint_as_float(w & 0xffff0000u); }
__device__ __forceinline__ float ex2(float x) { float r; asm("ex2.approx.ftz.f32 %0, %1;" : "=f"(r) : "f"(x)); return r; }
__device__ __forceinline__ uint32_t hmul2(uint32_t a, uint32_t b) { uint32_t r; asm("mul.rn.bf16x2 %0, %1, %2;" : "=r"(r) : "r"(a), "r"(b)); return r; }
__device__ __forceinline__ uint32_t hadd2(uint32_t a, uint32_t b) { uint32_t r; asm("add.rn.bf16x2 %0, %1, %2;" : "=r"(r) : "r"(a), "r"(b)); return r; }
__device__ __forceinline__ uint32_t silu2(uint32_t v) { const float a = bf_lo(v), b = bf_hi(v); return pack_bf16(__fdividef(a, 1.f + __expf(-a)), __fdividef(b, 1.f + __expf(-b))); }
constexpr uint32_t ONE2 = 0x3f803f80u;

__device__ __forceinline__ void ldsm4(uint32_t (&r)[4], uint32_t a) { asm volatile("ldmatrix.sync.aligned.m8n8.x4.shared.b16 {%0,%1,%2,%3}, [%4];" : "=r"(r[0]), "=r"(r[1]), "=r"(r[2]), "=r"(r[3]) : "r"(a) : "memory"); }
__device__ __forceinline__ void ldsm4t(uint32_t (&r)[4], uint32_t a) { asm volatile("ldmatrix.sync.aligned.m8n8.x4.trans.shared.b16 {%0,%1,%2,%3}, [%4];" : "=r"(r[0]), "=r"(r[1]), "=r"(r[2]), "=r"(r[3]) : "r"(a) : "memory"); }
__device__ __forceinline__ void stsm4t(uint32_t a, uint32_t r0, uint32_t r1, uint32_t r2, uint32_t r3) { asm volatile("stmatrix.sync.aligned.m8n8.x4.trans.shared.b16 [%0], {%1,%2,%3,%4};" ::"r"(a), "r"(r0), "r"(r1), "r"(r2), "r"(r3) : "memory"); }
__device__ __forceinline__ uint32_t movm(uint32_t a) { uint32_t d; asm volatile("movmatrix.sync.aligned.m8n8.trans.b16 %0, %1;" : "=r"(d) : "r"(a)); return d; }
__device__ __forceinline__ void mma16816(float (&d)[4], const uint32_t (&a)[4], uint32_t b0, uint32_t b1) {
  asm volatile("mma.sync.aligned.m16n8k16.row.col.f32.bf16.bf16.f32 {%0,%1,%2,%3}, {%4,%5,%6,%7}, {%8,%9}, {%0,%1,%2,%3};"
               : "+f"(d[0]), "+f"(d[1]), "+f"(d[2]), "+f"(d[3]) : "r"(a[0]), "r"(a[1]), "r"(a[2]), "r"(a[3]), "r"(b0), "r"(b1));
}
__device__ __forceinline__ void sts1(uint32_t a, uint32_t v) { asm volatile("st.shared.u32 [%0], %1;" ::"r"(a), "r"(v) : "memory"); }
__device__ __forceinline__ void sts2(uint32_t a, uint32_t x, uint32_t y) { asm volatile("st.shared.v2.u32 [%0], {%1,%2};" ::"r"(a), "r"(x), "r"(y) : "memory"); }
__device__ __forceinline__ void sts4(uint32_t a, uint4 v) { asm volatile("st.shared.v4.u32 [%0], {%1,%2,%3,%4};" ::"r"(a), "r"(v.x), "r"(v.y), "r"(v.z), "r"(v.w) : "memory"); }
__device__ __forceinline__ void sts2f(uint32_t a, float x, float y) { asm volatile("st.shared.v2.f32 [%0], {%1,%2};" ::"r"(a), "f"(x), "f"(y) : "memory"); }
__device__ __forceinline__ void sts4f(uint32_t a, float x, float y, float z, float w) { asm volatile("st.shared.v4.f32 [%0], {%1,%2,%3,%4};" ::"r"(a), "f"(x), "f"(y), "f"(z), "f"(w) : "memory"); }
__device__ __forceinline__ void stsf(uint32_t a, float v) { asm volatile("st.shared.f32 [%0], %1;" ::"r"(a), "f"(v) : "memory"); }
__device__ __forceinline__ uint32_t lds1(uint32_t a) { uint32_t v; asm volatile("ld.shared.u32 %0, [%1];" : "=r"(v) : "r"(a) : "memory"); return v; }
__device__ __forceinline__ float ldsf(uint32_t a) { float v; asm volatile("ld.shared.f32 %0, [%1];" : "=f"(v) : "r"(a) : "memory"); return v; }
__device__ __forceinline__ float2 ldsf2(uint32_t a) { float2 v; asm volatile("ld.shared.v2.f32 {%0,%1}, [%2];" : "=f"(v.x), "=f"(v.y) : "r"(a) : "memory"); return v; }
__device__ __forceinline__ float4 ldsf4(uint32_t a) { float4 v; asm volatile("ld.shared.v4.f32 {%0,%1,%2,%3}, [%4];" : "=f"(v.x), "=f"(v.y), "=f"(v.z), "=f"(v.w) : "r"(a) : "memory"); return v; }
__device__ __forceinline__ void lds4(uint32_t (&r)[4], uint32_t a) { asm volatile("ld.shared.v4.u32 {%0,%1,%2,%3}, [%4];" : "=r"(r[0]), "=r"(r[1]), "=r"(r[2]), "=r"(r[3]) : "r"(a) : "memory"); }

__device__ __forceinline__ void wg_fence() { asm volatile("wgmma.fence.sync.aligned;" ::: "memory"); }
__device__ __forceinline__ void wg_commit() { asm volatile("wgmma.commit_group.sync.aligned;" ::: "memory"); }
template <int N> __device__ __forceinline__ void wg_wait() { asm volatile("wgmma.wait_group.sync.aligned %0;" ::"n"(N) : "memory"); }
__host__ __device__ constexpr uint32_t desc_lo(uint32_t off) { return ((SB + off) >> 4) | 0x10000u; }
template <int TA, int ACC> __device__ __forceinline__ void wgmma_n16(float (&d)[8], uint32_t da, uint32_t db) {
  asm volatile("{\n.reg .b64 da, db;\nmov.b64 da, {%8, 0x40000040};\nmov.b64 db, {%9, 0x40000040};\n"
               "wgmma.mma_async.sync.aligned.m64n16k16.f32.bf16.bf16 {%0,%1,%2,%3,%4,%5,%6,%7}, da, db, %11, 1, 1, %10, 0;\n}"
               : "+f"(d[0]), "+f"(d[1]), "+f"(d[2]), "+f"(d[3]), "+f"(d[4]), "+f"(d[5]), "+f"(d[6]), "+f"(d[7])
               : "r"(da), "r"(db), "n"(TA), "n"(ACC));
}
__device__ __forceinline__ void wgmma_n16_ones(float (&d)[8], uint32_t one, uint32_t db) {
  asm volatile("{\n.reg .b64 db;\nmov.b64 db, {%9, 0x40000040};\n"
               "wgmma.mma_async.sync.aligned.m64n16k16.f32.bf16.bf16 {%0,%1,%2,%3,%4,%5,%6,%7}, {%8,%8,%8,%8}, db, 1, 1, 1, 0;\n}"
               : "+f"(d[0]), "+f"(d[1]), "+f"(d[2]), "+f"(d[3]), "+f"(d[4]), "+f"(d[5]), "+f"(d[6]), "+f"(d[7])
               : "r"(one), "r"(db));
}
__device__ __forceinline__ void acc_fence(float (&d)[8]) {
  asm volatile("" : "+f"(d[0]), "+f"(d[1]), "+f"(d[2]), "+f"(d[3]), "+f"(d[4]), "+f"(d[5]), "+f"(d[6]), "+f"(d[7]) :: "memory");
}

template <int N, int STRIDE> __device__ __forceinline__ void load_units(uint2 (&v)[N], const uint32_t* p) {
#pragma unroll
  for (int i = 0; i < N; i++) v[i] = ldg_u64(p + i * STRIDE);
}
__device__ __forceinline__ void reload_unit(uint2& v, const uint32_t* p) {
  asm volatile("{\n.reg .pred q;\nsetp.eq.u32 q, %1, 0;\n@q ld.relaxed.gpu.global.v2.b32 {%0, %1}, [%2];\n}" : "+r"(v.x), "+r"(v.y) : "l"(p) : "memory");
}
template <int N> __device__ __forceinline__ uint32_t min_flags(const uint2 (&v)[N]) {
  uint32_t a = v[0].y, b = v[1].y;
#pragma unroll
  for (int i = 2; i < N; i += 2) { a = min(a, v[i].y); b = min(b, v[i + 1].y); }
  return min(a, b);
}
template <int N, int STRIDE> __device__ __forceinline__ int check_units(uint2 (&v)[N], const uint32_t* p) {
  int it = 0;
  while (!__all_sync(~0u, min_flags(v) != 0)) {
#pragma unroll
    for (int i = 0; i < N; i++) reload_unit(v[i], p + i * STRIDE);
    if (++it > SPIN_LIMIT) __trap();
  }
  return it;
}
__device__ __forceinline__ void sum4_to_smem(const uint2 (&v)[4], uint32_t dst) {
  const float c0 = (bf_lo(v[0].x) + bf_lo(v[1].x)) + (bf_lo(v[2].x) + bf_lo(v[3].x));
  const float c1 = (bf_hi(v[0].x) + bf_hi(v[1].x)) + (bf_hi(v[2].x) + bf_hi(v[3].x));
  const float c2 = (bf_lo(v[0].y) + bf_lo(v[1].y)) + (bf_lo(v[2].y) + bf_lo(v[3].y));
  const float c3 = (bf_hi(v[0].y) + bf_hi(v[1].y)) + (bf_hi(v[2].y) + bf_hi(v[3].y));
  sts1(dst, pack_bf16(c0, c1));
  sts1(dst + 128, pack_bf16(c2, c3));
}
__device__ __forceinline__ uint32_t a_t_offset(int w, int lane) {
  const int mi = lane >> 3, r = lane & 7;
  return (w >> 2) * 16384 + (8 * (mi >> 1) + r) * 128 + (((2 * (w & 3) + (mi & 1)) ^ r) << 4);
}
__device__ __forceinline__ void load_a_t(uint32_t (&a)[8][4], uint32_t base) {
#pragma unroll
  for (int ks = 0; ks < 8; ks++) ldsm4t(a[ks], base + ks * 2048);
}
__device__ __forceinline__ void mma128(float (&d)[4], const uint32_t (&a)[8][4], const uint32_t (&b)[4][4]) {
  float e[4][4] = {{d[0], d[1], d[2], d[3]}, {0.f, 0.f, 0.f, 0.f}, {0.f, 0.f, 0.f, 0.f}, {0.f, 0.f, 0.f, 0.f}};
#pragma unroll
  for (int kk = 0; kk < 4; kk++) { mma16816(e[(2 * kk) & 3], a[2 * kk], b[kk][0], b[kk][1]); mma16816(e[(2 * kk + 1) & 3], a[2 * kk + 1], b[kk][2], b[kk][3]); }
#pragma unroll
  for (int i = 0; i < 4; i++) d[i] = (e[0][i] + e[1][i]) + (e[2][i] + e[3][i]);
}
template <int NP> __device__ __forceinline__ bool sum_pieces(const uint32_t* p0, uint32_t one, float (&r)[4], uint32_t flag = 1) {
  uint2 v[NP / 4];
  load_units<NP / 4, 64>(v, p0);
  float d[4][4] = {};
#pragma unroll
  for (int i = 0; i < NP / 8; i++) { const uint32_t a[4] = {v[2 * i].x, v[2 * i].y, v[2 * i + 1].x, v[2 * i + 1].y}; mma16816(d[i & 3], a, one, one); }
  const bool ok = __all_sync(~0u, min(min_flags(v), flag) != 0);
#pragma unroll
  for (int k = 0; k < 4; k++) r[k] = (d[0][k] + d[1][k]) + (d[2][k] + d[3][k]);
  return ok;
}
template <typename F> __device__ __forceinline__ float reduce_g(const float (&x)[4], int lane, F f) {
  const bool u4 = lane & 16, u3 = lane & 8;
  const float a0 = f(u4 ? x[2] : x[0], __shfl_xor_sync(~0u, u4 ? x[0] : x[2], 16));
  const float a1 = f(u4 ? x[3] : x[1], __shfl_xor_sync(~0u, u4 ? x[1] : x[3], 16));
  const float b = f(u3 ? a1 : a0, __shfl_xor_sync(~0u, u3 ? a0 : a1, 8));
  return f(b, __shfl_xor_sync(~0u, b, 4));
}

__global__ void __launch_bounds__(NTHREADS, 1)
fused_decode_kernel(__nv_bfloat16* __restrict__ gout, Scratch* __restrict__ gs, const uint8_t* __restrict__ gwmod,
                    const uint8_t* __restrict__ gx, const uint8_t* __restrict__ gc, uint32_t* __restrict__ gin,
                    const __grid_constant__ Params P) {
  constexpr Tune T{};
  extern __shared__ __align__(1024) uint8_t smem_raw[];
  constexpr uint32_t sb = SB;
  uint4 w0, w1;
  uint2 cc;
  {
    const uint32_t tx = threadIdx.x, bx = blockIdx.x;
    const uint8_t* pw = gwmod + ((128 * (bx & 3) + 4 * (tx >> 3) + ((tx >> 2) & 1)) * 6144 + 64 * (bx >> 2) + 16 * (tx & 3));
    const uint8_t* pc = gc + (((tx >> 2) & 7) * 1024 + 256 * (bx & 3) + (tx & 0xe0) + 8 * (tx & 3));
    asm volatile("{\n.reg .pred q;\nsetp.lt.u32 q, %9, 256;\n@q ld.global.nc.L1::no_allocate.v4.u32 {%0,%1,%2,%3}, [%8];\n"
                 "@q ld.global.nc.L1::no_allocate.v4.u32 {%4,%5,%6,%7}, [%8+12288];\n}"
                 : "=r"(w0.x), "=r"(w0.y), "=r"(w0.z), "=r"(w0.w), "=r"(w1.x), "=r"(w1.y), "=r"(w1.z), "=r"(w1.w) : "l"(pw), "r"(tx));
    if (tx == 288) asm volatile("prefetch.global.L2 [%0];" ::"l"((bx & 1 ? gx : gc) + (bx >> 1) * 128));
    if (tx < 256) {
      backoff(T.D_CC);
      asm volatile("ld.global.nc.v2.u32 {%0,%1}, [%2];" : "=r"(cc.x), "=r"(cc.y) : "l"(pc));
    }
  }
  const int tid = __shfl_xor_sync(0xffffffffu, threadIdx.x ^ 1, 1), lane = tid & 31;
  const int w = __shfl_sync(0xffffffffu, threadIdx.x >> 5, 0);
  const int cta = blockIdx.x;
  auto keep = [&](uint32_t v) { return __shfl_sync(~0u, v, lane); };
  auto BAR = [](int i) { return SB + OFF_BARS + 8 * i; };
  auto selector = [&](int c) { uint32_t v; asm volatile("ld.shared.u8 %0, [%1];" : "=r"(v) : "r"(sb + OFF_SEL + c) : "memory"); return v; };
  auto inbox = [&](int c, int k) { return gin + blk(c, k, selector(c)); };
  auto nearbox = [&](int c, int k) { return gin + blk(c, k, selector(cta) ^ flip((c ^ cta) & 15)); };
  const int g = lane >> 2, t = lane & 3;
  const int hI = cta >> 2, jI = cta & 3;
  const int bs = cta >> 1, hh = cta & 1;

  if (w == 8) {
    const uint32_t t_entry = gtime32();
    if (lane == 0) {
      if ((uint32_t)__cvta_generic_to_shared(smem_raw) != SB) __trap();
      mbar_init(BAR(BAR_WQ), 1); mbar_init(BAR(BAR_WQ + 1), 1); mbar_init(BAR(BAR_XC), 1); mbar_init(BAR(BAR_C), 1);
      asm volatile("fence.mbarrier_init.release.cluster;" ::: "memory");
      asm volatile("prefetch.tensormap [%0];" ::"l"(&P.wq) : "memory");
      mbar_expect(BAR(BAR_XC), 8192); mbar_expect(BAR(BAR_C), 8192); mbar_expect(BAR(BAR_WQ), 16384); mbar_expect(BAR(BAR_WQ + 1), 16384);
    }
    __syncwarp();
    asm volatile("barrier.cta.arrive.aligned 0, %0;" ::"n"(NTHREADS) : "memory");
    uint32_t tn = t_entry + (uint32_t)(T.PC_T0 + ((bs * 37) & 63) * T.PC_STAG / 64);
    const int h = hI, j = jI;
    if (lane == 0) {
      uint64_t pol; asm volatile("createpolicy.fractional.L2::evict_first.b64 %0, 1.0;" : "=l"(pol));
#pragma unroll
      for (int u = 0; u < 4; u++) {
        until_ns(tn + u * T.PC_P1);
        tma2d(sb + OFF_WQ + u * 8192, &P.wq, 128 * h + 64 * (u >> 1), 128 * j + 64 * (u & 1), BAR(BAR_WQ + (u >> 1)), pol);
        if (u == 0) {
#pragma unroll
          for (int i = 0; i < 8; i++) { const int o = ((i + cta) & 3) * 2048; bulk_ld(sb + OFF_XS + (i >> 2) * 8192 + o, (i < 4 ? gx : gc) + o, 2048, BAR(i < 4 ? BAR_XC : BAR_C)); }
          asm volatile("prefetch.tensormap [%0];" ::"l"(&P.wuk) : "memory");
          asm volatile("prefetch.tensormap [%0];" ::"l"(&P.wm2) : "memory");
          asm volatile("prefetch.tensormap [%0];" ::"l"(&P.ckv2) : "memory");
        }
      }
    }
    __syncwarp();
    tn += 4 * T.PC_P1;
    bar_sync(5, 64);
    if (lane == 0) {
      uint64_t pol; asm volatile("createpolicy.fractional.L2::evict_first.b64 %0, 1.0;" : "=l"(pol));
#pragma unroll
      for (int u = 0; u < 4; u++) {
        if (u & 1) mbar_wait(BAR(BAR_WQ + (u >> 1)));
        slot(tn, T.PC_SL);
        tma5d(sb + OFF_WUK + u * 8192, &P.wuk, 128 * h + 64 * (u >> 1), 0, 0, 0, 8 * j + 4 * (u & 1), BAR(BAR_WUK + (u >> 1)), pol);
        tn += T.PC_P1;
      }
#pragma unroll
      for (int u = 0; u < 2; u++) {
        if (u) mbar_wait(BAR(BAR_WUK));
        slot(tn, T.PC_SL);
        if (j != 3) tma2d_nohint(sb + OFF_WM2 + u * 8192, &P.wm2, 1024 + 16 * (3 * h + j), 256 * u, BAR(BAR_WM2));
        tn += T.PC_PM;
      }
      const int row0 = (bs >> 3) * 4096 + (bs & 7) * 64;
      uint32_t dst = sb + OFF_RING;
#pragma unroll 1
      for (int n = 0; n < 31; n++) {
        if (n >= 4 && (n < 12 || (n & 3) == 0)) mbar_wait(BAR(n >= 12 ? BAR_EMPTY + (n >> 2) - 3 : (n == 7 && j != 3) ? BAR_P0BD : (n == 8 || n == 9) ? BAR_P2D : BAR_P1D));
        if (n < T.PC_NW) {
          if (n >= 4) mbar_wait(BAR(BAR_FULL + n - 4));
          else if (n & 1) mbar_wait(BAR((n < 2 || j == 3) ? BAR_WUK + 1 : BAR_WM2));
        }
        slot(tn, T.PC_SL);
        tma3d(dst, &P.ckv2, 0, row0 + (n >> 2) * 512, 2 * (n & 3), BAR(BAR_FULL + n), pol);
        dst = (n == 11 || n == 23) ? sb + OFF_RING : dst + 16384;
        tn += T.PC_P2;
        if (n == 24) {
          asm volatile("prefetch.tensormap [%0];" ::"l"(&P.ckv1) : "memory");
          asm volatile("prefetch.tensormap [%0];" ::"l"(&P.wuv) : "memory");
          asm volatile("prefetch.tensormap [%0];" ::"l"(&P.wo) : "memory");
          asm volatile("prefetch.tensormap [%0];" ::"l"(cta < NFF ? &P.w1 : &P.wm3) : "memory");
          asm volatile("prefetch.tensormap [%0];" ::"l"(&P.w2) : "memory");
        }
      }
      slot(tn, T.PC_SL);
      tma3d(dst, &P.ckv1, 0, row0 + 7 * 512, 6, BAR(BAR_LAST + 3), pol);
      tma3d(dst + 8192, &P.ckv1, 0, row0 + 7 * 512, 7, BAR(BAR_LAST + 4), pol);
      tn += T.PC_P2;
      auto unit = [&](int u) {
        if (u < 4) tma5d(sb + OFF_WUV + u * 8192, &P.wuv, 128 * h + 64 * (u >> 1), 0, 4 * (j >> 1), 0, 2 * (j & 1) + (u & 1), BAR(BAR_WUV + (u >> 1)), pol);
        else if (u < 8) tma2d(sb + OFF_WO + (u - 4) * 8192, &P.wo, 128 * j + 64 * ((u - 4) >> 1), 128 * h + 64 * (u & 1), BAR(BAR_WO + ((u - 4) >> 1)), pol);
        else if (u < 10) { if (cta < NFF) tma2d_nohint(sb + OFF_W1 + (u - 8) * 16384, &P.w1, 32 * bs, 256 * (u - 8), BAR(BAR_W1)); }
        else if (cta < NFF) tma3d(sb + OFF_W2 + (u - 10) * 8192, &P.w2, 0, 32 * bs, 4 * hh + 2 * (u - 10), BAR(BAR_W2), pol);
        else tma2d_nohint(sb + OFF_W1 + (u - 10) * 16384, &P.wm3, 2560 + 32 * (cta - NFF), 256 * (u - 10), BAR(BAR_W1));
      };
      mbar_wait(BAR(BAR_EMPTY + 5));
#pragma unroll
      for (int u = 0; u < 12; u++) {
        if (u == 8) mbar_wait(BAR(BAR_EMPTY + 6));
        until_ns(tn + (u < 4 ? T.T_UV + u * T.P_UV : u < 8 ? T.T_O + (u - 4) * T.P_O : u < 10 ? T.T_1 + (u - 8) * T.P_F : (cta < NFF ? T.T_2 : T.T_GB) + (u - 10) * T.P_F));
        unit(u);
        if (u == 3) {
#pragma unroll
          for (int q = 0; q < 4; q++)
            if (q < T.PF_N) {
              until_ns(tn + T.T_PF + q * T.P_PF);
              asm volatile("cp.async.bulk.prefetch.tensor.2d.L2.global.tile [%0, {%1,%2}];" ::"l"(&P.wo), "r"(128 * j + 64 * (q >> 1)), "r"(128 * h + 64 * (q & 1)) : "memory");
            }
        }
      }
    }
    return;
  }

  uint32_t epoch;
  if (w == 9) {
    if (lane == 0) {
#pragma unroll
      for (int i = 0; i < NBARS; i++) mbar_init(BAR(i), i >= BAR_P1D ? 8 : i >= BAR_EMPTY ? 4 : 1);
      asm volatile("fence.mbarrier_init.release.cluster;" ::: "memory");
    }
    __syncwarp();
    mbar_expect(BAR(lane), lane == BAR_LAST + 3 ? 8192 : 16384);
    if (lane < BAR_ALLCLR - 32) mbar_expect(BAR(32 + lane), lane == 0 ? 8192 : lane == BAR_W1 - 32 ? 32768 : 16384);
    asm volatile("barrier.cta.arrive.aligned 5, 64;" ::: "memory");
    if (cta != 8) backoff(T.D_EP);
    epoch = ldg_rlx1(&gs->epoch);
    sts1(sb + OFF_EPOCH, epoch);
    asm volatile("barrier.cta.arrive.aligned 0, %0;" ::"n"(NTHREADS) : "memory");
  }

  if (w == 9) {
    const int mo = g * 512 + 16 * hI + 2 * jI;
    const uint32_t xo0 = ldg_nc1(gx + mo * 2), xo1 = ldg_nc1(gx + mo * 2 + 16);
    const int par = epoch & 1;
    const uint32_t t0 = gtime32();
    const uint4 z = make_uint4(0, 0, 0, 0);
    uint32_t sel;
    {
      uint32_t* pa = gin + blk(cta, 5, 0) + 960;
      uint32_t* pb = gin + blk(cta, 5, 1) + 960;
      until_ns(t0 + T.PR_T0);
      if (lane < 4) stg4(reinterpret_cast<uint4*>(lane & 2 ? pa : pb) + (lane & 1), z);
      uint32_t ma = 0xffffffffu, mb = 0xffffffffu;
#pragma unroll 1
      for (int i = 0; i < 2 * T.PR_N; i++) {
        const uint32_t c0 = clk32();
        asm volatile("{\n.reg .pred q;\n.reg .b32 v;\nsetp.eq.u32 q, %1, 0;\nmov.u32 v, 0;\n@q atom.relaxed.gpu.global.add.u32 v, [%0], 1;\n"
                     "setp.eq.u32 q, v, 0xffffffff;\n@q trap;\n}" ::"l"(i & 1 ? pb : pa), "r"(lane) : "memory");
        const uint32_t d = clk32() - c0;
        if (i & 1) mb = min(mb, d); else ma = min(ma, d);
      }
      sel = __shfl_sync(~0u, (uint32_t)(mb < ma), 0);
      const uint32_t sw = 2 * (epoch + 1) + sel;
      if (lane < 2) stg4(reinterpret_cast<uint4*>(gin + blk(cta, 5, 1) + 896) + lane, make_uint4(sw, sw, sw, sw));
    }
    until_ns(t0 + T.CLR_T0);
    {
#pragma unroll 1
      for (int i0 = 0; i0 < 13; i0++) {
        uint4* q = reinterpret_cast<uint4*>(gin + (i0 < 12 ? blk(cta, i0 >> 1, sel) + (i0 & 1) * 512 : blk(cta, 4, sel ^ 1) + 512)) + lane;
#pragma unroll
        for (int i = 0; i < 4; i++) if (i0 != 11 || i < 3) stg4(q + i * 32, z);
        backoff(T.CLR_CLK);
      }
#pragma unroll
      for (int i = 0; i < 2; i++) {
        if (jI == 1) stg4(reinterpret_cast<uint4*>(gin + blk(cta, 6, i)) + lane, z);
        if (lane < 2) stg4(reinterpret_cast<uint4*>(gin + blk(cta, 5, i) + 928) + lane, z);
      }
      stg4(reinterpret_cast<uint4*>(gin + blk(32 * (g >> 1), 6 + (cta >> 6), g) + (cta & 63) * 16) + t, z);
      {
        uint32_t sv = 0;
        uint32_t u[4];
        int it = 0;
        do {
#pragma unroll
          for (int i = 0; i < 4; i++) u[i] = ldg_rlx1(gin + blk(4 * lane + i, 5, 1) + 896) ^ (2 * (epoch + 1));
          if (++it > SPIN_LIMIT) __trap();
        } while (!__all_sync(~0u, (u[0] | u[1] | u[2] | u[3]) < 2));
#pragma unroll
        for (int i = 0; i < 4; i++) sv |= u[i] << (8 * i);
        sts1(sb + OFF_SEL + lane * 4, sv);
      }
      asm volatile("fence.acq_rel.gpu;" ::: "memory");
      __syncwarp();
      if (lane < NSYNC) asm volatile("red.relaxed.gpu.global.add.u32 [%0], 1;" ::"l"(&gs->sync[lane][0]) : "memory");
#pragma unroll
      for (int i = 0; i < 4; i++) stg4(reinterpret_cast<uint4*>(gs->QP[par ^ 1] + cta * 512) + i * 32 + lane, z);
      backoff(T.CLR_CLK);
#pragma unroll
      for (int i = 0; i < 4; i++) stg4(reinterpret_cast<uint4*>(gs->QX[par ^ 1] + cta * 512) + i * 32 + lane, z);
      stg4(reinterpret_cast<uint4*>(gs->MOD1[par ^ 1] + cta * 128) + lane, z);
      if (lane < 16) stg4(reinterpret_cast<uint4*>(gs->MOD2[par ^ 1] + cta * 64) + lane, z);
      const uint32_t target = (epoch + 1) * NCTA;
      uint32_t c; int it = 0;
      do {
        backoff(T.CLR_CLK);
        asm volatile("ld.acquire.gpu.global.u32 %0, [%1];" : "=r"(c) : "l"(&gs->sync[cta % NSYNC][0]) : "memory");
        if (++it > SPIN_LIMIT) __trap();
      } while (!__all_sync(~0u, (int)(c - target) >= 0));
      if (lane == 0) mbar_arrive(BAR(BAR_ALLCLR));
    }
    const uint32_t* const pg = gs->MOD2[par] + cta * 16 + g * 2;
    auto gate = [&](const uint32_t* q) { uint2 u; int it = 0; do { u = ldg_u64(q); if (++it > SPIN_LIMIT) __trap(); } while (!__all_sync(~0u, u.y != 0)); return u; };
    const uint2 gau = gate(pg);
    uint32_t anchor;
    {
      uint32_t* const po = gin + blk(16 * (lane & 7), 5, lane >> 3) + 928;
      const uint32_t* const pi = nearbox(cta & ~15, 5) + 928;
      mbar_wait(BAR(BAR_LAST + T.TS_P));
      unsigned long long now; asm volatile("mov.u64 %0, %%globaltimer;" : "=l"(now));
      if (lane < 16) asm volatile("red.relaxed.gpu.global.add.u64 [%0], %1;" ::"l"(po), "l"((now << 8) + 1) : "memory");
      backoff(T.D_TS);
      uint2 v; int it = 0;
      do { v = ldg_u64(pi); if (++it > SPIN_LIMIT) __trap(); } while (!__all_sync(~0u, (v.x & 255) == NCTA));
      const uint32_t mean = __funnelshift_r(v.x, v.y, 15);
      const int age = min(max((int)(gtime32() - mean), 0), 4000);
      anchor = clk32() - age * 7 / 4 + T.TS_O;
      if (lane == 0) { sts1(sb + OFF_TS, anchor); mbar_arrive(BAR(BAR_TS)); }
      if (cta == 0 && lane == 0) stg1(&gs->epoch, epoch + 1);
    }
    {
      const uint32_t* pm = pin(nearbox(4 * hI + 1, 6) + lane * 4);
      wait_clk(anchor, T.A_M);
      uint4 ml = ldg_2u64(pm);
      int it = 0;
      while (!__all_sync(~0u, ml.y != 0 && ml.w != 0)) { ml = ldg_2u64(pm); if (++it > SPIN_LIMIT) __trap(); }
      float M = fmaxf(__uint_as_float(ml.x), __uint_as_float(ml.z));
      M = fmaxf(M, __shfl_xor_sync(~0u, M, 1)); M = fmaxf(M, __shfl_xor_sync(~0u, M, 2));
      const float e0 = ex2(__uint_as_float(ml.x) - M), e1 = ex2(__uint_as_float(ml.z) - M);
      float l = e0 * __uint_as_float(ml.y) + e1 * __uint_as_float(ml.w);
      l += __shfl_xor_sync(~0u, l, 1); l += __shfl_xor_sync(~0u, l, 2);
      const float inv = __fdividef(1.f, l);
      sts2f(sb + OFF_WV + lane * 8, e0 * inv, e1 * inv);
      __syncwarp();
      if (lane == 0) mbar_arrive(BAR(BAR_WV));
    }
    uint32_t* x3o[2];
#pragma unroll
    for (int i = 0; i < 2; i++) x3o[i] = pin(gin + blk(64 * i + 32 * (t >> 1), 6 + (cta >> 6), t) + (cta & 63) * 16 + g * 2);
    const uint32_t* const p3 = pin(gin + blk(cta, 4, sel) + t * 16 + g * 2);
    const uint32_t* const p4 = pin(gin + blk(cta, 5, sel) + t * 16 + g * 2);
    const uint32_t one = pin((g & 1) ? 0x3f800000u : 0x00003f80u);
    const float xf[4] = {pin(bf_lo(xo0)), pin(bf_hi(xo0)), pin(bf_lo(xo1)), pin(bf_hi(xo1))};
    const float ga[4] = {pin(bf_lo(gau.x)), pin(bf_hi(gau.x)), pin(bf_lo(gau.y)), pin(bf_hi(gau.y))};
    mbar_wait(BAR(BAR_P5D));
    backoff(T.D_X3A);
    wait_clk(anchor, T.A_X1 + T.R_X3A);
    float r[4];
    uint32_t x20, x21;
    int it = 0;
    bool ok;
    do {
      ok = sum_pieces<32>(p3, one, r);
      x20 = pack_bf16(xf[0] + ga[0] * r[0], xf[1] + ga[1] * r[1]); x21 = pack_bf16(xf[2] + ga[2] * r[2], xf[3] + ga[3] * r[3]);
#pragma unroll
      for (int i = 0; i < 2; i++) stg_u64_unless(!ok, x3o[i], x20, x21);
    } while (!ok && ++it < SPIN_LIMIT);
    if (!ok) __trap();
    const int bo = 2 * (g & 3) + (t & 1);
    const uint32_t xs0 = __shfl_sync(~0u, x20, 4 * bo), xs1 = __shfl_sync(~0u, x21, 4 * bo), psel = keep((t & 2 ? 0x4400u : 0u) + (g & 4 ? 0x3200u : 0x1000u));
    const float xa = pin(__uint_as_float(__byte_perm(xs0, xs1, psel) & 0xffff0000u));
    const uint32_t one2 = keep((g & 2) ? 0x3f800000u : 0x00003f80u);
    __nv_bfloat16* const fo = gout + keep(bo * 512 + 16 * hI + 2 * jI + (g >> 2) + 8 * (t >> 1));
    const uint32_t* const pgb = gs->MOD2[par] + 3 * 2048 + cta * 16 + bo * 2;
    if (cta < NFF) mbar_wait(BAR(BAR_P7D)); else wait_clk(anchor, T.A_X1 + T.R_X3A + T.R_X3B + T.R_FIN - T.D_FIN);
    uint2 gbu = ldg_u64(pgb);
    backoff(T.D_FIN);
    while (true) {
      ok = sum_pieces<NFG>(p4, one2, r, gbu.y);
      const float gb = __uint_as_float(__byte_perm(gbu.x, gbu.y, psel) & 0xffff0000u);
      const uint32_t o = pack_bf16(xa + gb * ((t & 2) ? r[2] : r[0]), 0.f);
      asm volatile("st.global.u16 [%0], %1;" ::"l"(fo), "h"((uint16_t)o) : "memory");
      if (ok) {
        return;
      }
      reload_unit(gbu, pgb);
      if (++it > SPIN_LIMIT) __trap();
    }
  }

  const int wg = w >> 2, wq = w & 3;
  uint32_t tstore;
  {
    const uint32_t a[4] = {silu2(cc.x), 0u, silu2(cc.y), 0u};
    float d[4][4] = {{0.f, 0.f, 0.f, 0.f}, {0.f, 0.f, 0.f, 0.f}, {0.f, 0.f, 0.f, 0.f}, {0.f, 0.f, 0.f, 0.f}};
    mma16816(d[0], a, movm(w0.x), movm(w1.x)); mma16816(d[1], a, movm(w0.y), movm(w1.y));
    mma16816(d[2], a, movm(w0.z), movm(w1.z)); mma16816(d[3], a, movm(w0.w), movm(w1.w));
    sts4f(sb + OFF_P0S + w * 1088 + lane * 16, d[0][0], d[0][1], d[1][0], d[1][1]);
    sts4f(sb + OFF_P0S + w * 1088 + 544 + lane * 16, d[2][0], d[2][1], d[3][0], d[3][1]);
    bar_sync(0, NTHREADS);
    epoch = lds1(sb + OFF_EPOCH);
    if (tid < 128) {
      const uint32_t src = sb + OFF_P0S + ((tid >> 2) & 1) * 544 + (((tid >> 3) & 7) * 4 + 2 * (tid >> 6) + (tid & 1)) * 16 + ((tid >> 1) & 1) * 8;
      float2 v[8];
#pragma unroll
      for (int i = 0; i < 8; i++) v[i] = ldsf2(src + i * 1088);
      const float ax = ((v[0].x + v[1].x) + (v[2].x + v[3].x)) + ((v[4].x + v[5].x) + (v[6].x + v[7].x));
      const float ay = ((v[0].y + v[1].y) + (v[2].y + v[3].y)) + ((v[4].y + v[5].y) + (v[6].y + v[7].y));
      stg1(gs->MOD1[epoch & 1] + jI * 4096 + hI * 128 + tid, nz(pack_bf16(ax, ay)));
    }
    tstore = clk32();
  }
  const int par = epoch & 1;
  uint32_t cf[4][4];
  mbar_wait(BAR(BAR_XC));
  {
    uint32_t u[2][4];
    lds4(u[0], sb + OFF_XS + w * 1024 + lane * 16); lds4(u[1], sb + OFF_XS + w * 1024 + 512 + lane * 16);
    float v[16];
#pragma unroll
    for (int i = 0; i < 8; i++) { v[2 * i] = bf_lo(u[i >> 2][i & 3]); v[2 * i + 1] = bf_hi(u[i >> 2][i & 3]); }
    float s = 0.f;
#pragma unroll
    for (int i = 0; i < 16; i++) s += v[i];
#pragma unroll
    for (int o = 16; o; o >>= 1) s += __shfl_xor_sync(~0u, s, o);
    const float mu = s * (1.f / 512.f);
    float q = 0.f;
#pragma unroll
    for (int i = 0; i < 16; i++) { v[i] -= mu; q += v[i] * v[i]; }
#pragma unroll
    for (int o = 16; o; o >>= 1) q += __shfl_xor_sync(~0u, q, o);
    const float rs = rsqrtf(q * (1.f / 512.f) + 1e-5f);
    const bool hi = jI & 2;
    uint32_t o[4];
#pragma unroll
    for (int i = 0; i < 4; i++) o[i] = pack_bf16((hi ? v[8 + 2 * i] : v[2 * i]) * rs, (hi ? v[9 + 2 * i] : v[2 * i + 1]) * rs);
    if ((lane >> 4) == (jI & 1)) sts4(sb + OFF_XN + w * 272 + (lane & 15) * 16, make_uint4(o[0], o[1], o[2], o[3]));
  }
  uint32_t aw[8][4];
  const uint32_t abase = keep(sb + a_t_offset(w, lane));
  {
    const uint32_t* pm = pin(gs->MOD1[par] + (8 * jI + w) * 64 + lane * 2);
    uint32_t* const qpo = pin(gs->QP[par] + (cta * 256 + tid) * 2);
    float d[4] = {0.f, 0.f, 0.f, 0.f};
    wait_clk(tstore, T.D_MOD);
    uint2 v[8];
    load_units<8, 2048>(v, pm);
    cbar();
    const uint32_t xn0 = lds1(sb + OFF_XN + g * 272 + w * 32 + t * 4), xn1 = lds1(sb + OFF_XN + g * 272 + w * 32 + 16 + t * 4);
    const bool early = __all_sync(~0u, mbar_test(BAR(BAR_WQ + wg)));
    if (early) load_a_t(aw, abase + OFF_WQ);
    int it = 0;
    while (true) {
      uint32_t mn = 0xffffffffu;
#pragma unroll
      for (int i = 0; i < 8; i++) mn = min(mn, min(v[i].x, v[i].y));
      if (__all_sync(~0u, mn != 0)) break;
#pragma unroll
      for (int i = 0; i < 8; i++) { if (v[i].x == 0) v[i].y = 0; reload_unit(v[i], pm + i * 2048); }
      if (++it > SPIN_LIMIT) __trap();
    }
    float sc[2][4];
#pragma unroll
    for (int i = 0; i < 2; i++) {
      sc[i][0] = (bf_lo(v[i].x) + bf_lo(v[2 + i].x)) + (bf_lo(v[4 + i].x) + bf_lo(v[6 + i].x));
      sc[i][1] = (bf_hi(v[i].x) + bf_hi(v[2 + i].x)) + (bf_hi(v[4 + i].x) + bf_hi(v[6 + i].x));
      sc[i][2] = (bf_lo(v[i].y) + bf_lo(v[2 + i].y)) + (bf_lo(v[4 + i].y) + bf_lo(v[6 + i].y));
      sc[i][3] = (bf_hi(v[i].y) + bf_hi(v[2 + i].y)) + (bf_hi(v[4 + i].y) + bf_hi(v[6 + i].y));
    }
    sts2(sb + OFF_BS1 + (w >> 1) * 512 + lane * 16 + (w & 1) * 8,
         pack_bf16(bf_lo(xn0) * (1.f + sc[1][0]) + sc[0][0], bf_hi(xn0) * (1.f + sc[1][1]) + sc[0][1]),
         pack_bf16(bf_lo(xn1) * (1.f + sc[1][2]) + sc[0][2], bf_hi(xn1) * (1.f + sc[1][3]) + sc[0][3]));
    if (!early) { mbar_wait(BAR(BAR_WQ + wg)); load_a_t(aw, abase + OFF_WQ); }
    cbar();
    uint32_t b[4][4];
#pragma unroll
    for (int kk = 0; kk < 4; kk++) lds4(b[kk], sb + OFF_BS1 + kk * 512 + lane * 16);
    mma128(d, aw, b);
    stg_u64(qpo, pack_bf16(d[0], d[1]), pack_bf16(d[2], d[3]));
    tstore = clk32();
    if (wg) {
      mbar_wait(BAR(BAR_C));
#pragma unroll
      for (int i = 0; i < 4; i++) lds4(cf[i], sb + OFF_CS + g * 1024 + wq * 256 + i * 64 + t * 16);
#pragma unroll
      for (int i = 0; i < 16; i++) cf[i >> 2][i & 3] = silu2(cf[i >> 2][i & 3]);
    }
    __syncwarp();
    if (lane == 0) mbar_arrive(BAR(BAR_P1D));
  }
  {
    const uint32_t* pq = pin(gs->QP[par] + (hI * 4 * 256 + tid) * 2);
    uint32_t* const qxo = pin(gs->QX[par] + (g * 32 + hI) * 256 + 64 * jI + 8 * w + 2 * t);
    uint2 v[4];
    float d[4] = {0.f, 0.f, 0.f, 0.f};
    wait_clk(tstore, T.D_QP);
    load_units<4, 512>(v, pq);
    const uint32_t kbase = sb + OFF_WUK + (16 * w + (lane & 15)) * 128;
    auto load_half = [&](int hf) {
#pragma unroll
      for (int ks = 0; ks < 4; ks++) ldsm4(aw[4 * hf + ks], kbase + hf * 16384 + (((2 * ks + (lane >> 4)) ^ (lane & 7)) << 4));
    };
    mbar_wait(BAR(BAR_WUK));
    load_half(0);
    const bool early = __all_sync(~0u, mbar_test(BAR(BAR_WUK + 1)));
    if (early) load_half(1);
    check_units<4, 512>(v, pq);
    sum4_to_smem(v, sb + OFF_BS2 + (16 * w + g) * 16 + t * 4);
    if (!early) { mbar_wait(BAR(BAR_WUK + 1)); load_half(1); }
    cbar();
    uint32_t b[4][4];
#pragma unroll
    for (int kk = 0; kk < 4; kk++) ldsm4t(b[kk], sb + OFF_BS2 + (32 * kk + lane) * 16);
    mma128(d, aw, b);
    const float sc = 0.08838834764831845f * 1.4426950408889634f;
    stg_u64(qxo, movm(pack_bf16(d[0] * sc, d[1] * sc)), movm(pack_bf16(d[2] * sc, d[3] * sc)));
    tstore = clk32();
    if (lane == 0) mbar_arrive(BAR(BAR_P2D));
  }
  if (wg && jI != 3) {
    const int mi = lane >> 3, r = lane & 7;
    const uint32_t a0 = sb + OFF_WM2 + (8 * (r >> 1) + (r & 1) + 2 * (mi >> 1)) * 32 + (mi & 1) * 16;
    mbar_wait(BAR(BAR_WM2));
#pragma unroll
    for (int s = 0; s < 8; s++) ldsm4t(aw[s], a0 + (128 * wq + 32 * (s >> 1) + 4 * (s & 1)) * 32);
    float d[4] = {0.f, 0.f, 0.f, 0.f};
    mma128(d, aw, cf);
    sts4f(sb + OFF_P0B + (tid - 128) * 16, d[0], d[1], d[2], d[3]);
    if (lane == 0) mbar_arrive(BAR(BAR_P0BD));
    bar_sync(3, 128);
    if (w == 4) {
      float4 v[4];
#pragma unroll
      for (int i = 0; i < 4; i++) v[i] = ldsf4(sb + OFF_P0B + (i * 32 + lane) * 16);
      stg_u64(gs->MOD2[par] + (3 * hI + jI) * 64 + t * 16 + g * 2, movm(pack_bf16((v[0].x + v[1].x) + (v[2].x + v[3].x), (v[0].y + v[1].y) + (v[2].y + v[3].y))),
              movm(pack_bf16((v[0].z + v[1].z) + (v[2].z + v[3].z), (v[0].w + v[1].w) + (v[2].w + v[3].w))));
    }
  }
  {
    const uint32_t* qx = pin(gs->QX[par] + ((bs >> 3) * 32 + 16 * hh) * 256 + tid * 4);
    const int ch = tid & 63, h0 = tid >> 6;
    const uint32_t dst = sb + OFF_Q + (ch >> 3) * 2048 + h0 * 128;
    wait_clk(tstore, T.D_QX);
    uint4 v[4];
#pragma unroll
    for (int i = 0; i < 4; i++) v[i] = ldg_2u64(qx + i * 1024);
    int it = 0;
    while (true) {
      uint32_t mn = 0xffffffffu;
#pragma unroll
      for (int i = 0; i < 4; i++) mn = min(mn, min(v[i].y, v[i].w));
      if (__all_sync(~0u, mn != 0)) break;
#pragma unroll
      for (int i = 0; i < 4; i++)
        asm volatile("{\n.reg .pred q;\nsetp.eq.u32 q, %5, 0;\n@q ld.relaxed.gpu.global.v4.b32 {%0, %1, %2, %3}, [%4];\n}"
                     : "+r"(v[i].x), "+r"(v[i].y), "+r"(v[i].z), "+r"(v[i].w) : "l"(qx + i * 1024), "r"(min(v[i].y, v[i].w)) : "memory");
      if (++it > SPIN_LIMIT) __trap();
    }
#pragma unroll
    for (int i = 0; i < 4; i++) sts4(dst + i * 512 + (((ch & 7) ^ ((4 * i + h0) & 7)) << 4), v[i]);
    asm volatile("fence.proxy.async.shared::cta;" ::: "memory");
    cbar();
  }

  uint2 cbf[4], sbf[4];
  const uint32_t* const pcb = gs->MOD2[par] + 2048 + (16 * w + t) * 16 + g * 2;
  auto load_frags = [&] {
    if (cta < NFF) { load_units<4, 64>(sbf, pcb); load_units<4, 64>(cbf, pcb + 2048); }
    else {
#pragma unroll
      for (int s = 0; s < 4; s++) { cbf[s].x = ldg_nc1(gc + g * 1024 + w * 128 + s * 32 + t * 4); cbf[s].y = ldg_nc1(gc + g * 1024 + w * 128 + s * 32 + 16 + t * 4); }
    }
  };
  uint32_t thand, anchor;
  const uint32_t opaque0 = w >> 4;
  if (wg == 0) {
    float mh[4];
    float L[8];
#pragma unroll
    for (int i = 0; i < 4; i++) { L[2 * i] = L[2 * i + 1] = 0.f; mh[i] = -INFINITY; }
    constexpr uint32_t dq = desc_lo(OFF_Q);
    const uint32_t ptw = sb + OFF_PT + (8 * (lane >> 4) + (lane & 7)) * 128 + (((2 * wq + ((lane >> 3) & 1)) ^ (lane & 7)) << 4);
    float S[8];
    auto softmax = [&](int tl) {
      auto write_p = [&](const float (&x)[8]) {
        float p[8];
#pragma unroll
        for (int i = 0; i < 8; i++) p[i] = ex2(x[i]);
        stsm4t(ptw + (tl & 1) * 2048, pack_bf16(p[0], p[1]), pack_bf16(p[2], p[3]), pack_bf16(p[4], p[5]), pack_bf16(p[6], p[7]));
        asm volatile("fence.proxy.async.shared::cta;" ::: "memory");
      };
      float x[8];
#pragma unroll
      for (int i = 0; i < 8; i++) x[i] = S[i] - mh[2 * (i >> 2) + (i & 1)];
      if (tl) write_p(x);
      const float ex = fmaxf(fmaxf(fmaxf(x[0], x[1]), fmaxf(x[2], x[3])), fmaxf(fmaxf(x[4], x[5]), fmaxf(x[6], x[7])));
      if (tl == 0 || bar_over(ex)) {
        float mx[4];
#pragma unroll
        for (int i = 0; i < 4; i++) mx[i] = fmaxf(S[4 * (i >> 1) + (i & 1)], S[4 * (i >> 1) + 2 + (i & 1)]);
        const float a = reduce_g(mx, lane, [](float u, float v) { return fmaxf(u, v); });
        stsf(sb + OFF_RED + wq * 64 + (8 * (lane >> 4) + 2 * t + ((lane >> 3) & 1)) * 4, a);
        bar_sync(2, 128);
#pragma unroll
        for (int jn = 0; jn < 2; jn++) {
          float m0 = mh[2 * jn], m1 = mh[2 * jn + 1];
#pragma unroll
          for (int i = 0; i < 4; i++) { const float2 v = ldsf2(sb + OFF_RED + i * 64 + (8 * jn + 2 * t) * 4); m0 = fmaxf(m0, v.x); m1 = fmaxf(m1, v.y); }
          const float a0 = ex2(mh[2 * jn] - m0), a1 = ex2(mh[2 * jn + 1] - m1);
          mh[2 * jn] = m0; mh[2 * jn + 1] = m1;
          L[4 * jn] *= a0; L[4 * jn + 1] *= a1; L[4 * jn + 2] *= a0; L[4 * jn + 3] *= a1;
          if (tid < 4) sts2f(sb + OFF_ALPHA + (8 * jn + 2 * t) * 4, a0, a1);
        }
        asm volatile("barrier.cta.arrive.aligned 1, 256;" ::: "memory");
#pragma unroll
        for (int i = 0; i < 8; i++) x[i] = S[i] - mh[2 * (i >> 2) + (i & 1)];
        write_p(x);
        bar_over(0.f);
      }
      const uint32_t dpt = __shfl_sync(~0u, desc_lo(OFF_PT) + (tl & 1) * 128, 0);
      wg_fence();
#pragma unroll
      for (int ks = 0; ks < 4; ks++) wgmma_n16_ones(L, ONE2, dpt + ks * 2);
      wg_commit();
    };
    uint32_t da = desc_lo(OFF_RING);
#pragma unroll 1
    for (int tl = 0; tl < 7; tl++) {
      if (tl == 1) mbar_wait(BAR(BAR_EMPTY));
      if (tl == 5) { load_frags(); }
      uint32_t ok = 0;
#pragma unroll
      for (int u = 0; u < 4; u++) ok += mbar_test(BAR(BAR_FULL + 4 * tl + u));
      ok = __reduce_min_sync(~0u, ok);
      const uint32_t du = __shfl_sync(~0u, da, 0);
#pragma unroll
      for (int u = 0; u < 4; u++) {
        if (ok != 4) mbar_wait(BAR(BAR_FULL + 4 * tl + u));
        wg_fence();
#pragma unroll
        for (int k = 0; k < 8; k++) {
          const int i = 8 * u + k;
          if (i == 0) wgmma_n16<0, 0>(S, du, dq); else wgmma_n16<0, 1>(S, du + (i >> 2) * 512 + (i & 3) * 2, dq + (i >> 2) * 128 + (i & 3) * 2);
        }
        wg_commit();
      }
      wg_wait<0>();
      acc_fence(S); acc_fence(L);
      softmax(tl);
      da = (tl == 2 || tl == 5) ? da - 8192 : da + 4096;
    }
    mbar_wait(BAR(BAR_ALLCLR));
    uint32_t* const mlo = pin(gin + blk(4 * (16 * hh + 4 * (g & 2) + 2 * t + (g & 1)) + 1, 6, g >> 2) + bs * 2);
#pragma unroll
    for (int i = 0; i < 32; i++) {
      if (i == 0 || i == 8 || i == 16 || i == 24 || i == 28) {
        if (i) wg_commit();
        mbar_wait(BAR(BAR_LAST + (i == 28 ? 4 : i >> 3)));
        wg_fence();
      }
      if (i == 0) wgmma_n16<0, 0>(S, desc_lo(65536), dq); else wgmma_n16<0, 1>(S, desc_lo(65536) + (i >> 2) * 512 + (i & 3) * 2, dq + (i >> 2) * 128 + (i & 3) * 2);
    }
    wg_commit();
    wg_wait<0>();
    acc_fence(S); acc_fence(L);
    softmax(7);
    thand = clk32();
    wg_wait<0>();
    acc_fence(L);
    if (tid < 32) red_u64(mlo, __float_as_uint(g & 2 ? (g & 1 ? mh[3] : mh[2]) : (g & 1 ? mh[1] : mh[0])), __float_as_uint(g & 2 ? (g & 1 ? L[5] : L[4]) : (g & 1 ? L[1] : L[0])));
  } else {
    float O[8][8];
#pragma unroll
    for (int i = 0; i < 8; i++)
#pragma unroll
      for (int k = 0; k < 8; k++) O[i][k] = 0.f;
    constexpr uint32_t dp = desc_lo(OFF_PT);
    auto handover = [&](int tl) {
      uint32_t over = opaque0 + (tl == 0);
#pragma unroll 1
      do {
        if (over) {
          cbar();
#pragma unroll
          for (int jn = 0; jn < 2; jn++) {
            const float2 a = ldsf2(sb + OFF_ALPHA + (8 * jn + 2 * t) * 4);
#pragma unroll
            for (int mb = 0; mb < 8; mb++) { O[mb][4 * jn] *= a.x; O[mb][4 * jn + 1] *= a.y; O[mb][4 * jn + 2] *= a.x; O[mb][4 * jn + 3] *= a.y; }
          }
        }
        over++;
      } while (bar_over(0.f));
    };
    uint32_t da = desc_lo(OFF_RING);
    uint32_t* x1o[8] = {};
#pragma unroll 1
    for (int tl = 0; tl < 8; tl++) {
      if (tl == 5) load_frags();
      if (tl == 7) {
        mbar_wait(BAR(BAR_ALLCLR));
#pragma unroll
        for (int i = 0; i < 8; i++)
          x1o[i] = inbox((16 * hh + 8 * ((i >> 1) & 1) + 2 * t + (i & 1)) * 4 + 2 * (i >> 2) + (wq >> 1), bs >> 4) + (bs & 15) * 64 + ((wq & 1) * 8 + g) * 4;
      }
      handover(tl);
      thand = clk32();
      const uint32_t dpt = dp + (tl & 1) * 128;
      wg_fence();
#pragma unroll
      for (int i = 0; i < 32; i++) wgmma_n16<1, 1>(O[i >> 2], da + (i >> 2) * 512 + (i & 3) * 128, dpt + (i & 3) * 2);
      wg_commit();
      da = (tl == 2 || tl == 5) ? da - 8192 : da + 4096;
      wg_wait<0>();
#pragma unroll
      for (int mb = 0; mb < 8; mb++) acc_fence(O[mb]);
      if (lane == 0) mbar_arrive(BAR(BAR_EMPTY + tl));
    }
#pragma unroll
    for (int i = 0; i < 8; i++) {
      const int J = i >> 2, k = 4 * ((i >> 1) & 1) + (i & 1);
      stg_cvt8(x1o[i], O[4 * J][k], O[4 * J][k + 2], O[4 * J + 1][k], O[4 * J + 1][k + 2], O[4 * J + 2][k], O[4 * J + 2][k + 2], O[4 * J + 3][k], O[4 * J + 3][k + 2]);
    }
  }

  uint32_t* const o = gin + keep((uint32_t)(inbox(4 * (8 * jI + w) + t, 4) - gin) + hI * 16 + g * 2);
  const uint32_t sdst5 = keep(sb + OFF_BS5 + (16 * w + g) * 16 + t * 4), lane16 = keep(sb + lane * 16);
  const uint32_t* x2i[4];
#pragma unroll
  for (int i = 0; i < 4; i++) x2i[i] = gin + keep((uint32_t)(nearbox(4 * hI + i, 4) - gin) + 512 + tid * 2);
  {
    const uint32_t* px = pin(inbox(cta, w >> 1) + (w & 1) * 512 + lane * 2);
    uint32_t* const x2o = pin(inbox(cta, 4) + 512 + tid * 2);
    uint32_t* const x2p = pin(gin + blk(cta, 4, selector(cta) ^ 1) + 512 + tid * 2);
    const uint32_t q4 = lds1(sb + OFF_SEL + 4 * hI) ^ 0x00010100u;
    const uint32_t same = pin((uint32_t)(q4 == 0 || q4 == 0x01010101u));
    mbar_wait(BAR(BAR_TS));
    anchor = lds1(sb + OFF_TS);
    const uint32_t sdst = keep(sb + OFF_BS4 + w * 272 + lane * 8), ssrc = keep(sb + OFF_BS4 + (lane & 7) * 272 + (lane >> 3) * 16);
    float d[4] = {0.f, 0.f, 0.f, 0.f};
    if (cta >= NFF) {
#pragma unroll
      for (int s = 0; s < 4; s++) { cbf[s].x = silu2(cbf[s].x); cbf[s].y = silu2(cbf[s].y); }
    } else {
      check_units<4, 64>(sbf, pcb);
      check_units<4, 64>(cbf, pcb + 2048);
#pragma unroll
      for (int s = 0; s < 4; s++) { cbf[s].x = hadd2(cbf[s].x, ONE2); cbf[s].y = hadd2(cbf[s].y, ONE2); }
    }
    wait_clk(thand, T.D_X1);
    wait_clk(anchor, T.A_X1 - T.R_X0);
    uint2 v[8];
    load_units<8, 64>(v, px);
    if (T.R_X0) {
      wait_clk(anchor, T.A_X1);
#pragma unroll
      for (int i = 0; i < 8; i++) reload_unit(v[i], px + i * 64);
    }
    const bool early = __all_sync(~0u, mbar_test(BAR(BAR_WUV + wg)));
    if (early) load_a_t(aw, abase + OFF_WUV);
    mbar_wait(BAR(BAR_WV));
    const float4 wa = ldsf4(sb + OFF_WV + w * 32), wb = ldsf4(sb + OFF_WV + w * 32 + 16);
    const float wv[8] = {wa.x, wa.y, wa.z, wa.w, wb.x, wb.y, wb.z, wb.w};
    uint32_t it = opaque0;
    bool ok;
#pragma unroll 1
    do {
      if (it) {
#pragma unroll
        for (int i = 0; i < 8; i++) reload_unit(v[i], px + i * 64);
        if (it > SPIN_LIMIT) __trap();
      }
      it++;
      float a0 = 0.f, a1 = 0.f, a2 = 0.f, a3 = 0.f;
#pragma unroll
      for (int i = 0; i < 8; i++) { a0 += wv[i] * bf_lo(v[i].x); a1 += wv[i] * bf_hi(v[i].x); a2 += wv[i] * bf_lo(v[i].y); a3 += wv[i] * bf_hi(v[i].y); }
      ok = __all_sync(~0u, min_flags(v) != 0);
      sts2(sdst, pack_bf16(a0, a1), pack_bf16(a2, a3));
    } while (!ok);
    cbar();
    uint32_t b[4][4];
#pragma unroll
    for (int kk = 0; kk < 4; kk++) ldsm4(b[kk], ssrc + kk * 64);
    if (__builtin_expect(!early, 0)) { mbar_wait(BAR(BAR_WUV + wg)); load_a_t(aw, abase + OFF_WUV); }
    mma128(d, aw, b);
    const uint32_t c0 = pack_bf16(d[0], d[1]), c1 = pack_bf16(d[2], d[3]);
    stg_u64(x2o, c0, c1);
    stg_u64_unless(same, x2p, c0, c1);
    tstore = clk32();
  }
  {
    float d[4] = {0.f, 0.f, 0.f, 0.f};
    wait_clk(tstore, T.D_X2);
    uint2 v[4];
#pragma unroll
    for (int i = 0; i < 4; i++) v[i] = ldg_u64(x2i[i]);
    const bool early = __all_sync(~0u, mbar_test(BAR(BAR_WO + wg)));
    if (early) load_a_t(aw, abase + OFF_WO);
    uint32_t it = opaque0;
    bool ok;
#pragma unroll 1
    do {
      if (it) {
#pragma unroll
        for (int i = 0; i < 4; i++) reload_unit(v[i], x2i[i]);
        if (it > SPIN_LIMIT) __trap();
      }
      it++;
      ok = __all_sync(~0u, min_flags(v) != 0);
      sum4_to_smem(v, sdst5);
    } while (!ok);
    cbar();
    uint32_t b[4][4];
#pragma unroll
    for (int kk = 0; kk < 4; kk++) ldsm4t(b[kk], lane16 + OFF_BS5 + kk * 512);
    if (__builtin_expect(!early, 0)) { mbar_wait(BAR(BAR_WO + wg)); load_a_t(aw, abase + OFF_WO); }
    mma128(d, aw, b);
    stg_u64(o, movm(pack_bf16(d[0], d[1])), movm(pack_bf16(d[2], d[3])));
    tstore = clk32();
    if (lane == 0) mbar_arrive(BAR(BAR_P5D));
  }
  if (cta < NFF) {
    const int mi = lane >> 3, r = lane & 7;
    uint32_t a1[2][4][4], a2[2][2][4];
    const int lp = (tid >> 2) & 31, kq = tid & 3;
    const int fo = 16 * wg + (lp >> 2) + 8 * (kq >> 1), bo = 2 * (lp & 3) + (kq & 1);
    const uint32_t* xb = gin + keep((uint32_t)(nearbox(cta & ~31, 6 + wg) - gin) + (16 * wq + t) * 16 + g * 2);
    uint32_t* const ox[2] = {gin + keep((uint32_t)(inbox(64 * hh + 8 * w + (g >> 1), 5) - gin) + bs * 16 + (lane & 7) * 2),
                             gin + keep((uint32_t)(inbox(64 * hh + 8 * w + 4 + (g >> 1), 5) - gin) + bs * 16 + (lane & 7) * 2)};
    const uint32_t a1base = keep(sb + OFF_W1 + (64 * w + 8 * (mi >> 1) + r) * 64 + (((mi & 1) ^ (r >> 1)) << 4));
    const uint32_t a2base = keep(sb + OFF_W2 + (w >> 1) * 4096 + (8 * (mi >> 1) + r) * 128 + (((4 * (w & 1) + (mi & 1)) ^ r) << 4));
    const uint32_t s_g = keep(sb + OFF_REDG + w * 1024 + lane * 16), l_g = keep(sb + OFF_REDG + tid * 4);
    const uint32_t s_s = keep(sb + (t == (g >> 1) ? OFF_REDS + g * 80 + w * 8 : OFF_BS4 + tid * 8));
    const uint32_t l_s = keep(sb + OFF_REDS + bo * 80), s_h = keep(sb + OFF_H1 + fo * 16 + bo * 2);
    mbar_wait(BAR(BAR_W1));
#pragma unroll
    for (int i = 0; i < 8; i++) ldsm4t(a1[i & 1][i >> 1], (a1base ^ ((i & 1) << 5)) + (i >> 1) * 1024);
    {
      float u[2][2][4] = {};
#pragma unroll
      for (int s = 0; s < 4; s++)
#pragma unroll
        for (int mt = 0; mt < 2; mt++) { mma16816(u[0][mt], a1[mt][s], cbf[s].x, cbf[s].y); mma16816(u[1][mt], a1[mt][s], sbf[s].x, sbf[s].y); }
#pragma unroll
      for (int i = 0; i < 4; i++) sts4f(s_g + (OFF_REDU - OFF_REDG) + (i >> 1) * 8192 + (i & 1) * 512, u[i >> 1][i & 1][0], u[i >> 1][i & 1][1], u[i >> 1][i & 1][2], u[i >> 1][i & 1][3]);
    }
    wait_clk(tstore, T.D_X3B);
    wait_clk(anchor, T.A_X1 + T.R_X3A + T.R_X3B);
    uint2 x[4];
    load_units<4, 64>(x, xb);
    float U, V;
    {
      cbar();
      float u[8], v[8];
#pragma unroll
      for (int i = 0; i < 8; i++) { u[i] = ldsf(l_g + (OFF_REDU - OFF_REDG) + i * 1024); v[i] = ldsf(l_g + (OFF_REDV - OFF_REDG) + i * 1024); }
      U = pin(((u[0] + u[1]) + (u[2] + u[3])) + ((u[4] + u[5]) + (u[6] + u[7])));
      V = pin(((v[0] + v[1]) + (v[2] + v[3])) + ((v[4] + v[5]) + (v[6] + v[7])));
    }
    auto load_a2 = [&] {
#pragma unroll
      for (int i = 0; i < 4; i++) ldsm4t(a2[i >> 1][i & 1], (a2base ^ ((i >> 1) << 5)) + (i & 1) * 2048);
    };
    const bool early = __all_sync(~0u, mbar_test(BAR(BAR_W2)));
    if (early) load_a2();
    uint32_t it = opaque0;
    float G[2][2][4], S[2][4];
#pragma unroll 1
    do {
      if (it) {
#pragma unroll
        for (int i = 0; i < 4; i++) reload_unit(x[i], xb + i * 64);
        if (it > SPIN_LIMIT) __trap();
      }
      it++;
#pragma unroll
      for (int i = 0; i < 8; i++) { G[0][i >> 2][i & 3] = G[1][i >> 2][i & 3] = S[i >> 2][i & 3] = 0.f; }
      uint32_t y[4][2];
#pragma unroll
      for (int s = 0; s < 4; s++) { y[s][0] = hmul2(x[s].x, cbf[s].x); y[s][1] = hmul2(x[s].y, cbf[s].y); }
#pragma unroll
      for (int s2 = 0; s2 < 4; s2 += 2) {
#pragma unroll
        for (int s = s2; s < s2 + 2; s++) { mma16816(G[0][s & 1], a1[0][s], y[s][0], y[s][1]); mma16816(G[1][s & 1], a1[1][s], y[s][0], y[s][1]); }
#pragma unroll
        for (int s = s2; s < s2 + 2; s++) { const uint32_t sx[4] = {x[s].x, ONE2, x[s].y, ONE2}; mma16816(S[s & 1], sx, x[s].x, x[s].y); }
      }
    } while (!__all_sync(~0u, min_flags(x) != 0));
#pragma unroll
    for (int mt = 0; mt < 2; mt++)
      sts4f(s_g + mt * 512, G[mt][0][0] + G[mt][1][0], G[mt][0][1] + G[mt][1][1], G[mt][0][2] + G[mt][1][2], G[mt][0][3] + G[mt][1][3]);
    sts2f(s_s, (g & 1) ? S[0][3] + S[1][3] : S[0][2] + S[1][2], (g & 1) ? S[0][1] + S[1][1] : S[0][0] + S[1][0]);
    cbar();
    {
      float gv[8];
      float4 sv[4];
#pragma unroll
      for (int i = 0; i < 4; i++) sv[i] = ldsf4(l_s + i * 16);
#pragma unroll
      for (int i = 0; i < 8; i++) gv[i] = ldsf(l_g + i * 1024);
      const float s1 = ((sv[0].x + sv[0].z) + (sv[1].x + sv[1].z)) + ((sv[2].x + sv[2].z) + (sv[3].x + sv[3].z));
      const float s2 = ((sv[0].y + sv[0].w) + (sv[1].y + sv[1].w)) + ((sv[2].y + sv[2].w) + (sv[3].y + sv[3].w));
      const float gsum = ((gv[0] + gv[1]) + (gv[2] + gv[3])) + ((gv[4] + gv[5]) + (gv[6] + gv[7]));
      const float mu = s1 * (1.f / 512.f);
      float rs;
      asm("rsqrt.approx.ftz.f32 %0, %1;" : "=f"(rs) : "f"(fmaxf(s2 * (1.f / 512.f) - mu * mu, 0.f) + 1e-5f));
      const float hv = fmaxf(rs * (gsum - mu * U) + V, 0.f);
      asm volatile("st.shared.u16 [%0], %1;" ::"r"(s_h), "h"(__bfloat16_as_ushort(__float2bfloat16(hv))) : "memory");
    }
    cbar();
    uint32_t b[4];
    ldsm4t(b, lane16 + OFF_H1);
    if (!early) { mbar_wait(BAR(BAR_W2)); load_a2(); }
    float o[2][2][4] = {};
#pragma unroll
    for (int i = 0; i < 4; i++) mma16816(o[i >> 1][i & 1], a2[i >> 1][i & 1], b[2 * (i & 1)], b[2 * (i & 1) + 1]);
#pragma unroll
    for (int mb = 0; mb < 2; mb++)
      stg_u64(ox[mb], pack_bf16(o[mb][0][0] + o[mb][1][0], o[mb][0][1] + o[mb][1][1]), pack_bf16(o[mb][0][2] + o[mb][1][2], o[mb][0][3] + o[mb][1][3]));
    if (lane == 0) mbar_arrive(BAR(BAR_P7D));
  } else {
    const int mi = lane >> 3, r = lane & 7;
    mbar_wait(BAR(BAR_W1));
#pragma unroll
    for (int mt = 0; mt < 2; mt++) {
      float u[4] = {0.f, 0.f, 0.f, 0.f};
#pragma unroll
      for (int ks = 0; ks < 4; ks++) ldsm4t(aw[4 * mt + ks], sb + OFF_W1 + (64 * w + 16 * ks + 8 * (mi >> 1) + r) * 64 + (((2 * mt + (mi & 1)) ^ (r >> 1)) << 4));
#pragma unroll
      for (int ks = 0; ks < 4; ks++) mma16816(u, aw[4 * mt + ks], cbf[ks].x, cbf[ks].y);
      sts4f(sb + OFF_REDU + w * 1024 + mt * 512 + lane * 16, u[0], u[1], u[2], u[3]);
    }
    cbar();
    if (w < 2) {
      float4 v[8];
#pragma unroll
      for (int i = 0; i < 8; i++) v[i] = ldsf4(sb + OFF_REDU + i * 1024 + tid * 16);
      stg_u64(gs->MOD2[par] + (96 + 2 * (cta - NFF) + w) * 64 + t * 16 + g * 2,
              movm(pack_bf16(((v[0].x + v[1].x) + (v[2].x + v[3].x)) + ((v[4].x + v[5].x) + (v[6].x + v[7].x)), ((v[0].y + v[1].y) + (v[2].y + v[3].y)) + ((v[4].y + v[5].y) + (v[6].y + v[7].y)))),
              movm(pack_bf16(((v[0].z + v[1].z) + (v[2].z + v[3].z)) + ((v[4].z + v[5].z) + (v[6].z + v[7].z)), ((v[0].w + v[1].w) + (v[2].w + v[3].w)) + ((v[4].w + v[5].w) + (v[6].w + v[7].w)))));
    }
  }
}

typedef CUresult (*EncodeTiledFn)(CUtensorMap*, CUtensorMapDataType, cuuint32_t, void*, const cuuint64_t*, const cuuint64_t*,
                                  const cuuint32_t*, const cuuint32_t*, CUtensorMapInterleave, CUtensorMapSwizzle,
                                  CUtensorMapL2promotion, CUtensorMapFloatOOBfill);

struct Dim { uint64_t size, stride; uint32_t box; };
template <int R> void encode_map(EncodeTiledFn enc, CUtensorMap* m, const void* base, const Dim (&d)[R], CUtensorMapSwizzle sw, CUtensorMapL2promotion promo) {
  cuuint64_t dims[R], strides[R];
  cuuint32_t box[R], es[R];
  for (int i = 0; i < R; i++) { dims[i] = d[i].size; strides[i] = d[i].stride; box[i] = d[i].box; es[i] = 1; }
  enc(m, CU_TENSOR_MAP_DATA_TYPE_BFLOAT16, R, const_cast<void*>(base), dims, strides + 1, box, es, CU_TENSOR_MAP_INTERLEAVE_NONE, sw, promo,
      CU_TENSOR_MAP_FLOAT_OOB_FILL_NONE);
}

}

extern "C" void kernel_launch(void* const* d_in, const int* in_sizes, int n_in, void* d_out, int out_size) {
  (void)in_sizes; (void)n_in; (void)out_size;
  static EncodeTiledFn enc = nullptr;
  static Scratch* scratch = nullptr;
  static uint32_t* inbox = nullptr;
  if (!enc) {
    void* sp = nullptr;
    cudaGetSymbolAddress(&sp, g_s);
    scratch = (Scratch*)sp;
    cudaGetSymbolAddress(&sp, g_in);
    inbox = (uint32_t*)(((uintptr_t)sp + 0x1fffff) & ~(uintptr_t)0x1fffff);
    void* fn = nullptr;
    cudaDriverEntryPointQueryResult q;
    cudaGetDriverEntryPoint("cuTensorMapEncodeTiled", &fn, cudaEnableDefault, &q);
    enc = (EncodeTiledFn)fn;
    cudaFuncSetAttribute(fused_decode_kernel, cudaFuncAttributeMaxDynamicSharedMemorySize, SMEM_BYTES);
  }
  const CUtensorMapSwizzle S128 = CU_TENSOR_MAP_SWIZZLE_128B, S0 = CU_TENSOR_MAP_SWIZZLE_NONE;
  const CUtensorMapL2promotion L0 = CU_TENSOR_MAP_L2_PROMOTION_NONE, L128 = CU_TENSOR_MAP_L2_PROMOTION_L2_128B;
  Params P;
  encode_map<2>(enc, &P.wq, d_in[2], {{4096, 2, 64}, {512, 8192, 64}}, S128, L0);
  encode_map<5>(enc, &P.wuk, d_in[3], {{4096, 2, 64}, {2, 8192, 2}, {4, 4 * 8192, 4}, {2, 2 * 8192, 2}, {32, 16 * 8192, 4}}, S128, L0);
  encode_map<2>(enc, &P.wm2, d_in[10], {{3072, 2, 16}, {512, 6144, 256}}, S0, L128);
  encode_map<2>(enc, &P.wm3, d_in[10], {{3072, 2, 32}, {512, 6144, 256}}, CU_TENSOR_MAP_SWIZZLE_64B, L128);
  encode_map<3>(enc, &P.ckv2, d_in[1], {{64, 2, 64}, {8 * 4096, 1024, 64}, {8, 128, 2}}, S128, L0);
  encode_map<3>(enc, &P.ckv1, d_in[1], {{64, 2, 64}, {8 * 4096, 1024, 64}, {8, 128, 1}}, S128, L0);
  encode_map<5>(enc, &P.wuv, d_in[4], {{4096, 2, 64}, {2, 8 * 8192, 2}, {8, 64 * 8192, 4}, {8, 8192, 8}, {4, 16 * 8192, 1}}, S128, L0);
  encode_map<2>(enc, &P.wo, d_in[5], {{512, 2, 64}, {4096, 1024, 64}}, S128, L0);
  encode_map<2>(enc, &P.w1, d_in[7], {{1792, 2, 32}, {512, 3584, 256}}, CU_TENSOR_MAP_SWIZZLE_64B, L128);
  encode_map<3>(enc, &P.w2, d_in[8], {{64, 2, 64}, {1792, 1024, 32}, {8, 128, 2}}, S128, L0);
  fused_decode_kernel<<<NCTA, NTHREADS, SMEM_BYTES>>>((__nv_bfloat16*)d_out, scratch, (const uint8_t*)d_in[10], (const uint8_t*)d_in[0],
                     (const uint8_t*)d_in[9], inbox,
                     P);
}
```
